```python
import torch

def _softmax(x, axis=-1):
    return torch.softmax(x, dim=axis)
def _gelu(x):
    return torch.nn.functional.gelu(x, approximate="tanh")
def _silu(x):
    return torch.nn.functional.silu(x)
def _sigmoid(x):
    return torch.sigmoid(x)
def _layernorm(x, axis=-1, eps=1e-5):
    m = x.mean(dim=axis, keepdim=True)
    v = x.var(dim=axis, keepdim=True, unbiased=False)
    return (x - m) / torch.sqrt(v + eps)
def _scatter_add(tgt, idx, src, axis=0):
    return tgt.clone().index_add_(axis, idx, src)
def _segment_sum(src, seg, n):
    out = torch.zeros((n,) + src.shape[1:], dtype=src.dtype)
    return out.index_add_(0, seg, src)
def _pad(x, pw):
    flat = tuple(v for pair in reversed(pw) for v in pair)
    return torch.nn.functional.pad(x, flat)

kernel_name = 'gated_mix__grouped_kv_mqa__sliding_local_dilated__prompt'

def setup_inputs():

    _w = (lambda a: (lambda t: t.to(torch.bfloat16) if t.is_floating_point() else t)(torch.as_tensor(a)))
    def _A_setup():
        B, S, D, H = 1, 2048, 640, 32
        Dh = D // H
        return {
            "x": _w((lambda *s: torch.randn(*s, dtype=torch.bfloat16) * 0.05)(B, S, D)),
            "wq": _w((lambda *s: torch.randn(*s, dtype=torch.bfloat16) * 1.6)(D, H * Dh)),
            "wk": _w((lambda *s: torch.randn(*s, dtype=torch.bfloat16) * 1.6)(D, Dh)),
            "wv": _w((lambda *s: torch.randn(*s, dtype=torch.bfloat16) * 0.2)(D, Dh)),
            "wo": _w((lambda *s: torch.randn(*s, dtype=torch.bfloat16) * 0.2)(H * Dh, D)),
        }
    _A_in = _A_setup()

    def _B_setup():
        B, S, D = 1, 2048, 640
        return {
            "x": _w((lambda *s: torch.randn(*s, dtype=torch.bfloat16) * 0.05)(B, S, D)),
            "wqkv": _w((lambda *s: torch.randn(*s, dtype=torch.bfloat16) * 0.8)(D, 3 * D)),
            "wo": _w((lambda *s: torch.randn(*s, dtype=torch.bfloat16) * 0.05)(D, D)),
        }
    _B_in = _B_setup()

    return {
        "A_x": _A_in["x"],
        "A_wq": _A_in["wq"],
        "A_wk": _A_in["wk"],
        "A_wv": _A_in["wv"],
        "A_wo": _A_in["wo"],
        "B_x": _B_in["x"],
        "B_wqkv": _B_in["wqkv"],
        "B_wo": _B_in["wo"],
        "gate_w": _w((lambda *s: torch.randn(*s, dtype=torch.bfloat16) * 0.05)(640) * 16.0),
    }

def reference(A_x, A_wq, A_wk, A_wv, A_wo, B_x, B_wqkv, B_wo, gate_w):
    def _A_ref(x, wq, wk, wv, wo):
        B, S, D = x.shape
        H = 32
        Dh = D // H
        q = (lambda x, *d: x.permute(*d))((x @ wq).reshape(B, S, H, Dh), 0, 2, 1, 3)
        k = x @ wk
        v = x @ wv
        scores = torch.einsum("bhqd,bkd->bhqk", q, k) * (Dh ** -0.5)
        p = _softmax(scores, axis=-1)
        o = torch.einsum("bhqk,bkd->bhqd", p, v)
        return (lambda x, *d: x.permute(*d))(o, 0, 2, 1, 3).reshape(B, S, H * Dh) @ wo

    def _B_ref(x, wqkv, wo):
        B, S, D = x.shape
        H = 32; Dh = D // H
        W, dil = 8, 2
        qkv = (lambda x, *d: x.permute(*d))((x @ wqkv).reshape(B, S, 3, H, Dh), 2, 0, 3, 1, 4)
        q, k, v = qkv[0], qkv[1], qkv[2]
        scale = Dh ** -0.5
        pos = torch.arange(S)
        off = torch.arange(W) * dil
        idx = pos[:, None] - off[None, :]
        mask = idx >= 0
        idx_c = torch.where(mask, idx, 0).reshape(-1)
        kg = k[:, :, idx_c, :].reshape(B, H, S, W, Dh)
        vg = v[:, :, idx_c, :].reshape(B, H, S, W, Dh)
        logits = torch.einsum("bhsd,bhswd->bhsw", q, kg) * scale
        logits = torch.where(mask[None, None, :, :], logits, -1e9)
        attn = _softmax(logits, axis=-1)
        o = torch.einsum("bhsw,bhswd->bhsd", attn, vg)
        return (lambda x, *d: x.permute(*d))(o, 0, 2, 1, 3).reshape(B, S, D) @ wo

    x = A_x
    g = _sigmoid((x * gate_w).sum(-1, keepdims=True))
    a = _A_ref(x, A_wq, A_wk, A_wv, A_wo)
    b = _B_ref(x, B_wqkv, B_wo)
    return g * a + (1 - g) * b
```

```cpp
#include <cuda_runtime.h>
#include <cuda_bf16.h>
#include <cuda.h>
#include <stdint.h>

namespace {

constexpr int S_LEN = 2048, D_MODEL = 640, DH = 20;

constexpr int GRP = 128;
constexpr int PLANE = GRP * 16;
constexpr int GRP_BYTES = GRP * 16 * 6;
constexpr int NGRP = S_LEN / GRP;
constexpr uint32_t TMASK = 0x6DB6u;

__device__ __align__(1024) __nv_bfloat16 g_q[S_LEN * D_MODEL];
__device__ __align__(1024) __nv_bfloat16 g_qkv[S_LEN * 3 * D_MODEL];
__device__ __align__(1024) __nv_bfloat16 g_a2[S_LEN * 2 * D_MODEL];
__device__ __align__(1024) uint8_t g_kvimg[NGRP * GRP_BYTES];
__device__ float g_gate[S_LEN];
__device__ float g_kmax2[128];
__device__ float g_vmax[128];

__device__ __forceinline__ uint32_t smem_u32(const void* p) { return (uint32_t)__cvta_generic_to_shared(p); }
__device__ __forceinline__ uint64_t mkd(uint32_t lo, uint32_t hi) {
  uint64_t d; asm("mov.b64 %0, {%1, %2};" : "=l"(d) : "r"(lo), "r"(hi)); return d;
}
__device__ __forceinline__ void wg_fence() { asm volatile("wgmma.fence.sync.aligned;" ::: "memory"); }
__device__ __forceinline__ void wg_commit() { asm volatile("wgmma.commit_group.sync.aligned;" ::: "memory"); }
template <int N> __device__ __forceinline__ void wg_wait() { asm volatile("wgmma.wait_group.sync.aligned %0;" :: "n"(N) : "memory"); }
template <int N> __device__ __forceinline__ void fence_regs(float (&d)[N]) {
#pragma unroll
  for (int i = 0; i < N; i++) asm volatile("" : "+f"(d[i]) :: "memory");
}
template <int N> __device__ __forceinline__ void fence_regs(uint32_t (&d)[N]) {
#pragma unroll
  for (int i = 0; i < N; i++) asm volatile("" : "+r"(d[i]) :: "memory");
}
__device__ __forceinline__ void mbar_init(uint32_t bar, uint32_t cnt) { asm volatile("mbarrier.init.shared::cta.b64 [%0], %1;" :: "r"(bar), "r"(cnt)); }
__device__ __forceinline__ void mbar_expect_tx(uint32_t bar, uint32_t bytes) {
  asm volatile("mbarrier.arrive.expect_tx.shared::cta.b64 _, [%0], %1;" :: "r"(bar), "r"(bytes) : "memory");
}
__device__ __forceinline__ void mbar_arrive(uint32_t bar) { asm volatile("mbarrier.arrive.shared::cta.b64 _, [%0];" :: "r"(bar) : "memory"); }
__device__ __forceinline__ void mbar_wait(uint32_t bar, uint32_t parity) {
  asm volatile("{\n.reg .pred p;\nWAIT_%=:\nmbarrier.try_wait.parity.shared::cta.b64 p, [%0], %1;\n@p bra DONE_%=;\nbra WAIT_%=;\nDONE_%=:\n}\n"
               :: "r"(bar), "r"(parity) : "memory");
}
__device__ __forceinline__ void fence_mbar_init() { asm volatile("fence.mbarrier_init.release.cluster;" ::: "memory"); }
__device__ __forceinline__ void fence_proxy_async() { asm volatile("fence.proxy.async.shared::cta;" ::: "memory"); }
__device__ __forceinline__ void bulk_g2s(uint32_t dst, const void* src, uint32_t bytes, uint32_t bar) {
  asm volatile("cp.async.bulk.shared::cluster.global.mbarrier::complete_tx::bytes [%0], [%1], %2, [%3];"
               :: "r"(dst), "l"(src), "r"(bytes), "r"(bar) : "memory");
}
__device__ __forceinline__ void tma_2d(uint32_t dst, const CUtensorMap* tm, int c0, int c1, uint32_t bar) {
  asm volatile("cp.async.bulk.tensor.2d.shared::cluster.global.mbarrier::complete_tx::bytes [%0], [%1, {%3, %4}], [%2];"
               :: "r"(dst), "l"((uint64_t)tm), "r"(bar), "r"(c0), "r"(c1) : "memory");
}
__device__ __forceinline__ void tma_3d(uint32_t dst, const CUtensorMap* tm, int c0, int c1, int c2, uint32_t bar) {
  asm volatile("cp.async.bulk.tensor.3d.shared::cluster.global.mbarrier::complete_tx::bytes [%0], [%1, {%3, %4, %5}], [%2];"
               :: "r"(dst), "l"((uint64_t)tm), "r"(bar), "r"(c0), "r"(c1), "r"(c2) : "memory");
}
__device__ __forceinline__ void prefetch_tmap(const CUtensorMap* tm) { asm volatile("prefetch.tensormap [%0];" :: "l"((uint64_t)tm) : "memory"); }
__device__ __forceinline__ void pdl_wait() { asm volatile("griddepcontrol.wait;" ::: "memory"); }
__device__ __forceinline__ void pdl_launch() { asm volatile("griddepcontrol.launch_dependents;" ::: "memory"); }
__device__ __forceinline__ float ex2(float x) { float y; asm("ex2.approx.ftz.f32 %0, %1;" : "=f"(y) : "f"(x)); return y; }
__device__ __forceinline__ uint32_t pack_bf16(float lo, float hi) {
  uint32_t r; asm("cvt.rn.bf16x2.f32 %0, %1, %2;" : "=r"(r) : "f"(hi), "f"(lo)); return r;
}
__device__ __forceinline__ float bf_lo(uint32_t x) { return __uint_as_float(x << 16); }
__device__ __forceinline__ float bf_hi(uint32_t x) { return __uint_as_float(x & 0xffff0000u); }
__device__ __forceinline__ void stsm4(uint32_t addr, uint32_t r0, uint32_t r1, uint32_t r2, uint32_t r3) {
  asm volatile("stmatrix.sync.aligned.m8n8.x4.shared.b16 [%0], {%1, %2, %3, %4};" :: "r"(addr), "r"(r0), "r"(r1), "r"(r2), "r"(r3) : "memory");
}

__device__ __forceinline__ void wgmma_ss_n160_tb(float (&d)[80], uint64_t descA, uint64_t descB) {
  asm volatile("wgmma.mma_async.sync.aligned.m64n160k16.f32.bf16.bf16 {%0, %1, %2, %3, %4, %5, %6, %7, %8, %9, %10, %11, %12, %13, %14, %15, %16, %17, %18, %19, %20, %21, %22, %23, %24, %25, %26, %27, %28, %29, %30, %31, %32, %33, %34, %35, %36, %37, %38, %39, %40, %41, %42, %43, %44, %45, %46, %47, %48, %49, %50, %51, %52, %53, %54, %55, %56, %57, %58, %59, %60, %61, %62, %63, %64, %65, %66, %67, %68, %69, %70, %71, %72, %73, %74, %75, %76, %77, %78, %79}, %80, %81, 1, 1, 1, 0, 1;\n"
    : "+f"(d[0]), "+f"(d[1]), "+f"(d[2]), "+f"(d[3]), "+f"(d[4]), "+f"(d[5]), "+f"(d[6]), "+f"(d[7]), "+f"(d[8]), "+f"(d[9]), "+f"(d[10]), "+f"(d[11]), "+f"(d[12]), "+f"(d[13]), "+f"(d[14]), "+f"(d[15]), "+f"(d[16]), "+f"(d[17]), "+f"(d[18]), "+f"(d[19]), "+f"(d[20]), "+f"(d[21]), "+f"(d[22]), "+f"(d[23]), "+f"(d[24]), "+f"(d[25]), "+f"(d[26]), "+f"(d[27]), "+f"(d[28]), "+f"(d[29]), "+f"(d[30]), "+f"(d[31]), "+f"(d[32]), "+f"(d[33]), "+f"(d[34]), "+f"(d[35]), "+f"(d[36]), "+f"(d[37]), "+f"(d[38]), "+f"(d[39]), "+f"(d[40]), "+f"(d[41]), "+f"(d[42]), "+f"(d[43]), "+f"(d[44]), "+f"(d[45]), "+f"(d[46]), "+f"(d[47]), "+f"(d[48]), "+f"(d[49]), "+f"(d[50]), "+f"(d[51]), "+f"(d[52]), "+f"(d[53]), "+f"(d[54]), "+f"(d[55]), "+f"(d[56]), "+f"(d[57]), "+f"(d[58]), "+f"(d[59]), "+f"(d[60]), "+f"(d[61]), "+f"(d[62]), "+f"(d[63]), "+f"(d[64]), "+f"(d[65]), "+f"(d[66]), "+f"(d[67]), "+f"(d[68]), "+f"(d[69]), "+f"(d[70]), "+f"(d[71]), "+f"(d[72]), "+f"(d[73]), "+f"(d[74]), "+f"(d[75]), "+f"(d[76]), "+f"(d[77]), "+f"(d[78]), "+f"(d[79])
    : "l"(descA), "l"(descB));
}
__device__ __forceinline__ void wgmma_ss_n48_tb(float (&d)[24], uint64_t descA, uint64_t descB) {
  asm volatile("wgmma.mma_async.sync.aligned.m64n48k16.f32.bf16.bf16 {%0, %1, %2, %3, %4, %5, %6, %7, %8, %9, %10, %11, %12, %13, %14, %15, %16, %17, %18, %19, %20, %21, %22, %23}, %24, %25, 1, 1, 1, 0, 1;\n"
    : "+f"(d[0]), "+f"(d[1]), "+f"(d[2]), "+f"(d[3]), "+f"(d[4]), "+f"(d[5]), "+f"(d[6]), "+f"(d[7]), "+f"(d[8]), "+f"(d[9]), "+f"(d[10]), "+f"(d[11]), "+f"(d[12]), "+f"(d[13]), "+f"(d[14]), "+f"(d[15]), "+f"(d[16]), "+f"(d[17]), "+f"(d[18]), "+f"(d[19]), "+f"(d[20]), "+f"(d[21]), "+f"(d[22]), "+f"(d[23])
    : "l"(descA), "l"(descB));
}
__device__ __forceinline__ void wgmma_ss_n80_tb(float (&d)[40], uint64_t descA, uint64_t descB) {
  asm volatile("wgmma.mma_async.sync.aligned.m64n80k16.f32.bf16.bf16 {%0, %1, %2, %3, %4, %5, %6, %7, %8, %9, %10, %11, %12, %13, %14, %15, %16, %17, %18, %19, %20, %21, %22, %23, %24, %25, %26, %27, %28, %29, %30, %31, %32, %33, %34, %35, %36, %37, %38, %39}, %40, %41, 1, 1, 1, 0, 1;\n"
    : "+f"(d[0]), "+f"(d[1]), "+f"(d[2]), "+f"(d[3]), "+f"(d[4]), "+f"(d[5]), "+f"(d[6]), "+f"(d[7]), "+f"(d[8]), "+f"(d[9]), "+f"(d[10]), "+f"(d[11]), "+f"(d[12]), "+f"(d[13]), "+f"(d[14]), "+f"(d[15]), "+f"(d[16]), "+f"(d[17]), "+f"(d[18]), "+f"(d[19]), "+f"(d[20]), "+f"(d[21]), "+f"(d[22]), "+f"(d[23]), "+f"(d[24]), "+f"(d[25]), "+f"(d[26]), "+f"(d[27]), "+f"(d[28]), "+f"(d[29]), "+f"(d[30]), "+f"(d[31]), "+f"(d[32]), "+f"(d[33]), "+f"(d[34]), "+f"(d[35]), "+f"(d[36]), "+f"(d[37]), "+f"(d[38]), "+f"(d[39])
    : "l"(descA), "l"(descB));
}
template <int SCALE_D>
__device__ __forceinline__ void wgmma_rs_n64(float (&d)[32], uint32_t a0, uint32_t a1, uint32_t a2, uint32_t a3, uint64_t descB) {
  asm volatile("wgmma.mma_async.sync.aligned.m64n64k16.f32.bf16.bf16 {%0, %1, %2, %3, %4, %5, %6, %7, %8, %9, %10, %11, %12, %13, %14, %15, %16, %17, %18, %19, %20, %21, %22, %23, %24, %25, %26, %27, %28, %29, %30, %31}, {%32, %33, %34, %35}, %36, %37, 1, 1, 0;\n"
    : "+f"(d[0]), "+f"(d[1]), "+f"(d[2]), "+f"(d[3]), "+f"(d[4]), "+f"(d[5]), "+f"(d[6]), "+f"(d[7]), "+f"(d[8]), "+f"(d[9]), "+f"(d[10]), "+f"(d[11]), "+f"(d[12]), "+f"(d[13]), "+f"(d[14]), "+f"(d[15]), "+f"(d[16]), "+f"(d[17]), "+f"(d[18]), "+f"(d[19]), "+f"(d[20]), "+f"(d[21]), "+f"(d[22]), "+f"(d[23]), "+f"(d[24]), "+f"(d[25]), "+f"(d[26]), "+f"(d[27]), "+f"(d[28]), "+f"(d[29]), "+f"(d[30]), "+f"(d[31])
    : "r"(a0), "r"(a1), "r"(a2), "r"(a3), "l"(descB), "n"(SCALE_D));
}
template <int SCALE_D>
__device__ __forceinline__ void wgmma_rs_n24_tb(float (&d)[12], uint32_t a0, uint32_t a1, uint32_t a2, uint32_t a3, uint64_t descB) {
  asm volatile("wgmma.mma_async.sync.aligned.m64n24k16.f32.bf16.bf16 {%0, %1, %2, %3, %4, %5, %6, %7, %8, %9, %10, %11}, {%12, %13, %14, %15}, %16, %17, 1, 1, 1;\n"
    : "+f"(d[0]), "+f"(d[1]), "+f"(d[2]), "+f"(d[3]), "+f"(d[4]), "+f"(d[5]), "+f"(d[6]), "+f"(d[7]), "+f"(d[8]), "+f"(d[9]), "+f"(d[10]), "+f"(d[11])
    : "r"(a0), "r"(a1), "r"(a2), "r"(a3), "l"(descB), "n"(SCALE_D));
}

constexpr uint32_t DHI_SW128_K = (1024 >> 4) | (1u << 30);
constexpr uint32_t DHI_SW64_MN = (512 >> 4) | (2u << 30);
constexpr uint32_t DHI_SW32_MN = (256 >> 4) | (3u << 30);

template <int NC>
__device__ __forceinline__ void store_tile_bf16(const float (&acc)[NC / 2], float scale, uint32_t stage, uint8_t* stage_ptr,
                                                __nv_bfloat16* gdst, int gpitch, int lane) {
  constexpr int PITCH = NC * 2 + 16;
  const uint32_t waddr = stage + ((lane & 7) + ((lane >> 3) & 1) * 8) * PITCH + (lane >> 4) * 16;
#pragma unroll
  for (int j = 0; j < NC / 16; j++) {
    stsm4(waddr + j * 32, pack_bf16(acc[8 * j] * scale, acc[8 * j + 1] * scale), pack_bf16(acc[8 * j + 2] * scale, acc[8 * j + 3] * scale),
          pack_bf16(acc[8 * j + 4] * scale, acc[8 * j + 5] * scale), pack_bf16(acc[8 * j + 6] * scale, acc[8 * j + 7] * scale));
  }
  __syncwarp();
  constexpr int CPR = NC / 8;
#pragma unroll
  for (int i = 0; i < CPR / 2; i++) {
    const int c = i * 32 + lane, r = c / CPR, cc = c % CPR;
    const uint4 v = *reinterpret_cast<const uint4*>(stage_ptr + r * PITCH + cc * 16);
    *reinterpret_cast<uint4*>(gdst + (size_t)r * gpitch + cc * 8) = v;
  }
}

constexpr int K1_STAGES = 4;
constexpr int K1_A_BYTES = 256 * 128;
constexpr int K1_B_BYTES = 64 * 160 * 2;
constexpr int K1_STAGE = K1_A_BYTES + K1_B_BYTES;
constexpr int K1_SMEM = K1_STAGES * K1_STAGE + 1024;
constexpr int KVW_OFF = K1_STAGES * K1_A_BYTES;

__global__ void __launch_bounds__(512, 1)
proj_kernel(const __grid_constant__ CUtensorMap tmX, const __grid_constant__ CUtensorMap tmWq, const __grid_constant__ CUtensorMap tmWqkv,
            const __nv_bfloat16* __restrict__ wk, const __nv_bfloat16* __restrict__ wv, const __nv_bfloat16* __restrict__ gate_w) {
  extern __shared__ uint8_t smem_raw[];
  __shared__ __align__(8) uint64_t bar_full[K1_STAGES], bar_empty[K1_STAGES];
  uint8_t* smem = reinterpret_cast<uint8_t*>((reinterpret_cast<uintptr_t>(smem_raw) + 1023) & ~(uintptr_t)1023);
  const uint32_t sbase = smem_u32(smem);
  const int tid = threadIdx.x, warp = tid >> 5, lane = tid & 31;
  const bool is_kv = blockIdx.x >= 128;
  pdl_launch();
  if (tid == 0) {
    for (int i = 0; i < K1_STAGES; i++) { mbar_init(smem_u32(&bar_full[i]), 1); mbar_init(smem_u32(&bar_empty[i]), 16); }
    fence_mbar_init();
  }
  __syncthreads();

  if (!is_kv) {
    const int mb = blockIdx.x >> 4, nb = blockIdx.x & 15;
    const CUtensorMap* tw = nb < 4 ? &tmWq : &tmWqkv;
    const int j0 = (nb < 4 ? nb : nb - 4) * 5;
    auto load = [&](int kt) {
      const int s = kt % K1_STAGES;
      const uint32_t fb = smem_u32(&bar_full[s]);
      mbar_expect_tx(fb, K1_STAGE);
      tma_2d(sbase + s * K1_STAGE, &tmX, kt * 64, mb * 256, fb);
      tma_3d(sbase + s * K1_STAGE + K1_A_BYTES, tw, 0, kt * 64, j0, fb);
    };
    if (tid == 0) for (int kt = 0; kt < K1_STAGES; kt++) load(kt);
    {
      const int wg = warp >> 2;
      float acc[80];
#pragma unroll
      for (int i = 0; i < 80; i++) acc[i] = 0.f;
      for (int kt = 0; kt < 10; kt++) {
        const int s = kt % K1_STAGES;
        mbar_wait(smem_u32(&bar_full[s]), (kt / K1_STAGES) & 1);
        const uint32_t alo = ((sbase + s * K1_STAGE + wg * 8192) >> 4) | (1u << 16);
        const uint32_t blo = ((sbase + s * K1_STAGE + K1_A_BYTES) >> 4) | ((4096u >> 4) << 16);
        fence_regs(acc);
        wg_fence();
#pragma unroll
        for (int k = 0; k < 4; k++) wgmma_ss_n160_tb(acc, mkd(alo + k * 2, DHI_SW128_K), mkd(blo + k * 64, DHI_SW64_MN));
        wg_commit();
        if (kt > 0 && kt - 1 + K1_STAGES < 10) {
          wg_wait<1>();
          const uint32_t eb = smem_u32(&bar_empty[(kt - 1) % K1_STAGES]);
          if (lane == 0) mbar_arrive(eb);
          if (tid == 0) { mbar_wait(eb, ((kt - 1) / K1_STAGES) & 1); load(kt - 1 + K1_STAGES); }
          __syncwarp();
        }
      }
      wg_wait<0>();
      fence_regs(acc);
      asm volatile("bar.sync %0, 128;" :: "r"(wg + 1) : "memory");
      const int w4 = warp & 3;
      const uint32_t off = w4 * K1_STAGE + wg * 8192;
      const int row0 = mb * 256 + wg * 64 + w4 * 16;
      if (nb < 4) {
        store_tile_bf16<160>(acc, 0.22360679774997896f * 1.4426950408889634f, sbase + off, smem + off,
                             g_q + (size_t)row0 * D_MODEL + nb * 160, D_MODEL, lane);
      } else {
        store_tile_bf16<160>(acc, 1.0f, sbase + off, smem + off, g_qkv + (size_t)row0 * (3 * D_MODEL) + (nb - 4) * 160, 3 * D_MODEL, lane);
      }
    }
  } else {
    const int cb = blockIdx.x - 128;
    auto load = [&](int it) {
      const int s = it % K1_STAGES;
      const uint32_t fb = smem_u32(&bar_full[s]);
      mbar_expect_tx(fb, K1_A_BYTES);
      tma_2d(sbase + s * K1_A_BYTES, &tmX, (it % 10) * 64, cb * 512 + (it / 10) * 256, fb);
    };
    if (tid == 0) for (int it = 0; it < K1_STAGES; it++) load(it);
    {
      for (int idx = tid; idx < 640 * 24; idx += 512) {
        const int k = idx / 24, pr = idx % 24, n = pr * 2;
        uint32_t val = 0;
        if (n < 20) val = *reinterpret_cast<const uint32_t*>(wk + k * 20 + n);
        else if (n >= 24 && n < 44) val = *reinterpret_cast<const uint32_t*>(wv + k * 20 + (n - 24));
        else if (n == 44) val = (uint32_t)__bfloat16_as_ushort(gate_w[k]);
        *reinterpret_cast<uint32_t*>(smem + KVW_OFF + (n >> 3) * 10240 + k * 16 + (n & 7) * 2) = val;
      }
      fence_proxy_async();
      asm volatile("bar.sync 1, 512;" ::: "memory");
      const int wg = warp >> 2, w4 = warp & 3, g = lane >> 2, t = lane & 3;
      for (int pass = 0; pass < 2; pass++) {
        float acc[24];
#pragma unroll
        for (int i = 0; i < 24; i++) acc[i] = 0.f;
        for (int kt = 0; kt < 10; kt++) {
          const int it = pass * 10 + kt, s = it % K1_STAGES;
          mbar_wait(smem_u32(&bar_full[s]), (it / K1_STAGES) & 1);
          const uint32_t alo = ((sbase + s * K1_A_BYTES + wg * 8192) >> 4) | (1u << 16);
          const uint32_t blo = ((sbase + KVW_OFF + kt * 1024) >> 4) | ((128u >> 4) << 16);
          fence_regs(acc);
          wg_fence();
#pragma unroll
          for (int k = 0; k < 4; k++) wgmma_ss_n48_tb(acc, mkd(alo + k * 2, DHI_SW128_K), mkd(blo + k * 16, 10240u >> 4));
          wg_commit();
          wg_wait<0>();
          if (it + K1_STAGES < 20) {
            const uint32_t eb = smem_u32(&bar_empty[s]);
            if (lane == 0) mbar_arrive(eb);
            if (tid == 0) { mbar_wait(eb, (it / K1_STAGES) & 1); load(it + K1_STAGES); }
            __syncwarp();
          }
        }
        fence_regs(acc);
        float kmax2 = 0.f, vmax = 0.f;
#pragma unroll
        for (int h = 0; h < 2; h++) {
          const int key = cb * 512 + pass * 256 + wg * 64 + w4 * 16 + g + h * 8;
          const int grp = key >> 7, kk = key & 127;
          const bool poly = (TMASK >> (kk >> 3)) & 1;
          uint8_t* gp = g_kvimg + grp * GRP_BYTES;
          const uint32_t k0 = pack_bf16(acc[2 * h], acc[2 * h + 1]);
          const uint32_t k1 = pack_bf16(acc[4 + 2 * h], acc[5 + 2 * h]);
          uint32_t k2 = pack_bf16(acc[8 + 2 * h], acc[9 + 2 * h]);
          float n2 = bf_lo(k0) * bf_lo(k0) + bf_hi(k0) * bf_hi(k0) + bf_lo(k1) * bf_lo(k1) + bf_hi(k1) * bf_hi(k1);
          if (t < 2) {
            n2 += bf_lo(k2) * bf_lo(k2) + bf_hi(k2) * bf_hi(k2);
            k2 = pack_bf16(bf_lo(k2) * 0.5f, bf_hi(k2) * 0.5f);
          } else if (t == 2) k2 = poly ? pack_bf16(24.f, 2.5f) : pack_bf16(0.5f, 0.f);
          else k2 = poly ? pack_bf16(0.5f, 0.f) : 0u;
          *reinterpret_cast<uint32_t*>(gp + kk * 16 + t * 4) = k0;
          *reinterpret_cast<uint32_t*>(gp + PLANE + kk * 16 + t * 4) = k1;
          *reinterpret_cast<uint32_t*>(gp + 2 * PLANE + kk * 16 + t * 4) = k2;
          n2 += __shfl_xor_sync(0xffffffffu, n2, 1);
          n2 += __shfl_xor_sync(0xffffffffu, n2, 2);
          kmax2 = (n2 > kmax2 || n2 != n2) ? n2 : kmax2;
          uint32_t v0 = pack_bf16(acc[12 + 2 * h], acc[13 + 2 * h]);
          uint32_t v1 = pack_bf16(acc[16 + 2 * h], acc[17 + 2 * h]);
          uint32_t v2 = pack_bf16(acc[20 + 2 * h], acc[21 + 2 * h]);
          float vm = fmaxf(fmaxf(fabsf(bf_lo(v0)), fabsf(bf_hi(v0))), fmaxf(fabsf(bf_lo(v1)), fabsf(bf_hi(v1))));
          if (t < 2) vm = fmaxf(vm, fmaxf(fabsf(bf_lo(v2)), fabsf(bf_hi(v2))));
          else if (t == 2) {
            const float z = acc[20 + 2 * h];
            g_gate[key] = 1.f / (1.f + __expf(-z));
            v2 = 0x00003F80u;
          } else v2 = 0u;
          vmax = fmaxf(vmax, vm);
          if (poly) { v0 ^= 0x80008000u; v1 ^= 0x80008000u; v2 ^= 0x80008000u; }
          uint8_t* vp = gp + 3 * PLANE + (kk >> 3) * 384 + (kk & 7) * 16 + t * 4;
          *reinterpret_cast<uint32_t*>(vp) = v0;
          *reinterpret_cast<uint32_t*>(vp + 128) = v1;
          *reinterpret_cast<uint32_t*>(vp + 256) = v2;
        }
#pragma unroll
        for (int o = 1; o < 32; o <<= 1) {
          const float a = __shfl_xor_sync(0xffffffffu, kmax2, o);
          kmax2 = (a > kmax2 || a != a) ? a : kmax2;
          vmax = fmaxf(vmax, __shfl_xor_sync(0xffffffffu, vmax, o));
        }
        if (lane == 0) { g_kmax2[cb * 32 + pass * 16 + warp] = kmax2; g_vmax[cb * 32 + pass * 16 + warp] = vmax; }
      }
    }
  }
}

__device__ __forceinline__ uint32_t ex2_pair_poly(float u0, float u1, uint32_t one2) {
  const uint32_t W = __byte_perm(__float_as_uint(u0), __float_as_uint(u1), 0x6521);
  uint32_t v; asm("lop3.b32 %0, %1, 0x007F007F, %2, 0xEA;" : "=r"(v) : "r"(W), "r"(one2));
  uint32_t L, p;
  asm("fma.rn.bf16x2 %0, %1, %2, %3;" : "=r"(L) : "r"(v), "r"(0x1f961f96u), "r"(0x9fe39fe3u));
  asm("fma.rn.bf16x2 %0, %1, %1, %2;" : "=r"(p) : "r"(L), "r"(0x00f500f5u));
  return W + p;
}
template <int JOFF>
__device__ __forceinline__ void softmax_fast(const float (&S)[32], uint32_t (&P)[16], uint32_t one2) {
#pragma unroll
  for (int i = 0; i < 16; i++) {
    if ((TMASK >> (JOFF + i / 2)) & 1) P[i] = ex2_pair_poly(S[2 * i], S[2 * i + 1], one2);
    else P[i] = pack_bf16(ex2(S[2 * i]), ex2(S[2 * i + 1]));
  }
}
template <int JOFF>
__device__ __forceinline__ void softmax_slow(const float (&S)[32], uint32_t (&P)[16], float (&O)[12], float& m0, float& m1) {
  float a0 = m0, a1 = m1;
#pragma unroll
  for (int j = 0; j < 8; j++) {
    a0 = fmaxf(a0, fmaxf(S[4 * j], S[4 * j + 1]));
    a1 = fmaxf(a1, fmaxf(S[4 * j + 2], S[4 * j + 3]));
  }
  a0 = fmaxf(a0, __shfl_xor_sync(0xffffffffu, a0, 1)); a0 = fmaxf(a0, __shfl_xor_sync(0xffffffffu, a0, 2));
  a1 = fmaxf(a1, __shfl_xor_sync(0xffffffffu, a1, 1)); a1 = fmaxf(a1, __shfl_xor_sync(0xffffffffu, a1, 2));
  const float c0 = ex2(m0 - a0), c1 = ex2(m1 - a1);
  m0 = a0; m1 = a1;
#pragma unroll
  for (int j = 0; j < 3; j++) { O[4 * j] *= c0; O[4 * j + 1] *= c0; O[4 * j + 2] *= c1; O[4 * j + 3] *= c1; }
#pragma unroll
  for (int i = 0; i < 16; i++) {
    const float m = (i & 1) ? a1 : a0;
    const uint32_t p = pack_bf16(ex2(S[2 * i] - m), ex2(S[2 * i + 1] - m));
    P[i] = ((TMASK >> (JOFF + i / 2)) & 1) ? (p ^ 0x80008000u) : p;
  }
}
constexpr uint32_t DHI_KV = 128 >> 4;
__device__ __forceinline__ void issue_qk(float (&S)[32], const uint32_t (&q)[6], uint32_t base) {
  wgmma_rs_n64<0>(S, q[0], q[1], q[2], q[3], mkd(base + ((PLANE >> 4) << 16), DHI_KV));
  wgmma_rs_n64<1>(S, q[4], q[5], q[4], q[5], mkd(base + (2 * PLANE >> 4), DHI_KV));
}
__device__ __forceinline__ void issue_pv(float (&O)[12], const uint32_t (&P)[16], uint32_t vbase) {
#pragma unroll
  for (int kk = 0; kk < 4; kk++)
    wgmma_rs_n24_tb<1>(O, P[4 * kk], P[4 * kk + 1], P[4 * kk + 2], P[4 * kk + 3], mkd(vbase + kk * (768 >> 4), DHI_KV));
}

template <bool FAST>
__device__ __forceinline__ void attn_tile(const uint32_t (&q)[6], float (&O)[12], uint32_t sbase, uint32_t bars, bool first, uint32_t one2) {
  float S[32]; uint32_t P[16];
  float m0 = -INFINITY, m1 = -INFINITY;
#pragma unroll
  for (int i = 0; i < 32; i++) S[i] = 0.f;
  uint32_t kb = sbase >> 4;
  const uint32_t klast = kb + (NGRP - 1) * (GRP_BYTES >> 4);
  constexpr uint32_t VOFF = ((3 * PLANE) >> 4) + ((384u >> 4) << 16);
  if (first) mbar_wait(bars, 0);
  fence_regs(S); fence_regs(O);
  wg_fence();
  issue_qk(S, q, kb);
  wg_commit();
#pragma unroll 1
  for (int grp = 0; grp < NGRP; grp++) {
    if (first) mbar_wait(bars + 8 * min(grp + 1, NGRP - 1), 0);
    const uint32_t knext = min(kb + (GRP_BYTES >> 4), klast);
    wg_wait<0>();
    fence_regs(S); fence_regs(P); fence_regs(O);
    if (FAST) softmax_fast<0>(S, P, one2); else softmax_slow<0>(S, P, O, m0, m1);
    fence_regs(S); fence_regs(P); fence_regs(O);
    wg_fence();
    issue_qk(S, q, kb + 64);
    issue_pv(O, P, kb + VOFF);
    wg_commit();
    wg_wait<0>();
    fence_regs(S); fence_regs(P); fence_regs(O);
    if (FAST) softmax_fast<8>(S, P, one2); else softmax_slow<8>(S, P, O, m0, m1);
    fence_regs(S); fence_regs(P); fence_regs(O);
    wg_fence();
    issue_qk(S, q, knext);
    issue_pv(O, P, kb + VOFF + 4 * (768 >> 4));
    wg_commit();
    kb = knext;
  }
  wg_wait<0>();
  fence_regs(O); fence_regs(S);
}

constexpr int K2_SMEM = NGRP * GRP_BYTES + 1024;

__global__ void __launch_bounds__(512, 1)
attn_kernel(uint32_t one2) {
  extern __shared__ uint8_t smem_raw[];
  __shared__ __align__(8) uint64_t bars[NGRP];
  uint8_t* smem = reinterpret_cast<uint8_t*>((reinterpret_cast<uintptr_t>(smem_raw) + 1023) & ~(uintptr_t)1023);
  const uint32_t sbase = smem_u32(smem);
  const int tid = threadIdx.x, wg = tid >> 7, warp = (tid >> 5) & 3, lane = tid & 31, g = lane >> 2, t = lane & 3;
  pdl_launch();
  if (tid == 0) {
    for (int i = 0; i < NGRP; i++) mbar_init(smem_u32(&bars[i]), 1);
    fence_mbar_init();
  }
  __syncthreads();
  pdl_wait();
  if (tid == 0) {
    for (int i = 0; i < NGRP; i++) {
      mbar_expect_tx(smem_u32(&bars[i]), GRP_BYTES);
      bulk_g2s(sbase + i * GRP_BYTES, g_kvimg + i * GRP_BYTES, GRP_BYTES, smem_u32(&bars[i]));
    }
  }
  {
    const int token = blockIdx.x * 16 + (tid >> 5);
    const __nv_bfloat16* base = g_qkv + (size_t)token * (3 * D_MODEL) + lane * DH;
    float qf[20];
    {
      const uint2* p = reinterpret_cast<const uint2*>(base);
#pragma unroll
      for (int i = 0; i < 5; i++) { const uint2 v = p[i]; qf[4 * i] = bf_lo(v.x); qf[4 * i + 1] = bf_hi(v.x); qf[4 * i + 2] = bf_lo(v.y); qf[4 * i + 3] = bf_hi(v.y); }
    }
    float sc[8];
    float mx = -INFINITY;
#pragma unroll
    for (int w = 0; w < 8; w++) {
      const bool ok = token - 2 * w >= 0;
      const uint2* p = reinterpret_cast<const uint2*>(base + D_MODEL - (ok ? (size_t)(2 * w) * (3 * D_MODEL) : 0));
      float s = 0.f;
#pragma unroll
      for (int i = 0; i < 5; i++) {
        const uint2 v = p[i];
        s = fmaf(qf[4 * i], bf_lo(v.x), s); s = fmaf(qf[4 * i + 1], bf_hi(v.x), s);
        s = fmaf(qf[4 * i + 2], bf_lo(v.y), s); s = fmaf(qf[4 * i + 3], bf_hi(v.y), s);
      }
      s *= 0.22360679774997896f * 1.4426950408889634f;
      sc[w] = ok ? s : -1e9f * 1.4426950408889634f;
      mx = fmaxf(mx, sc[w]);
    }
    float l = 0.f;
#pragma unroll
    for (int w = 0; w < 8; w++) { sc[w] = ex2(sc[w] - mx); l += sc[w]; }
    float o[20];
#pragma unroll
    for (int i = 0; i < 20; i++) o[i] = 0.f;
#pragma unroll
    for (int w = 0; w < 8; w++) {
      const bool ok = token - 2 * w >= 0;
      const uint2* p = reinterpret_cast<const uint2*>(base + 2 * D_MODEL - (ok ? (size_t)(2 * w) * (3 * D_MODEL) : (size_t)token * (3 * D_MODEL)));
#pragma unroll
      for (int i = 0; i < 5; i++) {
        const uint2 v = p[i];
        o[4 * i] = fmaf(sc[w], bf_lo(v.x), o[4 * i]); o[4 * i + 1] = fmaf(sc[w], bf_hi(v.x), o[4 * i + 1]);
        o[4 * i + 2] = fmaf(sc[w], bf_lo(v.y), o[4 * i + 2]); o[4 * i + 3] = fmaf(sc[w], bf_hi(v.y), o[4 * i + 3]);
      }
    }
    const float f = (1.f - g_gate[token]) / l;
    uint2* dst = reinterpret_cast<uint2*>(g_a2 + (size_t)token * (2 * D_MODEL) + D_MODEL + lane * DH);
#pragma unroll
    for (int i = 0; i < 5; i++) dst[i] = make_uint2(pack_bf16(o[4 * i] * f, o[4 * i + 1] * f), pack_bf16(o[4 * i + 2] * f, o[4 * i + 3] * f));
  }
  float kmax2 = 0.f, vmax = 0.f;
#pragma unroll
  for (int i = 0; i < 4; i++) {
    const float a = g_kmax2[lane + 32 * i];
    kmax2 = (a > kmax2 || a != a) ? a : kmax2;
    vmax = fmaxf(vmax, g_vmax[lane + 32 * i]);
  }
#pragma unroll
  for (int o = 1; o < 32; o <<= 1) {
    const float a = __shfl_xor_sync(0xffffffffu, kmax2, o);
    kmax2 = (a > kmax2 || a != a) ? a : kmax2;
    vmax = fmaxf(vmax, __shfl_xor_sync(0xffffffffu, vmax, o));
  }
  const bool v_ok = vmax >= 0.00390625f && vmax <= 256.f;

#pragma unroll 1
  for (int it = 0; it < 2; it++) {
    const int row0 = (blockIdx.x * 8 + it * 4 + wg) * 64 + warp * 16 + g;
    uint32_t q[6];
    {
      const uint32_t* r0 = reinterpret_cast<const uint32_t*>(g_q + (size_t)row0 * DH);
      const uint32_t* r1 = reinterpret_cast<const uint32_t*>(g_q + (size_t)(row0 + 8) * DH);
      q[0] = r0[t]; q[1] = r1[t]; q[2] = r0[t + 4]; q[3] = r1[t + 4];
      q[4] = t < 2 ? r0[8 + t] : 0u;
      q[5] = t < 2 ? r1[8 + t] : 0u;
    }
    float n0 = bf_lo(q[0]) * bf_lo(q[0]) + bf_hi(q[0]) * bf_hi(q[0]) + bf_lo(q[2]) * bf_lo(q[2]) + bf_hi(q[2]) * bf_hi(q[2]) +
               bf_lo(q[4]) * bf_lo(q[4]) + bf_hi(q[4]) * bf_hi(q[4]);
    float n1 = bf_lo(q[1]) * bf_lo(q[1]) + bf_hi(q[1]) * bf_hi(q[1]) + bf_lo(q[3]) * bf_lo(q[3]) + bf_hi(q[3]) * bf_hi(q[3]) +
               bf_lo(q[5]) * bf_lo(q[5]) + bf_hi(q[5]) * bf_hi(q[5]);
    n0 += __shfl_xor_sync(0xffffffffu, n0, 1); n0 += __shfl_xor_sync(0xffffffffu, n0, 2);
    n1 += __shfl_xor_sync(0xffffffffu, n1, 1); n1 += __shfl_xor_sync(0xffffffffu, n1, 2);
    const bool safe = v_ok && (n0 * kmax2 <= 9025.f) && (n1 * kmax2 <= 9025.f);
    uint32_t unsafe_any;
    asm volatile("{\n.reg .pred p, r;\nsetp.eq.u32 p, %1, 0;\nbarrier.cta.red.or.pred r, %2, 128, p;\nselp.u32 %0, 1, 0, r;\n}\n"
                 : "=r"(unsafe_any) : "r"((uint32_t)safe), "r"(wg + 1) : "memory");
    float O[12];
#pragma unroll
    for (int i = 0; i < 12; i++) O[i] = 0.f;
    if (!unsafe_any) {
      if (t >= 2) { q[4] = q[5] = (t == 2) ? 0x3F804100u : 0x00003B80u; }
      attn_tile<true>(q, O, sbase, smem_u32(&bars[0]), it == 0, one2);
    } else {
      attn_tile<false>(q, O, sbase, smem_u32(&bars[0]), it == 0, one2);
    }
    const float l0 = __shfl_sync(0xffffffffu, O[8], (lane & ~3) | 2);
    const float l1 = __shfl_sync(0xffffffffu, O[10], (lane & ~3) | 2);
    const int tok = row0 >> 5;
    const float gt = g_gate[tok];
    const float i0 = gt / l0, i1 = gt / l1;
    uint32_t* o0 = reinterpret_cast<uint32_t*>(g_a2 + (size_t)tok * (2 * D_MODEL) + (row0 & 31) * DH);
    uint32_t* o1 = o0 + 8 * (DH / 2);
    o0[t] = pack_bf16(O[0] * i0, O[1] * i0); o1[t] = pack_bf16(O[2] * i1, O[3] * i1);
    o0[t + 4] = pack_bf16(O[4] * i0, O[5] * i0); o1[t + 4] = pack_bf16(O[6] * i1, O[7] * i1);
    if (t < 2) { o0[t + 8] = pack_bf16(O[8] * i0, O[9] * i0); o1[t + 8] = pack_bf16(O[10] * i1, O[11] * i1); }
  }
}

constexpr int K3_STAGES = 8;
constexpr int K3_A_BYTES = 128 * 128;
constexpr int K3_B_BYTES = 64 * 80 * 2;
constexpr int K3_STAGE = K3_A_BYTES + K3_B_BYTES;
constexpr int K3_SMEM = K3_STAGES * K3_STAGE + 1024;

__global__ void __launch_bounds__(288, 1)
out_kernel(const __grid_constant__ CUtensorMap tmA2, const __grid_constant__ CUtensorMap tmWoA, const __grid_constant__ CUtensorMap tmWoB,
           __nv_bfloat16* __restrict__ out) {
  extern __shared__ uint8_t smem_raw[];
  __shared__ __align__(8) uint64_t bar_full[K3_STAGES], bar_empty[K3_STAGES];
  uint8_t* smem = reinterpret_cast<uint8_t*>((reinterpret_cast<uintptr_t>(smem_raw) + 1023) & ~(uintptr_t)1023);
  const uint32_t sbase = smem_u32(smem);
  const int tid = threadIdx.x, warp = tid >> 5, lane = tid & 31;
  const int mb = blockIdx.x >> 3, nb = blockIdx.x & 7;
  if (tid == 0) {
    for (int i = 0; i < K3_STAGES; i++) { mbar_init(smem_u32(&bar_full[i]), 2); mbar_init(smem_u32(&bar_empty[i]), 8); }
    fence_mbar_init();
  }
  __syncthreads();
  if (warp == 8) {
    if (lane == 0) {
      for (int kt = 0; kt < K3_STAGES; kt++) {
        const uint32_t fb = smem_u32(&bar_full[kt]);
        mbar_expect_tx(fb, K3_B_BYTES);
        tma_3d(sbase + kt * K3_STAGE + K3_A_BYTES, &tmWoA, 0, kt * 64, nb * 5, fb);
      }
      pdl_wait();
      for (int kt = 0; kt < 20; kt++) {
        const int s = kt % K3_STAGES;
        const uint32_t fb = smem_u32(&bar_full[s]);
        if (kt >= K3_STAGES) {
          mbar_wait(smem_u32(&bar_empty[s]), ((kt / K3_STAGES) - 1) & 1);
          mbar_expect_tx(fb, K3_B_BYTES);
          tma_3d(sbase + s * K3_STAGE + K3_A_BYTES, kt < 10 ? &tmWoA : &tmWoB, 0, (kt % 10) * 64, nb * 5, fb);
        }
        mbar_expect_tx(fb, K3_A_BYTES);
        tma_2d(sbase + s * K3_STAGE, &tmA2, kt * 64, mb * 128, fb);
      }
    }
  } else {
    const int wg = warp >> 2;
    float acc[40];
#pragma unroll
    for (int i = 0; i < 40; i++) acc[i] = 0.f;
    for (int kt = 0; kt < 20; kt++) {
      const int s = kt % K3_STAGES;
      mbar_wait(smem_u32(&bar_full[s]), (kt / K3_STAGES) & 1);
      const uint32_t alo = ((sbase + s * K3_STAGE + wg * 8192) >> 4) | (1u << 16);
      const uint32_t blo = ((sbase + s * K3_STAGE + K3_A_BYTES) >> 4) | ((2048u >> 4) << 16);
      fence_regs(acc);
      wg_fence();
#pragma unroll
      for (int k = 0; k < 4; k++) wgmma_ss_n80_tb(acc, mkd(alo + k * 2, DHI_SW128_K), mkd(blo + k * 32, DHI_SW32_MN));
      wg_commit();
      if (kt > 0) {
        wg_wait<1>();
        if (lane == 0) mbar_arrive(smem_u32(&bar_empty[(kt - 1) % K3_STAGES]));
      }
    }
    wg_wait<0>();
    fence_regs(acc);
    asm volatile("bar.sync %0, 128;" :: "r"(wg + 1) : "memory");
    const int w4 = warp & 3;
    const uint32_t off = w4 * K3_STAGE + wg * 8192;
    const int row0 = mb * 128 + wg * 64 + w4 * 16;
    store_tile_bf16<80>(acc, 1.0f, sbase + off, smem + off, out + (size_t)row0 * D_MODEL + nb * 80, D_MODEL, lane);
  }
}

typedef CUresult (*EncodeFn)(CUtensorMap*, CUtensorMapDataType, cuuint32_t, void*, const cuuint64_t*, const cuuint64_t*,
                             const cuuint32_t*, const cuuint32_t*, CUtensorMapInterleave, CUtensorMapSwizzle,
                             CUtensorMapL2promotion, CUtensorMapFloatOOBfill);

void make_map(EncodeFn fn, CUtensorMap* tm, const void* ptr, int rank, const cuuint64_t* dims, const cuuint64_t* strides,
              const cuuint32_t* box, CUtensorMapSwizzle sw) {
  const cuuint32_t es[3] = {1, 1, 1};
  fn(tm, CU_TENSOR_MAP_DATA_TYPE_BFLOAT16, rank, const_cast<void*>(ptr), dims, strides, box, es, CU_TENSOR_MAP_INTERLEAVE_NONE, sw,
     CU_TENSOR_MAP_L2_PROMOTION_L2_256B, CU_TENSOR_MAP_FLOAT_OOB_FILL_NONE);
}
void map_a(EncodeFn fn, CUtensorMap* tm, const void* p, int rows, int cols, int box_rows) {
  const cuuint64_t dims[2] = {(cuuint64_t)cols, (cuuint64_t)rows};
  const cuuint64_t str[1] = {(cuuint64_t)cols * 2};
  const cuuint32_t box[2] = {64, (cuuint32_t)box_rows};
  make_map(fn, tm, p, 2, dims, str, box, CU_TENSOR_MAP_SWIZZLE_128B);
}
void map_w(EncodeFn fn, CUtensorMap* tm, const void* p, int K, int N, int atom, CUtensorMapSwizzle sw) {
  const cuuint64_t dims[3] = {(cuuint64_t)atom, (cuuint64_t)K, (cuuint64_t)(N / atom)};
  const cuuint64_t str[2] = {(cuuint64_t)N * 2, (cuuint64_t)atom * 2};
  const cuuint32_t box[3] = {(cuuint32_t)atom, 64, 5};
  make_map(fn, tm, p, 3, dims, str, box, sw);
}

template <typename... KArgs, typename... Args>
void launch(void (*kern)(KArgs...), int grid, int block, int smem, bool pdl, Args... args) {
  cudaLaunchConfig_t cfg = {};
  cfg.gridDim = dim3(grid); cfg.blockDim = dim3(block); cfg.dynamicSmemBytes = smem; cfg.stream = cudaStreamPerThread;
  cudaLaunchAttribute at[1];
  at[0].id = cudaLaunchAttributeProgrammaticStreamSerialization;
  at[0].val.programmaticStreamSerializationAllowed = 1;
  cfg.attrs = at; cfg.numAttrs = pdl ? 1 : 0;
  cudaLaunchKernelEx(&cfg, kern, KArgs(args)...);
}

}

extern "C" void kernel_launch(void* const* d_in, const int* in_sizes, int n_in, void* d_out, int out_size) {
  (void)in_sizes; (void)n_in; (void)out_size;
  const __nv_bfloat16* x = (const __nv_bfloat16*)d_in[0];
  const __nv_bfloat16* wq = (const __nv_bfloat16*)d_in[1];
  const __nv_bfloat16* wk = (const __nv_bfloat16*)d_in[2];
  const __nv_bfloat16* wv = (const __nv_bfloat16*)d_in[3];
  const __nv_bfloat16* woA = (const __nv_bfloat16*)d_in[4];
  const __nv_bfloat16* wqkv = (const __nv_bfloat16*)d_in[6];
  const __nv_bfloat16* woB = (const __nv_bfloat16*)d_in[7];
  const __nv_bfloat16* gate_w = (const __nv_bfloat16*)d_in[8];

  static EncodeFn enc = nullptr;
  static void* a2_ptr = nullptr;
  if (!enc) {
    void* fp = nullptr;
    cudaDriverEntryPointQueryResult qr;
    cudaGetDriverEntryPoint("cuTensorMapEncodeTiled", &fp, cudaEnableDefault, &qr);
    enc = (EncodeFn)fp;
    cudaGetSymbolAddress(&a2_ptr, g_a2);
    cudaFuncSetAttribute(proj_kernel, cudaFuncAttributeMaxDynamicSharedMemorySize, K1_SMEM);
    cudaFuncSetAttribute(attn_kernel, cudaFuncAttributeMaxDynamicSharedMemorySize, K2_SMEM);
    cudaFuncSetAttribute(out_kernel, cudaFuncAttributeMaxDynamicSharedMemorySize, K3_SMEM);
  }
  CUtensorMap tmX, tmWq, tmWqkv, tmA2, tmWoA, tmWoB;
  map_a(enc, &tmX, x, S_LEN, D_MODEL, 256);
  map_w(enc, &tmWq, wq, D_MODEL, D_MODEL, 32, CU_TENSOR_MAP_SWIZZLE_64B);
  map_w(enc, &tmWqkv, wqkv, D_MODEL, 3 * D_MODEL, 32, CU_TENSOR_MAP_SWIZZLE_64B);
  map_a(enc, &tmA2, a2_ptr, S_LEN, 2 * D_MODEL, 128);
  map_w(enc, &tmWoA, woA, D_MODEL, D_MODEL, 16, CU_TENSOR_MAP_SWIZZLE_32B);
  map_w(enc, &tmWoB, woB, D_MODEL, D_MODEL, 16, CU_TENSOR_MAP_SWIZZLE_32B);

  launch(proj_kernel, 132, 512, K1_SMEM, false, tmX, tmWq, tmWqkv, wk, wv, gate_w);
  launch(attn_kernel, 128, 512, K2_SMEM, true, 0x3F803F80u);
  launch(out_kernel, 128, 288, K3_SMEM, true, tmA2, tmWoA, tmWoB, (__nv_bfloat16*)d_out);
}
```

```cpp
#include <cuda_runtime.h>
#include <cuda_bf16.h>
#include <cuda.h>
#include <stdint.h>

namespace {

constexpr int S_LEN = 2048, D_MODEL = 640, DH = 20;

constexpr int GRP = 128;
constexpr int PLANE = GRP * 16;
constexpr int GRP_BYTES = GRP * 16 * 6;
constexpr int NGRP = S_LEN / GRP;
constexpr uint32_t TMASK = 0x6DB6u;

__device__ __align__(1024) __nv_bfloat16 g_q[S_LEN * D_MODEL];
__device__ __align__(1024) __nv_bfloat16 g_qkv[S_LEN * 3 * D_MODEL];
__device__ __align__(1024) __nv_bfloat16 g_a2[S_LEN * 2 * D_MODEL];
__device__ __align__(1024) uint8_t g_kvimg[NGRP * GRP_BYTES];
__device__ float g_gate[S_LEN];
__device__ float g_kmax2[128];
__device__ float g_vmax[128];

#define PROF(k, slot)
__device__ __forceinline__ uint32_t smem_u32(const void* p) { return (uint32_t)__cvta_generic_to_shared(p); }
__device__ __forceinline__ uint64_t mkd(uint32_t lo, uint32_t hi) {
  uint64_t d; asm("mov.b64 %0, {%1, %2};" : "=l"(d) : "r"(lo), "r"(hi)); return d;
}
__device__ __forceinline__ void wg_fence() { asm volatile("wgmma.fence.sync.aligned;" ::: "memory"); }
__device__ __forceinline__ void wg_commit() { asm volatile("wgmma.commit_group.sync.aligned;" ::: "memory"); }
template <int N> __device__ __forceinline__ void wg_wait() { asm volatile("wgmma.wait_group.sync.aligned %0;" :: "n"(N) : "memory"); }
template <int N> __device__ __forceinline__ void fence_regs(float (&d)[N]) {
#pragma unroll
  for (int i = 0; i < N; i++) asm volatile("" : "+f"(d[i]) :: "memory");
}
template <int N> __device__ __forceinline__ void fence_regs(uint32_t (&d)[N]) {
#pragma unroll
  for (int i = 0; i < N; i++) asm volatile("" : "+r"(d[i]) :: "memory");
}
__device__ __forceinline__ void mbar_init(uint32_t bar, uint32_t cnt) { asm volatile("mbarrier.init.shared::cta.b64 [%0], %1;" :: "r"(bar), "r"(cnt)); }
__device__ __forceinline__ void mbar_expect_tx(uint32_t bar, uint32_t bytes) {
  asm volatile("mbarrier.arrive.expect_tx.shared::cta.b64 _, [%0], %1;" :: "r"(bar), "r"(bytes) : "memory");
}
__device__ __forceinline__ void mbar_arrive(uint32_t bar) { asm volatile("mbarrier.arrive.shared::cta.b64 _, [%0];" :: "r"(bar) : "memory"); }
__device__ __forceinline__ void mbar_wait(uint32_t bar, uint32_t parity) {
  asm volatile("{\n.reg .pred p;\nWAIT_%=:\nmbarrier.try_wait.parity.shared::cta.b64 p, [%0], %1;\n@p bra DONE_%=;\nbra WAIT_%=;\nDONE_%=:\n}\n"
               :: "r"(bar), "r"(parity) : "memory");
}
__device__ __forceinline__ void fence_mbar_init() { asm volatile("fence.mbarrier_init.release.cluster;" ::: "memory"); }
__device__ __forceinline__ void fence_proxy_async() { asm volatile("fence.proxy.async.shared::cta;" ::: "memory"); }
__device__ __forceinline__ void bulk_g2s(uint32_t dst, const void* src, uint32_t bytes, uint32_t bar) {
  asm volatile("cp.async.bulk.shared::cluster.global.mbarrier::complete_tx::bytes [%0], [%1], %2, [%3];"
               :: "r"(dst), "l"(src), "r"(bytes), "r"(bar) : "memory");
}
__device__ __forceinline__ void tma_2d(uint32_t dst, const CUtensorMap* tm, int c0, int c1, uint32_t bar) {
  asm volatile("cp.async.bulk.tensor.2d.shared::cluster.global.mbarrier::complete_tx::bytes [%0], [%1, {%3, %4}], [%2];"
               :: "r"(dst), "l"((uint64_t)tm), "r"(bar), "r"(c0), "r"(c1) : "memory");
}
__device__ __forceinline__ void tma_3d(uint32_t dst, const CUtensorMap* tm, int c0, int c1, int c2, uint32_t bar) {
  asm volatile("cp.async.bulk.tensor.3d.shared::cluster.global.mbarrier::complete_tx::bytes [%0], [%1, {%3, %4, %5}], [%2];"
               :: "r"(dst), "l"((uint64_t)tm), "r"(bar), "r"(c0), "r"(c1), "r"(c2) : "memory");
}
__device__ __forceinline__ void prefetch_tmap(const CUtensorMap* tm) { asm volatile("prefetch.tensormap [%0];" :: "l"((uint64_t)tm) : "memory"); }
__device__ __forceinline__ void pdl_wait() { asm volatile("griddepcontrol.wait;" ::: "memory"); }
__device__ __forceinline__ void pdl_launch() { asm volatile("griddepcontrol.launch_dependents;" ::: "memory"); }
__device__ __forceinline__ float ex2(float x) { float y; asm("ex2.approx.ftz.f32 %0, %1;" : "=f"(y) : "f"(x)); return y; }
__device__ __forceinline__ uint32_t pack_bf16(float lo, float hi) {
  uint32_t r; asm("cvt.rn.bf16x2.f32 %0, %1, %2;" : "=r"(r) : "f"(hi), "f"(lo)); return r;
}
__device__ __forceinline__ float bf_lo(uint32_t x) { return __uint_as_float(x << 16); }
__device__ __forceinline__ float bf_hi(uint32_t x) { return __uint_as_float(x & 0xffff0000u); }
__device__ __forceinline__ void stsm4(uint32_t addr, uint32_t r0, uint32_t r1, uint32_t r2, uint32_t r3) {
  asm volatile("stmatrix.sync.aligned.m8n8.x4.shared.b16 [%0], {%1, %2, %3, %4};" :: "r"(addr), "r"(r0), "r"(r1), "r"(r2), "r"(r3) : "memory");
}

__device__ __forceinline__ void wgmma_ss_n160_tb(float (&d)[80], uint64_t descA, uint64_t descB) {
  asm volatile("wgmma.mma_async.sync.aligned.m64n160k16.f32.bf16.bf16 {%0, %1, %2, %3, %4, %5, %6, %7, %8, %9, %10, %11, %12, %13, %14, %15, %16, %17, %18, %19, %20, %21, %22, %23, %24, %25, %26, %27, %28, %29, %30, %31, %32, %33, %34, %35, %36, %37, %38, %39, %40, %41, %42, %43, %44, %45, %46, %47, %48, %49, %50, %51, %52, %53, %54, %55, %56, %57, %58, %59, %60, %61, %62, %63, %64, %65, %66, %67, %68, %69, %70, %71, %72, %73, %74, %75, %76, %77, %78, %79}, %80, %81, 1, 1, 1, 0, 1;\n"
    : "+f"(d[0]), "+f"(d[1]), "+f"(d[2]), "+f"(d[3]), "+f"(d[4]), "+f"(d[5]), "+f"(d[6]), "+f"(d[7]), "+f"(d[8]), "+f"(d[9]), "+f"(d[10]), "+f"(d[11]), "+f"(d[12]), "+f"(d[13]), "+f"(d[14]), "+f"(d[15]), "+f"(d[16]), "+f"(d[17]), "+f"(d[18]), "+f"(d[19]), "+f"(d[20]), "+f"(d[21]), "+f"(d[22]), "+f"(d[23]), "+f"(d[24]), "+f"(d[25]), "+f"(d[26]), "+f"(d[27]), "+f"(d[28]), "+f"(d[29]), "+f"(d[30]), "+f"(d[31]), "+f"(d[32]), "+f"(d[33]), "+f"(d[34]), "+f"(d[35]), "+f"(d[36]), "+f"(d[37]), "+f"(d[38]), "+f"(d[39]), "+f"(d[40]), "+f"(d[41]), "+f"(d[42]), "+f"(d[43]), "+f"(d[44]), "+f"(d[45]), "+f"(d[46]), "+f"(d[47]), "+f"(d[48]), "+f"(d[49]), "+f"(d[50]), "+f"(d[51]), "+f"(d[52]), "+f"(d[53]), "+f"(d[54]), "+f"(d[55]), "+f"(d[56]), "+f"(d[57]), "+f"(d[58]), "+f"(d[59]), "+f"(d[60]), "+f"(d[61]), "+f"(d[62]), "+f"(d[63]), "+f"(d[64]), "+f"(d[65]), "+f"(d[66]), "+f"(d[67]), "+f"(d[68]), "+f"(d[69]), "+f"(d[70]), "+f"(d[71]), "+f"(d[72]), "+f"(d[73]), "+f"(d[74]), "+f"(d[75]), "+f"(d[76]), "+f"(d[77]), "+f"(d[78]), "+f"(d[79])
    : "l"(descA), "l"(descB));
}
__device__ __forceinline__ void wgmma_ss_n48_tb(float (&d)[24], uint64_t descA, uint64_t descB) {
  asm volatile("wgmma.mma_async.sync.aligned.m64n48k16.f32.bf16.bf16 {%0, %1, %2, %3, %4, %5, %6, %7, %8, %9, %10, %11, %12, %13, %14, %15, %16, %17, %18, %19, %20, %21, %22, %23}, %24, %25, 1, 1, 1, 0, 1;\n"
    : "+f"(d[0]), "+f"(d[1]), "+f"(d[2]), "+f"(d[3]), "+f"(d[4]), "+f"(d[5]), "+f"(d[6]), "+f"(d[7]), "+f"(d[8]), "+f"(d[9]), "+f"(d[10]), "+f"(d[11]), "+f"(d[12]), "+f"(d[13]), "+f"(d[14]), "+f"(d[15]), "+f"(d[16]), "+f"(d[17]), "+f"(d[18]), "+f"(d[19]), "+f"(d[20]), "+f"(d[21]), "+f"(d[22]), "+f"(d[23])
    : "l"(descA), "l"(descB));
}
__device__ __forceinline__ void wgmma_ss_n80_tb(float (&d)[40], uint64_t descA, uint64_t descB) {
  asm volatile("wgmma.mma_async.sync.aligned.m64n80k16.f32.bf16.bf16 {%0, %1, %2, %3, %4, %5, %6, %7, %8, %9, %10, %11, %12, %13, %14, %15, %16, %17, %18, %19, %20, %21, %22, %23, %24, %25, %26, %27, %28, %29, %30, %31, %32, %33, %34, %35, %36, %37, %38, %39}, %40, %41, 1, 1, 1, 0, 1;\n"
    : "+f"(d[0]), "+f"(d[1]), "+f"(d[2]), "+f"(d[3]), "+f"(d[4]), "+f"(d[5]), "+f"(d[6]), "+f"(d[7]), "+f"(d[8]), "+f"(d[9]), "+f"(d[10]), "+f"(d[11]), "+f"(d[12]), "+f"(d[13]), "+f"(d[14]), "+f"(d[15]), "+f"(d[16]), "+f"(d[17]), "+f"(d[18]), "+f"(d[19]), "+f"(d[20]), "+f"(d[21]), "+f"(d[22]), "+f"(d[23]), "+f"(d[24]), "+f"(d[25]), "+f"(d[26]), "+f"(d[27]), "+f"(d[28]), "+f"(d[29]), "+f"(d[30]), "+f"(d[31]), "+f"(d[32]), "+f"(d[33]), "+f"(d[34]), "+f"(d[35]), "+f"(d[36]), "+f"(d[37]), "+f"(d[38]), "+f"(d[39])
    : "l"(descA), "l"(descB));
}
template <int SCALE_D>
__device__ __forceinline__ void wgmma_rs_n64(float (&d)[32], uint32_t a0, uint32_t a1, uint32_t a2, uint32_t a3, uint64_t descB) {
  asm volatile("wgmma.mma_async.sync.aligned.m64n64k16.f32.bf16.bf16 {%0, %1, %2, %3, %4, %5, %6, %7, %8, %9, %10, %11, %12, %13, %14, %15, %16, %17, %18, %19, %20, %21, %22, %23, %24, %25, %26, %27, %28, %29, %30, %31}, {%32, %33, %34, %35}, %36, %37, 1, 1, 0;\n"
    : "+f"(d[0]), "+f"(d[1]), "+f"(d[2]), "+f"(d[3]), "+f"(d[4]), "+f"(d[5]), "+f"(d[6]), "+f"(d[7]), "+f"(d[8]), "+f"(d[9]), "+f"(d[10]), "+f"(d[11]), "+f"(d[12]), "+f"(d[13]), "+f"(d[14]), "+f"(d[15]), "+f"(d[16]), "+f"(d[17]), "+f"(d[18]), "+f"(d[19]), "+f"(d[20]), "+f"(d[21]), "+f"(d[22]), "+f"(d[23]), "+f"(d[24]), "+f"(d[25]), "+f"(d[26]), "+f"(d[27]), "+f"(d[28]), "+f"(d[29]), "+f"(d[30]), "+f"(d[31])
    : "r"(a0), "r"(a1), "r"(a2), "r"(a3), "l"(descB), "n"(SCALE_D));
}
template <int SCALE_D>
__device__ __forceinline__ void wgmma_rs_n24_tb(float (&d)[12], uint32_t a0, uint32_t a1, uint32_t a2, uint32_t a3, uint64_t descB) {
  asm volatile("wgmma.mma_async.sync.aligned.m64n24k16.f32.bf16.bf16 {%0, %1, %2, %3, %4, %5, %6, %7, %8, %9, %10, %11}, {%12, %13, %14, %15}, %16, %17, 1, 1, 1;\n"
    : "+f"(d[0]), "+f"(d[1]), "+f"(d[2]), "+f"(d[3]), "+f"(d[4]), "+f"(d[5]), "+f"(d[6]), "+f"(d[7]), "+f"(d[8]), "+f"(d[9]), "+f"(d[10]), "+f"(d[11])
    : "r"(a0), "r"(a1), "r"(a2), "r"(a3), "l"(descB), "n"(SCALE_D));
}

constexpr uint32_t DHI_SW128_K = (1024 >> 4) | (1u << 30);
constexpr uint32_t DHI_SW64_MN = (512 >> 4) | (2u << 30);
constexpr uint32_t DHI_SW32_MN = (256 >> 4) | (3u << 30);

template <int NC>
__device__ __forceinline__ void store_tile_bf16(const float (&acc)[NC / 2], float scale, uint32_t stage, uint8_t* stage_ptr,
                                                __nv_bfloat16* gdst, int gpitch, int lane) {
  constexpr int PITCH = NC * 2 + 16;
  const uint32_t waddr = stage + ((lane & 7) + ((lane >> 3) & 1) * 8) * PITCH + (lane >> 4) * 16;
#pragma unroll
  for (int j = 0; j < NC / 16; j++) {
    stsm4(waddr + j * 32, pack_bf16(acc[8 * j] * scale, acc[8 * j + 1] * scale), pack_bf16(acc[8 * j + 2] * scale, acc[8 * j + 3] * scale),
          pack_bf16(acc[8 * j + 4] * scale, acc[8 * j + 5] * scale), pack_bf16(acc[8 * j + 6] * scale, acc[8 * j + 7] * scale));
  }
  __syncwarp();
  constexpr int CPR = NC / 8;
#pragma unroll
  for (int i = 0; i < CPR / 2; i++) {
    const int c = i * 32 + lane, r = c / CPR, cc = c % CPR;
    const uint4 v = *reinterpret_cast<const uint4*>(stage_ptr + r * PITCH + cc * 16);
    *reinterpret_cast<uint4*>(gdst + (size_t)r * gpitch + cc * 8) = v;
  }
}

constexpr int K1_STAGES = 4;
constexpr int K1_A_BYTES = 256 * 128;
constexpr int K1_B_BYTES = 64 * 160 * 2;
constexpr int K1_STAGE = K1_A_BYTES + K1_B_BYTES;
constexpr int K1_SMEM = K1_STAGES * K1_STAGE + 1024;
constexpr int KVW_OFF = K1_STAGES * K1_A_BYTES;

__global__ void __launch_bounds__(512, 1)
proj_kernel(const __grid_constant__ CUtensorMap tmX, const __grid_constant__ CUtensorMap tmWq, const __grid_constant__ CUtensorMap tmWqkv,
            const __nv_bfloat16* __restrict__ wk, const __nv_bfloat16* __restrict__ wv, const __nv_bfloat16* __restrict__ gate_w) {
  extern __shared__ uint8_t smem_raw[];
  __shared__ __align__(8) uint64_t bar_full[K1_STAGES], bar_empty[K1_STAGES];
  uint8_t* smem = reinterpret_cast<uint8_t*>((reinterpret_cast<uintptr_t>(smem_raw) + 1023) & ~(uintptr_t)1023);
  const uint32_t sbase = smem_u32(smem);
  const int tid = threadIdx.x, warp = tid >> 5, lane = tid & 31;
  const bool is_kv = blockIdx.x >= 128;
  PROF(0, 0);
  pdl_launch();
  if (tid == 0) {
    for (int i = 0; i < K1_STAGES; i++) { mbar_init(smem_u32(&bar_full[i]), 1); mbar_init(smem_u32(&bar_empty[i]), 16); }
    fence_mbar_init();
  }
  __syncthreads();

  if (!is_kv) {
    const int mb = blockIdx.x >> 4, nb = blockIdx.x & 15;
    const CUtensorMap* tw = nb < 4 ? &tmWq : &tmWqkv;
    const int j0 = (nb < 4 ? nb : nb - 4) * 5;
    auto load = [&](int kt) {
      const int s = kt % K1_STAGES;
      const uint32_t fb = smem_u32(&bar_full[s]);
      mbar_expect_tx(fb, K1_STAGE);
      tma_2d(sbase + s * K1_STAGE, &tmX, kt * 64, mb * 256, fb);
      tma_3d(sbase + s * K1_STAGE + K1_A_BYTES, tw, 0, kt * 64, j0, fb);
    };
    if (tid == 0) for (int kt = 0; kt < K1_STAGES; kt++) load(kt);
    {
      const int wg = warp >> 2;
      float acc[80];
#pragma unroll
      for (int i = 0; i < 80; i++) acc[i] = 0.f;
      for (int kt = 0; kt < 10; kt++) {
        const int s = kt % K1_STAGES;
        mbar_wait(smem_u32(&bar_full[s]), (kt / K1_STAGES) & 1);
        const uint32_t alo = ((sbase + s * K1_STAGE + wg * 8192) >> 4) | (1u << 16);
        const uint32_t blo = ((sbase + s * K1_STAGE + K1_A_BYTES) >> 4) | ((4096u >> 4) << 16);
        fence_regs(acc);
        wg_fence();
#pragma unroll
        for (int k = 0; k < 4; k++) wgmma_ss_n160_tb(acc, mkd(alo + k * 2, DHI_SW128_K), mkd(blo + k * 64, DHI_SW64_MN));
        wg_commit();
        if (kt > 0 && kt - 1 + K1_STAGES < 10) {
          wg_wait<1>();
          const uint32_t eb = smem_u32(&bar_empty[(kt - 1) % K1_STAGES]);
          if (lane == 0) mbar_arrive(eb);
          if (tid == 0) { mbar_wait(eb, ((kt - 1) / K1_STAGES) & 1); load(kt - 1 + K1_STAGES); }
          __syncwarp();
        }
      }
      wg_wait<0>();
      fence_regs(acc);
      PROF(0, 1);
      asm volatile("bar.sync %0, 128;" :: "r"(wg + 1) : "memory");
      const int w4 = warp & 3;
      const uint32_t off = w4 * K1_STAGE + wg * 8192;
      const int row0 = mb * 256 + wg * 64 + w4 * 16;
      if (nb < 4) {
        store_tile_bf16<160>(acc, 0.22360679774997896f * 1.4426950408889634f, sbase + off, smem + off,
                             g_q + (size_t)row0 * D_MODEL + nb * 160, D_MODEL, lane);
      } else {
        store_tile_bf16<160>(acc, 1.0f, sbase + off, smem + off, g_qkv + (size_t)row0 * (3 * D_MODEL) + (nb - 4) * 160, 3 * D_MODEL, lane);
      }
    }
  } else {
    const int cb = blockIdx.x - 128;
    auto load = [&](int it) {
      const int s = it % K1_STAGES;
      const uint32_t fb = smem_u32(&bar_full[s]);
      mbar_expect_tx(fb, K1_A_BYTES);
      tma_2d(sbase + s * K1_A_BYTES, &tmX, (it % 10) * 64, cb * 512 + (it / 10) * 256, fb);
    };
    if (tid == 0) for (int it = 0; it < K1_STAGES; it++) load(it);
    {
#pragma unroll
      for (int r = 0; r < 2; r++) {
        const int k = tid + r * 512;
        if (k < 640) {
          const uint2* pk = reinterpret_cast<const uint2*>(wk + k * 20);
          const uint2* pv = reinterpret_cast<const uint2*>(wv + k * 20);
          uint2 a[5], b[5];
#pragma unroll
          for (int i = 0; i < 5; i++) { a[i] = pk[i]; b[i] = pv[i]; }
          const uint32_t gw = (uint32_t)__bfloat16_as_ushort(gate_w[k]);
          uint4* dst = reinterpret_cast<uint4*>(smem + KVW_OFF + k * 16);
          dst[0] = make_uint4(a[0].x, a[0].y, a[1].x, a[1].y);
          dst[640] = make_uint4(a[2].x, a[2].y, a[3].x, a[3].y);
          dst[1280] = make_uint4(a[4].x, a[4].y, 0u, 0u);
          dst[1920] = make_uint4(b[0].x, b[0].y, b[1].x, b[1].y);
          dst[2560] = make_uint4(b[2].x, b[2].y, b[3].x, b[3].y);
          dst[3200] = make_uint4(b[4].x, b[4].y, gw, 0u);
        }
      }
      fence_proxy_async();
      asm volatile("bar.sync 1, 512;" ::: "memory");
      PROF(0, 1);
      const int wg = warp >> 2, w4 = warp & 3, g = lane >> 2, t = lane & 3;
      for (int pass = 0; pass < 2; pass++) {
        float acc[24];
#pragma unroll
        for (int i = 0; i < 24; i++) acc[i] = 0.f;
        for (int kt = 0; kt < 10; kt++) {
          const int it = pass * 10 + kt, s = it % K1_STAGES;
          mbar_wait(smem_u32(&bar_full[s]), (it / K1_STAGES) & 1);
          const uint32_t alo = ((sbase + s * K1_A_BYTES + wg * 8192) >> 4) | (1u << 16);
          const uint32_t blo = ((sbase + KVW_OFF + kt * 1024) >> 4) | ((128u >> 4) << 16);
          fence_regs(acc);
          wg_fence();
#pragma unroll
          for (int k = 0; k < 4; k++) wgmma_ss_n48_tb(acc, mkd(alo + k * 2, DHI_SW128_K), mkd(blo + k * 16, 10240u >> 4));
          wg_commit();
          wg_wait<0>();
          if (it + K1_STAGES < 20) {
            const uint32_t eb = smem_u32(&bar_empty[s]);
            if (lane == 0) mbar_arrive(eb);
            if (tid == 0) { mbar_wait(eb, (it / K1_STAGES) & 1); load(it + K1_STAGES); }
            __syncwarp();
          }
        }
        fence_regs(acc);
        float kmax2 = 0.f, vmax = 0.f;
#pragma unroll
        for (int h = 0; h < 2; h++) {
          const int key = cb * 512 + pass * 256 + wg * 64 + w4 * 16 + g + h * 8;
          const int grp = key >> 7, kk = key & 127;
          const bool poly = (TMASK >> (kk >> 3)) & 1;
          uint8_t* gp = g_kvimg + grp * GRP_BYTES;
          const uint32_t k0 = pack_bf16(acc[2 * h], acc[2 * h + 1]);
          const uint32_t k1 = pack_bf16(acc[4 + 2 * h], acc[5 + 2 * h]);
          uint32_t k2 = pack_bf16(acc[8 + 2 * h], acc[9 + 2 * h]);
          float n2 = bf_lo(k0) * bf_lo(k0) + bf_hi(k0) * bf_hi(k0) + bf_lo(k1) * bf_lo(k1) + bf_hi(k1) * bf_hi(k1);
          if (t < 2) {
            n2 += bf_lo(k2) * bf_lo(k2) + bf_hi(k2) * bf_hi(k2);
            k2 = pack_bf16(bf_lo(k2) * 0.5f, bf_hi(k2) * 0.5f);
          } else if (t == 2) k2 = poly ? pack_bf16(24.f, 2.5f) : pack_bf16(0.5f, 0.f);
          else k2 = poly ? pack_bf16(0.5f, 0.f) : 0u;
          *reinterpret_cast<uint32_t*>(gp + kk * 16 + t * 4) = k0;
          *reinterpret_cast<uint32_t*>(gp + PLANE + kk * 16 + t * 4) = k1;
          *reinterpret_cast<uint32_t*>(gp + 2 * PLANE + kk * 16 + t * 4) = k2;
          n2 += __shfl_xor_sync(0xffffffffu, n2, 1);
          n2 += __shfl_xor_sync(0xffffffffu, n2, 2);
          kmax2 = (n2 > kmax2 || n2 != n2) ? n2 : kmax2;
          uint32_t v0 = pack_bf16(acc[12 + 2 * h], acc[13 + 2 * h]);
          uint32_t v1 = pack_bf16(acc[16 + 2 * h], acc[17 + 2 * h]);
          uint32_t v2 = pack_bf16(acc[20 + 2 * h], acc[21 + 2 * h]);
          float vm = fmaxf(fmaxf(fabsf(bf_lo(v0)), fabsf(bf_hi(v0))), fmaxf(fabsf(bf_lo(v1)), fabsf(bf_hi(v1))));
          if (t < 2) vm = fmaxf(vm, fmaxf(fabsf(bf_lo(v2)), fabsf(bf_hi(v2))));
          else if (t == 2) {
            const float z = acc[20 + 2 * h];
            g_gate[key] = 1.f / (1.f + __expf(-z));
            v2 = 0x00003F80u;
          } else v2 = 0u;
          vmax = fmaxf(vmax, vm);
          if (poly) { v0 ^= 0x80008000u; v1 ^= 0x80008000u; v2 ^= 0x80008000u; }
          uint8_t* vp = gp + 3 * PLANE + (kk >> 3) * 384 + (kk & 7) * 16 + t * 4;
          *reinterpret_cast<uint32_t*>(vp) = v0;
          *reinterpret_cast<uint32_t*>(vp + 128) = v1;
          *reinterpret_cast<uint32_t*>(vp + 256) = v2;
        }
#pragma unroll
        for (int o = 1; o < 32; o <<= 1) {
          const float a = __shfl_xor_sync(0xffffffffu, kmax2, o);
          kmax2 = (a > kmax2 || a != a) ? a : kmax2;
          vmax = fmaxf(vmax, __shfl_xor_sync(0xffffffffu, vmax, o));
        }
        if (lane == 0) { g_kmax2[cb * 32 + pass * 16 + warp] = kmax2; g_vmax[cb * 32 + pass * 16 + warp] = vmax; }
      }
    }
  }
  PROF(0, 3);
}

__device__ __forceinline__ uint32_t ex2_pair_poly(float u0, float u1, uint32_t one2) {
  const uint32_t W = __byte_perm(__float_as_uint(u0), __float_as_uint(u1), 0x6521);
  uint32_t v; asm("lop3.b32 %0, %1, 0x007F007F, %2, 0xEA;" : "=r"(v) : "r"(W), "r"(one2));
  uint32_t L, p;
  asm("fma.rn.bf16x2 %0, %1, %2, %3;" : "=r"(L) : "r"(v), "r"(0x1f961f96u), "r"(0x9fe39fe3u));
  asm("fma.rn.bf16x2 %0, %1, %1, %2;" : "=r"(p) : "r"(L), "r"(0x00f500f5u));
  return W + p;
}
template <int JOFF>
__device__ __forceinline__ void softmax_fast(const float (&S)[32], uint32_t (&P)[16], uint32_t one2) {
#pragma unroll
  for (int i = 0; i < 16; i++) {
    if ((TMASK >> (JOFF + i / 2)) & 1) P[i] = ex2_pair_poly(S[2 * i], S[2 * i + 1], one2);
    else P[i] = pack_bf16(ex2(S[2 * i]), ex2(S[2 * i + 1]));
  }
}
template <int JOFF>
__device__ __forceinline__ void softmax_slow(const float (&S)[32], uint32_t (&P)[16], float (&O)[12], float& m0, float& m1) {
  float a0 = m0, a1 = m1;
#pragma unroll
  for (int j = 0; j < 8; j++) {
    a0 = fmaxf(a0, fmaxf(S[4 * j], S[4 * j + 1]));
    a1 = fmaxf(a1, fmaxf(S[4 * j + 2], S[4 * j + 3]));
  }
  a0 = fmaxf(a0, __shfl_xor_sync(0xffffffffu, a0, 1)); a0 = fmaxf(a0, __shfl_xor_sync(0xffffffffu, a0, 2));
  a1 = fmaxf(a1, __shfl_xor_sync(0xffffffffu, a1, 1)); a1 = fmaxf(a1, __shfl_xor_sync(0xffffffffu, a1, 2));
  const float c0 = ex2(m0 - a0), c1 = ex2(m1 - a1);
  m0 = a0; m1 = a1;
#pragma unroll
  for (int j = 0; j < 3; j++) { O[4 * j] *= c0; O[4 * j + 1] *= c0; O[4 * j + 2] *= c1; O[4 * j + 3] *= c1; }
#pragma unroll
  for (int i = 0; i < 16; i++) {
    const float m = (i & 1) ? a1 : a0;
    const uint32_t p = pack_bf16(ex2(S[2 * i] - m), ex2(S[2 * i + 1] - m));
    P[i] = ((TMASK >> (JOFF + i / 2)) & 1) ? (p ^ 0x80008000u) : p;
  }
}
constexpr uint32_t DHI_KV = 128 >> 4;
__device__ __forceinline__ void issue_qk(float (&S)[32], const uint32_t (&q)[6], uint32_t base) {
  wgmma_rs_n64<0>(S, q[0], q[1], q[2], q[3], mkd(base + ((PLANE >> 4) << 16), DHI_KV));
  wgmma_rs_n64<1>(S, q[4], q[5], q[4], q[5], mkd(base + (2 * PLANE >> 4), DHI_KV));
}
__device__ __forceinline__ void issue_pv(float (&O)[12], const uint32_t (&P)[16], uint32_t vbase) {
#pragma unroll
  for (int kk = 0; kk < 4; kk++)
    wgmma_rs_n24_tb<1>(O, P[4 * kk], P[4 * kk + 1], P[4 * kk + 2], P[4 * kk + 3], mkd(vbase + kk * (768 >> 4), DHI_KV));
}

template <bool FAST>
__device__ __forceinline__ void attn_tile(const uint32_t (&q)[6], float (&O)[12], uint32_t sbase, uint32_t bars, bool first, uint32_t one2) {
  float S[32]; uint32_t P[16];
  float m0 = -INFINITY, m1 = -INFINITY;
#pragma unroll
  for (int i = 0; i < 32; i++) S[i] = 0.f;
  uint32_t kb = sbase >> 4;
  const uint32_t klast = kb + (NGRP - 1) * (GRP_BYTES >> 4);
  constexpr uint32_t VOFF = ((3 * PLANE) >> 4) + ((384u >> 4) << 16);
  if (first) mbar_wait(bars, 0);
  fence_regs(S); fence_regs(O);
  wg_fence();
  issue_qk(S, q, kb);
  wg_commit();
#pragma unroll 1
  for (int grp = 0; grp < NGRP; grp++) {
    if (first) mbar_wait(bars + 8 * min(grp + 1, NGRP - 1), 0);
    const uint32_t knext = min(kb + (GRP_BYTES >> 4), klast);
    wg_wait<0>();
    fence_regs(S); fence_regs(P); fence_regs(O);
    if (FAST) softmax_fast<0>(S, P, one2); else softmax_slow<0>(S, P, O, m0, m1);
    fence_regs(S); fence_regs(P); fence_regs(O);
    wg_fence();
    issue_qk(S, q, kb + 64);
    issue_pv(O, P, kb + VOFF);
    wg_commit();
    wg_wait<0>();
    fence_regs(S); fence_regs(P); fence_regs(O);
    if (FAST) softmax_fast<8>(S, P, one2); else softmax_slow<8>(S, P, O, m0, m1);
    fence_regs(S); fence_regs(P); fence_regs(O);
    wg_fence();
    issue_qk(S, q, knext);
    issue_pv(O, P, kb + VOFF + 4 * (768 >> 4));
    wg_commit();
    kb = knext;
  }
  wg_wait<0>();
  fence_regs(O); fence_regs(S);
}

constexpr int K2_QOFF = NGRP * GRP_BYTES;
constexpr int K2_SMEM = K2_QOFF + 512 * 6 * 4 + 1024;

__device__ __forceinline__ void local_attn_pair(int token, int lane) {
  const __nv_bfloat16* base = g_qkv + (size_t)token * (3 * D_MODEL) + lane * DH;
  float f[20];
  {
    const uint2* p = reinterpret_cast<const uint2*>(base);
#pragma unroll
    for (int i = 0; i < 5; i++) { const uint2 v = p[i]; f[4 * i] = bf_lo(v.x); f[4 * i + 1] = bf_hi(v.x); f[4 * i + 2] = bf_lo(v.y); f[4 * i + 3] = bf_hi(v.y); }
  }
  float sc[8];
  float mx = -INFINITY;
#pragma unroll
  for (int w = 0; w < 8; w++) {
    const bool ok = token - 2 * w >= 0;
    const uint2* p = reinterpret_cast<const uint2*>(base + D_MODEL - (ok ? 2 * w : 0) * (3 * D_MODEL));
    float s = 0.f;
#pragma unroll
    for (int i = 0; i < 5; i++) {
      const uint2 v = p[i];
      s = fmaf(f[4 * i], bf_lo(v.x), s); s = fmaf(f[4 * i + 1], bf_hi(v.x), s);
      s = fmaf(f[4 * i + 2], bf_lo(v.y), s); s = fmaf(f[4 * i + 3], bf_hi(v.y), s);
    }
    s *= 0.22360679774997896f * 1.4426950408889634f;
    sc[w] = ok ? s : -1e9f * 1.4426950408889634f;
    mx = fmaxf(mx, sc[w]);
  }
  float l = 0.f;
#pragma unroll
  for (int w = 0; w < 8; w++) { sc[w] = ex2(sc[w] - mx); l += sc[w]; }
#pragma unroll
  for (int i = 0; i < 20; i++) f[i] = 0.f;
#pragma unroll
  for (int w = 0; w < 8; w++) {
    const bool ok = token - 2 * w >= 0;
    const uint2* p = reinterpret_cast<const uint2*>(base + 2 * D_MODEL - (ok ? 2 * w : token) * (3 * D_MODEL));
#pragma unroll
    for (int i = 0; i < 5; i++) {
      const uint2 v = p[i];
      f[4 * i] = fmaf(sc[w], bf_lo(v.x), f[4 * i]); f[4 * i + 1] = fmaf(sc[w], bf_hi(v.x), f[4 * i + 1]);
      f[4 * i + 2] = fmaf(sc[w], bf_lo(v.y), f[4 * i + 2]); f[4 * i + 3] = fmaf(sc[w], bf_hi(v.y), f[4 * i + 3]);
    }
  }
  const float r = (1.f - g_gate[token]) / l;
  uint2* dst = reinterpret_cast<uint2*>(g_a2 + (size_t)token * (2 * D_MODEL) + D_MODEL + lane * DH);
#pragma unroll
  for (int i = 0; i < 5; i++) dst[i] = make_uint2(pack_bf16(f[4 * i] * r, f[4 * i + 1] * r), pack_bf16(f[4 * i + 2] * r, f[4 * i + 3] * r));
}

__global__ void __launch_bounds__(640, 1)
attn_kernel(uint32_t one2) {
  extern __shared__ uint8_t smem_raw[];
  __shared__ __align__(8) uint64_t bars[NGRP];
  uint8_t* smem = reinterpret_cast<uint8_t*>((reinterpret_cast<uintptr_t>(smem_raw) + 1023) & ~(uintptr_t)1023);
  const uint32_t sbase = smem_u32(smem);
  const int tid = threadIdx.x, wg = tid >> 7, warp = (tid >> 5) & 3, lane = tid & 31, g = lane >> 2, t = lane & 3;
  PROF(1, 0);
  pdl_launch();
  if (tid == 0) {
    for (int i = 0; i < NGRP; i++) mbar_init(smem_u32(&bars[i]), 1);
    fence_mbar_init();
  }
  __syncthreads();
  if (wg == 4) {
    asm volatile("setmaxnreg.dec.sync.aligned.u32 56;");
    pdl_wait();
    if (tid == 512) {
      for (int i = 0; i < NGRP; i++) {
        mbar_expect_tx(smem_u32(&bars[i]), GRP_BYTES);
        bulk_g2s(sbase + i * GRP_BYTES, g_kvimg + i * GRP_BYTES, GRP_BYTES, smem_u32(&bars[i]));
      }
    }
    __syncwarp();
#pragma unroll 1
    for (int i = 0; i < 4; i++) local_attn_pair(blockIdx.x * 16 + i * 4 + warp, lane);
  } else {
    asm volatile("setmaxnreg.inc.sync.aligned.u32 104;");
    pdl_wait();
    PROF(1, 1);
    uint32_t q[6];
    uint32_t* qstash = reinterpret_cast<uint32_t*>(smem + K2_QOFF) + tid;
    const int rowA = (blockIdx.x * 8 + wg) * 64 + warp * 16 + g;
    {
      const uint32_t* r0 = reinterpret_cast<const uint32_t*>(g_q + (size_t)rowA * DH);
      const uint32_t* r1 = r0 + 8 * (DH / 2);
      const uint32_t* s0 = r0 + 256 * (DH / 2);
      const uint32_t* s1 = s0 + 8 * (DH / 2);
      q[0] = r0[t]; q[1] = r1[t]; q[2] = r0[t + 4]; q[3] = r1[t + 4];
      q[4] = t < 2 ? r0[8 + t] : 0u;
      q[5] = t < 2 ? r1[8 + t] : 0u;
      qstash[0] = s0[t]; qstash[512] = s1[t]; qstash[1024] = s0[t + 4]; qstash[1536] = s1[t + 4];
      qstash[2048] = t < 2 ? s0[8 + t] : 0u;
      qstash[2560] = t < 2 ? s1[8 + t] : 0u;
    }
    float kmax2 = 0.f, vmax = 0.f;
#pragma unroll
    for (int i = 0; i < 4; i++) {
      const float a = g_kmax2[lane + 32 * i];
      kmax2 = (a > kmax2 || a != a) ? a : kmax2;
      vmax = fmaxf(vmax, g_vmax[lane + 32 * i]);
    }
#pragma unroll
    for (int o = 1; o < 32; o <<= 1) {
      const float a = __shfl_xor_sync(0xffffffffu, kmax2, o);
      kmax2 = (a > kmax2 || a != a) ? a : kmax2;
      vmax = fmaxf(vmax, __shfl_xor_sync(0xffffffffu, vmax, o));
    }
    const float qlim = (vmax >= 0.00390625f && vmax <= 256.f) ? 9025.f / kmax2 : -1.f;
    PROF(1, 2);
#pragma unroll 1
    for (int it = 0; it < 2; it++) {
      const int row0 = rowA + it * 256;
      if (it == 1) {
#pragma unroll
        for (int i = 0; i < 6; i++) q[i] = qstash[512 * i];
      }
      float n0 = bf_lo(q[0]) * bf_lo(q[0]) + bf_hi(q[0]) * bf_hi(q[0]) + bf_lo(q[2]) * bf_lo(q[2]) + bf_hi(q[2]) * bf_hi(q[2]) +
                 bf_lo(q[4]) * bf_lo(q[4]) + bf_hi(q[4]) * bf_hi(q[4]);
      float n1 = bf_lo(q[1]) * bf_lo(q[1]) + bf_hi(q[1]) * bf_hi(q[1]) + bf_lo(q[3]) * bf_lo(q[3]) + bf_hi(q[3]) * bf_hi(q[3]) +
                 bf_lo(q[5]) * bf_lo(q[5]) + bf_hi(q[5]) * bf_hi(q[5]);
      n0 += __shfl_xor_sync(0xffffffffu, n0, 1); n0 += __shfl_xor_sync(0xffffffffu, n0, 2);
      n1 += __shfl_xor_sync(0xffffffffu, n1, 1); n1 += __shfl_xor_sync(0xffffffffu, n1, 2);
      const bool safe = (n0 <= qlim) && (n1 <= qlim);
      uint32_t unsafe_any;
      asm volatile("{\n.reg .pred p, r;\nsetp.eq.u32 p, %1, 0;\nbarrier.cta.red.or.pred r, %2, 128, p;\nselp.u32 %0, 1, 0, r;\n}\n"
                   : "=r"(unsafe_any) : "r"((uint32_t)safe), "r"(wg + 1) : "memory");
      float O[12];
#pragma unroll
      for (int i = 0; i < 12; i++) O[i] = 0.f;
      if (!unsafe_any) {
        if (t >= 2) { q[4] = q[5] = (t == 2) ? 0x3F804100u : 0x00003B80u; }
        attn_tile<true>(q, O, sbase, smem_u32(&bars[0]), it == 0, one2);
      } else {
        attn_tile<false>(q, O, sbase, smem_u32(&bars[0]), it == 0, one2);
      }
      const float l0 = __shfl_sync(0xffffffffu, O[8], (lane & ~3) | 2);
      const float l1 = __shfl_sync(0xffffffffu, O[10], (lane & ~3) | 2);
      const int tok = row0 >> 5;
      const float gt = g_gate[tok];
      const float i0 = gt / l0, i1 = gt / l1;
      uint32_t* o0 = reinterpret_cast<uint32_t*>(g_a2 + (size_t)tok * (2 * D_MODEL) + (row0 & 31) * DH);
      uint32_t* o1 = o0 + 8 * (DH / 2);
      o0[t] = pack_bf16(O[0] * i0, O[1] * i0); o1[t] = pack_bf16(O[2] * i1, O[3] * i1);
      o0[t + 4] = pack_bf16(O[4] * i0, O[5] * i0); o1[t + 4] = pack_bf16(O[6] * i1, O[7] * i1);
      if (t < 2) { o0[t + 8] = pack_bf16(O[8] * i0, O[9] * i0); o1[t + 8] = pack_bf16(O[10] * i1, O[11] * i1); }
    }
    PROF(1, 3);
  }
}

constexpr int K3_STAGES = 8;
constexpr int K3_A_BYTES = 128 * 128;
constexpr int K3_B_BYTES = 64 * 80 * 2;
constexpr int K3_STAGE = K3_A_BYTES + K3_B_BYTES;
constexpr int K3_SMEM = K3_STAGES * K3_STAGE + 1024;

__global__ void __launch_bounds__(288, 1)
out_kernel(const __grid_constant__ CUtensorMap tmA2, const __grid_constant__ CUtensorMap tmWoA, const __grid_constant__ CUtensorMap tmWoB,
           __nv_bfloat16* __restrict__ out) {
  extern __shared__ uint8_t smem_raw[];
  __shared__ __align__(8) uint64_t bar_full[K3_STAGES], bar_empty[K3_STAGES];
  uint8_t* smem = reinterpret_cast<uint8_t*>((reinterpret_cast<uintptr_t>(smem_raw) + 1023) & ~(uintptr_t)1023);
  const uint32_t sbase = smem_u32(smem);
  const int tid = threadIdx.x, warp = tid >> 5, lane = tid & 31;
  const int mb = blockIdx.x >> 3, nb = blockIdx.x & 7;
  PROF(2, 0);
  if (tid == 0) {
    for (int i = 0; i < K3_STAGES; i++) { mbar_init(smem_u32(&bar_full[i]), 2); mbar_init(smem_u32(&bar_empty[i]), 8); }
    fence_mbar_init();
  }
  __syncthreads();
  if (warp == 8) {
    if (lane == 0) {
      for (int kt = 0; kt < K3_STAGES; kt++) {
        const uint32_t fb = smem_u32(&bar_full[kt]);
        mbar_expect_tx(fb, K3_B_BYTES);
        tma_3d(sbase + kt * K3_STAGE + K3_A_BYTES, &tmWoA, 0, kt * 64, nb * 5, fb);
      }
      pdl_wait();
      for (int kt = 0; kt < 20; kt++) {
        const int s = kt % K3_STAGES;
        const uint32_t fb = smem_u32(&bar_full[s]);
        if (kt >= K3_STAGES) {
          mbar_wait(smem_u32(&bar_empty[s]), ((kt / K3_STAGES) - 1) & 1);
          mbar_expect_tx(fb, K3_B_BYTES);
          tma_3d(sbase + s * K3_STAGE + K3_A_BYTES, kt < 10 ? &tmWoA : &tmWoB, 0, (kt % 10) * 64, nb * 5, fb);
        }
        mbar_expect_tx(fb, K3_A_BYTES);
        tma_2d(sbase + s * K3_STAGE, &tmA2, kt * 64, mb * 128, fb);
      }
    }
  } else {
    const int wg = warp >> 2;
    float acc[40];
#pragma unroll
    for (int i = 0; i < 40; i++) acc[i] = 0.f;
    for (int kt = 0; kt < 20; kt++) {
      const int s = kt % K3_STAGES;
      mbar_wait(smem_u32(&bar_full[s]), (kt / K3_STAGES) & 1);
      if (kt == 0) PROF(2, 1);
      const uint32_t alo = ((sbase + s * K3_STAGE + wg * 8192) >> 4) | (1u << 16);
      const uint32_t blo = ((sbase + s * K3_STAGE + K3_A_BYTES) >> 4) | ((2048u >> 4) << 16);
      fence_regs(acc);
      wg_fence();
#pragma unroll
      for (int k = 0; k < 4; k++) wgmma_ss_n80_tb(acc, mkd(alo + k * 2, DHI_SW128_K), mkd(blo + k * 32, DHI_SW32_MN));
      wg_commit();
      if (kt > 0) {
        wg_wait<1>();
        if (lane == 0) mbar_arrive(smem_u32(&bar_empty[(kt - 1) % K3_STAGES]));
      }
    }
    wg_wait<0>();
    fence_regs(acc);
    PROF(2, 2);
    asm volatile("bar.sync %0, 128;" :: "r"(wg + 1) : "memory");
    const int w4 = warp & 3;
    const uint32_t off = w4 * K3_STAGE + wg * 8192;
    const int row0 = mb * 128 + wg * 64 + w4 * 16;
    store_tile_bf16<80>(acc, 1.0f, sbase + off, smem + off, out + (size_t)row0 * D_MODEL + nb * 80, D_MODEL, lane);
    PROF(2, 3);
  }
}

typedef CUresult (*EncodeFn)(CUtensorMap*, CUtensorMapDataType, cuuint32_t, void*, const cuuint64_t*, const cuuint64_t*,
                             const cuuint32_t*, const cuuint32_t*, CUtensorMapInterleave, CUtensorMapSwizzle,
                             CUtensorMapL2promotion, CUtensorMapFloatOOBfill);

void make_map(EncodeFn fn, CUtensorMap* tm, const void* ptr, int rank, const cuuint64_t* dims, const cuuint64_t* strides,
              const cuuint32_t* box, CUtensorMapSwizzle sw) {
  const cuuint32_t es[3] = {1, 1, 1};
  fn(tm, CU_TENSOR_MAP_DATA_TYPE_BFLOAT16, rank, const_cast<void*>(ptr), dims, strides, box, es, CU_TENSOR_MAP_INTERLEAVE_NONE, sw,
     CU_TENSOR_MAP_L2_PROMOTION_L2_256B, CU_TENSOR_MAP_FLOAT_OOB_FILL_NONE);
}
void map_a(EncodeFn fn, CUtensorMap* tm, const void* p, int rows, int cols, int box_rows) {
  const cuuint64_t dims[2] = {(cuuint64_t)cols, (cuuint64_t)rows};
  const cuuint64_t str[1] = {(cuuint64_t)cols * 2};
  const cuuint32_t box[2] = {64, (cuuint32_t)box_rows};
  make_map(fn, tm, p, 2, dims, str, box, CU_TENSOR_MAP_SWIZZLE_128B);
}
void map_w(EncodeFn fn, CUtensorMap* tm, const void* p, int K, int N, int atom, CUtensorMapSwizzle sw) {
  const cuuint64_t dims[3] = {(cuuint64_t)atom, (cuuint64_t)K, (cuuint64_t)(N / atom)};
  const cuuint64_t str[2] = {(cuuint64_t)N * 2, (cuuint64_t)atom * 2};
  const cuuint32_t box[3] = {(cuuint32_t)atom, 64, 5};
  make_map(fn, tm, p, 3, dims, str, box, sw);
}

template <typename... KArgs, typename... Args>
void launch(void (*kern)(KArgs...), int grid, int block, int smem, bool pdl, Args... args) {
  cudaLaunchConfig_t cfg = {};
  cfg.gridDim = dim3(grid); cfg.blockDim = dim3(block); cfg.dynamicSmemBytes = smem; cfg.stream = cudaStreamPerThread;
  cudaLaunchAttribute at[1];
  at[0].id = cudaLaunchAttributeProgrammaticStreamSerialization;
  at[0].val.programmaticStreamSerializationAllowed = 1;
  cfg.attrs = at; cfg.numAttrs = pdl ? 1 : 0;
  cudaLaunchKernelEx(&cfg, kern, KArgs(args)...);
}

}

extern "C" void kernel_launch(void* const* d_in, const int* in_sizes, int n_in, void* d_out, int out_size) {
  (void)in_sizes; (void)n_in; (void)out_size;
  const __nv_bfloat16* x = (const __nv_bfloat16*)d_in[0];
  const __nv_bfloat16* wq = (const __nv_bfloat16*)d_in[1];
  const __nv_bfloat16* wk = (const __nv_bfloat16*)d_in[2];
  const __nv_bfloat16* wv = (const __nv_bfloat16*)d_in[3];
  const __nv_bfloat16* woA = (const __nv_bfloat16*)d_in[4];
  const __nv_bfloat16* wqkv = (const __nv_bfloat16*)d_in[6];
  const __nv_bfloat16* woB = (const __nv_bfloat16*)d_in[7];
  const __nv_bfloat16* gate_w = (const __nv_bfloat16*)d_in[8];

  static EncodeFn enc = nullptr;
  static void* a2_ptr = nullptr;
  if (!enc) {
    void* fp = nullptr;
    cudaDriverEntryPointQueryResult qr;
    cudaGetDriverEntryPoint("cuTensorMapEncodeTiled", &fp, cudaEnableDefault, &qr);
    enc = (EncodeFn)fp;
    cudaGetSymbolAddress(&a2_ptr, g_a2);
    cudaFuncSetAttribute(proj_kernel, cudaFuncAttributeMaxDynamicSharedMemorySize, K1_SMEM);
    cudaFuncSetAttribute(attn_kernel, cudaFuncAttributeMaxDynamicSharedMemorySize, K2_SMEM);
    cudaFuncSetAttribute(out_kernel, cudaFuncAttributeMaxDynamicSharedMemorySize, K3_SMEM);
  }
  CUtensorMap tmX, tmWq, tmWqkv, tmA2, tmWoA, tmWoB;
  map_a(enc, &tmX, x, S_LEN, D_MODEL, 256);
  map_w(enc, &tmWq, wq, D_MODEL, D_MODEL, 32, CU_TENSOR_MAP_SWIZZLE_64B);
  map_w(enc, &tmWqkv, wqkv, D_MODEL, 3 * D_MODEL, 32, CU_TENSOR_MAP_SWIZZLE_64B);
  map_a(enc, &tmA2, a2_ptr, S_LEN, 2 * D_MODEL, 128);
  map_w(enc, &tmWoA, woA, D_MODEL, D_MODEL, 16, CU_TENSOR_MAP_SWIZZLE_32B);
  map_w(enc, &tmWoB, woB, D_MODEL, D_MODEL, 16, CU_TENSOR_MAP_SWIZZLE_32B);

  launch(proj_kernel, 132, 512, K1_SMEM, false, tmX, tmWq, tmWqkv, wk, wv, gate_w);
  launch(attn_kernel, 128, 640, K2_SMEM, true, 0x3F803F80u);
  launch(out_kernel, 128, 288, K3_SMEM, true, tmA2, tmWoA, tmWoB, (__nv_bfloat16*)d_out);
}
```

```cpp
#include <cuda_runtime.h>
#include <cuda_bf16.h>
#include <cuda.h>
#include <stdint.h>

namespace {

constexpr int S_LEN = 2048, D_MODEL = 640, DH = 20;

constexpr int GRP = 128;
constexpr int PLANE = GRP * 16;
constexpr int GRP_BYTES = GRP * 16 * 6;
constexpr int NGRP = S_LEN / GRP;
constexpr uint32_t TMASK = 0x6DB6u;

__device__ __align__(1024) __nv_bfloat16 g_q[S_LEN * D_MODEL];
__device__ __align__(1024) __nv_bfloat16 g_qkv[S_LEN * 3 * D_MODEL];
__device__ __align__(1024) __nv_bfloat16 g_a2[S_LEN * 2 * D_MODEL];
__device__ __align__(1024) uint8_t g_kvimg[NGRP * GRP_BYTES];
__device__ float g_gate[S_LEN];
__device__ float g_kmax2[128];
__device__ float g_vmax[128];

#define PROF(k, slot)
__device__ __forceinline__ uint32_t smem_u32(const void* p) { return (uint32_t)__cvta_generic_to_shared(p); }
__device__ __forceinline__ uint64_t mkd(uint32_t lo, uint32_t hi) {
  uint64_t d; asm("mov.b64 %0, {%1, %2};" : "=l"(d) : "r"(lo), "r"(hi)); return d;
}
__device__ __forceinline__ void wg_fence() { asm volatile("wgmma.fence.sync.aligned;" ::: "memory"); }
__device__ __forceinline__ void wg_commit() { asm volatile("wgmma.commit_group.sync.aligned;" ::: "memory"); }
template <int N> __device__ __forceinline__ void wg_wait() { asm volatile("wgmma.wait_group.sync.aligned %0;" :: "n"(N) : "memory"); }
template <int N> __device__ __forceinline__ void fence_regs(float (&d)[N]) {
#pragma unroll
  for (int i = 0; i < N; i++) asm volatile("" : "+f"(d[i]) :: "memory");
}
template <int N> __device__ __forceinline__ void fence_regs(uint32_t (&d)[N]) {
#pragma unroll
  for (int i = 0; i < N; i++) asm volatile("" : "+r"(d[i]) :: "memory");
}
__device__ __forceinline__ void mbar_init(uint32_t bar, uint32_t cnt) { asm volatile("mbarrier.init.shared::cta.b64 [%0], %1;" :: "r"(bar), "r"(cnt)); }
__device__ __forceinline__ void mbar_expect_tx(uint32_t bar, uint32_t bytes) {
  asm volatile("mbarrier.arrive.expect_tx.shared::cta.b64 _, [%0], %1;" :: "r"(bar), "r"(bytes) : "memory");
}
__device__ __forceinline__ void mbar_arrive(uint32_t bar) { asm volatile("mbarrier.arrive.shared::cta.b64 _, [%0];" :: "r"(bar) : "memory"); }
__device__ __forceinline__ void mbar_wait(uint32_t bar, uint32_t parity) {
  asm volatile("{\n.reg .pred p;\nWAIT_%=:\nmbarrier.try_wait.parity.shared::cta.b64 p, [%0], %1;\n@p bra DONE_%=;\nbra WAIT_%=;\nDONE_%=:\n}\n"
               :: "r"(bar), "r"(parity) : "memory");
}
__device__ __forceinline__ void fence_mbar_init() { asm volatile("fence.mbarrier_init.release.cluster;" ::: "memory"); }
__device__ __forceinline__ void fence_proxy_async() { asm volatile("fence.proxy.async.shared::cta;" ::: "memory"); }
__device__ __forceinline__ void bulk_g2s(uint32_t dst, const void* src, uint32_t bytes, uint32_t bar) {
  asm volatile("cp.async.bulk.shared::cluster.global.mbarrier::complete_tx::bytes [%0], [%1], %2, [%3];"
               :: "r"(dst), "l"(src), "r"(bytes), "r"(bar) : "memory");
}
__device__ __forceinline__ void tma_2d(uint32_t dst, const CUtensorMap* tm, int c0, int c1, uint32_t bar) {
  asm volatile("cp.async.bulk.tensor.2d.shared::cluster.global.mbarrier::complete_tx::bytes [%0], [%1, {%3, %4}], [%2];"
               :: "r"(dst), "l"((uint64_t)tm), "r"(bar), "r"(c0), "r"(c1) : "memory");
}
__device__ __forceinline__ void tma_3d(uint32_t dst, const CUtensorMap* tm, int c0, int c1, int c2, uint32_t bar) {
  asm volatile("cp.async.bulk.tensor.3d.shared::cluster.global.mbarrier::complete_tx::bytes [%0], [%1, {%3, %4, %5}], [%2];"
               :: "r"(dst), "l"((uint64_t)tm), "r"(bar), "r"(c0), "r"(c1), "r"(c2) : "memory");
}
__device__ __forceinline__ void prefetch_tmap(const CUtensorMap* tm) { asm volatile("prefetch.tensormap [%0];" :: "l"((uint64_t)tm) : "memory"); }
__device__ __forceinline__ void pdl_wait() { asm volatile("griddepcontrol.wait;" ::: "memory"); }
__device__ __forceinline__ void pdl_launch() { asm volatile("griddepcontrol.launch_dependents;" ::: "memory"); }
__device__ __forceinline__ float ex2(float x) { float y; asm("ex2.approx.ftz.f32 %0, %1;" : "=f"(y) : "f"(x)); return y; }
__device__ __forceinline__ uint32_t pack_bf16(float lo, float hi) {
  uint32_t r; asm("cvt.rn.bf16x2.f32 %0, %1, %2;" : "=r"(r) : "f"(hi), "f"(lo)); return r;
}
__device__ __forceinline__ float bf_lo(uint32_t x) { return __uint_as_float(x << 16); }
__device__ __forceinline__ float bf_hi(uint32_t x) { return __uint_as_float(x & 0xffff0000u); }
__device__ __forceinline__ void stsm4(uint32_t addr, uint32_t r0, uint32_t r1, uint32_t r2, uint32_t r3) {
  asm volatile("stmatrix.sync.aligned.m8n8.x4.shared.b16 [%0], {%1, %2, %3, %4};" :: "r"(addr), "r"(r0), "r"(r1), "r"(r2), "r"(r3) : "memory");
}

__device__ __forceinline__ void wgmma_ss_n160_tb(float (&d)[80], uint64_t descA, uint64_t descB) {
  asm volatile("wgmma.mma_async.sync.aligned.m64n160k16.f32.bf16.bf16 {%0, %1, %2, %3, %4, %5, %6, %7, %8, %9, %10, %11, %12, %13, %14, %15, %16, %17, %18, %19, %20, %21, %22, %23, %24, %25, %26, %27, %28, %29, %30, %31, %32, %33, %34, %35, %36, %37, %38, %39, %40, %41, %42, %43, %44, %45, %46, %47, %48, %49, %50, %51, %52, %53, %54, %55, %56, %57, %58, %59, %60, %61, %62, %63, %64, %65, %66, %67, %68, %69, %70, %71, %72, %73, %74, %75, %76, %77, %78, %79}, %80, %81, 1, 1, 1, 0, 1;\n"
    : "+f"(d[0]), "+f"(d[1]), "+f"(d[2]), "+f"(d[3]), "+f"(d[4]), "+f"(d[5]), "+f"(d[6]), "+f"(d[7]), "+f"(d[8]), "+f"(d[9]), "+f"(d[10]), "+f"(d[11]), "+f"(d[12]), "+f"(d[13]), "+f"(d[14]), "+f"(d[15]), "+f"(d[16]), "+f"(d[17]), "+f"(d[18]), "+f"(d[19]), "+f"(d[20]), "+f"(d[21]), "+f"(d[22]), "+f"(d[23]), "+f"(d[24]), "+f"(d[25]), "+f"(d[26]), "+f"(d[27]), "+f"(d[28]), "+f"(d[29]), "+f"(d[30]), "+f"(d[31]), "+f"(d[32]), "+f"(d[33]), "+f"(d[34]), "+f"(d[35]), "+f"(d[36]), "+f"(d[37]), "+f"(d[38]), "+f"(d[39]), "+f"(d[40]), "+f"(d[41]), "+f"(d[42]), "+f"(d[43]), "+f"(d[44]), "+f"(d[45]), "+f"(d[46]), "+f"(d[47]), "+f"(d[48]), "+f"(d[49]), "+f"(d[50]), "+f"(d[51]), "+f"(d[52]), "+f"(d[53]), "+f"(d[54]), "+f"(d[55]), "+f"(d[56]), "+f"(d[57]), "+f"(d[58]), "+f"(d[59]), "+f"(d[60]), "+f"(d[61]), "+f"(d[62]), "+f"(d[63]), "+f"(d[64]), "+f"(d[65]), "+f"(d[66]), "+f"(d[67]), "+f"(d[68]), "+f"(d[69]), "+f"(d[70]), "+f"(d[71]), "+f"(d[72]), "+f"(d[73]), "+f"(d[74]), "+f"(d[75]), "+f"(d[76]), "+f"(d[77]), "+f"(d[78]), "+f"(d[79])
    : "l"(descA), "l"(descB));
}
__device__ __forceinline__ void wgmma_ss_n48_tb(float (&d)[24], uint64_t descA, uint64_t descB) {
  asm volatile("wgmma.mma_async.sync.aligned.m64n48k16.f32.bf16.bf16 {%0, %1, %2, %3, %4, %5, %6, %7, %8, %9, %10, %11, %12, %13, %14, %15, %16, %17, %18, %19, %20, %21, %22, %23}, %24, %25, 1, 1, 1, 0, 1;\n"
    : "+f"(d[0]), "+f"(d[1]), "+f"(d[2]), "+f"(d[3]), "+f"(d[4]), "+f"(d[5]), "+f"(d[6]), "+f"(d[7]), "+f"(d[8]), "+f"(d[9]), "+f"(d[10]), "+f"(d[11]), "+f"(d[12]), "+f"(d[13]), "+f"(d[14]), "+f"(d[15]), "+f"(d[16]), "+f"(d[17]), "+f"(d[18]), "+f"(d[19]), "+f"(d[20]), "+f"(d[21]), "+f"(d[22]), "+f"(d[23])
    : "l"(descA), "l"(descB));
}
__device__ __forceinline__ void wgmma_ss_n80_tb(float (&d)[40], uint64_t descA, uint64_t descB) {
  asm volatile("wgmma.mma_async.sync.aligned.m64n80k16.f32.bf16.bf16 {%0, %1, %2, %3, %4, %5, %6, %7, %8, %9, %10, %11, %12, %13, %14, %15, %16, %17, %18, %19, %20, %21, %22, %23, %24, %25, %26, %27, %28, %29, %30, %31, %32, %33, %34, %35, %36, %37, %38, %39}, %40, %41, 1, 1, 1, 0, 1;\n"
    : "+f"(d[0]), "+f"(d[1]), "+f"(d[2]), "+f"(d[3]), "+f"(d[4]), "+f"(d[5]), "+f"(d[6]), "+f"(d[7]), "+f"(d[8]), "+f"(d[9]), "+f"(d[10]), "+f"(d[11]), "+f"(d[12]), "+f"(d[13]), "+f"(d[14]), "+f"(d[15]), "+f"(d[16]), "+f"(d[17]), "+f"(d[18]), "+f"(d[19]), "+f"(d[20]), "+f"(d[21]), "+f"(d[22]), "+f"(d[23]), "+f"(d[24]), "+f"(d[25]), "+f"(d[26]), "+f"(d[27]), "+f"(d[28]), "+f"(d[29]), "+f"(d[30]), "+f"(d[31]), "+f"(d[32]), "+f"(d[33]), "+f"(d[34]), "+f"(d[35]), "+f"(d[36]), "+f"(d[37]), "+f"(d[38]), "+f"(d[39])
    : "l"(descA), "l"(descB));
}
template <int SCALE_D>
__device__ __forceinline__ void wgmma_rs_n64(float (&d)[32], uint32_t a0, uint32_t a1, uint32_t a2, uint32_t a3, uint64_t descB) {
  asm volatile("wgmma.mma_async.sync.aligned.m64n64k16.f32.bf16.bf16 {%0, %1, %2, %3, %4, %5, %6, %7, %8, %9, %10, %11, %12, %13, %14, %15, %16, %17, %18, %19, %20, %21, %22, %23, %24, %25, %26, %27, %28, %29, %30, %31}, {%32, %33, %34, %35}, %36, %37, 1, 1, 0;\n"
    : "+f"(d[0]), "+f"(d[1]), "+f"(d[2]), "+f"(d[3]), "+f"(d[4]), "+f"(d[5]), "+f"(d[6]), "+f"(d[7]), "+f"(d[8]), "+f"(d[9]), "+f"(d[10]), "+f"(d[11]), "+f"(d[12]), "+f"(d[13]), "+f"(d[14]), "+f"(d[15]), "+f"(d[16]), "+f"(d[17]), "+f"(d[18]), "+f"(d[19]), "+f"(d[20]), "+f"(d[21]), "+f"(d[22]), "+f"(d[23]), "+f"(d[24]), "+f"(d[25]), "+f"(d[26]), "+f"(d[27]), "+f"(d[28]), "+f"(d[29]), "+f"(d[30]), "+f"(d[31])
    : "r"(a0), "r"(a1), "r"(a2), "r"(a3), "l"(descB), "n"(SCALE_D));
}
template <int SCALE_D>
__device__ __forceinline__ void wgmma_rs_n24_tb(float (&d)[12], uint32_t a0, uint32_t a1, uint32_t a2, uint32_t a3, uint64_t descB) {
  asm volatile("wgmma.mma_async.sync.aligned.m64n24k16.f32.bf16.bf16 {%0, %1, %2, %3, %4, %5, %6, %7, %8, %9, %10, %11}, {%12, %13, %14, %15}, %16, %17, 1, 1, 1;\n"
    : "+f"(d[0]), "+f"(d[1]), "+f"(d[2]), "+f"(d[3]), "+f"(d[4]), "+f"(d[5]), "+f"(d[6]), "+f"(d[7]), "+f"(d[8]), "+f"(d[9]), "+f"(d[10]), "+f"(d[11])
    : "r"(a0), "r"(a1), "r"(a2), "r"(a3), "l"(descB), "n"(SCALE_D));
}

constexpr uint32_t DHI_SW128_K = (1024 >> 4) | (1u << 30);
constexpr uint32_t DHI_SW64_MN = (512 >> 4) | (2u << 30);
constexpr uint32_t DHI_SW32_MN = (256 >> 4) | (3u << 30);

template <int NC>
__device__ __forceinline__ void store_tile_bf16(const float (&acc)[NC / 2], float scale, uint32_t stage, uint8_t* stage_ptr,
                                                __nv_bfloat16* gdst, int gpitch, int lane) {
  constexpr int PITCH = NC * 2 + 16;
  const uint32_t waddr = stage + ((lane & 7) + ((lane >> 3) & 1) * 8) * PITCH + (lane >> 4) * 16;
#pragma unroll
  for (int j = 0; j < NC / 16; j++) {
    stsm4(waddr + j * 32, pack_bf16(acc[8 * j] * scale, acc[8 * j + 1] * scale), pack_bf16(acc[8 * j + 2] * scale, acc[8 * j + 3] * scale),
          pack_bf16(acc[8 * j + 4] * scale, acc[8 * j + 5] * scale), pack_bf16(acc[8 * j + 6] * scale, acc[8 * j + 7] * scale));
  }
  __syncwarp();
  constexpr int CPR = NC / 8;
#pragma unroll
  for (int i = 0; i < CPR / 2; i++) {
    const int c = i * 32 + lane, r = c / CPR, cc = c % CPR;
    const uint4 v = *reinterpret_cast<const uint4*>(stage_ptr + r * PITCH + cc * 16);
    *reinterpret_cast<uint4*>(gdst + (size_t)r * gpitch + cc * 8) = v;
  }
}

constexpr int K1_STAGES = 4;
constexpr int K1_A_BYTES = 256 * 128;
constexpr int K1_B_BYTES = 64 * 160 * 2;
constexpr int K1_STAGE = K1_A_BYTES + K1_B_BYTES;
constexpr int K1_SMEM = 5 * K1_A_BYTES + 61440 + 1024;
constexpr int KV_STAGES = 5;
constexpr int KVW_OFF = KV_STAGES * K1_A_BYTES;

__global__ void __launch_bounds__(512, 1)
proj_kernel(const __grid_constant__ CUtensorMap tmX, const __grid_constant__ CUtensorMap tmWq, const __grid_constant__ CUtensorMap tmWqkv,
            const __nv_bfloat16* __restrict__ wk, const __nv_bfloat16* __restrict__ wv, const __nv_bfloat16* __restrict__ gate_w) {
  extern __shared__ uint8_t smem_raw[];
  __shared__ __align__(8) uint64_t bar_full[KV_STAGES], bar_empty[KV_STAGES];
  uint8_t* smem = reinterpret_cast<uint8_t*>((reinterpret_cast<uintptr_t>(smem_raw) + 1023) & ~(uintptr_t)1023);
  const uint32_t sbase = smem_u32(smem);
  const int tid = threadIdx.x, warp = tid >> 5, lane = tid & 31;
  const bool is_kv = blockIdx.x >= 128;
  PROF(0, 0);
  pdl_launch();
  if (tid == 0) {
    for (int i = 0; i < KV_STAGES; i++) { mbar_init(smem_u32(&bar_full[i]), 1); mbar_init(smem_u32(&bar_empty[i]), 16); }
    fence_mbar_init();
  }
  __syncthreads();

  if (!is_kv) {
    const int mb = blockIdx.x >> 4, nb = blockIdx.x & 15;
    const CUtensorMap* tw = nb < 4 ? &tmWq : &tmWqkv;
    const int j0 = (nb < 4 ? nb : nb - 4) * 5;
    auto load = [&](int kt) {
      const int s = kt % K1_STAGES;
      const uint32_t fb = smem_u32(&bar_full[s]);
      mbar_expect_tx(fb, K1_STAGE);
      tma_2d(sbase + s * K1_STAGE, &tmX, kt * 64, mb * 256, fb);
      tma_3d(sbase + s * K1_STAGE + K1_A_BYTES, tw, 0, kt * 64, j0, fb);
    };
    if (tid == 0) for (int kt = 0; kt < K1_STAGES; kt++) load(kt);
    {
      const int wg = warp >> 2;
      float acc[80];
#pragma unroll
      for (int i = 0; i < 80; i++) acc[i] = 0.f;
      for (int kt = 0; kt < 10; kt++) {
        const int s = kt % K1_STAGES;
        mbar_wait(smem_u32(&bar_full[s]), (kt / K1_STAGES) & 1);
        const uint32_t alo = ((sbase + s * K1_STAGE + wg * 8192) >> 4) | (1u << 16);
        const uint32_t blo = ((sbase + s * K1_STAGE + K1_A_BYTES) >> 4) | ((4096u >> 4) << 16);
        fence_regs(acc);
        wg_fence();
#pragma unroll
        for (int k = 0; k < 4; k++) wgmma_ss_n160_tb(acc, mkd(alo + k * 2, DHI_SW128_K), mkd(blo + k * 64, DHI_SW64_MN));
        wg_commit();
        if (kt > 0 && kt - 1 + K1_STAGES < 10) {
          wg_wait<1>();
          const uint32_t eb = smem_u32(&bar_empty[(kt - 1) % K1_STAGES]);
          if (lane == 0) mbar_arrive(eb);
          if (tid == 0) { mbar_wait(eb, ((kt - 1) / K1_STAGES) & 1); load(kt - 1 + K1_STAGES); }
          __syncwarp();
        }
      }
      wg_wait<0>();
      fence_regs(acc);
      PROF(0, 1);
      asm volatile("bar.sync %0, 128;" :: "r"(wg + 1) : "memory");
      const int w4 = warp & 3;
      const uint32_t off = w4 * K1_STAGE + wg * 8192;
      const int row0 = mb * 256 + wg * 64 + w4 * 16;
      if (nb < 4) {
        store_tile_bf16<160>(acc, 0.22360679774997896f * 1.4426950408889634f, sbase + off, smem + off,
                             g_q + (size_t)row0 * D_MODEL + nb * 160, D_MODEL, lane);
      } else {
        store_tile_bf16<160>(acc, 1.0f, sbase + off, smem + off, g_qkv + (size_t)row0 * (3 * D_MODEL) + (nb - 4) * 160, 3 * D_MODEL, lane);
      }
    }
  } else {
    const int cb = blockIdx.x - 128;
    auto load = [&](int it) {
      const int s = it % KV_STAGES;
      const uint32_t fb = smem_u32(&bar_full[s]);
      mbar_expect_tx(fb, K1_A_BYTES);
      tma_2d(sbase + s * K1_A_BYTES, &tmX, (it % 10) * 64, cb * 512 + (it / 10) * 256, fb);
    };
    if (tid == 0) for (int it = 0; it < KV_STAGES; it++) load(it);
    {
      if (tid < 320) {
        uint2 a[2][5], b[2][5]; uint32_t gw[2];
#pragma unroll
        for (int r = 0; r < 2; r++) {
          const int k = tid + r * 320;
          const uint2* pk = reinterpret_cast<const uint2*>(wk + k * 20);
          const uint2* pv = reinterpret_cast<const uint2*>(wv + k * 20);
#pragma unroll
          for (int i = 0; i < 5; i++) { a[r][i] = __ldg(pk + i); b[r][i] = __ldg(pv + i); }
          gw[r] = (uint32_t)__bfloat16_as_ushort(gate_w[k]);
        }
#pragma unroll
        for (int r = 0; r < 2; r++) {
          uint4* dst = reinterpret_cast<uint4*>(smem + KVW_OFF + (tid + r * 320) * 16);
          dst[0] = make_uint4(a[r][0].x, a[r][0].y, a[r][1].x, a[r][1].y);
          dst[640] = make_uint4(a[r][2].x, a[r][2].y, a[r][3].x, a[r][3].y);
          dst[1280] = make_uint4(a[r][4].x, a[r][4].y, 0u, 0u);
          dst[1920] = make_uint4(b[r][0].x, b[r][0].y, b[r][1].x, b[r][1].y);
          dst[2560] = make_uint4(b[r][2].x, b[r][2].y, b[r][3].x, b[r][3].y);
          dst[3200] = make_uint4(b[r][4].x, b[r][4].y, gw[r], 0u);
        }
      }
      fence_proxy_async();
      asm volatile("bar.sync 1, 512;" ::: "memory");
      PROF(0, 1);
      const int wg = warp >> 2, w4 = warp & 3, g = lane >> 2, t = lane & 3;
      for (int pass = 0; pass < 2; pass++) {
        float acc[24];
#pragma unroll
        for (int i = 0; i < 24; i++) acc[i] = 0.f;
        for (int kt = 0; kt < 10; kt++) {
          const int it = pass * 10 + kt, s = it % KV_STAGES;
          mbar_wait(smem_u32(&bar_full[s]), (it / KV_STAGES) & 1);
          const uint32_t alo = ((sbase + s * K1_A_BYTES + wg * 8192) >> 4) | (1u << 16);
          const uint32_t blo = ((sbase + KVW_OFF + kt * 1024) >> 4) | ((128u >> 4) << 16);
          fence_regs(acc);
          wg_fence();
#pragma unroll
          for (int k = 0; k < 4; k++) wgmma_ss_n48_tb(acc, mkd(alo + k * 2, DHI_SW128_K), mkd(blo + k * 16, 10240u >> 4));
          wg_commit();
          wg_wait<0>();
          if (it + KV_STAGES < 20) {
            const uint32_t eb = smem_u32(&bar_empty[s]);
            if (lane == 0) mbar_arrive(eb);
            if (tid == 0) { mbar_wait(eb, (it / KV_STAGES) & 1); load(it + KV_STAGES); }
            __syncwarp();
          }
        }
        fence_regs(acc);
        float kmax2 = 0.f, vmax = 0.f;
#pragma unroll
        for (int h = 0; h < 2; h++) {
          const int key = cb * 512 + pass * 256 + wg * 64 + w4 * 16 + g + h * 8;
          const int grp = key >> 7, kk = key & 127;
          const bool poly = (TMASK >> (kk >> 3)) & 1;
          uint8_t* gp = g_kvimg + grp * GRP_BYTES;
          const uint32_t k0 = pack_bf16(acc[2 * h], acc[2 * h + 1]);
          const uint32_t k1 = pack_bf16(acc[4 + 2 * h], acc[5 + 2 * h]);
          uint32_t k2 = pack_bf16(acc[8 + 2 * h], acc[9 + 2 * h]);
          float n2 = bf_lo(k0) * bf_lo(k0) + bf_hi(k0) * bf_hi(k0) + bf_lo(k1) * bf_lo(k1) + bf_hi(k1) * bf_hi(k1);
          if (t < 2) {
            n2 += bf_lo(k2) * bf_lo(k2) + bf_hi(k2) * bf_hi(k2);
            k2 = pack_bf16(bf_lo(k2) * 0.5f, bf_hi(k2) * 0.5f);
          } else if (t == 2) k2 = poly ? pack_bf16(24.f, 2.5f) : pack_bf16(0.5f, 0.f);
          else k2 = poly ? pack_bf16(0.5f, 0.f) : 0u;
          *reinterpret_cast<uint32_t*>(gp + kk * 16 + t * 4) = k0;
          *reinterpret_cast<uint32_t*>(gp + PLANE + kk * 16 + t * 4) = k1;
          *reinterpret_cast<uint32_t*>(gp + 2 * PLANE + kk * 16 + t * 4) = k2;
          n2 += __shfl_xor_sync(0xffffffffu, n2, 1);
          n2 += __shfl_xor_sync(0xffffffffu, n2, 2);
          kmax2 = (n2 > kmax2 || n2 != n2) ? n2 : kmax2;
          uint32_t v0 = pack_bf16(acc[12 + 2 * h], acc[13 + 2 * h]);
          uint32_t v1 = pack_bf16(acc[16 + 2 * h], acc[17 + 2 * h]);
          uint32_t v2 = pack_bf16(acc[20 + 2 * h], acc[21 + 2 * h]);
          float vm = fmaxf(fmaxf(fabsf(bf_lo(v0)), fabsf(bf_hi(v0))), fmaxf(fabsf(bf_lo(v1)), fabsf(bf_hi(v1))));
          if (t < 2) vm = fmaxf(vm, fmaxf(fabsf(bf_lo(v2)), fabsf(bf_hi(v2))));
          else if (t == 2) {
            const float z = acc[20 + 2 * h];
            g_gate[key] = 1.f / (1.f + __expf(-z));
            v2 = 0x00003F80u;
          } else v2 = 0u;
          vmax = fmaxf(vmax, vm);
          if (poly) { v0 ^= 0x80008000u; v1 ^= 0x80008000u; v2 ^= 0x80008000u; }
          uint8_t* vp = gp + 3 * PLANE + (kk >> 3) * 384 + (kk & 7) * 16 + t * 4;
          *reinterpret_cast<uint32_t*>(vp) = v0;
          *reinterpret_cast<uint32_t*>(vp + 128) = v1;
          *reinterpret_cast<uint32_t*>(vp + 256) = v2;
        }
#pragma unroll
        for (int o = 1; o < 32; o <<= 1) {
          const float a = __shfl_xor_sync(0xffffffffu, kmax2, o);
          kmax2 = (a > kmax2 || a != a) ? a : kmax2;
          vmax = fmaxf(vmax, __shfl_xor_sync(0xffffffffu, vmax, o));
        }
        if (lane == 0) { g_kmax2[cb * 32 + pass * 16 + warp] = kmax2; g_vmax[cb * 32 + pass * 16 + warp] = vmax; }
      }
    }
  }
  PROF(0, 3);
}

__device__ __forceinline__ uint32_t ex2_pair_poly(float u0, float u1, uint32_t one2) {
  const uint32_t W = __byte_perm(__float_as_uint(u0), __float_as_uint(u1), 0x6521);
  uint32_t v; asm("lop3.b32 %0, %1, 0x007F007F, %2, 0xEA;" : "=r"(v) : "r"(W), "r"(one2));
  uint32_t L, p;
  asm("fma.rn.bf16x2 %0, %1, %2, %3;" : "=r"(L) : "r"(v), "r"(0x1f961f96u), "r"(0x9fe39fe3u));
  asm("fma.rn.bf16x2 %0, %1, %1, %2;" : "=r"(p) : "r"(L), "r"(0x00f500f5u));
  return W + p;
}
template <int JOFF>
__device__ __forceinline__ void softmax_fast(const float (&S)[32], uint32_t (&P)[16], uint32_t one2) {
#pragma unroll
  for (int i = 0; i < 16; i++) {
    if ((TMASK >> (JOFF + i / 2)) & 1) P[i] = ex2_pair_poly(S[2 * i], S[2 * i + 1], one2);
    else P[i] = pack_bf16(ex2(S[2 * i]), ex2(S[2 * i + 1]));
  }
}
template <int JOFF>
__device__ __forceinline__ void softmax_slow(const float (&S)[32], uint32_t (&P)[16], float (&O)[12], float& m0, float& m1) {
  float a0 = m0, a1 = m1;
#pragma unroll
  for (int j = 0; j < 8; j++) {
    a0 = fmaxf(a0, fmaxf(S[4 * j], S[4 * j + 1]));
    a1 = fmaxf(a1, fmaxf(S[4 * j + 2], S[4 * j + 3]));
  }
  a0 = fmaxf(a0, __shfl_xor_sync(0xffffffffu, a0, 1)); a0 = fmaxf(a0, __shfl_xor_sync(0xffffffffu, a0, 2));
  a1 = fmaxf(a1, __shfl_xor_sync(0xffffffffu, a1, 1)); a1 = fmaxf(a1, __shfl_xor_sync(0xffffffffu, a1, 2));
  const float c0 = ex2(m0 - a0), c1 = ex2(m1 - a1);
  m0 = a0; m1 = a1;
#pragma unroll
  for (int j = 0; j < 3; j++) { O[4 * j] *= c0; O[4 * j + 1] *= c0; O[4 * j + 2] *= c1; O[4 * j + 3] *= c1; }
#pragma unroll
  for (int i = 0; i < 16; i++) {
    const float m = (i & 1) ? a1 : a0;
    const uint32_t p = pack_bf16(ex2(S[2 * i] - m), ex2(S[2 * i + 1] - m));
    P[i] = ((TMASK >> (JOFF + i / 2)) & 1) ? (p ^ 0x80008000u) : p;
  }
}
constexpr uint32_t DHI_KV = 128 >> 4;
__device__ __forceinline__ void issue_qk(float (&S)[32], const uint32_t (&q)[6], uint32_t base) {
  wgmma_rs_n64<0>(S, q[0], q[1], q[2], q[3], mkd(base + ((PLANE >> 4) << 16), DHI_KV));
  wgmma_rs_n64<1>(S, q[4], q[5], q[4], q[5], mkd(base + (2 * PLANE >> 4), DHI_KV));
}
__device__ __forceinline__ void issue_pv(float (&O)[12], const uint32_t (&P)[16], uint32_t vbase) {
#pragma unroll
  for (int kk = 0; kk < 4; kk++)
    wgmma_rs_n24_tb<1>(O, P[4 * kk], P[4 * kk + 1], P[4 * kk + 2], P[4 * kk + 3], mkd(vbase + kk * (768 >> 4), DHI_KV));
}

constexpr uint32_t VOFF = ((3 * PLANE) >> 4) + ((384u >> 4) << 16);
__device__ __forceinline__ void attn_tile_fast(const uint32_t (&q)[6], float (&O)[12], uint32_t sbase, uint32_t bars, bool first, uint32_t one2) {
  float S[32]; uint32_t P[16];
#pragma unroll
  for (int i = 0; i < 32; i++) S[i] = 0.f;
  uint32_t kb = sbase >> 4;
  const uint32_t klast = kb + (NGRP - 1) * (GRP_BYTES >> 4);
  if (first) mbar_wait(bars, 0);
  fence_regs(S); fence_regs(O);
  wg_fence();
  issue_qk(S, q, kb);
  wg_commit();
#pragma unroll 1
  for (int grp = 0; grp < NGRP; grp++) {
    if (first) mbar_wait(bars + 8 * min(grp + 1, NGRP - 1), 0);
    const uint32_t knext = min(kb + (GRP_BYTES >> 4), klast);
    wg_wait<0>();
    fence_regs(S); fence_regs(P); fence_regs(O);
    softmax_fast<0>(S, P, one2);
    fence_regs(S); fence_regs(P); fence_regs(O);
    wg_fence();
    issue_qk(S, q, kb + 64);
    issue_pv(O, P, kb + VOFF);
    wg_commit();
    wg_wait<0>();
    fence_regs(S); fence_regs(P); fence_regs(O);
    softmax_fast<8>(S, P, one2);
    fence_regs(S); fence_regs(P); fence_regs(O);
    wg_fence();
    issue_qk(S, q, knext);
    issue_pv(O, P, kb + VOFF + 4 * (768 >> 4));
    wg_commit();
    kb = knext;
  }
  wg_wait<0>();
  fence_regs(O); fence_regs(S);
}
template <int H>
__device__ __forceinline__ void slow_step(const uint32_t (&q)[6], float (&O)[12], uint32_t kb, float& m0, float& m1) {
  float S[32]; uint32_t P[16];
#pragma unroll
  for (int i = 0; i < 32; i++) S[i] = 0.f;
  fence_regs(S);
  wg_fence();
  issue_qk(S, q, kb + 64 * H);
  wg_commit();
  wg_wait<0>();
  fence_regs(S);
  softmax_slow<8 * H>(S, P, O, m0, m1);
  fence_regs(P); fence_regs(O);
  wg_fence();
  issue_pv(O, P, kb + VOFF + H * 4 * (768 >> 4));
  wg_commit();
  wg_wait<0>();
  fence_regs(O); fence_regs(P);
}
__device__ __noinline__ void attn_tile_slow(const uint32_t (&q)[6], float (&O)[12], uint32_t sbase, uint32_t bars, bool first) {
  float m0 = -INFINITY, m1 = -INFINITY;
#pragma unroll 1
  for (int grp = 0; grp < NGRP; grp++) {
    if (first) mbar_wait(bars + 8 * grp, 0);
    const uint32_t kb = (sbase >> 4) + grp * (GRP_BYTES >> 4);
    slow_step<0>(q, O, kb, m0, m1);
    slow_step<1>(q, O, kb, m0, m1);
  }
}

constexpr int K2_QOFF = NGRP * GRP_BYTES;
constexpr int K2_SMEM = K2_QOFF + 512 * 6 * 4 + 1024;

__device__ __forceinline__ void local_attn_pair(int token, int lane) {
  const __nv_bfloat16* base = g_qkv + (size_t)token * (3 * D_MODEL) + lane * DH;
  float f[20];
  {
    const uint2* p = reinterpret_cast<const uint2*>(base);
#pragma unroll
    for (int i = 0; i < 5; i++) { const uint2 v = p[i]; f[4 * i] = bf_lo(v.x); f[4 * i + 1] = bf_hi(v.x); f[4 * i + 2] = bf_lo(v.y); f[4 * i + 3] = bf_hi(v.y); }
  }
  float sc[8];
  float mx = -INFINITY;
#pragma unroll
  for (int w = 0; w < 8; w++) {
    const bool ok = token - 2 * w >= 0;
    const uint2* p = reinterpret_cast<const uint2*>(base + D_MODEL - (ok ? 2 * w : 0) * (3 * D_MODEL));
    float s = 0.f;
#pragma unroll
    for (int i = 0; i < 5; i++) {
      const uint2 v = p[i];
      s = fmaf(f[4 * i], bf_lo(v.x), s); s = fmaf(f[4 * i + 1], bf_hi(v.x), s);
      s = fmaf(f[4 * i + 2], bf_lo(v.y), s); s = fmaf(f[4 * i + 3], bf_hi(v.y), s);
    }
    s *= 0.22360679774997896f * 1.4426950408889634f;
    sc[w] = ok ? s : -1e9f * 1.4426950408889634f;
    mx = fmaxf(mx, sc[w]);
  }
  float l = 0.f;
#pragma unroll
  for (int w = 0; w < 8; w++) { sc[w] = ex2(sc[w] - mx); l += sc[w]; }
#pragma unroll
  for (int i = 0; i < 20; i++) f[i] = 0.f;
#pragma unroll
  for (int w = 0; w < 8; w++) {
    const bool ok = token - 2 * w >= 0;
    const uint2* p = reinterpret_cast<const uint2*>(base + 2 * D_MODEL - (ok ? 2 * w : token) * (3 * D_MODEL));
#pragma unroll
    for (int i = 0; i < 5; i++) {
      const uint2 v = p[i];
      f[4 * i] = fmaf(sc[w], bf_lo(v.x), f[4 * i]); f[4 * i + 1] = fmaf(sc[w], bf_hi(v.x), f[4 * i + 1]);
      f[4 * i + 2] = fmaf(sc[w], bf_lo(v.y), f[4 * i + 2]); f[4 * i + 3] = fmaf(sc[w], bf_hi(v.y), f[4 * i + 3]);
    }
  }
  const float r = (1.f - g_gate[token]) / l;
  uint2* dst = reinterpret_cast<uint2*>(g_a2 + (size_t)token * (2 * D_MODEL) + D_MODEL + lane * DH);
#pragma unroll
  for (int i = 0; i < 5; i++) dst[i] = make_uint2(pack_bf16(f[4 * i] * r, f[4 * i + 1] * r), pack_bf16(f[4 * i + 2] * r, f[4 * i + 3] * r));
}

__global__ void __launch_bounds__(640, 1)
attn_kernel(uint32_t one2) {
  extern __shared__ uint8_t smem_raw[];
  __shared__ __align__(8) uint64_t bars[NGRP];
  uint8_t* smem = reinterpret_cast<uint8_t*>((reinterpret_cast<uintptr_t>(smem_raw) + 1023) & ~(uintptr_t)1023);
  const uint32_t sbase = smem_u32(smem);
  const int tid = threadIdx.x, wg = tid >> 7, warp = (tid >> 5) & 3, lane = tid & 31, g = lane >> 2, t = lane & 3;
  PROF(1, 0);
  pdl_launch();
  if (tid == 0) {
    for (int i = 0; i < NGRP; i++) mbar_init(smem_u32(&bars[i]), 1);
    fence_mbar_init();
  }
  __syncthreads();
  if (wg == 4) {
    asm volatile("setmaxnreg.dec.sync.aligned.u32 56;");
    pdl_wait();
    if (tid == 512) {
      for (int i = 0; i < 3; i++) {
        mbar_expect_tx(smem_u32(&bars[i]), GRP_BYTES);
        bulk_g2s(sbase + i * GRP_BYTES, g_kvimg + i * GRP_BYTES, GRP_BYTES, smem_u32(&bars[i]));
      }
    }
    __syncwarp();
#pragma unroll 1
    for (int i = 0; i < 4; i++) {
      local_attn_pair(blockIdx.x * 16 + i * 4 + warp, lane);
      if (i == 0 && tid == 512) {
        for (int j = 3; j < NGRP; j++) {
          if (j >= 4) mbar_wait(smem_u32(&bars[j - 4]), 0);
          mbar_expect_tx(smem_u32(&bars[j]), GRP_BYTES);
          bulk_g2s(sbase + j * GRP_BYTES, g_kvimg + j * GRP_BYTES, GRP_BYTES, smem_u32(&bars[j]));
        }
      }
      __syncwarp();
    }
  } else {
    asm volatile("setmaxnreg.inc.sync.aligned.u32 104;");
    pdl_wait();
    PROF(1, 1);
    uint32_t q[6];
    uint32_t* qstash = reinterpret_cast<uint32_t*>(smem + K2_QOFF) + tid;
    const int rowA = (blockIdx.x * 8 + wg) * 64 + warp * 16 + g;
    {
      const uint32_t* r0 = reinterpret_cast<const uint32_t*>(g_q + (size_t)rowA * DH);
      const uint32_t* r1 = r0 + 8 * (DH / 2);
      const uint32_t* s0 = r0 + 256 * (DH / 2);
      const uint32_t* s1 = s0 + 8 * (DH / 2);
      q[0] = r0[t]; q[1] = r1[t]; q[2] = r0[t + 4]; q[3] = r1[t + 4];
      q[4] = t < 2 ? r0[8 + t] : 0u;
      q[5] = t < 2 ? r1[8 + t] : 0u;
      qstash[0] = s0[t]; qstash[512] = s1[t]; qstash[1024] = s0[t + 4]; qstash[1536] = s1[t + 4];
      qstash[2048] = t < 2 ? s0[8 + t] : 0u;
      qstash[2560] = t < 2 ? s1[8 + t] : 0u;
    }
    float kmax2 = 0.f, vmax = 0.f;
#pragma unroll
    for (int i = 0; i < 4; i++) {
      const float a = g_kmax2[lane + 32 * i];
      kmax2 = (a > kmax2 || a != a) ? a : kmax2;
      vmax = fmaxf(vmax, g_vmax[lane + 32 * i]);
    }
#pragma unroll
    for (int o = 1; o < 32; o <<= 1) {
      const float a = __shfl_xor_sync(0xffffffffu, kmax2, o);
      kmax2 = (a > kmax2 || a != a) ? a : kmax2;
      vmax = fmaxf(vmax, __shfl_xor_sync(0xffffffffu, vmax, o));
    }
    const float qlim = (vmax >= 0.00390625f && vmax <= 256.f) ? 9025.f / kmax2 : -1.f;
    PROF(1, 2);
#pragma unroll 1
    for (int it = 0; it < 2; it++) {
      const int row0 = rowA + it * 256;
      if (it == 1) {
#pragma unroll
        for (int i = 0; i < 6; i++) q[i] = qstash[512 * i];
      }
      float n0 = bf_lo(q[0]) * bf_lo(q[0]) + bf_hi(q[0]) * bf_hi(q[0]) + bf_lo(q[2]) * bf_lo(q[2]) + bf_hi(q[2]) * bf_hi(q[2]) +
                 bf_lo(q[4]) * bf_lo(q[4]) + bf_hi(q[4]) * bf_hi(q[4]);
      float n1 = bf_lo(q[1]) * bf_lo(q[1]) + bf_hi(q[1]) * bf_hi(q[1]) + bf_lo(q[3]) * bf_lo(q[3]) + bf_hi(q[3]) * bf_hi(q[3]) +
                 bf_lo(q[5]) * bf_lo(q[5]) + bf_hi(q[5]) * bf_hi(q[5]);
      n0 += __shfl_xor_sync(0xffffffffu, n0, 1); n0 += __shfl_xor_sync(0xffffffffu, n0, 2);
      n1 += __shfl_xor_sync(0xffffffffu, n1, 1); n1 += __shfl_xor_sync(0xffffffffu, n1, 2);
      const bool safe = (n0 <= qlim) && (n1 <= qlim);
      uint32_t unsafe_any;
      asm volatile("{\n.reg .pred p, r;\nsetp.eq.u32 p, %1, 0;\nbarrier.cta.red.or.pred r, %2, 128, p;\nselp.u32 %0, 1, 0, r;\n}\n"
                   : "=r"(unsafe_any) : "r"((uint32_t)safe), "r"(wg + 1) : "memory");
      float O[12];
#pragma unroll
      for (int i = 0; i < 12; i++) O[i] = 0.f;
      if (!unsafe_any) {
        if (t >= 2) { q[4] = q[5] = (t == 2) ? 0x3F804100u : 0x00003B80u; }
        attn_tile_fast(q, O, sbase, smem_u32(&bars[0]), it == 0, one2);
      } else {
        attn_tile_slow(q, O, sbase, smem_u32(&bars[0]), it == 0);
      }
      const float l0 = __shfl_sync(0xffffffffu, O[8], (lane & ~3) | 2);
      const float l1 = __shfl_sync(0xffffffffu, O[10], (lane & ~3) | 2);
      const int tok = row0 >> 5;
      const float gt = g_gate[tok];
      const float i0 = gt / l0, i1 = gt / l1;
      uint32_t* o0 = reinterpret_cast<uint32_t*>(g_a2 + (size_t)tok * (2 * D_MODEL) + (row0 & 31) * DH);
      uint32_t* o1 = o0 + 8 * (DH / 2);
      o0[t] = pack_bf16(O[0] * i0, O[1] * i0); o1[t] = pack_bf16(O[2] * i1, O[3] * i1);
      o0[t + 4] = pack_bf16(O[4] * i0, O[5] * i0); o1[t + 4] = pack_bf16(O[6] * i1, O[7] * i1);
      if (t < 2) { o0[t + 8] = pack_bf16(O[8] * i0, O[9] * i0); o1[t + 8] = pack_bf16(O[10] * i1, O[11] * i1); }
    }
    PROF(1, 3);
  }
}

constexpr int K3_STAGES = 8;
constexpr int K3_A_BYTES = 128 * 128;
constexpr int K3_B_BYTES = 64 * 80 * 2;
constexpr int K3_STAGE = K3_A_BYTES + K3_B_BYTES;
constexpr int K3_SMEM = K3_STAGES * K3_STAGE + 1024;

__global__ void __launch_bounds__(288, 1)
out_kernel(const __grid_constant__ CUtensorMap tmA2, const __grid_constant__ CUtensorMap tmWoA, const __grid_constant__ CUtensorMap tmWoB,
           __nv_bfloat16* __restrict__ out) {
  extern __shared__ uint8_t smem_raw[];
  __shared__ __align__(8) uint64_t bar_full[K3_STAGES], bar_empty[K3_STAGES];
  uint8_t* smem = reinterpret_cast<uint8_t*>((reinterpret_cast<uintptr_t>(smem_raw) + 1023) & ~(uintptr_t)1023);
  const uint32_t sbase = smem_u32(smem);
  const int tid = threadIdx.x, warp = tid >> 5, lane = tid & 31;
  const int mb = blockIdx.x >> 3, nb = blockIdx.x & 7;
  PROF(2, 0);
  if (tid == 0) {
    for (int i = 0; i < K3_STAGES; i++) { mbar_init(smem_u32(&bar_full[i]), 2); mbar_init(smem_u32(&bar_empty[i]), 8); }
    fence_mbar_init();
  }
  __syncthreads();
  if (warp == 8) {
    if (lane == 0) {
      for (int kt = 0; kt < K3_STAGES; kt++) {
        const uint32_t fb = smem_u32(&bar_full[kt]);
        mbar_expect_tx(fb, K3_B_BYTES);
        tma_3d(sbase + kt * K3_STAGE + K3_A_BYTES, &tmWoA, 0, kt * 64, nb * 5, fb);
      }
      pdl_wait();
      for (int kt = 0; kt < 20; kt++) {
        const int s = kt % K3_STAGES;
        const uint32_t fb = smem_u32(&bar_full[s]);
        if (kt >= K3_STAGES) {
          mbar_wait(smem_u32(&bar_empty[s]), ((kt / K3_STAGES) - 1) & 1);
          mbar_expect_tx(fb, K3_B_BYTES);
          tma_3d(sbase + s * K3_STAGE + K3_A_BYTES, kt < 10 ? &tmWoA : &tmWoB, 0, (kt % 10) * 64, nb * 5, fb);
        }
        mbar_expect_tx(fb, K3_A_BYTES);
        tma_2d(sbase + s * K3_STAGE, &tmA2, kt * 64, mb * 128, fb);
      }
    }
  } else {
    const int wg = warp >> 2;
    float acc[40];
#pragma unroll
    for (int i = 0; i < 40; i++) acc[i] = 0.f;
    for (int kt = 0; kt < 20; kt++) {
      const int s = kt % K3_STAGES;
      mbar_wait(smem_u32(&bar_full[s]), (kt / K3_STAGES) & 1);
      if (kt == 0) PROF(2, 1);
      const uint32_t alo = ((sbase + s * K3_STAGE + wg * 8192) >> 4) | (1u << 16);
      const uint32_t blo = ((sbase + s * K3_STAGE + K3_A_BYTES) >> 4) | ((2048u >> 4) << 16);
      fence_regs(acc);
      wg_fence();
#pragma unroll
      for (int k = 0; k < 4; k++) wgmma_ss_n80_tb(acc, mkd(alo + k * 2, DHI_SW128_K), mkd(blo + k * 32, DHI_SW32_MN));
      wg_commit();
      if (kt > 0) {
        wg_wait<1>();
        if (lane == 0) mbar_arrive(smem_u32(&bar_empty[(kt - 1) % K3_STAGES]));
      }
    }
    wg_wait<0>();
    fence_regs(acc);
    PROF(2, 2);
    asm volatile("bar.sync %0, 128;" :: "r"(wg + 1) : "memory");
    const int w4 = warp & 3;
    const uint32_t off = w4 * K3_STAGE + wg * 8192;
    const int row0 = mb * 128 + wg * 64 + w4 * 16;
    store_tile_bf16<80>(acc, 1.0f, sbase + off, smem + off, out + (size_t)row0 * D_MODEL + nb * 80, D_MODEL, lane);
    PROF(2, 3);
  }
}

typedef CUresult (*EncodeFn)(CUtensorMap*, CUtensorMapDataType, cuuint32_t, void*, const cuuint64_t*, const cuuint64_t*,
                             const cuuint32_t*, const cuuint32_t*, CUtensorMapInterleave, CUtensorMapSwizzle,
                             CUtensorMapL2promotion, CUtensorMapFloatOOBfill);

void make_map(EncodeFn fn, CUtensorMap* tm, const void* ptr, int rank, const cuuint64_t* dims, const cuuint64_t* strides,
              const cuuint32_t* box, CUtensorMapSwizzle sw) {
  const cuuint32_t es[3] = {1, 1, 1};
  fn(tm, CU_TENSOR_MAP_DATA_TYPE_BFLOAT16, rank, const_cast<void*>(ptr), dims, strides, box, es, CU_TENSOR_MAP_INTERLEAVE_NONE, sw,
     CU_TENSOR_MAP_L2_PROMOTION_L2_256B, CU_TENSOR_MAP_FLOAT_OOB_FILL_NONE);
}
void map_a(EncodeFn fn, CUtensorMap* tm, const void* p, int rows, int cols, int box_rows) {
  const cuuint64_t dims[2] = {(cuuint64_t)cols, (cuuint64_t)rows};
  const cuuint64_t str[1] = {(cuuint64_t)cols * 2};
  const cuuint32_t box[2] = {64, (cuuint32_t)box_rows};
  make_map(fn, tm, p, 2, dims, str, box, CU_TENSOR_MAP_SWIZZLE_128B);
}
void map_w(EncodeFn fn, CUtensorMap* tm, const void* p, int K, int N, int atom, CUtensorMapSwizzle sw) {
  const cuuint64_t dims[3] = {(cuuint64_t)atom, (cuuint64_t)K, (cuuint64_t)(N / atom)};
  const cuuint64_t str[2] = {(cuuint64_t)N * 2, (cuuint64_t)atom * 2};
  const cuuint32_t box[3] = {(cuuint32_t)atom, 64, 5};
  make_map(fn, tm, p, 3, dims, str, box, sw);
}

template <typename... KArgs, typename... Args>
void launch(void (*kern)(KArgs...), int grid, int block, int smem, bool pdl, Args... args) {
  cudaLaunchConfig_t cfg = {};
  cfg.gridDim = dim3(grid); cfg.blockDim = dim3(block); cfg.dynamicSmemBytes = smem; cfg.stream = cudaStreamPerThread;
  cudaLaunchAttribute at[1];
  at[0].id = cudaLaunchAttributeProgrammaticStreamSerialization;
  at[0].val.programmaticStreamSerializationAllowed = 1;
  cfg.attrs = at; cfg.numAttrs = pdl ? 1 : 0;
  cudaLaunchKernelEx(&cfg, kern, KArgs(args)...);
}

}

extern "C" void kernel_launch(void* const* d_in, const int* in_sizes, int n_in, void* d_out, int out_size) {
  (void)in_sizes; (void)n_in; (void)out_size;
  const __nv_bfloat16* x = (const __nv_bfloat16*)d_in[0];
  const __nv_bfloat16* wq = (const __nv_bfloat16*)d_in[1];
  const __nv_bfloat16* wk = (const __nv_bfloat16*)d_in[2];
  const __nv_bfloat16* wv = (const __nv_bfloat16*)d_in[3];
  const __nv_bfloat16* woA = (const __nv_bfloat16*)d_in[4];
  const __nv_bfloat16* wqkv = (const __nv_bfloat16*)d_in[6];
  const __nv_bfloat16* woB = (const __nv_bfloat16*)d_in[7];
  const __nv_bfloat16* gate_w = (const __nv_bfloat16*)d_in[8];

  static EncodeFn enc = nullptr;
  static void* a2_ptr = nullptr;
  if (!enc) {
    void* fp = nullptr;
    cudaDriverEntryPointQueryResult qr;
    cudaGetDriverEntryPoint("cuTensorMapEncodeTiled", &fp, cudaEnableDefault, &qr);
    enc = (EncodeFn)fp;
    cudaGetSymbolAddress(&a2_ptr, g_a2);
    cudaFuncSetAttribute(proj_kernel, cudaFuncAttributeMaxDynamicSharedMemorySize, K1_SMEM);
    cudaFuncSetAttribute(attn_kernel, cudaFuncAttributeMaxDynamicSharedMemorySize, K2_SMEM);
    cudaFuncSetAttribute(out_kernel, cudaFuncAttributeMaxDynamicSharedMemorySize, K3_SMEM);
  }
  CUtensorMap tmX, tmWq, tmWqkv, tmA2, tmWoA, tmWoB;
  map_a(enc, &tmX, x, S_LEN, D_MODEL, 256);
  map_w(enc, &tmWq, wq, D_MODEL, D_MODEL, 32, CU_TENSOR_MAP_SWIZZLE_64B);
  map_w(enc, &tmWqkv, wqkv, D_MODEL, 3 * D_MODEL, 32, CU_TENSOR_MAP_SWIZZLE_64B);
  map_a(enc, &tmA2, a2_ptr, S_LEN, 2 * D_MODEL, 128);
  map_w(enc, &tmWoA, woA, D_MODEL, D_MODEL, 16, CU_TENSOR_MAP_SWIZZLE_32B);
  map_w(enc, &tmWoB, woB, D_MODEL, D_MODEL, 16, CU_TENSOR_MAP_SWIZZLE_32B);

  launch(proj_kernel, 132, 512, K1_SMEM, false, tmX, tmWq, tmWqkv, wk, wv, gate_w);
  launch(attn_kernel, 128, 640, K2_SMEM, true, 0x3F803F80u);
  launch(out_kernel, 128, 288, K3_SMEM, true, tmA2, tmWoA, tmWoB, (__nv_bfloat16*)d_out);
}
```

```cpp
#include <cuda_runtime.h>
#include <cuda_bf16.h>
#include <cuda.h>
#include <stdint.h>

namespace {

constexpr int S_LEN = 2048, D_MODEL = 640, DH = 20;

constexpr int GRP = 128;
constexpr int PLANE = GRP * 16;
constexpr int GRP_BYTES = GRP * 16 * 6;
constexpr int NGRP = S_LEN / GRP;
constexpr uint32_t TMASK = 0x6DB6u;

__device__ __align__(1024) __nv_bfloat16 g_q[S_LEN * D_MODEL];
__device__ __align__(1024) __nv_bfloat16 g_qkv[S_LEN * 3 * D_MODEL];
__device__ __align__(1024) __nv_bfloat16 g_a2[S_LEN * 2 * D_MODEL];
__device__ __align__(1024) uint8_t g_kvimg[NGRP * GRP_BYTES];
__device__ float g_gate[S_LEN];
__device__ float g_kmax2[128];
__device__ float g_vmax[128];
__device__ unsigned int g_done[128];

#define PROF(k, slot)
__device__ __forceinline__ uint32_t smem_u32(const void* p) { return (uint32_t)__cvta_generic_to_shared(p); }
__device__ __forceinline__ uint64_t mkd(uint32_t lo, uint32_t hi) {
  uint64_t d; asm("mov.b64 %0, {%1, %2};" : "=l"(d) : "r"(lo), "r"(hi)); return d;
}
__device__ __forceinline__ void wg_fence() { asm volatile("wgmma.fence.sync.aligned;" ::: "memory"); }
__device__ __forceinline__ void wg_commit() { asm volatile("wgmma.commit_group.sync.aligned;" ::: "memory"); }
template <int N> __device__ __forceinline__ void wg_wait() { asm volatile("wgmma.wait_group.sync.aligned %0;" :: "n"(N) : "memory"); }
template <int N> __device__ __forceinline__ void fence_regs(float (&d)[N]) {
#pragma unroll
  for (int i = 0; i < N; i++) asm volatile("" : "+f"(d[i]) :: "memory");
}
template <int N> __device__ __forceinline__ void fence_regs(uint32_t (&d)[N]) {
#pragma unroll
  for (int i = 0; i < N; i++) asm volatile("" : "+r"(d[i]) :: "memory");
}
__device__ __forceinline__ void mbar_init(uint32_t bar, uint32_t cnt) { asm volatile("mbarrier.init.shared::cta.b64 [%0], %1;" :: "r"(bar), "r"(cnt)); }
__device__ __forceinline__ void mbar_expect_tx(uint32_t bar, uint32_t bytes) {
  asm volatile("mbarrier.arrive.expect_tx.shared::cta.b64 _, [%0], %1;" :: "r"(bar), "r"(bytes) : "memory");
}
__device__ __forceinline__ void mbar_arrive(uint32_t bar) { asm volatile("mbarrier.arrive.shared::cta.b64 _, [%0];" :: "r"(bar) : "memory"); }
__device__ __forceinline__ void mbar_wait(uint32_t bar, uint32_t parity) {
  asm volatile("{\n.reg .pred p;\nWAIT_%=:\nmbarrier.try_wait.parity.shared::cta.b64 p, [%0], %1;\n@p bra DONE_%=;\nbra WAIT_%=;\nDONE_%=:\n}\n"
               :: "r"(bar), "r"(parity) : "memory");
}
__device__ __forceinline__ void fence_mbar_init() { asm volatile("fence.mbarrier_init.release.cluster;" ::: "memory"); }
__device__ __forceinline__ void fence_proxy_async() { asm volatile("fence.proxy.async.shared::cta;" ::: "memory"); }
__device__ __forceinline__ void bulk_g2s(uint32_t dst, const void* src, uint32_t bytes, uint32_t bar) {
  asm volatile("cp.async.bulk.shared::cluster.global.mbarrier::complete_tx::bytes [%0], [%1], %2, [%3];"
               :: "r"(dst), "l"(src), "r"(bytes), "r"(bar) : "memory");
}
__device__ __forceinline__ void tma_2d(uint32_t dst, const CUtensorMap* tm, int c0, int c1, uint32_t bar) {
  asm volatile("cp.async.bulk.tensor.2d.shared::cluster.global.mbarrier::complete_tx::bytes [%0], [%1, {%3, %4}], [%2];"
               :: "r"(dst), "l"((uint64_t)tm), "r"(bar), "r"(c0), "r"(c1) : "memory");
}
__device__ __forceinline__ void tma_3d(uint32_t dst, const CUtensorMap* tm, int c0, int c1, int c2, uint32_t bar) {
  asm volatile("cp.async.bulk.tensor.3d.shared::cluster.global.mbarrier::complete_tx::bytes [%0], [%1, {%3, %4, %5}], [%2];"
               :: "r"(dst), "l"((uint64_t)tm), "r"(bar), "r"(c0), "r"(c1), "r"(c2) : "memory");
}
__device__ __forceinline__ void tma_2d_mc(uint32_t dst, const CUtensorMap* tm, int c0, int c1, uint32_t bar, uint16_t mask) {
  asm volatile("cp.async.bulk.tensor.2d.shared::cluster.global.mbarrier::complete_tx::bytes.multicast::cluster [%0], [%1, {%3, %4}], [%2], %5;"
               :: "r"(dst), "l"((uint64_t)tm), "r"(bar), "r"(c0), "r"(c1), "h"(mask) : "memory");
}
__device__ __forceinline__ void mbar_arrive_remote(uint32_t bar, uint32_t rank) {
  asm volatile("{\n.reg .b32 ra;\nmapa.shared::cluster.u32 ra, %0, %1;\nmbarrier.arrive.release.cluster.shared::cluster.b64 _, [ra];\n}\n"
               :: "r"(bar), "r"(rank) : "memory");
}
__device__ __forceinline__ void mbar_wait_cluster(uint32_t bar, uint32_t parity) {
  asm volatile("{\n.reg .pred p;\nWAIT_%=:\nmbarrier.try_wait.parity.acquire.cluster.shared::cta.b64 p, [%0], %1;\n@p bra DONE_%=;\nbra WAIT_%=;\nDONE_%=:\n}\n"
               :: "r"(bar), "r"(parity) : "memory");
}
__device__ __forceinline__ void cluster_arrive() { asm volatile("barrier.cluster.arrive.release.aligned;" ::: "memory"); }
__device__ __forceinline__ void cluster_wait() { asm volatile("barrier.cluster.wait.acquire.aligned;" ::: "memory"); }
__device__ __forceinline__ void prefetch_tmap(const CUtensorMap* tm) { asm volatile("prefetch.tensormap [%0];" :: "l"((uint64_t)tm) : "memory"); }
__device__ __forceinline__ void pdl_wait() { asm volatile("griddepcontrol.wait;" ::: "memory"); }
__device__ __forceinline__ void pdl_launch() { asm volatile("griddepcontrol.launch_dependents;" ::: "memory"); }
__device__ __forceinline__ float ex2(float x) { float y; asm("ex2.approx.ftz.f32 %0, %1;" : "=f"(y) : "f"(x)); return y; }
__device__ __forceinline__ uint32_t pack_bf16(float lo, float hi) {
  uint32_t r; asm("cvt.rn.bf16x2.f32 %0, %1, %2;" : "=r"(r) : "f"(hi), "f"(lo)); return r;
}
__device__ __forceinline__ float bf_lo(uint32_t x) { return __uint_as_float(x << 16); }
__device__ __forceinline__ float bf_hi(uint32_t x) { return __uint_as_float(x & 0xffff0000u); }
__device__ __forceinline__ void stsm4(uint32_t addr, uint32_t r0, uint32_t r1, uint32_t r2, uint32_t r3) {
  asm volatile("stmatrix.sync.aligned.m8n8.x4.shared.b16 [%0], {%1, %2, %3, %4};" :: "r"(addr), "r"(r0), "r"(r1), "r"(r2), "r"(r3) : "memory");
}

__device__ __forceinline__ void wgmma_ss_n160_tb(float (&d)[80], uint64_t descA, uint64_t descB) {
  asm volatile("wgmma.mma_async.sync.aligned.m64n160k16.f32.bf16.bf16 {%0, %1, %2, %3, %4, %5, %6, %7, %8, %9, %10, %11, %12, %13, %14, %15, %16, %17, %18, %19, %20, %21, %22, %23, %24, %25, %26, %27, %28, %29, %30, %31, %32, %33, %34, %35, %36, %37, %38, %39, %40, %41, %42, %43, %44, %45, %46, %47, %48, %49, %50, %51, %52, %53, %54, %55, %56, %57, %58, %59, %60, %61, %62, %63, %64, %65, %66, %67, %68, %69, %70, %71, %72, %73, %74, %75, %76, %77, %78, %79}, %80, %81, 1, 1, 1, 0, 1;\n"
    : "+f"(d[0]), "+f"(d[1]), "+f"(d[2]), "+f"(d[3]), "+f"(d[4]), "+f"(d[5]), "+f"(d[6]), "+f"(d[7]), "+f"(d[8]), "+f"(d[9]), "+f"(d[10]), "+f"(d[11]), "+f"(d[12]), "+f"(d[13]), "+f"(d[14]), "+f"(d[15]), "+f"(d[16]), "+f"(d[17]), "+f"(d[18]), "+f"(d[19]), "+f"(d[20]), "+f"(d[21]), "+f"(d[22]), "+f"(d[23]), "+f"(d[24]), "+f"(d[25]), "+f"(d[26]), "+f"(d[27]), "+f"(d[28]), "+f"(d[29]), "+f"(d[30]), "+f"(d[31]), "+f"(d[32]), "+f"(d[33]), "+f"(d[34]), "+f"(d[35]), "+f"(d[36]), "+f"(d[37]), "+f"(d[38]), "+f"(d[39]), "+f"(d[40]), "+f"(d[41]), "+f"(d[42]), "+f"(d[43]), "+f"(d[44]), "+f"(d[45]), "+f"(d[46]), "+f"(d[47]), "+f"(d[48]), "+f"(d[49]), "+f"(d[50]), "+f"(d[51]), "+f"(d[52]), "+f"(d[53]), "+f"(d[54]), "+f"(d[55]), "+f"(d[56]), "+f"(d[57]), "+f"(d[58]), "+f"(d[59]), "+f"(d[60]), "+f"(d[61]), "+f"(d[62]), "+f"(d[63]), "+f"(d[64]), "+f"(d[65]), "+f"(d[66]), "+f"(d[67]), "+f"(d[68]), "+f"(d[69]), "+f"(d[70]), "+f"(d[71]), "+f"(d[72]), "+f"(d[73]), "+f"(d[74]), "+f"(d[75]), "+f"(d[76]), "+f"(d[77]), "+f"(d[78]), "+f"(d[79])
    : "l"(descA), "l"(descB));
}
__device__ __forceinline__ void wgmma_ss_n48_tb(float (&d)[24], uint64_t descA, uint64_t descB) {
  asm volatile("wgmma.mma_async.sync.aligned.m64n48k16.f32.bf16.bf16 {%0, %1, %2, %3, %4, %5, %6, %7, %8, %9, %10, %11, %12, %13, %14, %15, %16, %17, %18, %19, %20, %21, %22, %23}, %24, %25, 1, 1, 1, 0, 1;\n"
    : "+f"(d[0]), "+f"(d[1]), "+f"(d[2]), "+f"(d[3]), "+f"(d[4]), "+f"(d[5]), "+f"(d[6]), "+f"(d[7]), "+f"(d[8]), "+f"(d[9]), "+f"(d[10]), "+f"(d[11]), "+f"(d[12]), "+f"(d[13]), "+f"(d[14]), "+f"(d[15]), "+f"(d[16]), "+f"(d[17]), "+f"(d[18]), "+f"(d[19]), "+f"(d[20]), "+f"(d[21]), "+f"(d[22]), "+f"(d[23])
    : "l"(descA), "l"(descB));
}
__device__ __forceinline__ void wgmma_ss_n80_tb(float (&d)[40], uint64_t descA, uint64_t descB) {
  asm volatile("wgmma.mma_async.sync.aligned.m64n80k16.f32.bf16.bf16 {%0, %1, %2, %3, %4, %5, %6, %7, %8, %9, %10, %11, %12, %13, %14, %15, %16, %17, %18, %19, %20, %21, %22, %23, %24, %25, %26, %27, %28, %29, %30, %31, %32, %33, %34, %35, %36, %37, %38, %39}, %40, %41, 1, 1, 1, 0, 1;\n"
    : "+f"(d[0]), "+f"(d[1]), "+f"(d[2]), "+f"(d[3]), "+f"(d[4]), "+f"(d[5]), "+f"(d[6]), "+f"(d[7]), "+f"(d[8]), "+f"(d[9]), "+f"(d[10]), "+f"(d[11]), "+f"(d[12]), "+f"(d[13]), "+f"(d[14]), "+f"(d[15]), "+f"(d[16]), "+f"(d[17]), "+f"(d[18]), "+f"(d[19]), "+f"(d[20]), "+f"(d[21]), "+f"(d[22]), "+f"(d[23]), "+f"(d[24]), "+f"(d[25]), "+f"(d[26]), "+f"(d[27]), "+f"(d[28]), "+f"(d[29]), "+f"(d[30]), "+f"(d[31]), "+f"(d[32]), "+f"(d[33]), "+f"(d[34]), "+f"(d[35]), "+f"(d[36]), "+f"(d[37]), "+f"(d[38]), "+f"(d[39])
    : "l"(descA), "l"(descB));
}
template <int SCALE_D>
__device__ __forceinline__ void wgmma_rs_n64(float (&d)[32], uint32_t a0, uint32_t a1, uint32_t a2, uint32_t a3, uint64_t descB) {
  asm volatile("wgmma.mma_async.sync.aligned.m64n64k16.f32.bf16.bf16 {%0, %1, %2, %3, %4, %5, %6, %7, %8, %9, %10, %11, %12, %13, %14, %15, %16, %17, %18, %19, %20, %21, %22, %23, %24, %25, %26, %27, %28, %29, %30, %31}, {%32, %33, %34, %35}, %36, %37, 1, 1, 0;\n"
    : "+f"(d[0]), "+f"(d[1]), "+f"(d[2]), "+f"(d[3]), "+f"(d[4]), "+f"(d[5]), "+f"(d[6]), "+f"(d[7]), "+f"(d[8]), "+f"(d[9]), "+f"(d[10]), "+f"(d[11]), "+f"(d[12]), "+f"(d[13]), "+f"(d[14]), "+f"(d[15]), "+f"(d[16]), "+f"(d[17]), "+f"(d[18]), "+f"(d[19]), "+f"(d[20]), "+f"(d[21]), "+f"(d[22]), "+f"(d[23]), "+f"(d[24]), "+f"(d[25]), "+f"(d[26]), "+f"(d[27]), "+f"(d[28]), "+f"(d[29]), "+f"(d[30]), "+f"(d[31])
    : "r"(a0), "r"(a1), "r"(a2), "r"(a3), "l"(descB), "n"(SCALE_D));
}
template <int SCALE_D>
__device__ __forceinline__ void wgmma_rs_n24_tb(float (&d)[12], uint32_t a0, uint32_t a1, uint32_t a2, uint32_t a3, uint64_t descB) {
  asm volatile("wgmma.mma_async.sync.aligned.m64n24k16.f32.bf16.bf16 {%0, %1, %2, %3, %4, %5, %6, %7, %8, %9, %10, %11}, {%12, %13, %14, %15}, %16, %17, 1, 1, 1;\n"
    : "+f"(d[0]), "+f"(d[1]), "+f"(d[2]), "+f"(d[3]), "+f"(d[4]), "+f"(d[5]), "+f"(d[6]), "+f"(d[7]), "+f"(d[8]), "+f"(d[9]), "+f"(d[10]), "+f"(d[11])
    : "r"(a0), "r"(a1), "r"(a2), "r"(a3), "l"(descB), "n"(SCALE_D));
}

constexpr uint32_t DHI_SW128_K = (1024 >> 4) | (1u << 30);
constexpr uint32_t DHI_SW64_MN = (512 >> 4) | (2u << 30);
constexpr uint32_t DHI_SW32_MN = (256 >> 4) | (3u << 30);

template <int NC>
__device__ __forceinline__ void store_tile_bf16(const float (&acc)[NC / 2], float scale, uint32_t stage, uint8_t* stage_ptr,
                                                __nv_bfloat16* gdst, int gpitch, int lane) {
  constexpr int PITCH = NC * 2 + 16;
  const uint32_t waddr = stage + ((lane & 7) + ((lane >> 3) & 1) * 8) * PITCH + (lane >> 4) * 16;
#pragma unroll
  for (int j = 0; j < NC / 16; j++) {
    stsm4(waddr + j * 32, pack_bf16(acc[8 * j] * scale, acc[8 * j + 1] * scale), pack_bf16(acc[8 * j + 2] * scale, acc[8 * j + 3] * scale),
          pack_bf16(acc[8 * j + 4] * scale, acc[8 * j + 5] * scale), pack_bf16(acc[8 * j + 6] * scale, acc[8 * j + 7] * scale));
  }
  __syncwarp();
  constexpr int CPR = NC / 8;
#pragma unroll
  for (int i = 0; i < CPR / 2; i++) {
    const int c = i * 32 + lane, r = c / CPR, cc = c % CPR;
    const uint4 v = *reinterpret_cast<const uint4*>(stage_ptr + r * PITCH + cc * 16);
    *reinterpret_cast<uint4*>(gdst + (size_t)r * gpitch + cc * 8) = v;
  }
}

constexpr int K1_STAGES = 4;
constexpr int K1_A_BYTES = 256 * 128;
constexpr int K1_B_BYTES = 64 * 160 * 2;
constexpr int K1_STAGE = K1_A_BYTES + K1_B_BYTES;
constexpr int K1_SMEM = 5 * K1_A_BYTES + 61440 + 1024;
constexpr int KV_STAGES = 5;
constexpr int KVW_OFF = KV_STAGES * K1_A_BYTES;

__global__ void __cluster_dims__(4, 1, 1) __launch_bounds__(512, 1)
proj_kernel(const __grid_constant__ CUtensorMap tmX, const __grid_constant__ CUtensorMap tmX64, const __grid_constant__ CUtensorMap tmWq, const __grid_constant__ CUtensorMap tmWqkv,
            const __nv_bfloat16* __restrict__ wk, const __nv_bfloat16* __restrict__ wv, const __nv_bfloat16* __restrict__ gate_w) {
  extern __shared__ uint8_t smem_raw[];
  __shared__ __align__(8) uint64_t bar_full[KV_STAGES], bar_empty[KV_STAGES];
  uint8_t* smem = reinterpret_cast<uint8_t*>((reinterpret_cast<uintptr_t>(smem_raw) + 1023) & ~(uintptr_t)1023);
  const uint32_t sbase = smem_u32(smem);
  const uint32_t dbase = sbase & 0x3FFFFu;
  const int tid = threadIdx.x, warp = tid >> 5, lane = tid & 31;
  const bool is_kv = blockIdx.x >= 128;
  PROF(0, 0);
  pdl_launch();
  if (tid == 0) {
    for (int i = 0; i < KV_STAGES; i++) { mbar_init(smem_u32(&bar_full[i]), 1); mbar_init(smem_u32(&bar_empty[i]), 16); }
    fence_mbar_init();
    if (!is_kv) g_done[blockIdx.x] = 0u;
  }
  cluster_arrive();
  cluster_wait();

  if (!is_kv) {
    const int mb = blockIdx.x >> 4, nb = blockIdx.x & 15;
    const CUtensorMap* tw = nb < 4 ? &tmWq : &tmWqkv;
    const int j0 = (nb < 4 ? nb : nb - 4) * 5;
    auto load = [&](int kt) {
      const int s = kt % K1_STAGES;
      const uint32_t fb = smem_u32(&bar_full[s]);
      mbar_expect_tx(fb, K1_STAGE);
      tma_2d_mc(sbase + s * K1_STAGE + (nb & 3) * 8192, &tmX64, kt * 64, mb * 256 + (nb & 3) * 64, fb, (uint16_t)0xF);
      tma_3d(sbase + s * K1_STAGE + K1_A_BYTES, tw, 0, kt * 64, j0, fb);
    };
    if (tid == 0) for (int kt = 0; kt < K1_STAGES; kt++) load(kt);
    {
      const int wg = warp >> 2;
      float acc[80];
#pragma unroll
      for (int i = 0; i < 80; i++) acc[i] = 0.f;
      for (int kt = 0; kt < 10; kt++) {
        const int s = kt % K1_STAGES;
        mbar_wait(smem_u32(&bar_full[s]), (kt / K1_STAGES) & 1);
        const uint32_t alo = ((dbase + s * K1_STAGE + wg * 8192) >> 4) | (1u << 16);
        const uint32_t blo = ((dbase + s * K1_STAGE + K1_A_BYTES) >> 4) | ((4096u >> 4) << 16);
        fence_regs(acc);
        wg_fence();
#pragma unroll
        for (int k = 0; k < 4; k++) wgmma_ss_n160_tb(acc, mkd(alo + k * 2, DHI_SW128_K), mkd(blo + k * 64, DHI_SW64_MN));
        wg_commit();
        if (kt > 0 && kt - 1 + K1_STAGES < 10) {
          wg_wait<1>();
          const uint32_t eb = smem_u32(&bar_empty[(kt - 1) % K1_STAGES]);
          if (lane == 1) mbar_arrive_remote(eb, warp & 3);
          if (tid == 0) { mbar_wait_cluster(eb, ((kt - 1) / K1_STAGES) & 1); load(kt - 1 + K1_STAGES); }
          __syncwarp();
        }
      }
      wg_wait<0>();
      fence_regs(acc);
      PROF(0, 1);
      asm volatile("bar.sync %0, 128;" :: "r"(wg + 1) : "memory");
      const int w4 = warp & 3;
      const uint32_t off = w4 * K1_STAGE + wg * 8192;
      const int row0 = mb * 256 + wg * 64 + w4 * 16;
      if (nb < 4) {
        store_tile_bf16<160>(acc, 0.22360679774997896f * 1.4426950408889634f, sbase + off, smem + off,
                             g_q + (size_t)row0 * D_MODEL + nb * 160, D_MODEL, lane);
      } else {
        store_tile_bf16<160>(acc, 1.0f, sbase + off, smem + off, g_qkv + (size_t)row0 * (3 * D_MODEL) + (nb - 4) * 160, 3 * D_MODEL, lane);
      }
    }
  } else {
    const int cb = blockIdx.x - 128;
    auto load = [&](int it) {
      const int s = it % KV_STAGES;
      const uint32_t fb = smem_u32(&bar_full[s]);
      mbar_expect_tx(fb, K1_A_BYTES);
      tma_2d(sbase + s * K1_A_BYTES, &tmX, (it % 10) * 64, cb * 512 + (it / 10) * 256, fb);
    };
    if (tid == 0) for (int it = 0; it < KV_STAGES; it++) load(it);
    {
      if (tid < 320) {
        uint2 a[2][5], b[2][5]; uint32_t gw[2];
#pragma unroll
        for (int r = 0; r < 2; r++) {
          const int k = tid + r * 320;
          const uint2* pk = reinterpret_cast<const uint2*>(wk + k * 20);
          const uint2* pv = reinterpret_cast<const uint2*>(wv + k * 20);
#pragma unroll
          for (int i = 0; i < 5; i++) { a[r][i] = __ldg(pk + i); b[r][i] = __ldg(pv + i); }
          gw[r] = (uint32_t)__bfloat16_as_ushort(gate_w[k]);
        }
#pragma unroll
        for (int r = 0; r < 2; r++) {
          uint4* dst = reinterpret_cast<uint4*>(smem + KVW_OFF + (tid + r * 320) * 16);
          dst[0] = make_uint4(a[r][0].x, a[r][0].y, a[r][1].x, a[r][1].y);
          dst[640] = make_uint4(a[r][2].x, a[r][2].y, a[r][3].x, a[r][3].y);
          dst[1280] = make_uint4(a[r][4].x, a[r][4].y, 0u, 0u);
          dst[1920] = make_uint4(b[r][0].x, b[r][0].y, b[r][1].x, b[r][1].y);
          dst[2560] = make_uint4(b[r][2].x, b[r][2].y, b[r][3].x, b[r][3].y);
          dst[3200] = make_uint4(b[r][4].x, b[r][4].y, gw[r], 0u);
        }
      }
      fence_proxy_async();
      asm volatile("bar.sync 1, 512;" ::: "memory");
      PROF(0, 1);
      const int wg = warp >> 2, w4 = warp & 3, g = lane >> 2, t = lane & 3;
      for (int pass = 0; pass < 2; pass++) {
        float acc[24];
#pragma unroll
        for (int i = 0; i < 24; i++) acc[i] = 0.f;
        for (int kt = 0; kt < 10; kt++) {
          const int it = pass * 10 + kt, s = it % KV_STAGES;
          mbar_wait(smem_u32(&bar_full[s]), (it / KV_STAGES) & 1);
          const uint32_t alo = ((dbase + s * K1_A_BYTES + wg * 8192) >> 4) | (1u << 16);
          const uint32_t blo = ((dbase + KVW_OFF + kt * 1024) >> 4) | ((128u >> 4) << 16);
          fence_regs(acc);
          wg_fence();
#pragma unroll
          for (int k = 0; k < 4; k++) wgmma_ss_n48_tb(acc, mkd(alo + k * 2, DHI_SW128_K), mkd(blo + k * 16, 10240u >> 4));
          wg_commit();
          wg_wait<0>();
          if (it + KV_STAGES < 20) {
            const uint32_t eb = smem_u32(&bar_empty[s]);
            if (lane == 0) mbar_arrive(eb);
            if (tid == 0) { mbar_wait(eb, (it / KV_STAGES) & 1); load(it + KV_STAGES); }
            __syncwarp();
          }
        }
        fence_regs(acc);
        float kmax2 = 0.f, vmax = 0.f;
#pragma unroll
        for (int h = 0; h < 2; h++) {
          const int key = cb * 512 + pass * 256 + wg * 64 + w4 * 16 + g + h * 8;
          const int grp = key >> 7, kk = key & 127;
          const bool poly = (TMASK >> (kk >> 3)) & 1;
          uint8_t* gp = g_kvimg + grp * GRP_BYTES;
          const uint32_t k0 = pack_bf16(acc[2 * h], acc[2 * h + 1]);
          const uint32_t k1 = pack_bf16(acc[4 + 2 * h], acc[5 + 2 * h]);
          uint32_t k2 = pack_bf16(acc[8 + 2 * h], acc[9 + 2 * h]);
          float n2 = bf_lo(k0) * bf_lo(k0) + bf_hi(k0) * bf_hi(k0) + bf_lo(k1) * bf_lo(k1) + bf_hi(k1) * bf_hi(k1);
          if (t < 2) {
            n2 += bf_lo(k2) * bf_lo(k2) + bf_hi(k2) * bf_hi(k2);
            k2 = pack_bf16(bf_lo(k2) * 0.5f, bf_hi(k2) * 0.5f);
          } else if (t == 2) k2 = poly ? pack_bf16(24.f, 2.5f) : pack_bf16(0.5f, 0.f);
          else k2 = poly ? pack_bf16(0.5f, 0.f) : 0u;
          *reinterpret_cast<uint32_t*>(gp + kk * 16 + t * 4) = k0;
          *reinterpret_cast<uint32_t*>(gp + PLANE + kk * 16 + t * 4) = k1;
          *reinterpret_cast<uint32_t*>(gp + 2 * PLANE + kk * 16 + t * 4) = k2;
          n2 += __shfl_xor_sync(0xffffffffu, n2, 1);
          n2 += __shfl_xor_sync(0xffffffffu, n2, 2);
          kmax2 = (n2 > kmax2 || n2 != n2) ? n2 : kmax2;
          uint32_t v0 = pack_bf16(acc[12 + 2 * h], acc[13 + 2 * h]);
          uint32_t v1 = pack_bf16(acc[16 + 2 * h], acc[17 + 2 * h]);
          uint32_t v2 = pack_bf16(acc[20 + 2 * h], acc[21 + 2 * h]);
          float vm = fmaxf(fmaxf(fabsf(bf_lo(v0)), fabsf(bf_hi(v0))), fmaxf(fabsf(bf_lo(v1)), fabsf(bf_hi(v1))));
          if (t < 2) vm = fmaxf(vm, fmaxf(fabsf(bf_lo(v2)), fabsf(bf_hi(v2))));
          else if (t == 2) {
            const float z = acc[20 + 2 * h];
            g_gate[key] = 1.f / (1.f + __expf(-z));
            v2 = 0x00003F80u;
          } else v2 = 0u;
          vmax = fmaxf(vmax, vm);
          if (poly) { v0 ^= 0x80008000u; v1 ^= 0x80008000u; v2 ^= 0x80008000u; }
          uint8_t* vp = gp + 3 * PLANE + (kk >> 3) * 384 + (kk & 7) * 16 + t * 4;
          *reinterpret_cast<uint32_t*>(vp) = v0;
          *reinterpret_cast<uint32_t*>(vp + 128) = v1;
          *reinterpret_cast<uint32_t*>(vp + 256) = v2;
        }
#pragma unroll
        for (int o = 1; o < 32; o <<= 1) {
          const float a = __shfl_xor_sync(0xffffffffu, kmax2, o);
          kmax2 = (a > kmax2 || a != a) ? a : kmax2;
          vmax = fmaxf(vmax, __shfl_xor_sync(0xffffffffu, vmax, o));
        }
        if (lane == 0) { g_kmax2[cb * 32 + pass * 16 + warp] = kmax2; g_vmax[cb * 32 + pass * 16 + warp] = vmax; }
      }
    }
  }
  PROF(0, 3);
}

__device__ __forceinline__ uint32_t ex2_pair_poly(float u0, float u1, uint32_t one2) {
  const uint32_t W = __byte_perm(__float_as_uint(u0), __float_as_uint(u1), 0x6521);
  uint32_t v; asm("lop3.b32 %0, %1, 0x007F007F, %2, 0xEA;" : "=r"(v) : "r"(W), "r"(one2));
  uint32_t L, p;
  asm("fma.rn.bf16x2 %0, %1, %2, %3;" : "=r"(L) : "r"(v), "r"(0x1f961f96u), "r"(0x9fe39fe3u));
  asm("fma.rn.bf16x2 %0, %1, %1, %2;" : "=r"(p) : "r"(L), "r"(0x00f500f5u));
  return W + p;
}
template <int JOFF>
__device__ __forceinline__ void softmax_fast(const float (&S)[32], uint32_t (&P)[16], uint32_t one2) {
#pragma unroll
  for (int i = 0; i < 16; i++) {
    if ((TMASK >> (JOFF + i / 2)) & 1) P[i] = ex2_pair_poly(S[2 * i], S[2 * i + 1], one2);
    else P[i] = pack_bf16(ex2(S[2 * i]), ex2(S[2 * i + 1]));
  }
}
template <int JOFF>
__device__ __forceinline__ void softmax_slow(const float (&S)[32], uint32_t (&P)[16], float (&O)[12], float& m0, float& m1) {
  float a0 = m0, a1 = m1;
#pragma unroll
  for (int j = 0; j < 8; j++) {
    a0 = fmaxf(a0, fmaxf(S[4 * j], S[4 * j + 1]));
    a1 = fmaxf(a1, fmaxf(S[4 * j + 2], S[4 * j + 3]));
  }
  a0 = fmaxf(a0, __shfl_xor_sync(0xffffffffu, a0, 1)); a0 = fmaxf(a0, __shfl_xor_sync(0xffffffffu, a0, 2));
  a1 = fmaxf(a1, __shfl_xor_sync(0xffffffffu, a1, 1)); a1 = fmaxf(a1, __shfl_xor_sync(0xffffffffu, a1, 2));
  const float c0 = ex2(m0 - a0), c1 = ex2(m1 - a1);
  m0 = a0; m1 = a1;
#pragma unroll
  for (int j = 0; j < 3; j++) { O[4 * j] *= c0; O[4 * j + 1] *= c0; O[4 * j + 2] *= c1; O[4 * j + 3] *= c1; }
#pragma unroll
  for (int i = 0; i < 16; i++) {
    const float m = (i & 1) ? a1 : a0;
    const uint32_t p = pack_bf16(ex2(S[2 * i] - m), ex2(S[2 * i + 1] - m));
    P[i] = ((TMASK >> (JOFF + i / 2)) & 1) ? (p ^ 0x80008000u) : p;
  }
}
constexpr uint32_t DHI_KV = 128 >> 4;
__device__ __forceinline__ void issue_qk(float (&S)[32], const uint32_t (&q)[6], uint32_t base) {
  wgmma_rs_n64<0>(S, q[0], q[1], q[2], q[3], mkd(base + ((PLANE >> 4) << 16), DHI_KV));
  wgmma_rs_n64<1>(S, q[4], q[5], q[4], q[5], mkd(base + (2 * PLANE >> 4), DHI_KV));
}
__device__ __forceinline__ void issue_pv(float (&O)[12], const uint32_t (&P)[16], uint32_t vbase) {
#pragma unroll
  for (int kk = 0; kk < 4; kk++)
    wgmma_rs_n24_tb<1>(O, P[4 * kk], P[4 * kk + 1], P[4 * kk + 2], P[4 * kk + 3], mkd(vbase + kk * (768 >> 4), DHI_KV));
}

constexpr uint32_t VOFF = ((3 * PLANE) >> 4) + ((384u >> 4) << 16);
__device__ __forceinline__ void attn_tile_fast(const uint32_t (&q)[6], float (&O)[12], uint32_t sbase, uint32_t bars, bool first, uint32_t one2) {
  float S[32]; uint32_t P[16];
#pragma unroll
  for (int i = 0; i < 32; i++) S[i] = 0.f;
  uint32_t kb = sbase >> 4;
  const uint32_t klast = kb + (NGRP - 1) * (GRP_BYTES >> 4);
  if (first) mbar_wait(bars, 0);
  fence_regs(S); fence_regs(O);
  wg_fence();
  issue_qk(S, q, kb);
  wg_commit();
#pragma unroll 1
  for (int grp = 0; grp < NGRP; grp++) {
    if (first) mbar_wait(bars + 8 * min(grp + 1, NGRP - 1), 0);
    const uint32_t knext = min(kb + (GRP_BYTES >> 4), klast);
    wg_wait<0>();
    fence_regs(S); fence_regs(P); fence_regs(O);
    softmax_fast<0>(S, P, one2);
    fence_regs(S); fence_regs(P); fence_regs(O);
    wg_fence();
    issue_qk(S, q, kb + 64);
    issue_pv(O, P, kb + VOFF);
    wg_commit();
    wg_wait<0>();
    fence_regs(S); fence_regs(P); fence_regs(O);
    softmax_fast<8>(S, P, one2);
    fence_regs(S); fence_regs(P); fence_regs(O);
    wg_fence();
    issue_qk(S, q, knext);
    issue_pv(O, P, kb + VOFF + 4 * (768 >> 4));
    wg_commit();
    kb = knext;
  }
  wg_wait<0>();
  fence_regs(O); fence_regs(S);
}
template <int H>
__device__ __forceinline__ void slow_step(const uint32_t (&q)[6], float (&O)[12], uint32_t kb, float& m0, float& m1) {
  float S[32]; uint32_t P[16];
#pragma unroll
  for (int i = 0; i < 32; i++) S[i] = 0.f;
  fence_regs(S);
  wg_fence();
  issue_qk(S, q, kb + 64 * H);
  wg_commit();
  wg_wait<0>();
  fence_regs(S);
  softmax_slow<8 * H>(S, P, O, m0, m1);
  fence_regs(P); fence_regs(O);
  wg_fence();
  issue_pv(O, P, kb + VOFF + H * 4 * (768 >> 4));
  wg_commit();
  wg_wait<0>();
  fence_regs(O); fence_regs(P);
}
__device__ __forceinline__ void attn_tile_slow(const uint32_t (&q)[6], float (&O)[12], uint32_t sbase, uint32_t bars, bool first) {
  float m0 = -INFINITY, m1 = -INFINITY;
#pragma unroll 1
  for (int grp = 0; grp < NGRP; grp++) {
    if (first) mbar_wait(bars + 8 * grp, 0);
    const uint32_t kb = (sbase >> 4) + grp * (GRP_BYTES >> 4);
    slow_step<0>(q, O, kb, m0, m1);
    slow_step<1>(q, O, kb, m0, m1);
  }
}

constexpr int K2_QOFF = NGRP * GRP_BYTES;
constexpr int K2_SMEM = K2_QOFF + 512 * 6 * 4 + 1024;

__device__ __forceinline__ void local_attn_pair(int token, int lane) {
  const __nv_bfloat16* base = g_qkv + (size_t)token * (3 * D_MODEL) + lane * DH;
  float f[20];
  {
    const uint2* p = reinterpret_cast<const uint2*>(base);
#pragma unroll
    for (int i = 0; i < 5; i++) { const uint2 v = p[i]; f[4 * i] = bf_lo(v.x); f[4 * i + 1] = bf_hi(v.x); f[4 * i + 2] = bf_lo(v.y); f[4 * i + 3] = bf_hi(v.y); }
  }
  float sc[8];
  float mx = -INFINITY;
#pragma unroll
  for (int w = 0; w < 8; w++) {
    const bool ok = token - 2 * w >= 0;
    const uint2* p = reinterpret_cast<const uint2*>(base + D_MODEL - (ok ? 2 * w : 0) * (3 * D_MODEL));
    float s = 0.f;
#pragma unroll
    for (int i = 0; i < 5; i++) {
      const uint2 v = p[i];
      s = fmaf(f[4 * i], bf_lo(v.x), s); s = fmaf(f[4 * i + 1], bf_hi(v.x), s);
      s = fmaf(f[4 * i + 2], bf_lo(v.y), s); s = fmaf(f[4 * i + 3], bf_hi(v.y), s);
    }
    s *= 0.22360679774997896f * 1.4426950408889634f;
    sc[w] = ok ? s : -1e9f * 1.4426950408889634f;
    mx = fmaxf(mx, sc[w]);
  }
  float l = 0.f;
#pragma unroll
  for (int w = 0; w < 8; w++) { sc[w] = ex2(sc[w] - mx); l += sc[w]; }
#pragma unroll
  for (int i = 0; i < 20; i++) f[i] = 0.f;
#pragma unroll
  for (int w = 0; w < 8; w++) {
    const bool ok = token - 2 * w >= 0;
    const uint2* p = reinterpret_cast<const uint2*>(base + 2 * D_MODEL - (ok ? 2 * w : token) * (3 * D_MODEL));
#pragma unroll
    for (int i = 0; i < 5; i++) {
      const uint2 v = p[i];
      f[4 * i] = fmaf(sc[w], bf_lo(v.x), f[4 * i]); f[4 * i + 1] = fmaf(sc[w], bf_hi(v.x), f[4 * i + 1]);
      f[4 * i + 2] = fmaf(sc[w], bf_lo(v.y), f[4 * i + 2]); f[4 * i + 3] = fmaf(sc[w], bf_hi(v.y), f[4 * i + 3]);
    }
  }
  const float r = (1.f - g_gate[token]) / l;
  uint2* dst = reinterpret_cast<uint2*>(g_a2 + (size_t)token * (2 * D_MODEL) + D_MODEL + lane * DH);
#pragma unroll
  for (int i = 0; i < 5; i++) dst[i] = make_uint2(pack_bf16(f[4 * i] * r, f[4 * i + 1] * r), pack_bf16(f[4 * i + 2] * r, f[4 * i + 3] * r));
}

__device__ __forceinline__ void signal_done(int wg, int tid) {
  asm volatile("bar.sync %0, 128;" :: "r"(wg + 1) : "memory");
  if ((tid & 127) == 0) asm volatile("red.release.gpu.global.add.u32 [%0], 1;" :: "l"(&g_done[blockIdx.x]) : "memory");
}

__global__ void __launch_bounds__(640, 1)
attn_kernel(uint32_t one2) {
  extern __shared__ uint8_t smem_raw[];
  __shared__ __align__(8) uint64_t bars[NGRP];
  uint8_t* smem = reinterpret_cast<uint8_t*>((reinterpret_cast<uintptr_t>(smem_raw) + 1023) & ~(uintptr_t)1023);
  const uint32_t sbase = smem_u32(smem);
  const uint32_t dbase = sbase & 0x3FFFFu;
  const int tid = threadIdx.x, wg = tid >> 7, warp = (tid >> 5) & 3, lane = tid & 31, g = lane >> 2, t = lane & 3;
  PROF(1, 0);
  pdl_launch();
  if (tid == 0) {
    for (int i = 0; i < NGRP; i++) mbar_init(smem_u32(&bars[i]), 1);
    fence_mbar_init();
  }
  __syncthreads();
  if (wg == 4) {
    asm volatile("setmaxnreg.dec.sync.aligned.u32 56;");
    pdl_wait();
    if (tid == 512) {
      for (int j = 0; j < NGRP; j++) {
        if (j >= 4) mbar_wait(smem_u32(&bars[j - 4]), 0);
        mbar_expect_tx(smem_u32(&bars[j]), GRP_BYTES);
        bulk_g2s(sbase + j * GRP_BYTES, g_kvimg + j * GRP_BYTES, GRP_BYTES, smem_u32(&bars[j]));
      }
    }
    __syncwarp();
#pragma unroll 1
    for (int i = 0; i < 4; i++) local_attn_pair(blockIdx.x * 16 + i * 4 + warp, lane);
    signal_done(wg, tid);
  } else {
    asm volatile("setmaxnreg.inc.sync.aligned.u32 104;");
    pdl_wait();
    PROF(1, 1);
    uint32_t q[6];
    uint32_t* qstash = reinterpret_cast<uint32_t*>(smem + K2_QOFF) + tid;
    const int rowA = (blockIdx.x * 8 + wg) * 64 + warp * 16 + g;
    {
      const uint32_t* r0 = reinterpret_cast<const uint32_t*>(g_q + (size_t)rowA * DH);
      const uint32_t* r1 = r0 + 8 * (DH / 2);
      const uint32_t* s0 = r0 + 256 * (DH / 2);
      const uint32_t* s1 = s0 + 8 * (DH / 2);
      q[0] = r0[t]; q[1] = r1[t]; q[2] = r0[t + 4]; q[3] = r1[t + 4];
      q[4] = t < 2 ? r0[8 + t] : 0u;
      q[5] = t < 2 ? r1[8 + t] : 0u;
      qstash[0] = s0[t]; qstash[512] = s1[t]; qstash[1024] = s0[t + 4]; qstash[1536] = s1[t + 4];
      qstash[2048] = t < 2 ? s0[8 + t] : 0u;
      qstash[2560] = t < 2 ? s1[8 + t] : 0u;
    }
    float kmax2 = 0.f, vmax = 0.f;
#pragma unroll
    for (int i = 0; i < 4; i++) {
      const float a = g_kmax2[lane + 32 * i];
      kmax2 = (a > kmax2 || a != a) ? a : kmax2;
      vmax = fmaxf(vmax, g_vmax[lane + 32 * i]);
    }
#pragma unroll
    for (int o = 1; o < 32; o <<= 1) {
      const float a = __shfl_xor_sync(0xffffffffu, kmax2, o);
      kmax2 = (a > kmax2 || a != a) ? a : kmax2;
      vmax = fmaxf(vmax, __shfl_xor_sync(0xffffffffu, vmax, o));
    }
    const float qlim = (vmax >= 0.00390625f && vmax <= 256.f) ? 9025.f / kmax2 : -1.f;
    PROF(1, 2);
#pragma unroll 1
    for (int it = 0; it < 2; it++) {
      const int row0 = rowA + it * 256;
      if (it == 1) {
#pragma unroll
        for (int i = 0; i < 6; i++) q[i] = qstash[512 * i];
      }
      float n0 = bf_lo(q[0]) * bf_lo(q[0]) + bf_hi(q[0]) * bf_hi(q[0]) + bf_lo(q[2]) * bf_lo(q[2]) + bf_hi(q[2]) * bf_hi(q[2]) +
                 bf_lo(q[4]) * bf_lo(q[4]) + bf_hi(q[4]) * bf_hi(q[4]);
      float n1 = bf_lo(q[1]) * bf_lo(q[1]) + bf_hi(q[1]) * bf_hi(q[1]) + bf_lo(q[3]) * bf_lo(q[3]) + bf_hi(q[3]) * bf_hi(q[3]) +
                 bf_lo(q[5]) * bf_lo(q[5]) + bf_hi(q[5]) * bf_hi(q[5]);
      n0 += __shfl_xor_sync(0xffffffffu, n0, 1); n0 += __shfl_xor_sync(0xffffffffu, n0, 2);
      n1 += __shfl_xor_sync(0xffffffffu, n1, 1); n1 += __shfl_xor_sync(0xffffffffu, n1, 2);
      const bool safe = (n0 <= qlim) && (n1 <= qlim);
      uint32_t unsafe_any;
      asm volatile("{\n.reg .pred p, r;\nsetp.eq.u32 p, %1, 0;\nbarrier.cta.red.or.pred r, %2, 128, p;\nselp.u32 %0, 1, 0, r;\n}\n"
                   : "=r"(unsafe_any) : "r"((uint32_t)safe), "r"(wg + 1) : "memory");
      float O[12];
#pragma unroll
      for (int i = 0; i < 12; i++) O[i] = 0.f;
      if (!unsafe_any) {
        if (t >= 2) { q[4] = q[5] = (t == 2) ? 0x3F804100u : 0x00003B80u; }
        attn_tile_fast(q, O, dbase, smem_u32(&bars[0]), it == 0, one2);
      } else {
        attn_tile_slow(q, O, dbase, smem_u32(&bars[0]), it == 0);
      }
      const float l0 = __shfl_sync(0xffffffffu, O[8], (lane & ~3) | 2);
      const float l1 = __shfl_sync(0xffffffffu, O[10], (lane & ~3) | 2);
      const int tok = row0 >> 5;
      const float gt = g_gate[tok];
      const float i0 = gt / l0, i1 = gt / l1;
      uint32_t* o0 = reinterpret_cast<uint32_t*>(g_a2 + (size_t)tok * (2 * D_MODEL) + (row0 & 31) * DH);
      uint32_t* o1 = o0 + 8 * (DH / 2);
      o0[t] = pack_bf16(O[0] * i0, O[1] * i0); o1[t] = pack_bf16(O[2] * i1, O[3] * i1);
      o0[t + 4] = pack_bf16(O[4] * i0, O[5] * i0); o1[t + 4] = pack_bf16(O[6] * i1, O[7] * i1);
      if (t < 2) { o0[t + 8] = pack_bf16(O[8] * i0, O[9] * i0); o1[t + 8] = pack_bf16(O[10] * i1, O[11] * i1); }
    }
    signal_done(wg, tid);
    PROF(1, 3);
  }
}

constexpr int K3_STAGES = 8;
constexpr int K3_A_BYTES = 128 * 128;
constexpr int K3_B_BYTES = 64 * 80 * 2;
constexpr int K3_STAGE = K3_A_BYTES + K3_B_BYTES;
constexpr int K3_SMEM = K3_STAGES * K3_STAGE + 1024;

__global__ void __cluster_dims__(4, 1, 1) __launch_bounds__(288, 1)
out_kernel(const __grid_constant__ CUtensorMap tmA2, const __grid_constant__ CUtensorMap tmWoA, const __grid_constant__ CUtensorMap tmWoB,
           __nv_bfloat16* __restrict__ out) {
  extern __shared__ uint8_t smem_raw[];
  __shared__ __align__(8) uint64_t bar_full[K3_STAGES], bar_empty[K3_STAGES];
  uint8_t* smem = reinterpret_cast<uint8_t*>((reinterpret_cast<uintptr_t>(smem_raw) + 1023) & ~(uintptr_t)1023);
  const uint32_t sbase = smem_u32(smem);
  const uint32_t dbase = sbase & 0x3FFFFu;
  const int tid = threadIdx.x, warp = tid >> 5, lane = tid & 31;
  const int mb = blockIdx.x >> 3, nb = blockIdx.x & 7, rank = nb & 3;
  PROF(2, 0);
  if (tid == 0) {
    for (int i = 0; i < K3_STAGES; i++) { mbar_init(smem_u32(&bar_full[i]), 1); mbar_init(smem_u32(&bar_empty[i]), 8); }
    fence_mbar_init();
  }
  cluster_arrive();
  cluster_wait();
  if (warp == 8) {
    if (lane == 0) {
      for (int kt = 0; kt < K3_STAGES; kt++) {
        const uint32_t fb = smem_u32(&bar_full[kt]);
        mbar_expect_tx(fb, K3_STAGE);
        tma_3d(sbase + kt * K3_STAGE + K3_A_BYTES, &tmWoA, 0, kt * 64, nb * 5, fb);
      }
      {
        const unsigned int* f = &g_done[mb * 8 + rank * 2];
        for (int spin = 0; spin < (1 << 26); spin++) {
          unsigned int a, b;
          asm volatile("ld.acquire.gpu.global.u32 %0, [%1];" : "=r"(a) : "l"(f) : "memory");
          asm volatile("ld.acquire.gpu.global.u32 %0, [%1];" : "=r"(b) : "l"(f + 1) : "memory");
          if (a >= 5u && b >= 5u) break;
          __nanosleep(20);
        }
        asm volatile("fence.proxy.async;" ::: "memory");
      }
      for (int kt = 0; kt < 20; kt++) {
        const int s = kt % K3_STAGES;
        const uint32_t fb = smem_u32(&bar_full[s]);
        if (kt >= K3_STAGES) {
          mbar_wait_cluster(smem_u32(&bar_empty[s]), ((kt / K3_STAGES) - 1) & 1);
          mbar_expect_tx(fb, K3_STAGE);
          tma_3d(sbase + s * K3_STAGE + K3_A_BYTES, kt < 10 ? &tmWoA : &tmWoB, 0, (kt % 10) * 64, nb * 5, fb);
        }
        tma_2d_mc(sbase + s * K3_STAGE + rank * 4096, &tmA2, kt * 64, mb * 128 + rank * 32, fb, (uint16_t)0xF);
      }
    }
    __syncwarp();
  } else {
    const int wg = warp >> 2;
    float acc[40];
#pragma unroll
    for (int i = 0; i < 40; i++) acc[i] = 0.f;
    for (int kt = 0; kt < 20; kt++) {
      const int s = kt % K3_STAGES;
      mbar_wait(smem_u32(&bar_full[s]), (kt / K3_STAGES) & 1);
      if (kt == 0) PROF(2, 1);
      const uint32_t alo = ((dbase + s * K3_STAGE + wg * 8192) >> 4) | (1u << 16);
      const uint32_t blo = ((dbase + s * K3_STAGE + K3_A_BYTES) >> 4) | ((2048u >> 4) << 16);
      fence_regs(acc);
      wg_fence();
#pragma unroll
      for (int k = 0; k < 4; k++) wgmma_ss_n80_tb(acc, mkd(alo + k * 2, DHI_SW128_K), mkd(blo + k * 32, DHI_SW32_MN));
      wg_commit();
      if (kt > 0 && kt - 1 + K3_STAGES < 20) {
        wg_wait<1>();
        if (lane == 0) mbar_arrive_remote(smem_u32(&bar_empty[(kt - 1) % K3_STAGES]), warp & 3);
      }
    }
    wg_wait<0>();
    fence_regs(acc);
    PROF(2, 2);
    asm volatile("bar.sync %0, 128;" :: "r"(wg + 1) : "memory");
    const int w4 = warp & 3;
    const uint32_t off = w4 * K3_STAGE + wg * 8192;
    const int row0 = mb * 128 + wg * 64 + w4 * 16;
    store_tile_bf16<80>(acc, 1.0f, sbase + off, smem + off, out + (size_t)row0 * D_MODEL + nb * 80, D_MODEL, lane);
    PROF(2, 3);
  }
}

typedef CUresult (*EncodeFn)(CUtensorMap*, CUtensorMapDataType, cuuint32_t, void*, const cuuint64_t*, const cuuint64_t*,
                             const cuuint32_t*, const cuuint32_t*, CUtensorMapInterleave, CUtensorMapSwizzle,
                             CUtensorMapL2promotion, CUtensorMapFloatOOBfill);

void make_map(EncodeFn fn, CUtensorMap* tm, const void* ptr, int rank, const cuuint64_t* dims, const cuuint64_t* strides,
              const cuuint32_t* box, CUtensorMapSwizzle sw) {
  const cuuint32_t es[3] = {1, 1, 1};
  fn(tm, CU_TENSOR_MAP_DATA_TYPE_BFLOAT16, rank, const_cast<void*>(ptr), dims, strides, box, es, CU_TENSOR_MAP_INTERLEAVE_NONE, sw,
     CU_TENSOR_MAP_L2_PROMOTION_L2_256B, CU_TENSOR_MAP_FLOAT_OOB_FILL_NONE);
}
void map_a(EncodeFn fn, CUtensorMap* tm, const void* p, int rows, int cols, int box_rows) {
  const cuuint64_t dims[2] = {(cuuint64_t)cols, (cuuint64_t)rows};
  const cuuint64_t str[1] = {(cuuint64_t)cols * 2};
  const cuuint32_t box[2] = {64, (cuuint32_t)box_rows};
  make_map(fn, tm, p, 2, dims, str, box, CU_TENSOR_MAP_SWIZZLE_128B);
}
void map_w(EncodeFn fn, CUtensorMap* tm, const void* p, int K, int N, int atom, CUtensorMapSwizzle sw) {
  const cuuint64_t dims[3] = {(cuuint64_t)atom, (cuuint64_t)K, (cuuint64_t)(N / atom)};
  const cuuint64_t str[2] = {(cuuint64_t)N * 2, (cuuint64_t)atom * 2};
  const cuuint32_t box[3] = {(cuuint32_t)atom, 64, 5};
  make_map(fn, tm, p, 3, dims, str, box, sw);
}

template <typename... KArgs, typename... Args>
void launch(void (*kern)(KArgs...), int grid, int block, int smem, bool pdl, Args... args) {
  cudaLaunchConfig_t cfg = {};
  cfg.gridDim = dim3(grid); cfg.blockDim = dim3(block); cfg.dynamicSmemBytes = smem; cfg.stream = cudaStreamPerThread;
  cudaLaunchAttribute at[1];
  at[0].id = cudaLaunchAttributeProgrammaticStreamSerialization;
  at[0].val.programmaticStreamSerializationAllowed = 1;
  cfg.attrs = at; cfg.numAttrs = pdl ? 1 : 0;
  cudaLaunchKernelEx(&cfg, kern, KArgs(args)...);
}

}

extern "C" void kernel_launch(void* const* d_in, const int* in_sizes, int n_in, void* d_out, int out_size) {
  (void)in_sizes; (void)n_in; (void)out_size;
  const __nv_bfloat16* x = (const __nv_bfloat16*)d_in[0];
  const __nv_bfloat16* wq = (const __nv_bfloat16*)d_in[1];
  const __nv_bfloat16* wk = (const __nv_bfloat16*)d_in[2];
  const __nv_bfloat16* wv = (const __nv_bfloat16*)d_in[3];
  const __nv_bfloat16* woA = (const __nv_bfloat16*)d_in[4];
  const __nv_bfloat16* wqkv = (const __nv_bfloat16*)d_in[6];
  const __nv_bfloat16* woB = (const __nv_bfloat16*)d_in[7];
  const __nv_bfloat16* gate_w = (const __nv_bfloat16*)d_in[8];

  static EncodeFn enc = nullptr;
  static void* a2_ptr = nullptr;
  if (!enc) {
    void* fp = nullptr;
    cudaDriverEntryPointQueryResult qr;
    cudaGetDriverEntryPoint("cuTensorMapEncodeTiled", &fp, cudaEnableDefault, &qr);
    enc = (EncodeFn)fp;
    cudaGetSymbolAddress(&a2_ptr, g_a2);
    cudaFuncSetAttribute(proj_kernel, cudaFuncAttributeMaxDynamicSharedMemorySize, K1_SMEM);
    cudaFuncSetAttribute(attn_kernel, cudaFuncAttributeMaxDynamicSharedMemorySize, K2_SMEM);
    cudaFuncSetAttribute(out_kernel, cudaFuncAttributeMaxDynamicSharedMemorySize, K3_SMEM);
  }
  CUtensorMap tmX, tmX64, tmWq, tmWqkv, tmA2, tmWoA, tmWoB;
  map_a(enc, &tmX, x, S_LEN, D_MODEL, 256);
  map_a(enc, &tmX64, x, S_LEN, D_MODEL, 64);
  map_w(enc, &tmWq, wq, D_MODEL, D_MODEL, 32, CU_TENSOR_MAP_SWIZZLE_64B);
  map_w(enc, &tmWqkv, wqkv, D_MODEL, 3 * D_MODEL, 32, CU_TENSOR_MAP_SWIZZLE_64B);
  map_a(enc, &tmA2, a2_ptr, S_LEN, 2 * D_MODEL, 32);
  map_w(enc, &tmWoA, woA, D_MODEL, D_MODEL, 16, CU_TENSOR_MAP_SWIZZLE_32B);
  map_w(enc, &tmWoB, woB, D_MODEL, D_MODEL, 16, CU_TENSOR_MAP_SWIZZLE_32B);

  launch(proj_kernel, 132, 512, K1_SMEM, false, tmX, tmX64, tmWq, tmWqkv, wk, wv, gate_w);
  launch(attn_kernel, 128, 640, K2_SMEM, true, 0x3F803F80u);
  launch(out_kernel, 128, 288, K3_SMEM, true, tmA2, tmWoA, tmWoB, (__nv_bfloat16*)d_out);
}
```

```cpp
#include <cuda_runtime.h>
#include <cuda_bf16.h>
#include <cuda.h>
#include <stdint.h>

namespace {

constexpr int S_LEN = 2048, D_MODEL = 640, DH = 20;

constexpr int GRP = 128;
constexpr int PLANE = GRP * 16;
constexpr int GRP_BYTES = GRP * 16 * 6;
constexpr int NGRP = S_LEN / GRP;
constexpr uint32_t TMASK = 0x6DB6u;

__device__ __align__(1024) __nv_bfloat16 g_q[S_LEN * D_MODEL];
__device__ __align__(1024) __nv_bfloat16 g_qkv[S_LEN * 3 * D_MODEL];
__device__ __align__(1024) __nv_bfloat16 g_a2[S_LEN * 2 * D_MODEL];
__device__ __align__(1024) uint8_t g_kvimg[NGRP * GRP_BYTES];
__device__ float g_gate[S_LEN];
__device__ float g_kmax2[128];
__device__ float g_vmax[128];
__device__ unsigned int g_done[128];

#define PROF(k, slot)
__device__ __forceinline__ uint32_t smem_u32(const void* p) { return (uint32_t)__cvta_generic_to_shared(p); }
__device__ __forceinline__ uint64_t mkd(uint32_t lo, uint32_t hi) {
  uint64_t d; asm("mov.b64 %0, {%1, %2};" : "=l"(d) : "r"(lo), "r"(hi)); return d;
}
__device__ __forceinline__ void wg_fence() { asm volatile("wgmma.fence.sync.aligned;" ::: "memory"); }
__device__ __forceinline__ void wg_commit() { asm volatile("wgmma.commit_group.sync.aligned;" ::: "memory"); }
template <int N> __device__ __forceinline__ void wg_wait() { asm volatile("wgmma.wait_group.sync.aligned %0;" :: "n"(N) : "memory"); }
template <int N> __device__ __forceinline__ void fence_regs(float (&d)[N]) {
#pragma unroll
  for (int i = 0; i < N; i++) asm volatile("" : "+f"(d[i]) :: "memory");
}
template <int N> __device__ __forceinline__ void fence_regs(uint32_t (&d)[N]) {
#pragma unroll
  for (int i = 0; i < N; i++) asm volatile("" : "+r"(d[i]) :: "memory");
}
__device__ __forceinline__ void mbar_init(uint32_t bar, uint32_t cnt) { asm volatile("mbarrier.init.shared::cta.b64 [%0], %1;" :: "r"(bar), "r"(cnt)); }
__device__ __forceinline__ void mbar_expect_tx(uint32_t bar, uint32_t bytes) {
  asm volatile("mbarrier.arrive.expect_tx.shared::cta.b64 _, [%0], %1;" :: "r"(bar), "r"(bytes) : "memory");
}
__device__ __forceinline__ void mbar_arrive(uint32_t bar) { asm volatile("mbarrier.arrive.shared::cta.b64 _, [%0];" :: "r"(bar) : "memory"); }
__device__ __forceinline__ void mbar_wait(uint32_t bar, uint32_t parity) {
  asm volatile("{\n.reg .pred p;\nWAIT_%=:\nmbarrier.try_wait.parity.shared::cta.b64 p, [%0], %1;\n@p bra DONE_%=;\nbra WAIT_%=;\nDONE_%=:\n}\n"
               :: "r"(bar), "r"(parity) : "memory");
}
__device__ __forceinline__ void fence_mbar_init() { asm volatile("fence.mbarrier_init.release.cluster;" ::: "memory"); }
__device__ __forceinline__ void fence_proxy_async() { asm volatile("fence.proxy.async.shared::cta;" ::: "memory"); }
__device__ __forceinline__ void bulk_g2s(uint32_t dst, const void* src, uint32_t bytes, uint32_t bar) {
  asm volatile("cp.async.bulk.shared::cluster.global.mbarrier::complete_tx::bytes [%0], [%1], %2, [%3];"
               :: "r"(dst), "l"(src), "r"(bytes), "r"(bar) : "memory");
}
__device__ __forceinline__ void tma_2d(uint32_t dst, const CUtensorMap* tm, int c0, int c1, uint32_t bar) {
  asm volatile("cp.async.bulk.tensor.2d.shared::cluster.global.mbarrier::complete_tx::bytes [%0], [%1, {%3, %4}], [%2];"
               :: "r"(dst), "l"((uint64_t)tm), "r"(bar), "r"(c0), "r"(c1) : "memory");
}
__device__ __forceinline__ void tma_3d(uint32_t dst, const CUtensorMap* tm, int c0, int c1, int c2, uint32_t bar) {
  asm volatile("cp.async.bulk.tensor.3d.shared::cluster.global.mbarrier::complete_tx::bytes [%0], [%1, {%3, %4, %5}], [%2];"
               :: "r"(dst), "l"((uint64_t)tm), "r"(bar), "r"(c0), "r"(c1), "r"(c2) : "memory");
}
__device__ __forceinline__ void tma_2d_mc(uint32_t dst, const CUtensorMap* tm, int c0, int c1, uint32_t bar, uint16_t mask) {
  asm volatile("cp.async.bulk.tensor.2d.shared::cluster.global.mbarrier::complete_tx::bytes.multicast::cluster [%0], [%1, {%3, %4}], [%2], %5;"
               :: "r"(dst), "l"((uint64_t)tm), "r"(bar), "r"(c0), "r"(c1), "h"(mask) : "memory");
}
__device__ __forceinline__ void mbar_arrive_remote(uint32_t bar, uint32_t rank) {
  asm volatile("{\n.reg .b32 ra;\nmapa.shared::cluster.u32 ra, %0, %1;\nmbarrier.arrive.shared::cluster.b64 _, [ra];\n}\n"
               :: "r"(bar), "r"(rank) : "memory");
}
__device__ __forceinline__ void mbar_wait_cluster(uint32_t bar, uint32_t parity) {
  asm volatile("{\n.reg .pred p;\nWAIT_%=:\nmbarrier.try_wait.parity.shared::cta.b64 p, [%0], %1;\n@p bra DONE_%=;\nbra WAIT_%=;\nDONE_%=:\n}\n"
               :: "r"(bar), "r"(parity) : "memory");
}
__device__ __forceinline__ void cluster_arrive() { asm volatile("barrier.cluster.arrive.release.aligned;" ::: "memory"); }
__device__ __forceinline__ void cluster_wait() { asm volatile("barrier.cluster.wait.acquire.aligned;" ::: "memory"); }
__device__ __forceinline__ void prefetch_tmap(const CUtensorMap* tm) { asm volatile("prefetch.tensormap [%0];" :: "l"((uint64_t)tm) : "memory"); }
__device__ __forceinline__ void pdl_wait() { asm volatile("griddepcontrol.wait;" ::: "memory"); }
__device__ __forceinline__ void pdl_launch() { asm volatile("griddepcontrol.launch_dependents;" ::: "memory"); }
__device__ __forceinline__ float ex2(float x) { float y; asm("ex2.approx.ftz.f32 %0, %1;" : "=f"(y) : "f"(x)); return y; }
__device__ __forceinline__ uint32_t pack_bf16(float lo, float hi) {
  uint32_t r; asm("cvt.rn.bf16x2.f32 %0, %1, %2;" : "=r"(r) : "f"(hi), "f"(lo)); return r;
}
__device__ __forceinline__ float bf_lo(uint32_t x) { return __uint_as_float(x << 16); }
__device__ __forceinline__ float bf_hi(uint32_t x) { return __uint_as_float(x & 0xffff0000u); }
__device__ __forceinline__ void stsm4(uint32_t addr, uint32_t r0, uint32_t r1, uint32_t r2, uint32_t r3) {
  asm volatile("stmatrix.sync.aligned.m8n8.x4.shared.b16 [%0], {%1, %2, %3, %4};" :: "r"(addr), "r"(r0), "r"(r1), "r"(r2), "r"(r3) : "memory");
}

__device__ __forceinline__ void wgmma_ss_n160_tb(float (&d)[80], uint64_t descA, uint64_t descB) {
  asm volatile("wgmma.mma_async.sync.aligned.m64n160k16.f32.bf16.bf16 {%0, %1, %2, %3, %4, %5, %6, %7, %8, %9, %10, %11, %12, %13, %14, %15, %16, %17, %18, %19, %20, %21, %22, %23, %24, %25, %26, %27, %28, %29, %30, %31, %32, %33, %34, %35, %36, %37, %38, %39, %40, %41, %42, %43, %44, %45, %46, %47, %48, %49, %50, %51, %52, %53, %54, %55, %56, %57, %58, %59, %60, %61, %62, %63, %64, %65, %66, %67, %68, %69, %70, %71, %72, %73, %74, %75, %76, %77, %78, %79}, %80, %81, 1, 1, 1, 0, 1;\n"
    : "+f"(d[0]), "+f"(d[1]), "+f"(d[2]), "+f"(d[3]), "+f"(d[4]), "+f"(d[5]), "+f"(d[6]), "+f"(d[7]), "+f"(d[8]), "+f"(d[9]), "+f"(d[10]), "+f"(d[11]), "+f"(d[12]), "+f"(d[13]), "+f"(d[14]), "+f"(d[15]), "+f"(d[16]), "+f"(d[17]), "+f"(d[18]), "+f"(d[19]), "+f"(d[20]), "+f"(d[21]), "+f"(d[22]), "+f"(d[23]), "+f"(d[24]), "+f"(d[25]), "+f"(d[26]), "+f"(d[27]), "+f"(d[28]), "+f"(d[29]), "+f"(d[30]), "+f"(d[31]), "+f"(d[32]), "+f"(d[33]), "+f"(d[34]), "+f"(d[35]), "+f"(d[36]), "+f"(d[37]), "+f"(d[38]), "+f"(d[39]), "+f"(d[40]), "+f"(d[41]), "+f"(d[42]), "+f"(d[43]), "+f"(d[44]), "+f"(d[45]), "+f"(d[46]), "+f"(d[47]), "+f"(d[48]), "+f"(d[49]), "+f"(d[50]), "+f"(d[51]), "+f"(d[52]), "+f"(d[53]), "+f"(d[54]), "+f"(d[55]), "+f"(d[56]), "+f"(d[57]), "+f"(d[58]), "+f"(d[59]), "+f"(d[60]), "+f"(d[61]), "+f"(d[62]), "+f"(d[63]), "+f"(d[64]), "+f"(d[65]), "+f"(d[66]), "+f"(d[67]), "+f"(d[68]), "+f"(d[69]), "+f"(d[70]), "+f"(d[71]), "+f"(d[72]), "+f"(d[73]), "+f"(d[74]), "+f"(d[75]), "+f"(d[76]), "+f"(d[77]), "+f"(d[78]), "+f"(d[79])
    : "l"(descA), "l"(descB));
}
__device__ __forceinline__ void wgmma_ss_n48_tb(float (&d)[24], uint64_t descA, uint64_t descB) {
  asm volatile("wgmma.mma_async.sync.aligned.m64n48k16.f32.bf16.bf16 {%0, %1, %2, %3, %4, %5, %6, %7, %8, %9, %10, %11, %12, %13, %14, %15, %16, %17, %18, %19, %20, %21, %22, %23}, %24, %25, 1, 1, 1, 0, 1;\n"
    : "+f"(d[0]), "+f"(d[1]), "+f"(d[2]), "+f"(d[3]), "+f"(d[4]), "+f"(d[5]), "+f"(d[6]), "+f"(d[7]), "+f"(d[8]), "+f"(d[9]), "+f"(d[10]), "+f"(d[11]), "+f"(d[12]), "+f"(d[13]), "+f"(d[14]), "+f"(d[15]), "+f"(d[16]), "+f"(d[17]), "+f"(d[18]), "+f"(d[19]), "+f"(d[20]), "+f"(d[21]), "+f"(d[22]), "+f"(d[23])
    : "l"(descA), "l"(descB));
}
__device__ __forceinline__ void wgmma_ss_n80_tb(float (&d)[40], uint64_t descA, uint64_t descB) {
  asm volatile("wgmma.mma_async.sync.aligned.m64n80k16.f32.bf16.bf16 {%0, %1, %2, %3, %4, %5, %6, %7, %8, %9, %10, %11, %12, %13, %14, %15, %16, %17, %18, %19, %20, %21, %22, %23, %24, %25, %26, %27, %28, %29, %30, %31, %32, %33, %34, %35, %36, %37, %38, %39}, %40, %41, 1, 1, 1, 0, 1;\n"
    : "+f"(d[0]), "+f"(d[1]), "+f"(d[2]), "+f"(d[3]), "+f"(d[4]), "+f"(d[5]), "+f"(d[6]), "+f"(d[7]), "+f"(d[8]), "+f"(d[9]), "+f"(d[10]), "+f"(d[11]), "+f"(d[12]), "+f"(d[13]), "+f"(d[14]), "+f"(d[15]), "+f"(d[16]), "+f"(d[17]), "+f"(d[18]), "+f"(d[19]), "+f"(d[20]), "+f"(d[21]), "+f"(d[22]), "+f"(d[23]), "+f"(d[24]), "+f"(d[25]), "+f"(d[26]), "+f"(d[27]), "+f"(d[28]), "+f"(d[29]), "+f"(d[30]), "+f"(d[31]), "+f"(d[32]), "+f"(d[33]), "+f"(d[34]), "+f"(d[35]), "+f"(d[36]), "+f"(d[37]), "+f"(d[38]), "+f"(d[39])
    : "l"(descA), "l"(descB));
}
template <int SCALE_D>
__device__ __forceinline__ void wgmma_rs_n64(float (&d)[32], uint32_t a0, uint32_t a1, uint32_t a2, uint32_t a3, uint64_t descB) {
  asm volatile("wgmma.mma_async.sync.aligned.m64n64k16.f32.bf16.bf16 {%0, %1, %2, %3, %4, %5, %6, %7, %8, %9, %10, %11, %12, %13, %14, %15, %16, %17, %18, %19, %20, %21, %22, %23, %24, %25, %26, %27, %28, %29, %30, %31}, {%32, %33, %34, %35}, %36, %37, 1, 1, 0;\n"
    : "+f"(d[0]), "+f"(d[1]), "+f"(d[2]), "+f"(d[3]), "+f"(d[4]), "+f"(d[5]), "+f"(d[6]), "+f"(d[7]), "+f"(d[8]), "+f"(d[9]), "+f"(d[10]), "+f"(d[11]), "+f"(d[12]), "+f"(d[13]), "+f"(d[14]), "+f"(d[15]), "+f"(d[16]), "+f"(d[17]), "+f"(d[18]), "+f"(d[19]), "+f"(d[20]), "+f"(d[21]), "+f"(d[22]), "+f"(d[23]), "+f"(d[24]), "+f"(d[25]), "+f"(d[26]), "+f"(d[27]), "+f"(d[28]), "+f"(d[29]), "+f"(d[30]), "+f"(d[31])
    : "r"(a0), "r"(a1), "r"(a2), "r"(a3), "l"(descB), "n"(SCALE_D));
}
template <int SCALE_D>
__device__ __forceinline__ void wgmma_rs_n24_tb(float (&d)[12], uint32_t a0, uint32_t a1, uint32_t a2, uint32_t a3, uint64_t descB) {
  asm volatile("wgmma.mma_async.sync.aligned.m64n24k16.f32.bf16.bf16 {%0, %1, %2, %3, %4, %5, %6, %7, %8, %9, %10, %11}, {%12, %13, %14, %15}, %16, %17, 1, 1, 1;\n"
    : "+f"(d[0]), "+f"(d[1]), "+f"(d[2]), "+f"(d[3]), "+f"(d[4]), "+f"(d[5]), "+f"(d[6]), "+f"(d[7]), "+f"(d[8]), "+f"(d[9]), "+f"(d[10]), "+f"(d[11])
    : "r"(a0), "r"(a1), "r"(a2), "r"(a3), "l"(descB), "n"(SCALE_D));
}

constexpr uint32_t DHI_SW128_K = (1024 >> 4) | (1u << 30);
constexpr uint32_t DHI_SW64_MN = (512 >> 4) | (2u << 30);
constexpr uint32_t DHI_SW32_MN = (256 >> 4) | (3u << 30);

template <int NC>
__device__ __forceinline__ void store_tile_bf16(const float (&acc)[NC / 2], float scale, uint32_t stage, uint8_t* stage_ptr,
                                                __nv_bfloat16* gdst, int gpitch, int lane) {
  constexpr int PITCH = NC * 2 + 16;
  const uint32_t waddr = stage + ((lane & 7) + ((lane >> 3) & 1) * 8) * PITCH + (lane >> 4) * 16;
#pragma unroll
  for (int j = 0; j < NC / 16; j++) {
    stsm4(waddr + j * 32, pack_bf16(acc[8 * j] * scale, acc[8 * j + 1] * scale), pack_bf16(acc[8 * j + 2] * scale, acc[8 * j + 3] * scale),
          pack_bf16(acc[8 * j + 4] * scale, acc[8 * j + 5] * scale), pack_bf16(acc[8 * j + 6] * scale, acc[8 * j + 7] * scale));
  }
  __syncwarp();
  constexpr int CPR = NC / 8;
#pragma unroll
  for (int i = 0; i < CPR / 2; i++) {
    const int c = i * 32 + lane, r = c / CPR, cc = c % CPR;
    const uint4 v = *reinterpret_cast<const uint4*>(stage_ptr + r * PITCH + cc * 16);
    *reinterpret_cast<uint4*>(gdst + (size_t)r * gpitch + cc * 8) = v;
  }
}

constexpr int K1_STAGES = 4;
constexpr int K1_A_BYTES = 256 * 128;
constexpr int K1_B_BYTES = 64 * 160 * 2;
constexpr int K1_STAGE = K1_A_BYTES + K1_B_BYTES;
constexpr int K1_SMEM = 5 * K1_A_BYTES + 61440 + 1024;
constexpr int KV_STAGES = 5;
constexpr int KVW_OFF = KV_STAGES * K1_A_BYTES;

__global__ void __cluster_dims__(2, 1, 1) __launch_bounds__(512, 1)
proj_kernel(const __grid_constant__ CUtensorMap tmX, const __grid_constant__ CUtensorMap tmX64, const __grid_constant__ CUtensorMap tmWq, const __grid_constant__ CUtensorMap tmWqkv,
            const __nv_bfloat16* __restrict__ wk, const __nv_bfloat16* __restrict__ wv, const __nv_bfloat16* __restrict__ gate_w) {
  extern __shared__ uint8_t smem_raw[];
  __shared__ __align__(8) uint64_t bar_full[KV_STAGES], bar_empty[KV_STAGES];
  uint8_t* smem = reinterpret_cast<uint8_t*>((reinterpret_cast<uintptr_t>(smem_raw) + 1023) & ~(uintptr_t)1023);
  const uint32_t sbase = smem_u32(smem);
  const uint32_t dbase = sbase & 0x3FFFFu;
  const int tid = threadIdx.x, warp = tid >> 5, lane = tid & 31;
  const bool is_kv = blockIdx.x >= 128;
  PROF(0, 0);
  pdl_launch();
  if (tid == 0) {
    for (int i = 0; i < KV_STAGES; i++) { mbar_init(smem_u32(&bar_full[i]), 1); mbar_init(smem_u32(&bar_empty[i]), is_kv ? 16 : 8); }
    fence_mbar_init();
    if (!is_kv) g_done[blockIdx.x] = 0u;
  }
  cluster_arrive();
  cluster_wait();

  if (!is_kv) {
    const int mb = blockIdx.x >> 4, nb = blockIdx.x & 15;
    const CUtensorMap* tw = nb < 4 ? &tmWq : &tmWqkv;
    const int j0 = (nb < 4 ? nb : nb - 4) * 5;
    auto load = [&](int kt) {
      const int s = kt % K1_STAGES;
      const uint32_t fb = smem_u32(&bar_full[s]);
      mbar_expect_tx(fb, K1_STAGE);
      tma_2d_mc(sbase + s * K1_STAGE + (nb & 1) * 16384, &tmX64, kt * 64, mb * 256 + (nb & 1) * 128, fb, (uint16_t)0x3);
      tma_3d(sbase + s * K1_STAGE + K1_A_BYTES, tw, 0, kt * 64, j0, fb);
    };
    if (tid == 0) for (int kt = 0; kt < K1_STAGES; kt++) load(kt);
    {
      const int wg = warp >> 2;
      float acc[80];
#pragma unroll
      for (int i = 0; i < 80; i++) acc[i] = 0.f;
      for (int kt = 0; kt < 10; kt++) {
        const int s = kt % K1_STAGES;
        mbar_wait(smem_u32(&bar_full[s]), (kt / K1_STAGES) & 1);
        const uint32_t alo = ((dbase + s * K1_STAGE + wg * 8192) >> 4) | (1u << 16);
        const uint32_t blo = ((dbase + s * K1_STAGE + K1_A_BYTES) >> 4) | ((4096u >> 4) << 16);
        fence_regs(acc);
        wg_fence();
#pragma unroll
        for (int k = 0; k < 4; k++) wgmma_ss_n160_tb(acc, mkd(alo + k * 2, DHI_SW128_K), mkd(blo + k * 64, DHI_SW64_MN));
        wg_commit();
        if (kt > 0 && kt - 1 + K1_STAGES < 10) {
          wg_wait<1>();
          const uint32_t eb = smem_u32(&bar_empty[(kt - 1) % K1_STAGES]);
          if (lane == 1 && (warp & 2) == 2) mbar_arrive_remote(eb, warp & 1);
          if (tid == 0) { mbar_wait_cluster(eb, ((kt - 1) / K1_STAGES) & 1); load(kt - 1 + K1_STAGES); }
          __syncwarp();
        }
      }
      wg_wait<0>();
      fence_regs(acc);
      PROF(0, 1);
      asm volatile("bar.sync %0, 128;" :: "r"(wg + 1) : "memory");
      const int w4 = warp & 3;
      const uint32_t off = w4 * K1_STAGE + wg * 8192;
      const int row0 = mb * 256 + wg * 64 + w4 * 16;
      if (nb < 4) {
        store_tile_bf16<160>(acc, 0.22360679774997896f * 1.4426950408889634f, sbase + off, smem + off,
                             g_q + (size_t)row0 * D_MODEL + nb * 160, D_MODEL, lane);
      } else {
        store_tile_bf16<160>(acc, 1.0f, sbase + off, smem + off, g_qkv + (size_t)row0 * (3 * D_MODEL) + (nb - 4) * 160, 3 * D_MODEL, lane);
      }
    }
  } else {
    const int cb = blockIdx.x - 128;
    auto load = [&](int it) {
      const int s = it % KV_STAGES;
      const uint32_t fb = smem_u32(&bar_full[s]);
      mbar_expect_tx(fb, K1_A_BYTES);
      tma_2d(sbase + s * K1_A_BYTES, &tmX, (it % 10) * 64, cb * 512 + (it / 10) * 256, fb);
    };
    if (tid == 0) for (int it = 0; it < KV_STAGES; it++) load(it);
    {
      if (tid < 320) {
        uint2 a[2][5], b[2][5]; uint32_t gw[2];
#pragma unroll
        for (int r = 0; r < 2; r++) {
          const int k = tid + r * 320;
          const uint2* pk = reinterpret_cast<const uint2*>(wk + k * 20);
          const uint2* pv = reinterpret_cast<const uint2*>(wv + k * 20);
#pragma unroll
          for (int i = 0; i < 5; i++) { a[r][i] = __ldg(pk + i); b[r][i] = __ldg(pv + i); }
          gw[r] = (uint32_t)__bfloat16_as_ushort(gate_w[k]);
        }
#pragma unroll
        for (int r = 0; r < 2; r++) {
          uint4* dst = reinterpret_cast<uint4*>(smem + KVW_OFF + (tid + r * 320) * 16);
          dst[0] = make_uint4(a[r][0].x, a[r][0].y, a[r][1].x, a[r][1].y);
          dst[640] = make_uint4(a[r][2].x, a[r][2].y, a[r][3].x, a[r][3].y);
          dst[1280] = make_uint4(a[r][4].x, a[r][4].y, 0u, 0u);
          dst[1920] = make_uint4(b[r][0].x, b[r][0].y, b[r][1].x, b[r][1].y);
          dst[2560] = make_uint4(b[r][2].x, b[r][2].y, b[r][3].x, b[r][3].y);
          dst[3200] = make_uint4(b[r][4].x, b[r][4].y, gw[r], 0u);
        }
      }
      fence_proxy_async();
      asm volatile("bar.sync 1, 512;" ::: "memory");
      PROF(0, 1);
      const int wg = warp >> 2, w4 = warp & 3, g = lane >> 2, t = lane & 3;
      for (int pass = 0; pass < 2; pass++) {
        float acc[24];
#pragma unroll
        for (int i = 0; i < 24; i++) acc[i] = 0.f;
        for (int kt = 0; kt < 10; kt++) {
          const int it = pass * 10 + kt, s = it % KV_STAGES;
          mbar_wait(smem_u32(&bar_full[s]), (it / KV_STAGES) & 1);
          const uint32_t alo = ((dbase + s * K1_A_BYTES + wg * 8192) >> 4) | (1u << 16);
          const uint32_t blo = ((dbase + KVW_OFF + kt * 1024) >> 4) | ((128u >> 4) << 16);
          fence_regs(acc);
          wg_fence();
#pragma unroll
          for (int k = 0; k < 4; k++) wgmma_ss_n48_tb(acc, mkd(alo + k * 2, DHI_SW128_K), mkd(blo + k * 16, 10240u >> 4));
          wg_commit();
          wg_wait<0>();
          if (it + KV_STAGES < 20) {
            const uint32_t eb = smem_u32(&bar_empty[s]);
            if (lane == 0) mbar_arrive(eb);
            if (tid == 0) { mbar_wait(eb, (it / KV_STAGES) & 1); load(it + KV_STAGES); }
            __syncwarp();
          }
        }
        fence_regs(acc);
        float kmax2 = 0.f, vmax = 0.f;
#pragma unroll
        for (int h = 0; h < 2; h++) {
          const int key = cb * 512 + pass * 256 + wg * 64 + w4 * 16 + g + h * 8;
          const int grp = key >> 7, kk = key & 127;
          const bool poly = (TMASK >> (kk >> 3)) & 1;
          uint8_t* gp = g_kvimg + grp * GRP_BYTES;
          const uint32_t k0 = pack_bf16(acc[2 * h], acc[2 * h + 1]);
          const uint32_t k1 = pack_bf16(acc[4 + 2 * h], acc[5 + 2 * h]);
          uint32_t k2 = pack_bf16(acc[8 + 2 * h], acc[9 + 2 * h]);
          float n2 = bf_lo(k0) * bf_lo(k0) + bf_hi(k0) * bf_hi(k0) + bf_lo(k1) * bf_lo(k1) + bf_hi(k1) * bf_hi(k1);
          if (t < 2) {
            n2 += bf_lo(k2) * bf_lo(k2) + bf_hi(k2) * bf_hi(k2);
            k2 = pack_bf16(bf_lo(k2) * 0.5f, bf_hi(k2) * 0.5f);
          } else if (t == 2) k2 = poly ? pack_bf16(24.f, 2.5f) : pack_bf16(0.5f, 0.f);
          else k2 = poly ? pack_bf16(0.5f, 0.f) : 0u;
          *reinterpret_cast<uint32_t*>(gp + kk * 16 + t * 4) = k0;
          *reinterpret_cast<uint32_t*>(gp + PLANE + kk * 16 + t * 4) = k1;
          *reinterpret_cast<uint32_t*>(gp + 2 * PLANE + kk * 16 + t * 4) = k2;
          n2 += __shfl_xor_sync(0xffffffffu, n2, 1);
          n2 += __shfl_xor_sync(0xffffffffu, n2, 2);
          kmax2 = (n2 > kmax2 || n2 != n2) ? n2 : kmax2;
          uint32_t v0 = pack_bf16(acc[12 + 2 * h], acc[13 + 2 * h]);
          uint32_t v1 = pack_bf16(acc[16 + 2 * h], acc[17 + 2 * h]);
          uint32_t v2 = pack_bf16(acc[20 + 2 * h], acc[21 + 2 * h]);
          float vm = fmaxf(fmaxf(fabsf(bf_lo(v0)), fabsf(bf_hi(v0))), fmaxf(fabsf(bf_lo(v1)), fabsf(bf_hi(v1))));
          if (t < 2) vm = fmaxf(vm, fmaxf(fabsf(bf_lo(v2)), fabsf(bf_hi(v2))));
          else if (t == 2) {
            const float z = acc[20 + 2 * h];
            g_gate[key] = 1.f / (1.f + __expf(-z));
            v2 = 0x00003F80u;
          } else v2 = 0u;
          vmax = fmaxf(vmax, vm);
          if (poly) { v0 ^= 0x80008000u; v1 ^= 0x80008000u; v2 ^= 0x80008000u; }
          uint8_t* vp = gp + 3 * PLANE + (kk >> 3) * 384 + (kk & 7) * 16 + t * 4;
          *reinterpret_cast<uint32_t*>(vp) = v0;
          *reinterpret_cast<uint32_t*>(vp + 128) = v1;
          *reinterpret_cast<uint32_t*>(vp + 256) = v2;
        }
#pragma unroll
        for (int o = 1; o < 32; o <<= 1) {
          const float a = __shfl_xor_sync(0xffffffffu, kmax2, o);
          kmax2 = (a > kmax2 || a != a) ? a : kmax2;
          vmax = fmaxf(vmax, __shfl_xor_sync(0xffffffffu, vmax, o));
        }
        if (lane == 0) { g_kmax2[cb * 32 + pass * 16 + warp] = kmax2; g_vmax[cb * 32 + pass * 16 + warp] = vmax; }
      }
    }
  }
  PROF(0, 3);
}

__device__ __forceinline__ uint32_t ex2_pair_poly(float u0, float u1, uint32_t one2) {
  const uint32_t W = __byte_perm(__float_as_uint(u0), __float_as_uint(u1), 0x6521);
  uint32_t v; asm("lop3.b32 %0, %1, 0x007F007F, %2, 0xEA;" : "=r"(v) : "r"(W), "r"(one2));
  uint32_t L, p;
  asm("fma.rn.bf16x2 %0, %1, %2, %3;" : "=r"(L) : "r"(v), "r"(0x1f961f96u), "r"(0x9fe39fe3u));
  asm("fma.rn.bf16x2 %0, %1, %1, %2;" : "=r"(p) : "r"(L), "r"(0x00f500f5u));
  return W + p;
}
template <int JOFF>
__device__ __forceinline__ void softmax_fast(const float (&S)[32], uint32_t (&P)[16], uint32_t one2) {
#pragma unroll
  for (int i = 0; i < 16; i++) {
    if ((TMASK >> (JOFF + i / 2)) & 1) P[i] = ex2_pair_poly(S[2 * i], S[2 * i + 1], one2);
    else P[i] = pack_bf16(ex2(S[2 * i]), ex2(S[2 * i + 1]));
  }
}
template <int JOFF>
__device__ __forceinline__ void softmax_slow(const float (&S)[32], uint32_t (&P)[16], float (&O)[12], float& m0, float& m1) {
  float a0 = m0, a1 = m1;
#pragma unroll
  for (int j = 0; j < 8; j++) {
    a0 = fmaxf(a0, fmaxf(S[4 * j], S[4 * j + 1]));
    a1 = fmaxf(a1, fmaxf(S[4 * j + 2], S[4 * j + 3]));
  }
  a0 = fmaxf(a0, __shfl_xor_sync(0xffffffffu, a0, 1)); a0 = fmaxf(a0, __shfl_xor_sync(0xffffffffu, a0, 2));
  a1 = fmaxf(a1, __shfl_xor_sync(0xffffffffu, a1, 1)); a1 = fmaxf(a1, __shfl_xor_sync(0xffffffffu, a1, 2));
  const float c0 = ex2(m0 - a0), c1 = ex2(m1 - a1);
  m0 = a0; m1 = a1;
#pragma unroll
  for (int j = 0; j < 3; j++) { O[4 * j] *= c0; O[4 * j + 1] *= c0; O[4 * j + 2] *= c1; O[4 * j + 3] *= c1; }
#pragma unroll
  for (int i = 0; i < 16; i++) {
    const float m = (i & 1) ? a1 : a0;
    const uint32_t p = pack_bf16(ex2(S[2 * i] - m), ex2(S[2 * i + 1] - m));
    P[i] = ((TMASK >> (JOFF + i / 2)) & 1) ? (p ^ 0x80008000u) : p;
  }
}
constexpr uint32_t DHI_KV = 128 >> 4;
__device__ __forceinline__ void issue_qk(float (&S)[32], const uint32_t (&q)[6], uint32_t base) {
  wgmma_rs_n64<0>(S, q[0], q[1], q[2], q[3], mkd(base + ((PLANE >> 4) << 16), DHI_KV));
  wgmma_rs_n64<1>(S, q[4], q[5], q[4], q[5], mkd(base + (2 * PLANE >> 4), DHI_KV));
}
__device__ __forceinline__ void issue_pv(float (&O)[12], const uint32_t (&P)[16], uint32_t vbase) {
#pragma unroll
  for (int kk = 0; kk < 4; kk++)
    wgmma_rs_n24_tb<1>(O, P[4 * kk], P[4 * kk + 1], P[4 * kk + 2], P[4 * kk + 3], mkd(vbase + kk * (768 >> 4), DHI_KV));
}

constexpr uint32_t VOFF = ((3 * PLANE) >> 4) + ((384u >> 4) << 16);
__device__ __forceinline__ void attn_tile_fast(const uint32_t (&q)[6], float (&O)[12], uint32_t sbase, uint32_t bars, bool first, uint32_t one2) {
  float S[32]; uint32_t P[16];
#pragma unroll
  for (int i = 0; i < 32; i++) S[i] = 0.f;
  uint32_t kb = sbase >> 4;
  const uint32_t klast = kb + (NGRP - 1) * (GRP_BYTES >> 4);
  if (first) mbar_wait(bars, 0);
  fence_regs(S); fence_regs(O);
  wg_fence();
  issue_qk(S, q, kb);
  wg_commit();
#pragma unroll 1
  for (int grp = 0; grp < NGRP; grp++) {
    if (first) mbar_wait(bars + 8 * min(grp + 1, NGRP - 1), 0);
    const uint32_t knext = min(kb + (GRP_BYTES >> 4), klast);
    wg_wait<0>();
    fence_regs(S); fence_regs(P); fence_regs(O);
    softmax_fast<0>(S, P, one2);
    fence_regs(S); fence_regs(P); fence_regs(O);
    wg_fence();
    issue_qk(S, q, kb + 64);
    issue_pv(O, P, kb + VOFF);
    wg_commit();
    wg_wait<0>();
    fence_regs(S); fence_regs(P); fence_regs(O);
    softmax_fast<8>(S, P, one2);
    fence_regs(S); fence_regs(P); fence_regs(O);
    wg_fence();
    issue_qk(S, q, knext);
    issue_pv(O, P, kb + VOFF + 4 * (768 >> 4));
    wg_commit();
    kb = knext;
  }
  wg_wait<0>();
  fence_regs(O); fence_regs(S);
}
template <int H>
__device__ __forceinline__ void slow_step(const uint32_t (&q)[6], float (&O)[12], uint32_t kb, float& m0, float& m1) {
  float S[32]; uint32_t P[16];
#pragma unroll
  for (int i = 0; i < 32; i++) S[i] = 0.f;
  fence_regs(S);
  wg_fence();
  issue_qk(S, q, kb + 64 * H);
  wg_commit();
  wg_wait<0>();
  fence_regs(S);
  softmax_slow<8 * H>(S, P, O, m0, m1);
  fence_regs(P); fence_regs(O);
  wg_fence();
  issue_pv(O, P, kb + VOFF + H * 4 * (768 >> 4));
  wg_commit();
  wg_wait<0>();
  fence_regs(O); fence_regs(P);
}
__device__ __forceinline__ void attn_tile_slow(const uint32_t (&q)[6], float (&O)[12], uint32_t sbase, uint32_t bars, bool first) {
  float m0 = -INFINITY, m1 = -INFINITY;
#pragma unroll 1
  for (int grp = 0; grp < NGRP; grp++) {
    if (first) mbar_wait(bars + 8 * grp, 0);
    const uint32_t kb = (sbase >> 4) + grp * (GRP_BYTES >> 4);
    slow_step<0>(q, O, kb, m0, m1);
    slow_step<1>(q, O, kb, m0, m1);
  }
}

constexpr int K2_QOFF = NGRP * GRP_BYTES;
constexpr int K2_SMEM = K2_QOFF + 512 * 6 * 4 + 1024;

__device__ __forceinline__ void local_attn_pair(int token, int lane) {
  const __nv_bfloat16* base = g_qkv + (size_t)token * (3 * D_MODEL) + lane * DH;
  float f[20];
  {
    const uint2* p = reinterpret_cast<const uint2*>(base);
#pragma unroll
    for (int i = 0; i < 5; i++) { const uint2 v = p[i]; f[4 * i] = bf_lo(v.x); f[4 * i + 1] = bf_hi(v.x); f[4 * i + 2] = bf_lo(v.y); f[4 * i + 3] = bf_hi(v.y); }
  }
  float sc[8];
  float mx = -INFINITY;
#pragma unroll
  for (int w = 0; w < 8; w++) {
    const bool ok = token - 2 * w >= 0;
    const uint2* p = reinterpret_cast<const uint2*>(base + D_MODEL - (ok ? 2 * w : 0) * (3 * D_MODEL));
    float s = 0.f;
#pragma unroll
    for (int i = 0; i < 5; i++) {
      const uint2 v = p[i];
      s = fmaf(f[4 * i], bf_lo(v.x), s); s = fmaf(f[4 * i + 1], bf_hi(v.x), s);
      s = fmaf(f[4 * i + 2], bf_lo(v.y), s); s = fmaf(f[4 * i + 3], bf_hi(v.y), s);
    }
    s *= 0.22360679774997896f * 1.4426950408889634f;
    sc[w] = ok ? s : -1e9f * 1.4426950408889634f;
    mx = fmaxf(mx, sc[w]);
  }
  float l = 0.f;
#pragma unroll
  for (int w = 0; w < 8; w++) { sc[w] = ex2(sc[w] - mx); l += sc[w]; }
#pragma unroll
  for (int i = 0; i < 20; i++) f[i] = 0.f;
#pragma unroll
  for (int w = 0; w < 8; w++) {
    const bool ok = token - 2 * w >= 0;
    const uint2* p = reinterpret_cast<const uint2*>(base + 2 * D_MODEL - (ok ? 2 * w : token) * (3 * D_MODEL));
#pragma unroll
    for (int i = 0; i < 5; i++) {
      const uint2 v = p[i];
      f[4 * i] = fmaf(sc[w], bf_lo(v.x), f[4 * i]); f[4 * i + 1] = fmaf(sc[w], bf_hi(v.x), f[4 * i + 1]);
      f[4 * i + 2] = fmaf(sc[w], bf_lo(v.y), f[4 * i + 2]); f[4 * i + 3] = fmaf(sc[w], bf_hi(v.y), f[4 * i + 3]);
    }
  }
  const float r = (1.f - g_gate[token]) / l;
  uint2* dst = reinterpret_cast<uint2*>(g_a2 + (size_t)token * (2 * D_MODEL) + D_MODEL + lane * DH);
#pragma unroll
  for (int i = 0; i < 5; i++) dst[i] = make_uint2(pack_bf16(f[4 * i] * r, f[4 * i + 1] * r), pack_bf16(f[4 * i + 2] * r, f[4 * i + 3] * r));
}

__device__ __forceinline__ void signal_done(int wg, int tid) {
  asm volatile("bar.sync %0, 128;" :: "r"(wg + 1) : "memory");
  if ((tid & 127) == 0) asm volatile("red.release.gpu.global.add.u32 [%0], 1;" :: "l"(&g_done[blockIdx.x]) : "memory");
}

__global__ void __launch_bounds__(640, 1)
attn_kernel(uint32_t one2) {
  extern __shared__ uint8_t smem_raw[];
  __shared__ __align__(8) uint64_t bars[NGRP];
  uint8_t* smem = reinterpret_cast<uint8_t*>((reinterpret_cast<uintptr_t>(smem_raw) + 1023) & ~(uintptr_t)1023);
  const uint32_t sbase = smem_u32(smem);
  const uint32_t dbase = sbase & 0x3FFFFu;
  const int tid = threadIdx.x, wg = tid >> 7, warp = (tid >> 5) & 3, lane = tid & 31, g = lane >> 2, t = lane & 3;
  PROF(1, 0);
  pdl_launch();
  if (tid == 0) {
    for (int i = 0; i < NGRP; i++) mbar_init(smem_u32(&bars[i]), 1);
    fence_mbar_init();
  }
  __syncthreads();
  if (wg == 4) {
    asm volatile("setmaxnreg.dec.sync.aligned.u32 56;");
    pdl_wait();
    if (tid == 512) {
      for (int j = 0; j < NGRP; j++) {
        if (j >= 4) mbar_wait(smem_u32(&bars[j - 4]), 0);
        mbar_expect_tx(smem_u32(&bars[j]), GRP_BYTES);
        bulk_g2s(sbase + j * GRP_BYTES, g_kvimg + j * GRP_BYTES, GRP_BYTES, smem_u32(&bars[j]));
      }
    }
    __syncwarp();
#pragma unroll 1
    for (int i = 0; i < 4; i++) local_attn_pair(blockIdx.x * 16 + i * 4 + warp, lane);
    signal_done(wg, tid);
  } else {
    asm volatile("setmaxnreg.inc.sync.aligned.u32 104;");
    pdl_wait();
    PROF(1, 1);
    uint32_t q[6];
    uint32_t* qstash = reinterpret_cast<uint32_t*>(smem + K2_QOFF) + tid;
    const int rowA = (blockIdx.x * 8 + wg) * 64 + warp * 16 + g;
    {
      const uint32_t* r0 = reinterpret_cast<const uint32_t*>(g_q + (size_t)rowA * DH);
      const uint32_t* r1 = r0 + 8 * (DH / 2);
      const uint32_t* s0 = r0 + 256 * (DH / 2);
      const uint32_t* s1 = s0 + 8 * (DH / 2);
      q[0] = r0[t]; q[1] = r1[t]; q[2] = r0[t + 4]; q[3] = r1[t + 4];
      q[4] = t < 2 ? r0[8 + t] : 0u;
      q[5] = t < 2 ? r1[8 + t] : 0u;
      qstash[0] = s0[t]; qstash[512] = s1[t]; qstash[1024] = s0[t + 4]; qstash[1536] = s1[t + 4];
      qstash[2048] = t < 2 ? s0[8 + t] : 0u;
      qstash[2560] = t < 2 ? s1[8 + t] : 0u;
    }
    float kmax2 = 0.f, vmax = 0.f;
#pragma unroll
    for (int i = 0; i < 4; i++) {
      const float a = g_kmax2[lane + 32 * i];
      kmax2 = (a > kmax2 || a != a) ? a : kmax2;
      vmax = fmaxf(vmax, g_vmax[lane + 32 * i]);
    }
#pragma unroll
    for (int o = 1; o < 32; o <<= 1) {
      const float a = __shfl_xor_sync(0xffffffffu, kmax2, o);
      kmax2 = (a > kmax2 || a != a) ? a : kmax2;
      vmax = fmaxf(vmax, __shfl_xor_sync(0xffffffffu, vmax, o));
    }
    const float qlim = (vmax >= 0.00390625f && vmax <= 256.f) ? 9025.f / kmax2 : -1.f;
    PROF(1, 2);
#pragma unroll 1
    for (int it = 0; it < 2; it++) {
      const int row0 = rowA + it * 256;
      if (it == 1) {
#pragma unroll
        for (int i = 0; i < 6; i++) q[i] = qstash[512 * i];
      }
      float n0 = bf_lo(q[0]) * bf_lo(q[0]) + bf_hi(q[0]) * bf_hi(q[0]) + bf_lo(q[2]) * bf_lo(q[2]) + bf_hi(q[2]) * bf_hi(q[2]) +
                 bf_lo(q[4]) * bf_lo(q[4]) + bf_hi(q[4]) * bf_hi(q[4]);
      float n1 = bf_lo(q[1]) * bf_lo(q[1]) + bf_hi(q[1]) * bf_hi(q[1]) + bf_lo(q[3]) * bf_lo(q[3]) + bf_hi(q[3]) * bf_hi(q[3]) +
                 bf_lo(q[5]) * bf_lo(q[5]) + bf_hi(q[5]) * bf_hi(q[5]);
      n0 += __shfl_xor_sync(0xffffffffu, n0, 1); n0 += __shfl_xor_sync(0xffffffffu, n0, 2);
      n1 += __shfl_xor_sync(0xffffffffu, n1, 1); n1 += __shfl_xor_sync(0xffffffffu, n1, 2);
      const bool safe = (n0 <= qlim) && (n1 <= qlim);
      uint32_t unsafe_any;
      asm volatile("{\n.reg .pred p, r;\nsetp.eq.u32 p, %1, 0;\nbarrier.cta.red.or.pred r, %2, 128, p;\nselp.u32 %0, 1, 0, r;\n}\n"
                   : "=r"(unsafe_any) : "r"((uint32_t)safe), "r"(wg + 1) : "memory");
      float O[12];
#pragma unroll
      for (int i = 0; i < 12; i++) O[i] = 0.f;
      if (!unsafe_any) {
        if (t >= 2) { q[4] = q[5] = (t == 2) ? 0x3F804100u : 0x00003B80u; }
        attn_tile_fast(q, O, dbase, smem_u32(&bars[0]), it == 0, one2);
      } else {
        attn_tile_slow(q, O, dbase, smem_u32(&bars[0]), it == 0);
      }
      const float l0 = __shfl_sync(0xffffffffu, O[8], (lane & ~3) | 2);
      const float l1 = __shfl_sync(0xffffffffu, O[10], (lane & ~3) | 2);
      const int tok = row0 >> 5;
      const float gt = g_gate[tok];
      const float i0 = gt / l0, i1 = gt / l1;
      uint32_t* o0 = reinterpret_cast<uint32_t*>(g_a2 + (size_t)tok * (2 * D_MODEL) + (row0 & 31) * DH);
      uint32_t* o1 = o0 + 8 * (DH / 2);
      o0[t] = pack_bf16(O[0] * i0, O[1] * i0); o1[t] = pack_bf16(O[2] * i1, O[3] * i1);
      o0[t + 4] = pack_bf16(O[4] * i0, O[5] * i0); o1[t + 4] = pack_bf16(O[6] * i1, O[7] * i1);
      if (t < 2) { o0[t + 8] = pack_bf16(O[8] * i0, O[9] * i0); o1[t + 8] = pack_bf16(O[10] * i1, O[11] * i1); }
    }
    signal_done(wg, tid);
    PROF(1, 3);
  }
}

constexpr int K3_STAGES = 8;
constexpr int K3_A_BYTES = 128 * 128;
constexpr int K3_B_BYTES = 64 * 80 * 2;
constexpr int K3_STAGE = K3_A_BYTES + K3_B_BYTES;
constexpr int K3_SMEM = K3_STAGES * K3_STAGE + 1024;

__global__ void __cluster_dims__(2, 1, 1) __launch_bounds__(288, 1)
out_kernel(const __grid_constant__ CUtensorMap tmA2, const __grid_constant__ CUtensorMap tmWoA, const __grid_constant__ CUtensorMap tmWoB,
           __nv_bfloat16* __restrict__ out) {
  extern __shared__ uint8_t smem_raw[];
  __shared__ __align__(8) uint64_t bar_full[K3_STAGES], bar_empty[K3_STAGES];
  uint8_t* smem = reinterpret_cast<uint8_t*>((reinterpret_cast<uintptr_t>(smem_raw) + 1023) & ~(uintptr_t)1023);
  const uint32_t sbase = smem_u32(smem);
  const uint32_t dbase = sbase & 0x3FFFFu;
  const int tid = threadIdx.x, warp = tid >> 5, lane = tid & 31;
  const int mb = blockIdx.x >> 3, nb = blockIdx.x & 7, rank = nb & 1;
  PROF(2, 0);
  if (tid == 0) {
    for (int i = 0; i < K3_STAGES; i++) { mbar_init(smem_u32(&bar_full[i]), 1); mbar_init(smem_u32(&bar_empty[i]), 4); }
    fence_mbar_init();
  }
  cluster_arrive();
  cluster_wait();
  if (warp == 8) {
    if (lane == 0) {
      for (int kt = 0; kt < K3_STAGES; kt++) {
        const uint32_t fb = smem_u32(&bar_full[kt]);
        mbar_expect_tx(fb, K3_STAGE);
        tma_3d(sbase + kt * K3_STAGE + K3_A_BYTES, &tmWoA, 0, kt * 64, nb * 5, fb);
      }
      {
        const unsigned int* f = &g_done[mb * 8 + rank * 4];
        for (int spin = 0; spin < (1 << 26); spin++) {
          unsigned int a, b, c, d;
          asm volatile("ld.acquire.gpu.global.u32 %0, [%1];" : "=r"(a) : "l"(f) : "memory");
          asm volatile("ld.acquire.gpu.global.u32 %0, [%1];" : "=r"(b) : "l"(f + 1) : "memory");
          asm volatile("ld.acquire.gpu.global.u32 %0, [%1];" : "=r"(c) : "l"(f + 2) : "memory");
          asm volatile("ld.acquire.gpu.global.u32 %0, [%1];" : "=r"(d) : "l"(f + 3) : "memory");
          if (min(min(a, b), min(c, d)) >= 5u) break;
          __nanosleep(20);
        }
        asm volatile("fence.proxy.async;" ::: "memory");
      }
      for (int kt = 0; kt < 20; kt++) {
        const int s = kt % K3_STAGES;
        const uint32_t fb = smem_u32(&bar_full[s]);
        if (kt >= K3_STAGES) {
          mbar_wait_cluster(smem_u32(&bar_empty[s]), ((kt / K3_STAGES) - 1) & 1);
          mbar_expect_tx(fb, K3_STAGE);
          tma_3d(sbase + s * K3_STAGE + K3_A_BYTES, kt < 10 ? &tmWoA : &tmWoB, 0, (kt % 10) * 64, nb * 5, fb);
        }
        tma_2d_mc(sbase + s * K3_STAGE + rank * 8192, &tmA2, kt * 64, mb * 128 + rank * 64, fb, (uint16_t)0x3);
      }
    }
    __syncwarp();
  } else {
    const int wg = warp >> 2;
    float acc[40];
#pragma unroll
    for (int i = 0; i < 40; i++) acc[i] = 0.f;
    for (int kt = 0; kt < 20; kt++) {
      const int s = kt % K3_STAGES;
      mbar_wait(smem_u32(&bar_full[s]), (kt / K3_STAGES) & 1);
      if (kt == 0) PROF(2, 1);
      const uint32_t alo = ((dbase + s * K3_STAGE + wg * 8192) >> 4) | (1u << 16);
      const uint32_t blo = ((dbase + s * K3_STAGE + K3_A_BYTES) >> 4) | ((2048u >> 4) << 16);
      fence_regs(acc);
      wg_fence();
#pragma unroll
      for (int k = 0; k < 4; k++) wgmma_ss_n80_tb(acc, mkd(alo + k * 2, DHI_SW128_K), mkd(blo + k * 32, DHI_SW32_MN));
      wg_commit();
      if (kt > 0 && kt - 1 + K3_STAGES < 20) {
        wg_wait<1>();
        if (lane == 0 && (warp & 2) == 0) mbar_arrive_remote(smem_u32(&bar_empty[(kt - 1) % K3_STAGES]), warp & 1);
      }
    }
    wg_wait<0>();
    fence_regs(acc);
    PROF(2, 2);
    asm volatile("bar.sync %0, 128;" :: "r"(wg + 1) : "memory");
    const int w4 = warp & 3;
    const uint32_t off = w4 * K3_STAGE + wg * 8192;
    const int row0 = mb * 128 + wg * 64 + w4 * 16;
    store_tile_bf16<80>(acc, 1.0f, sbase + off, smem + off, out + (size_t)row0 * D_MODEL + nb * 80, D_MODEL, lane);
    PROF(2, 3);
  }
}

typedef CUresult (*EncodeFn)(CUtensorMap*, CUtensorMapDataType, cuuint32_t, void*, const cuuint64_t*, const cuuint64_t*,
                             const cuuint32_t*, const cuuint32_t*, CUtensorMapInterleave, CUtensorMapSwizzle,
                             CUtensorMapL2promotion, CUtensorMapFloatOOBfill);

void make_map(EncodeFn fn, CUtensorMap* tm, const void* ptr, int rank, const cuuint64_t* dims, const cuuint64_t* strides,
              const cuuint32_t* box, CUtensorMapSwizzle sw) {
  const cuuint32_t es[3] = {1, 1, 1};
  fn(tm, CU_TENSOR_MAP_DATA_TYPE_BFLOAT16, rank, const_cast<void*>(ptr), dims, strides, box, es, CU_TENSOR_MAP_INTERLEAVE_NONE, sw,
     CU_TENSOR_MAP_L2_PROMOTION_L2_256B, CU_TENSOR_MAP_FLOAT_OOB_FILL_NONE);
}
void map_a(EncodeFn fn, CUtensorMap* tm, const void* p, int rows, int cols, int box_rows) {
  const cuuint64_t dims[2] = {(cuuint64_t)cols, (cuuint64_t)rows};
  const cuuint64_t str[1] = {(cuuint64_t)cols * 2};
  const cuuint32_t box[2] = {64, (cuuint32_t)box_rows};
  make_map(fn, tm, p, 2, dims, str, box, CU_TENSOR_MAP_SWIZZLE_128B);
}
void map_w(EncodeFn fn, CUtensorMap* tm, const void* p, int K, int N, int atom, CUtensorMapSwizzle sw) {
  const cuuint64_t dims[3] = {(cuuint64_t)atom, (cuuint64_t)K, (cuuint64_t)(N / atom)};
  const cuuint64_t str[2] = {(cuuint64_t)N * 2, (cuuint64_t)atom * 2};
  const cuuint32_t box[3] = {(cuuint32_t)atom, 64, 5};
  make_map(fn, tm, p, 3, dims, str, box, sw);
}

template <typename... KArgs, typename... Args>
void launch(void (*kern)(KArgs...), int grid, int block, int smem, bool pdl, Args... args) {
  cudaLaunchConfig_t cfg = {};
  cfg.gridDim = dim3(grid); cfg.blockDim = dim3(block); cfg.dynamicSmemBytes = smem; cfg.stream = cudaStreamPerThread;
  cudaLaunchAttribute at[1];
  at[0].id = cudaLaunchAttributeProgrammaticStreamSerialization;
  at[0].val.programmaticStreamSerializationAllowed = 1;
  cfg.attrs = at; cfg.numAttrs = pdl ? 1 : 0;
  cudaLaunchKernelEx(&cfg, kern, KArgs(args)...);
}

}

extern "C" void kernel_launch(void* const* d_in, const int* in_sizes, int n_in, void* d_out, int out_size) {
  (void)in_sizes; (void)n_in; (void)out_size;
  const __nv_bfloat16* x = (const __nv_bfloat16*)d_in[0];
  const __nv_bfloat16* wq = (const __nv_bfloat16*)d_in[1];
  const __nv_bfloat16* wk = (const __nv_bfloat16*)d_in[2];
  const __nv_bfloat16* wv = (const __nv_bfloat16*)d_in[3];
  const __nv_bfloat16* woA = (const __nv_bfloat16*)d_in[4];
  const __nv_bfloat16* wqkv = (const __nv_bfloat16*)d_in[6];
  const __nv_bfloat16* woB = (const __nv_bfloat16*)d_in[7];
  const __nv_bfloat16* gate_w = (const __nv_bfloat16*)d_in[8];

  static EncodeFn enc = nullptr;
  static void* a2_ptr = nullptr;
  if (!enc) {
    void* fp = nullptr;
    cudaDriverEntryPointQueryResult qr;
    cudaGetDriverEntryPoint("cuTensorMapEncodeTiled", &fp, cudaEnableDefault, &qr);
    enc = (EncodeFn)fp;
    cudaGetSymbolAddress(&a2_ptr, g_a2);
    cudaFuncSetAttribute(proj_kernel, cudaFuncAttributeMaxDynamicSharedMemorySize, K1_SMEM);
    cudaFuncSetAttribute(attn_kernel, cudaFuncAttributeMaxDynamicSharedMemorySize, K2_SMEM);
    cudaFuncSetAttribute(out_kernel, cudaFuncAttributeMaxDynamicSharedMemorySize, K3_SMEM);
  }
  CUtensorMap tmX, tmX64, tmWq, tmWqkv, tmA2, tmWoA, tmWoB;
  map_a(enc, &tmX, x, S_LEN, D_MODEL, 256);
  map_a(enc, &tmX64, x, S_LEN, D_MODEL, 128);
  map_w(enc, &tmWq, wq, D_MODEL, D_MODEL, 32, CU_TENSOR_MAP_SWIZZLE_64B);
  map_w(enc, &tmWqkv, wqkv, D_MODEL, 3 * D_MODEL, 32, CU_TENSOR_MAP_SWIZZLE_64B);
  map_a(enc, &tmA2, a2_ptr, S_LEN, 2 * D_MODEL, 64);
  map_w(enc, &tmWoA, woA, D_MODEL, D_MODEL, 16, CU_TENSOR_MAP_SWIZZLE_32B);
  map_w(enc, &tmWoB, woB, D_MODEL, D_MODEL, 16, CU_TENSOR_MAP_SWIZZLE_32B);

  launch(proj_kernel, 132, 512, K1_SMEM, false, tmX, tmX64, tmWq, tmWqkv, wk, wv, gate_w);
  launch(attn_kernel, 128, 640, K2_SMEM, true, 0x3F803F80u);
  launch(out_kernel, 128, 288, K3_SMEM, true, tmA2, tmWoA, tmWoB, (__nv_bfloat16*)d_out);
}
```

```cpp
#include <cuda_runtime.h>
#include <cuda_bf16.h>
#include <cuda.h>
#include <stdint.h>

namespace {

constexpr int S_LEN = 2048, D_MODEL = 640, DH = 20;

constexpr int GRP = 128;
constexpr int PLANE = GRP * 16;
constexpr int GRP_BYTES = GRP * 16 * 6;
constexpr int NGRP = S_LEN / GRP;
constexpr uint32_t TMASK = 0x6DB6u;

__device__ __align__(1024) __nv_bfloat16 g_q[S_LEN * D_MODEL];
__device__ __align__(1024) __nv_bfloat16 g_qkv[S_LEN * 3 * D_MODEL];
__device__ __align__(1024) __nv_bfloat16 g_a2[S_LEN * 2 * D_MODEL];
__device__ __align__(1024) uint8_t g_kvimg[NGRP * GRP_BYTES];
__device__ float g_gate[S_LEN];
__device__ float g_kmax2[128];
__device__ float g_vmax[128];
__device__ __align__(16) unsigned int g_done[128];

#define PROF(k, slot)
__device__ __forceinline__ uint32_t smem_u32(const void* p) { return (uint32_t)__cvta_generic_to_shared(p); }
__device__ __forceinline__ uint64_t mkd(uint32_t lo, uint32_t hi) {
  uint64_t d; asm("mov.b64 %0, {%1, %2};" : "=l"(d) : "r"(lo), "r"(hi)); return d;
}
__device__ __forceinline__ void wg_fence() { asm volatile("wgmma.fence.sync.aligned;" ::: "memory"); }
__device__ __forceinline__ void wg_commit() { asm volatile("wgmma.commit_group.sync.aligned;" ::: "memory"); }
template <int N> __device__ __forceinline__ void wg_wait() { asm volatile("wgmma.wait_group.sync.aligned %0;" :: "n"(N) : "memory"); }
template <int N> __device__ __forceinline__ void fence_regs(float (&d)[N]) {
#pragma unroll
  for (int i = 0; i < N; i++) asm volatile("" : "+f"(d[i]) :: "memory");
}
template <int N> __device__ __forceinline__ void fence_regs(uint32_t (&d)[N]) {
#pragma unroll
  for (int i = 0; i < N; i++) asm volatile("" : "+r"(d[i]) :: "memory");
}
__device__ __forceinline__ void mbar_init(uint32_t bar, uint32_t cnt) { asm volatile("mbarrier.init.shared::cta.b64 [%0], %1;" :: "r"(bar), "r"(cnt)); }
__device__ __forceinline__ void mbar_expect_tx(uint32_t bar, uint32_t bytes) {
  asm volatile("mbarrier.arrive.expect_tx.shared::cta.b64 _, [%0], %1;" :: "r"(bar), "r"(bytes) : "memory");
}
__device__ __forceinline__ void mbar_arrive(uint32_t bar) { asm volatile("mbarrier.arrive.shared::cta.b64 _, [%0];" :: "r"(bar) : "memory"); }
__device__ __forceinline__ void mbar_wait(uint32_t bar, uint32_t parity) {
  asm volatile("{\n.reg .pred p;\nWAIT_%=:\nmbarrier.try_wait.parity.shared::cta.b64 p, [%0], %1;\n@p bra DONE_%=;\nbra WAIT_%=;\nDONE_%=:\n}\n"
               :: "r"(bar), "r"(parity) : "memory");
}
__device__ __forceinline__ void fence_mbar_init() { asm volatile("fence.mbarrier_init.release.cluster;" ::: "memory"); }
__device__ __forceinline__ void fence_proxy_async() { asm volatile("fence.proxy.async.shared::cta;" ::: "memory"); }
__device__ __forceinline__ void bulk_g2s(uint32_t dst, const void* src, uint32_t bytes, uint32_t bar) {
  asm volatile("cp.async.bulk.shared::cluster.global.mbarrier::complete_tx::bytes [%0], [%1], %2, [%3];"
               :: "r"(dst), "l"(src), "r"(bytes), "r"(bar) : "memory");
}
__device__ __forceinline__ void tma_2d(uint32_t dst, const CUtensorMap* tm, int c0, int c1, uint32_t bar) {
  asm volatile("cp.async.bulk.tensor.2d.shared::cluster.global.mbarrier::complete_tx::bytes [%0], [%1, {%3, %4}], [%2];"
               :: "r"(dst), "l"((uint64_t)tm), "r"(bar), "r"(c0), "r"(c1) : "memory");
}
__device__ __forceinline__ void tma_3d(uint32_t dst, const CUtensorMap* tm, int c0, int c1, int c2, uint32_t bar) {
  asm volatile("cp.async.bulk.tensor.3d.shared::cluster.global.mbarrier::complete_tx::bytes [%0], [%1, {%3, %4, %5}], [%2];"
               :: "r"(dst), "l"((uint64_t)tm), "r"(bar), "r"(c0), "r"(c1), "r"(c2) : "memory");
}
__device__ __forceinline__ void tma_2d_mc(uint32_t dst, const CUtensorMap* tm, int c0, int c1, uint32_t bar, uint16_t mask) {
  asm volatile("cp.async.bulk.tensor.2d.shared::cluster.global.mbarrier::complete_tx::bytes.multicast::cluster [%0], [%1, {%3, %4}], [%2], %5;"
               :: "r"(dst), "l"((uint64_t)tm), "r"(bar), "r"(c0), "r"(c1), "h"(mask) : "memory");
}
__device__ __forceinline__ void mbar_arrive_remote(uint32_t bar, uint32_t rank) {
  asm volatile("{\n.reg .b32 ra;\nmapa.shared::cluster.u32 ra, %0, %1;\nmbarrier.arrive.shared::cluster.b64 _, [ra];\n}\n"
               :: "r"(bar), "r"(rank) : "memory");
}
__device__ __forceinline__ void mbar_wait_cluster(uint32_t bar, uint32_t parity) {
  asm volatile("{\n.reg .pred p;\nWAIT_%=:\nmbarrier.try_wait.parity.shared::cta.b64 p, [%0], %1;\n@p bra DONE_%=;\nbra WAIT_%=;\nDONE_%=:\n}\n"
               :: "r"(bar), "r"(parity) : "memory");
}
__device__ __forceinline__ void cluster_arrive() { asm volatile("barrier.cluster.arrive.release.aligned;" ::: "memory"); }
__device__ __forceinline__ void cluster_wait() { asm volatile("barrier.cluster.wait.acquire.aligned;" ::: "memory"); }
__device__ __forceinline__ void prefetch_tmap(const CUtensorMap* tm) { asm volatile("prefetch.tensormap [%0];" :: "l"((uint64_t)tm) : "memory"); }
__device__ __forceinline__ void pdl_wait() { asm volatile("griddepcontrol.wait;" ::: "memory"); }
__device__ __forceinline__ void pdl_launch() { asm volatile("griddepcontrol.launch_dependents;" ::: "memory"); }
__device__ __forceinline__ float ex2(float x) { float y; asm("ex2.approx.ftz.f32 %0, %1;" : "=f"(y) : "f"(x)); return y; }
__device__ __forceinline__ uint32_t pack_bf16(float lo, float hi) {
  uint32_t r; asm("cvt.rn.bf16x2.f32 %0, %1, %2;" : "=r"(r) : "f"(hi), "f"(lo)); return r;
}
__device__ __forceinline__ float bf_lo(uint32_t x) { return __uint_as_float(x << 16); }
__device__ __forceinline__ float bf_hi(uint32_t x) { return __uint_as_float(x & 0xffff0000u); }
__device__ __forceinline__ void stsm4(uint32_t addr, uint32_t r0, uint32_t r1, uint32_t r2, uint32_t r3) {
  asm volatile("stmatrix.sync.aligned.m8n8.x4.shared.b16 [%0], {%1, %2, %3, %4};" :: "r"(addr), "r"(r0), "r"(r1), "r"(r2), "r"(r3) : "memory");
}

__device__ __forceinline__ void wgmma_ss_n160_tb(float (&d)[80], uint64_t descA, uint64_t descB) {
  asm volatile("wgmma.mma_async.sync.aligned.m64n160k16.f32.bf16.bf16 {%0, %1, %2, %3, %4, %5, %6, %7, %8, %9, %10, %11, %12, %13, %14, %15, %16, %17, %18, %19, %20, %21, %22, %23, %24, %25, %26, %27, %28, %29, %30, %31, %32, %33, %34, %35, %36, %37, %38, %39, %40, %41, %42, %43, %44, %45, %46, %47, %48, %49, %50, %51, %52, %53, %54, %55, %56, %57, %58, %59, %60, %61, %62, %63, %64, %65, %66, %67, %68, %69, %70, %71, %72, %73, %74, %75, %76, %77, %78, %79}, %80, %81, 1, 1, 1, 0, 1;\n"
    : "+f"(d[0]), "+f"(d[1]), "+f"(d[2]), "+f"(d[3]), "+f"(d[4]), "+f"(d[5]), "+f"(d[6]), "+f"(d[7]), "+f"(d[8]), "+f"(d[9]), "+f"(d[10]), "+f"(d[11]), "+f"(d[12]), "+f"(d[13]), "+f"(d[14]), "+f"(d[15]), "+f"(d[16]), "+f"(d[17]), "+f"(d[18]), "+f"(d[19]), "+f"(d[20]), "+f"(d[21]), "+f"(d[22]), "+f"(d[23]), "+f"(d[24]), "+f"(d[25]), "+f"(d[26]), "+f"(d[27]), "+f"(d[28]), "+f"(d[29]), "+f"(d[30]), "+f"(d[31]), "+f"(d[32]), "+f"(d[33]), "+f"(d[34]), "+f"(d[35]), "+f"(d[36]), "+f"(d[37]), "+f"(d[38]), "+f"(d[39]), "+f"(d[40]), "+f"(d[41]), "+f"(d[42]), "+f"(d[43]), "+f"(d[44]), "+f"(d[45]), "+f"(d[46]), "+f"(d[47]), "+f"(d[48]), "+f"(d[49]), "+f"(d[50]), "+f"(d[51]), "+f"(d[52]), "+f"(d[53]), "+f"(d[54]), "+f"(d[55]), "+f"(d[56]), "+f"(d[57]), "+f"(d[58]), "+f"(d[59]), "+f"(d[60]), "+f"(d[61]), "+f"(d[62]), "+f"(d[63]), "+f"(d[64]), "+f"(d[65]), "+f"(d[66]), "+f"(d[67]), "+f"(d[68]), "+f"(d[69]), "+f"(d[70]), "+f"(d[71]), "+f"(d[72]), "+f"(d[73]), "+f"(d[74]), "+f"(d[75]), "+f"(d[76]), "+f"(d[77]), "+f"(d[78]), "+f"(d[79])
    : "l"(descA), "l"(descB));
}
__device__ __forceinline__ void wgmma_ss_n48_tb(float (&d)[24], uint64_t descA, uint64_t descB) {
  asm volatile("wgmma.mma_async.sync.aligned.m64n48k16.f32.bf16.bf16 {%0, %1, %2, %3, %4, %5, %6, %7, %8, %9, %10, %11, %12, %13, %14, %15, %16, %17, %18, %19, %20, %21, %22, %23}, %24, %25, 1, 1, 1, 0, 1;\n"
    : "+f"(d[0]), "+f"(d[1]), "+f"(d[2]), "+f"(d[3]), "+f"(d[4]), "+f"(d[5]), "+f"(d[6]), "+f"(d[7]), "+f"(d[8]), "+f"(d[9]), "+f"(d[10]), "+f"(d[11]), "+f"(d[12]), "+f"(d[13]), "+f"(d[14]), "+f"(d[15]), "+f"(d[16]), "+f"(d[17]), "+f"(d[18]), "+f"(d[19]), "+f"(d[20]), "+f"(d[21]), "+f"(d[22]), "+f"(d[23])
    : "l"(descA), "l"(descB));
}
__device__ __forceinline__ void wgmma_ss_n80_tb(float (&d)[40], uint64_t descA, uint64_t descB) {
  asm volatile("wgmma.mma_async.sync.aligned.m64n80k16.f32.bf16.bf16 {%0, %1, %2, %3, %4, %5, %6, %7, %8, %9, %10, %11, %12, %13, %14, %15, %16, %17, %18, %19, %20, %21, %22, %23, %24, %25, %26, %27, %28, %29, %30, %31, %32, %33, %34, %35, %36, %37, %38, %39}, %40, %41, 1, 1, 1, 0, 1;\n"
    : "+f"(d[0]), "+f"(d[1]), "+f"(d[2]), "+f"(d[3]), "+f"(d[4]), "+f"(d[5]), "+f"(d[6]), "+f"(d[7]), "+f"(d[8]), "+f"(d[9]), "+f"(d[10]), "+f"(d[11]), "+f"(d[12]), "+f"(d[13]), "+f"(d[14]), "+f"(d[15]), "+f"(d[16]), "+f"(d[17]), "+f"(d[18]), "+f"(d[19]), "+f"(d[20]), "+f"(d[21]), "+f"(d[22]), "+f"(d[23]), "+f"(d[24]), "+f"(d[25]), "+f"(d[26]), "+f"(d[27]), "+f"(d[28]), "+f"(d[29]), "+f"(d[30]), "+f"(d[31]), "+f"(d[32]), "+f"(d[33]), "+f"(d[34]), "+f"(d[35]), "+f"(d[36]), "+f"(d[37]), "+f"(d[38]), "+f"(d[39])
    : "l"(descA), "l"(descB));
}
template <int SCALE_D>
__device__ __forceinline__ void wgmma_rs_n64(float (&d)[32], uint32_t a0, uint32_t a1, uint32_t a2, uint32_t a3, uint64_t descB) {
  asm volatile("wgmma.mma_async.sync.aligned.m64n64k16.f32.bf16.bf16 {%0, %1, %2, %3, %4, %5, %6, %7, %8, %9, %10, %11, %12, %13, %14, %15, %16, %17, %18, %19, %20, %21, %22, %23, %24, %25, %26, %27, %28, %29, %30, %31}, {%32, %33, %34, %35}, %36, %37, 1, 1, 0;\n"
    : "+f"(d[0]), "+f"(d[1]), "+f"(d[2]), "+f"(d[3]), "+f"(d[4]), "+f"(d[5]), "+f"(d[6]), "+f"(d[7]), "+f"(d[8]), "+f"(d[9]), "+f"(d[10]), "+f"(d[11]), "+f"(d[12]), "+f"(d[13]), "+f"(d[14]), "+f"(d[15]), "+f"(d[16]), "+f"(d[17]), "+f"(d[18]), "+f"(d[19]), "+f"(d[20]), "+f"(d[21]), "+f"(d[22]), "+f"(d[23]), "+f"(d[24]), "+f"(d[25]), "+f"(d[26]), "+f"(d[27]), "+f"(d[28]), "+f"(d[29]), "+f"(d[30]), "+f"(d[31])
    : "r"(a0), "r"(a1), "r"(a2), "r"(a3), "l"(descB), "n"(SCALE_D));
}
template <int SCALE_D>
__device__ __forceinline__ void wgmma_rs_n24_tb(float (&d)[12], uint32_t a0, uint32_t a1, uint32_t a2, uint32_t a3, uint64_t descB) {
  asm volatile("wgmma.mma_async.sync.aligned.m64n24k16.f32.bf16.bf16 {%0, %1, %2, %3, %4, %5, %6, %7, %8, %9, %10, %11}, {%12, %13, %14, %15}, %16, %17, 1, 1, 1;\n"
    : "+f"(d[0]), "+f"(d[1]), "+f"(d[2]), "+f"(d[3]), "+f"(d[4]), "+f"(d[5]), "+f"(d[6]), "+f"(d[7]), "+f"(d[8]), "+f"(d[9]), "+f"(d[10]), "+f"(d[11])
    : "r"(a0), "r"(a1), "r"(a2), "r"(a3), "l"(descB), "n"(SCALE_D));
}

constexpr uint32_t DHI_SW128_K = (1024 >> 4) | (1u << 30);
constexpr uint32_t DHI_SW64_MN = (512 >> 4) | (2u << 30);
constexpr uint32_t DHI_SW32_MN = (256 >> 4) | (3u << 30);

template <int NC>
__device__ __forceinline__ void store_tile_bf16(const float (&acc)[NC / 2], float scale, uint32_t stage, uint8_t* stage_ptr,
                                                __nv_bfloat16* gdst, int gpitch, int lane) {
  constexpr int PITCH = NC * 2 + 16;
  const uint32_t waddr = stage + ((lane & 7) + ((lane >> 3) & 1) * 8) * PITCH + (lane >> 4) * 16;
#pragma unroll
  for (int j = 0; j < NC / 16; j++) {
    stsm4(waddr + j * 32, pack_bf16(acc[8 * j] * scale, acc[8 * j + 1] * scale), pack_bf16(acc[8 * j + 2] * scale, acc[8 * j + 3] * scale),
          pack_bf16(acc[8 * j + 4] * scale, acc[8 * j + 5] * scale), pack_bf16(acc[8 * j + 6] * scale, acc[8 * j + 7] * scale));
  }
  __syncwarp();
  constexpr int CPR = NC / 8;
#pragma unroll
  for (int i = 0; i < CPR / 2; i++) {
    const int c = i * 32 + lane, r = c / CPR, cc = c % CPR;
    const uint4 v = *reinterpret_cast<const uint4*>(stage_ptr + r * PITCH + cc * 16);
    *reinterpret_cast<uint4*>(gdst + (size_t)r * gpitch + cc * 8) = v;
  }
}

constexpr int K1_STAGES = 4;
constexpr int K1_A_BYTES = 256 * 128;
constexpr int K1_B_BYTES = 64 * 160 * 2;
constexpr int K1_STAGE = K1_A_BYTES + K1_B_BYTES;
constexpr int K1_SMEM = 5 * K1_A_BYTES + 61440 + 1024;
constexpr int KV_STAGES = 5;
constexpr int KVW_OFF = KV_STAGES * K1_A_BYTES;

__global__ void __launch_bounds__(512, 1)
proj_kernel(const __grid_constant__ CUtensorMap tmX, const __grid_constant__ CUtensorMap tmWq, const __grid_constant__ CUtensorMap tmWqkv,
            const __nv_bfloat16* __restrict__ wk, const __nv_bfloat16* __restrict__ wv, const __nv_bfloat16* __restrict__ gate_w) {
  extern __shared__ uint8_t smem_raw[];
  __shared__ __align__(8) uint64_t bar_full[KV_STAGES], bar_empty[KV_STAGES];
  uint8_t* smem = reinterpret_cast<uint8_t*>((reinterpret_cast<uintptr_t>(smem_raw) + 1023) & ~(uintptr_t)1023);
  const uint32_t sbase = smem_u32(smem);
  const uint32_t dbase = sbase & 0x3FFFFu;
  const int tid = threadIdx.x, warp = tid >> 5, lane = tid & 31;
  const bool is_kv = blockIdx.x >= 128;
  PROF(0, 0);
  pdl_launch();
  if (tid == 0) {
    for (int i = 0; i < KV_STAGES; i++) { mbar_init(smem_u32(&bar_full[i]), 1); mbar_init(smem_u32(&bar_empty[i]), 16); }
    fence_mbar_init();
    if (!is_kv) g_done[blockIdx.x] = 0u;
  }
  __syncthreads();

  if (!is_kv) {
    const int mb = blockIdx.x >> 4, nb = blockIdx.x & 15;
    const CUtensorMap* tw = nb < 4 ? &tmWq : &tmWqkv;
    const int j0 = (nb < 4 ? nb : nb - 4) * 5;
    auto load = [&](int kt) {
      const int s = kt % K1_STAGES;
      const uint32_t fb = smem_u32(&bar_full[s]);
      mbar_expect_tx(fb, K1_STAGE);
      tma_2d(sbase + s * K1_STAGE, &tmX, kt * 64, mb * 256, fb);
      tma_3d(sbase + s * K1_STAGE + K1_A_BYTES, tw, 0, kt * 64, j0, fb);
    };
    if (tid == 0) for (int kt = 0; kt < K1_STAGES; kt++) load(kt);
    {
      const int wg = warp >> 2;
      float acc[80];
#pragma unroll
      for (int i = 0; i < 80; i++) acc[i] = 0.f;
      for (int kt = 0; kt < 10; kt++) {
        const int s = kt % K1_STAGES;
        mbar_wait(smem_u32(&bar_full[s]), (kt / K1_STAGES) & 1);
        const uint32_t alo = ((dbase + s * K1_STAGE + wg * 8192) >> 4) | (1u << 16);
        const uint32_t blo = ((dbase + s * K1_STAGE + K1_A_BYTES) >> 4) | ((4096u >> 4) << 16);
        fence_regs(acc);
        wg_fence();
#pragma unroll
        for (int k = 0; k < 4; k++) wgmma_ss_n160_tb(acc, mkd(alo + k * 2, DHI_SW128_K), mkd(blo + k * 64, DHI_SW64_MN));
        wg_commit();
        if (kt > 0 && kt - 1 + K1_STAGES < 10) {
          wg_wait<1>();
          const uint32_t eb = smem_u32(&bar_empty[(kt - 1) % K1_STAGES]);
          if (lane == 0) mbar_arrive(eb);
          if (tid == 0) { mbar_wait(eb, ((kt - 1) / K1_STAGES) & 1); load(kt - 1 + K1_STAGES); }
          __syncwarp();
        }
      }
      wg_wait<0>();
      fence_regs(acc);
      PROF(0, 1);
      asm volatile("bar.sync %0, 128;" :: "r"(wg + 1) : "memory");
      const int w4 = warp & 3;
      const uint32_t off = w4 * K1_STAGE + wg * 8192;
      const int row0 = mb * 256 + wg * 64 + w4 * 16;
      if (nb < 4) {
        store_tile_bf16<160>(acc, 0.22360679774997896f * 1.4426950408889634f, sbase + off, smem + off,
                             g_q + (size_t)row0 * D_MODEL + nb * 160, D_MODEL, lane);
      } else {
        store_tile_bf16<160>(acc, 1.0f, sbase + off, smem + off, g_qkv + (size_t)row0 * (3 * D_MODEL) + (nb - 4) * 160, 3 * D_MODEL, lane);
      }
    }
  } else {
    const int cb = blockIdx.x - 128;
    auto load = [&](int it) {
      const int s = it % KV_STAGES;
      const uint32_t fb = smem_u32(&bar_full[s]);
      mbar_expect_tx(fb, K1_A_BYTES);
      tma_2d(sbase + s * K1_A_BYTES, &tmX, (it % 10) * 64, cb * 512 + (it / 10) * 256, fb);
    };
    if (tid == 0) for (int it = 0; it < KV_STAGES; it++) load(it);
    {
      if (tid < 320) {
        uint2 a[2][5], b[2][5]; uint32_t gw[2];
#pragma unroll
        for (int r = 0; r < 2; r++) {
          const int k = tid + r * 320;
          const uint2* pk = reinterpret_cast<const uint2*>(wk + k * 20);
          const uint2* pv = reinterpret_cast<const uint2*>(wv + k * 20);
#pragma unroll
          for (int i = 0; i < 5; i++) { a[r][i] = __ldg(pk + i); b[r][i] = __ldg(pv + i); }
          gw[r] = (uint32_t)__bfloat16_as_ushort(gate_w[k]);
        }
#pragma unroll
        for (int r = 0; r < 2; r++) {
          uint4* dst = reinterpret_cast<uint4*>(smem + KVW_OFF + (tid + r * 320) * 16);
          dst[0] = make_uint4(a[r][0].x, a[r][0].y, a[r][1].x, a[r][1].y);
          dst[640] = make_uint4(a[r][2].x, a[r][2].y, a[r][3].x, a[r][3].y);
          dst[1280] = make_uint4(a[r][4].x, a[r][4].y, 0u, 0u);
          dst[1920] = make_uint4(b[r][0].x, b[r][0].y, b[r][1].x, b[r][1].y);
          dst[2560] = make_uint4(b[r][2].x, b[r][2].y, b[r][3].x, b[r][3].y);
          dst[3200] = make_uint4(b[r][4].x, b[r][4].y, gw[r], 0u);
        }
      }
      fence_proxy_async();
      asm volatile("bar.sync 1, 512;" ::: "memory");
      PROF(0, 1);
      const int wg = warp >> 2, w4 = warp & 3, g = lane >> 2, t = lane & 3;
      for (int pass = 0; pass < 2; pass++) {
        float acc[24];
#pragma unroll
        for (int i = 0; i < 24; i++) acc[i] = 0.f;
        for (int kt = 0; kt < 10; kt++) {
          const int it = pass * 10 + kt, s = it % KV_STAGES;
          mbar_wait(smem_u32(&bar_full[s]), (it / KV_STAGES) & 1);
          const uint32_t alo = ((dbase + s * K1_A_BYTES + wg * 8192) >> 4) | (1u << 16);
          const uint32_t blo = ((dbase + KVW_OFF + kt * 1024) >> 4) | ((128u >> 4) << 16);
          fence_regs(acc);
          wg_fence();
#pragma unroll
          for (int k = 0; k < 4; k++) wgmma_ss_n48_tb(acc, mkd(alo + k * 2, DHI_SW128_K), mkd(blo + k * 16, 10240u >> 4));
          wg_commit();
          wg_wait<0>();
          if (it + KV_STAGES < 20) {
            const uint32_t eb = smem_u32(&bar_empty[s]);
            if (lane == 0) mbar_arrive(eb);
            if (tid == 0) { mbar_wait(eb, (it / KV_STAGES) & 1); load(it + KV_STAGES); }
            __syncwarp();
          }
        }
        fence_regs(acc);
        float kmax2 = 0.f, vmax = 0.f;
#pragma unroll
        for (int h = 0; h < 2; h++) {
          const int key = cb * 512 + pass * 256 + wg * 64 + w4 * 16 + g + h * 8;
          const int grp = key >> 7, kk = key & 127;
          const bool poly = (TMASK >> (kk >> 3)) & 1;
          uint8_t* gp = g_kvimg + grp * GRP_BYTES;
          const uint32_t k0 = pack_bf16(acc[2 * h], acc[2 * h + 1]);
          const uint32_t k1 = pack_bf16(acc[4 + 2 * h], acc[5 + 2 * h]);
          uint32_t k2 = pack_bf16(acc[8 + 2 * h], acc[9 + 2 * h]);
          float n2 = bf_lo(k0) * bf_lo(k0) + bf_hi(k0) * bf_hi(k0) + bf_lo(k1) * bf_lo(k1) + bf_hi(k1) * bf_hi(k1);
          if (t < 2) {
            n2 += bf_lo(k2) * bf_lo(k2) + bf_hi(k2) * bf_hi(k2);
            k2 = pack_bf16(bf_lo(k2) * 0.5f, bf_hi(k2) * 0.5f);
          } else if (t == 2) k2 = poly ? pack_bf16(24.f, 2.5f) : pack_bf16(0.5f, 0.f);
          else k2 = poly ? pack_bf16(0.5f, 0.f) : 0u;
          *reinterpret_cast<uint32_t*>(gp + kk * 16 + t * 4) = k0;
          *reinterpret_cast<uint32_t*>(gp + PLANE + kk * 16 + t * 4) = k1;
          *reinterpret_cast<uint32_t*>(gp + 2 * PLANE + kk * 16 + t * 4) = k2;
          n2 += __shfl_xor_sync(0xffffffffu, n2, 1);
          n2 += __shfl_xor_sync(0xffffffffu, n2, 2);
          kmax2 = (n2 > kmax2 || n2 != n2) ? n2 : kmax2;
          uint32_t v0 = pack_bf16(acc[12 + 2 * h], acc[13 + 2 * h]);
          uint32_t v1 = pack_bf16(acc[16 + 2 * h], acc[17 + 2 * h]);
          uint32_t v2 = pack_bf16(acc[20 + 2 * h], acc[21 + 2 * h]);
          float vm = fmaxf(fmaxf(fabsf(bf_lo(v0)), fabsf(bf_hi(v0))), fmaxf(fabsf(bf_lo(v1)), fabsf(bf_hi(v1))));
          if (t < 2) vm = fmaxf(vm, fmaxf(fabsf(bf_lo(v2)), fabsf(bf_hi(v2))));
          else if (t == 2) {
            const float z = acc[20 + 2 * h];
            g_gate[key] = 1.f / (1.f + __expf(-z));
            v2 = 0x00003F80u;
          } else v2 = 0u;
          vmax = fmaxf(vmax, vm);
          if (poly) { v0 ^= 0x80008000u; v1 ^= 0x80008000u; v2 ^= 0x80008000u; }
          uint8_t* vp = gp + 3 * PLANE + (kk >> 3) * 384 + (kk & 7) * 16 + t * 4;
          *reinterpret_cast<uint32_t*>(vp) = v0;
          *reinterpret_cast<uint32_t*>(vp + 128) = v1;
          *reinterpret_cast<uint32_t*>(vp + 256) = v2;
        }
#pragma unroll
        for (int o = 1; o < 32; o <<= 1) {
          const float a = __shfl_xor_sync(0xffffffffu, kmax2, o);
          kmax2 = (a > kmax2 || a != a) ? a : kmax2;
          vmax = fmaxf(vmax, __shfl_xor_sync(0xffffffffu, vmax, o));
        }
        if (lane == 0) { g_kmax2[cb * 32 + pass * 16 + warp] = kmax2; g_vmax[cb * 32 + pass * 16 + warp] = vmax; }
      }
    }
  }
  PROF(0, 3);
}

__device__ __forceinline__ uint32_t ex2_pair_poly(float u0, float u1, uint32_t one2) {
  const uint32_t W = __byte_perm(__float_as_uint(u0), __float_as_uint(u1), 0x6521);
  uint32_t v; asm("lop3.b32 %0, %1, 0x007F007F, %2, 0xEA;" : "=r"(v) : "r"(W), "r"(one2));
  uint32_t L, p;
  asm("fma.rn.bf16x2 %0, %1, %2, %3;" : "=r"(L) : "r"(v), "r"(0x1f961f96u), "r"(0x9fe39fe3u));
  asm("fma.rn.bf16x2 %0, %1, %1, %2;" : "=r"(p) : "r"(L), "r"(0x00f500f5u));
  return W + p;
}
template <int JOFF>
__device__ __forceinline__ void softmax_fast(const float (&S)[32], uint32_t (&P)[16], uint32_t one2) {
#pragma unroll
  for (int i = 0; i < 16; i++) {
    if ((TMASK >> (JOFF + i / 2)) & 1) P[i] = ex2_pair_poly(S[2 * i], S[2 * i + 1], one2);
    else P[i] = pack_bf16(ex2(S[2 * i]), ex2(S[2 * i + 1]));
  }
}
template <int JOFF>
__device__ __forceinline__ void softmax_slow(const float (&S)[32], uint32_t (&P)[16], float (&O)[12], float& m0, float& m1) {
  float a0 = m0, a1 = m1;
#pragma unroll
  for (int j = 0; j < 8; j++) {
    a0 = fmaxf(a0, fmaxf(S[4 * j], S[4 * j + 1]));
    a1 = fmaxf(a1, fmaxf(S[4 * j + 2], S[4 * j + 3]));
  }
  a0 = fmaxf(a0, __shfl_xor_sync(0xffffffffu, a0, 1)); a0 = fmaxf(a0, __shfl_xor_sync(0xffffffffu, a0, 2));
  a1 = fmaxf(a1, __shfl_xor_sync(0xffffffffu, a1, 1)); a1 = fmaxf(a1, __shfl_xor_sync(0xffffffffu, a1, 2));
  const float c0 = ex2(m0 - a0), c1 = ex2(m1 - a1);
  m0 = a0; m1 = a1;
#pragma unroll
  for (int j = 0; j < 3; j++) { O[4 * j] *= c0; O[4 * j + 1] *= c0; O[4 * j + 2] *= c1; O[4 * j + 3] *= c1; }
#pragma unroll
  for (int i = 0; i < 16; i++) {
    const float m = (i & 1) ? a1 : a0;
    const uint32_t p = pack_bf16(ex2(S[2 * i] - m), ex2(S[2 * i + 1] - m));
    P[i] = ((TMASK >> (JOFF + i / 2)) & 1) ? (p ^ 0x80008000u) : p;
  }
}
constexpr uint32_t DHI_KV = 128 >> 4;
__device__ __forceinline__ void issue_qk(float (&S)[32], const uint32_t (&q)[6], uint32_t base) {
  wgmma_rs_n64<0>(S, q[0], q[1], q[2], q[3], mkd(base + ((PLANE >> 4) << 16), DHI_KV));
  wgmma_rs_n64<1>(S, q[4], q[5], q[4], q[5], mkd(base + (2 * PLANE >> 4), DHI_KV));
}
__device__ __forceinline__ void issue_pv(float (&O)[12], const uint32_t (&P)[16], uint32_t vbase) {
#pragma unroll
  for (int kk = 0; kk < 4; kk++)
    wgmma_rs_n24_tb<1>(O, P[4 * kk], P[4 * kk + 1], P[4 * kk + 2], P[4 * kk + 3], mkd(vbase + kk * (768 >> 4), DHI_KV));
}

constexpr uint32_t VOFF = ((3 * PLANE) >> 4) + ((384u >> 4) << 16);
__device__ __forceinline__ void attn_tile_fast(const uint32_t (&q)[6], float (&O)[12], uint32_t sbase, uint32_t bars, bool first, uint32_t one2) {
  float S[32]; uint32_t P[16];
#pragma unroll
  for (int i = 0; i < 32; i++) S[i] = 0.f;
  uint32_t kb = sbase >> 4;
  const uint32_t klast = kb + (NGRP - 1) * (GRP_BYTES >> 4);
  if (first) mbar_wait(bars, 0);
  fence_regs(S); fence_regs(O);
  wg_fence();
  issue_qk(S, q, kb);
  wg_commit();
#pragma unroll 1
  for (int grp = 0; grp < NGRP; grp++) {
    if (first) mbar_wait(bars + 8 * min(grp + 1, NGRP - 1), 0);
    const uint32_t knext = min(kb + (GRP_BYTES >> 4), klast);
    wg_wait<0>();
    fence_regs(S); fence_regs(P); fence_regs(O);
    softmax_fast<0>(S, P, one2);
    fence_regs(S); fence_regs(P); fence_regs(O);
    wg_fence();
    issue_qk(S, q, kb + 64);
    issue_pv(O, P, kb + VOFF);
    wg_commit();
    wg_wait<0>();
    fence_regs(S); fence_regs(P); fence_regs(O);
    softmax_fast<8>(S, P, one2);
    fence_regs(S); fence_regs(P); fence_regs(O);
    wg_fence();
    issue_qk(S, q, knext);
    issue_pv(O, P, kb + VOFF + 4 * (768 >> 4));
    wg_commit();
    kb = knext;
  }
  wg_wait<0>();
  fence_regs(O); fence_regs(S);
}
template <int H>
__device__ __forceinline__ void slow_step(const uint32_t (&q)[6], float (&O)[12], uint32_t kb, float& m0, float& m1) {
  float S[32]; uint32_t P[16];
#pragma unroll
  for (int i = 0; i < 32; i++) S[i] = 0.f;
  fence_regs(S);
  wg_fence();
  issue_qk(S, q, kb + 64 * H);
  wg_commit();
  wg_wait<0>();
  fence_regs(S);
  softmax_slow<8 * H>(S, P, O, m0, m1);
  fence_regs(P); fence_regs(O);
  wg_fence();
  issue_pv(O, P, kb + VOFF + H * 4 * (768 >> 4));
  wg_commit();
  wg_wait<0>();
  fence_regs(O); fence_regs(P);
}
__device__ __forceinline__ void attn_tile_slow(const uint32_t (&q)[6], float (&O)[12], uint32_t sbase, uint32_t bars, bool first) {
  float m0 = -INFINITY, m1 = -INFINITY;
#pragma unroll 1
  for (int grp = 0; grp < NGRP; grp++) {
    if (first) mbar_wait(bars + 8 * grp, 0);
    const uint32_t kb = (sbase >> 4) + grp * (GRP_BYTES >> 4);
    slow_step<0>(q, O, kb, m0, m1);
    slow_step<1>(q, O, kb, m0, m1);
  }
}

constexpr int K2_QOFF = NGRP * GRP_BYTES;
constexpr int K2_SMEM = K2_QOFF + 512 * 6 * 4 + 1024;

__device__ __forceinline__ void local_attn_pair(int token, int lane) {
  const __nv_bfloat16* base = g_qkv + (size_t)token * (3 * D_MODEL) + lane * DH;
  float f[20];
  {
    const uint2* p = reinterpret_cast<const uint2*>(base);
#pragma unroll
    for (int i = 0; i < 5; i++) { const uint2 v = p[i]; f[4 * i] = bf_lo(v.x); f[4 * i + 1] = bf_hi(v.x); f[4 * i + 2] = bf_lo(v.y); f[4 * i + 3] = bf_hi(v.y); }
  }
  float sc[8];
  float mx = -INFINITY;
#pragma unroll
  for (int w = 0; w < 8; w++) {
    const bool ok = token - 2 * w >= 0;
    const uint2* p = reinterpret_cast<const uint2*>(base + D_MODEL - (ok ? 2 * w : 0) * (3 * D_MODEL));
    float s = 0.f;
#pragma unroll
    for (int i = 0; i < 5; i++) {
      const uint2 v = p[i];
      s = fmaf(f[4 * i], bf_lo(v.x), s); s = fmaf(f[4 * i + 1], bf_hi(v.x), s);
      s = fmaf(f[4 * i + 2], bf_lo(v.y), s); s = fmaf(f[4 * i + 3], bf_hi(v.y), s);
    }
    s *= 0.22360679774997896f * 1.4426950408889634f;
    sc[w] = ok ? s : -1e9f * 1.4426950408889634f;
    mx = fmaxf(mx, sc[w]);
  }
  float l = 0.f;
#pragma unroll
  for (int w = 0; w < 8; w++) { sc[w] = ex2(sc[w] - mx); l += sc[w]; }
#pragma unroll
  for (int i = 0; i < 20; i++) f[i] = 0.f;
#pragma unroll
  for (int w = 0; w < 8; w++) {
    const bool ok = token - 2 * w >= 0;
    const uint2* p = reinterpret_cast<const uint2*>(base + 2 * D_MODEL - (ok ? 2 * w : token) * (3 * D_MODEL));
#pragma unroll
    for (int i = 0; i < 5; i++) {
      const uint2 v = p[i];
      f[4 * i] = fmaf(sc[w], bf_lo(v.x), f[4 * i]); f[4 * i + 1] = fmaf(sc[w], bf_hi(v.x), f[4 * i + 1]);
      f[4 * i + 2] = fmaf(sc[w], bf_lo(v.y), f[4 * i + 2]); f[4 * i + 3] = fmaf(sc[w], bf_hi(v.y), f[4 * i + 3]);
    }
  }
  const float r = (1.f - g_gate[token]) / l;
  uint2* dst = reinterpret_cast<uint2*>(g_a2 + (size_t)token * (2 * D_MODEL) + D_MODEL + lane * DH);
#pragma unroll
  for (int i = 0; i < 5; i++) dst[i] = make_uint2(pack_bf16(f[4 * i] * r, f[4 * i + 1] * r), pack_bf16(f[4 * i + 2] * r, f[4 * i + 3] * r));
}

__device__ __forceinline__ void signal_done(int wg, int tid) {
  asm volatile("bar.sync %0, 128;" :: "r"(wg + 1) : "memory");
  if ((tid & 127) == 0) asm volatile("red.release.gpu.global.add.u32 [%0], 1;" :: "l"(&g_done[blockIdx.x]) : "memory");
}

__global__ void __launch_bounds__(640, 1)
attn_kernel(uint32_t one2) {
  extern __shared__ uint8_t smem_raw[];
  __shared__ __align__(8) uint64_t bars[NGRP];
  uint8_t* smem = reinterpret_cast<uint8_t*>((reinterpret_cast<uintptr_t>(smem_raw) + 1023) & ~(uintptr_t)1023);
  const uint32_t sbase = smem_u32(smem);
  const uint32_t dbase = sbase & 0x3FFFFu;
  const int tid = threadIdx.x, wg = tid >> 7, warp = (tid >> 5) & 3, lane = tid & 31, g = lane >> 2, t = lane & 3;
  PROF(1, 0);
  pdl_launch();
  if (tid == 0) {
    for (int i = 0; i < NGRP; i++) mbar_init(smem_u32(&bars[i]), 1);
    fence_mbar_init();
  }
  __syncthreads();
  if (wg == 4) {
    asm volatile("setmaxnreg.dec.sync.aligned.u32 56;");
    pdl_wait();
    if (tid == 512) {
      for (int j = 0; j < NGRP; j++) {
        if (j >= 4) mbar_wait(smem_u32(&bars[j - 4]), 0);
        mbar_expect_tx(smem_u32(&bars[j]), GRP_BYTES);
        bulk_g2s(sbase + j * GRP_BYTES, g_kvimg + j * GRP_BYTES, GRP_BYTES, smem_u32(&bars[j]));
      }
    }
    __syncwarp();
#pragma unroll 1
    for (int i = 0; i < 4; i++) local_attn_pair(blockIdx.x * 16 + i * 4 + warp, lane);
    signal_done(wg, tid);
  } else {
    asm volatile("setmaxnreg.inc.sync.aligned.u32 104;");
    pdl_wait();
    PROF(1, 1);
    uint32_t q[6];
    uint32_t* qstash = reinterpret_cast<uint32_t*>(smem + K2_QOFF) + tid;
    const int rowA = (blockIdx.x * 8 + wg) * 64 + warp * 16 + g;
    {
      const uint32_t* r0 = reinterpret_cast<const uint32_t*>(g_q + (size_t)rowA * DH);
      const uint32_t* r1 = r0 + 8 * (DH / 2);
      const uint32_t* s0 = r0 + 256 * (DH / 2);
      const uint32_t* s1 = s0 + 8 * (DH / 2);
      q[0] = r0[t]; q[1] = r1[t]; q[2] = r0[t + 4]; q[3] = r1[t + 4];
      q[4] = t < 2 ? r0[8 + t] : 0u;
      q[5] = t < 2 ? r1[8 + t] : 0u;
      qstash[0] = s0[t]; qstash[512] = s1[t]; qstash[1024] = s0[t + 4]; qstash[1536] = s1[t + 4];
      qstash[2048] = t < 2 ? s0[8 + t] : 0u;
      qstash[2560] = t < 2 ? s1[8 + t] : 0u;
    }
    float kmax2 = 0.f, vmax = 0.f;
#pragma unroll
    for (int i = 0; i < 4; i++) {
      const float a = g_kmax2[lane + 32 * i];
      kmax2 = (a > kmax2 || a != a) ? a : kmax2;
      vmax = fmaxf(vmax, g_vmax[lane + 32 * i]);
    }
#pragma unroll
    for (int o = 1; o < 32; o <<= 1) {
      const float a = __shfl_xor_sync(0xffffffffu, kmax2, o);
      kmax2 = (a > kmax2 || a != a) ? a : kmax2;
      vmax = fmaxf(vmax, __shfl_xor_sync(0xffffffffu, vmax, o));
    }
    const float qlim = (vmax >= 0.00390625f && vmax <= 256.f) ? 9025.f / kmax2 : -1.f;
    PROF(1, 2);
#pragma unroll 1
    for (int it = 0; it < 2; it++) {
      const int row0 = rowA + it * 256;
      if (it == 1) {
#pragma unroll
        for (int i = 0; i < 6; i++) q[i] = qstash[512 * i];
      }
      float n0 = bf_lo(q[0]) * bf_lo(q[0]) + bf_hi(q[0]) * bf_hi(q[0]) + bf_lo(q[2]) * bf_lo(q[2]) + bf_hi(q[2]) * bf_hi(q[2]) +
                 bf_lo(q[4]) * bf_lo(q[4]) + bf_hi(q[4]) * bf_hi(q[4]);
      float n1 = bf_lo(q[1]) * bf_lo(q[1]) + bf_hi(q[1]) * bf_hi(q[1]) + bf_lo(q[3]) * bf_lo(q[3]) + bf_hi(q[3]) * bf_hi(q[3]) +
                 bf_lo(q[5]) * bf_lo(q[5]) + bf_hi(q[5]) * bf_hi(q[5]);
      n0 += __shfl_xor_sync(0xffffffffu, n0, 1); n0 += __shfl_xor_sync(0xffffffffu, n0, 2);
      n1 += __shfl_xor_sync(0xffffffffu, n1, 1); n1 += __shfl_xor_sync(0xffffffffu, n1, 2);
      const bool safe = (n0 <= qlim) && (n1 <= qlim);
      uint32_t unsafe_any;
      asm volatile("{\n.reg .pred p, r;\nsetp.eq.u32 p, %1, 0;\nbarrier.cta.red.or.pred r, %2, 128, p;\nselp.u32 %0, 1, 0, r;\n}\n"
                   : "=r"(unsafe_any) : "r"((uint32_t)safe), "r"(wg + 1) : "memory");
      float O[12];
#pragma unroll
      for (int i = 0; i < 12; i++) O[i] = 0.f;
      if (!unsafe_any) {
        if (t >= 2) { q[4] = q[5] = (t == 2) ? 0x3F804100u : 0x00003B80u; }
        attn_tile_fast(q, O, dbase, smem_u32(&bars[0]), it == 0, one2);
      } else {
        attn_tile_slow(q, O, dbase, smem_u32(&bars[0]), it == 0);
      }
      const float l0 = __shfl_sync(0xffffffffu, O[8], (lane & ~3) | 2);
      const float l1 = __shfl_sync(0xffffffffu, O[10], (lane & ~3) | 2);
      const int tok = row0 >> 5;
      const float gt = g_gate[tok];
      const float i0 = gt / l0, i1 = gt / l1;
      uint32_t* o0 = reinterpret_cast<uint32_t*>(g_a2 + (size_t)tok * (2 * D_MODEL) + (row0 & 31) * DH);
      uint32_t* o1 = o0 + 8 * (DH / 2);
      o0[t] = pack_bf16(O[0] * i0, O[1] * i0); o1[t] = pack_bf16(O[2] * i1, O[3] * i1);
      o0[t + 4] = pack_bf16(O[4] * i0, O[5] * i0); o1[t + 4] = pack_bf16(O[6] * i1, O[7] * i1);
      if (t < 2) { o0[t + 8] = pack_bf16(O[8] * i0, O[9] * i0); o1[t + 8] = pack_bf16(O[10] * i1, O[11] * i1); }
    }
    signal_done(wg, tid);
    PROF(1, 3);
  }
}

constexpr int K3_STAGES = 8;
constexpr int K3_A_BYTES = 128 * 128;
constexpr int K3_B_BYTES = 64 * 80 * 2;
constexpr int K3_STAGE = K3_A_BYTES + K3_B_BYTES;
constexpr int K3_SMEM = K3_STAGES * K3_STAGE + 1024;

__global__ void __cluster_dims__(2, 1, 1) __launch_bounds__(288, 1)
out_kernel(const __grid_constant__ CUtensorMap tmA2, const __grid_constant__ CUtensorMap tmWoA, const __grid_constant__ CUtensorMap tmWoB,
           __nv_bfloat16* __restrict__ out) {
  extern __shared__ uint8_t smem_raw[];
  __shared__ __align__(8) uint64_t bar_full[K3_STAGES], bar_empty[K3_STAGES];
  uint8_t* smem = reinterpret_cast<uint8_t*>((reinterpret_cast<uintptr_t>(smem_raw) + 1023) & ~(uintptr_t)1023);
  const uint32_t sbase = smem_u32(smem);
  const uint32_t dbase = sbase & 0x3FFFFu;
  const int tid = threadIdx.x, warp = tid >> 5, lane = tid & 31;
  const int mb = blockIdx.x >> 3, nb = blockIdx.x & 7, rank = nb & 1;
  PROF(2, 0);
  if (tid == 0) {
    for (int i = 0; i < K3_STAGES; i++) { mbar_init(smem_u32(&bar_full[i]), 1); mbar_init(smem_u32(&bar_empty[i]), 4); }
    fence_mbar_init();
  }
  cluster_arrive();
  cluster_wait();
  if (warp == 8) {
    if (lane == 0) {
      for (int kt = 0; kt < K3_STAGES; kt++) {
        const uint32_t fb = smem_u32(&bar_full[kt]);
        mbar_expect_tx(fb, K3_STAGE);
        tma_3d(sbase + kt * K3_STAGE + K3_A_BYTES, &tmWoA, 0, kt * 64, nb * 5, fb);
      }
      {
        const unsigned int* f = &g_done[mb * 8 + rank * 4];
        for (int spin = 0; spin < (1 << 26); spin++) {
          unsigned int a, b, c, d;
          asm volatile("ld.volatile.global.v4.u32 {%0, %1, %2, %3}, [%4];" : "=r"(a), "=r"(b), "=r"(c), "=r"(d) : "l"(f) : "memory");
          if (min(min(a, b), min(c, d)) >= 5u) break;
        }
        asm volatile("fence.acq_rel.gpu;" ::: "memory");
        asm volatile("fence.proxy.async;" ::: "memory");
      }
      for (int kt = 0; kt < 20; kt++) {
        const int s = kt % K3_STAGES;
        const uint32_t fb = smem_u32(&bar_full[s]);
        if (kt >= K3_STAGES) {
          mbar_wait_cluster(smem_u32(&bar_empty[s]), ((kt / K3_STAGES) - 1) & 1);
          mbar_expect_tx(fb, K3_STAGE);
          tma_3d(sbase + s * K3_STAGE + K3_A_BYTES, kt < 10 ? &tmWoA : &tmWoB, 0, (kt % 10) * 64, nb * 5, fb);
        }
        tma_2d_mc(sbase + s * K3_STAGE + rank * 8192, &tmA2, kt * 64, mb * 128 + rank * 64, fb, (uint16_t)0x3);
      }
    }
    __syncwarp();
  } else {
    const int wg = warp >> 2;
    float acc[40];
#pragma unroll
    for (int i = 0; i < 40; i++) acc[i] = 0.f;
    for (int kt = 0; kt < 20; kt++) {
      const int s = kt % K3_STAGES;
      mbar_wait(smem_u32(&bar_full[s]), (kt / K3_STAGES) & 1);
      if (kt == 0) PROF(2, 1);
      const uint32_t alo = ((dbase + s * K3_STAGE + wg * 8192) >> 4) | (1u << 16);
      const uint32_t blo = ((dbase + s * K3_STAGE + K3_A_BYTES) >> 4) | ((2048u >> 4) << 16);
      fence_regs(acc);
      wg_fence();
#pragma unroll
      for (int k = 0; k < 4; k++) wgmma_ss_n80_tb(acc, mkd(alo + k * 2, DHI_SW128_K), mkd(blo + k * 32, DHI_SW32_MN));
      wg_commit();
      if (kt > 0 && kt - 1 + K3_STAGES < 20) {
        wg_wait<1>();
        if (lane == 0 && (warp & 2) == 0) mbar_arrive_remote(smem_u32(&bar_empty[(kt - 1) % K3_STAGES]), warp & 1);
      }
    }
    wg_wait<0>();
    fence_regs(acc);
    PROF(2, 2);
    asm volatile("bar.sync %0, 128;" :: "r"(wg + 1) : "memory");
    const int w4 = warp & 3;
    const uint32_t off = w4 * K3_STAGE + wg * 8192;
    const int row0 = mb * 128 + wg * 64 + w4 * 16;
    store_tile_bf16<80>(acc, 1.0f, sbase + off, smem + off, out + (size_t)row0 * D_MODEL + nb * 80, D_MODEL, lane);
    PROF(2, 3);
  }
}

typedef CUresult (*EncodeFn)(CUtensorMap*, CUtensorMapDataType, cuuint32_t, void*, const cuuint64_t*, const cuuint64_t*,
                             const cuuint32_t*, const cuuint32_t*, CUtensorMapInterleave, CUtensorMapSwizzle,
                             CUtensorMapL2promotion, CUtensorMapFloatOOBfill);

void make_map(EncodeFn fn, CUtensorMap* tm, const void* ptr, int rank, const cuuint64_t* dims, const cuuint64_t* strides,
              const cuuint32_t* box, CUtensorMapSwizzle sw) {
  const cuuint32_t es[3] = {1, 1, 1};
  fn(tm, CU_TENSOR_MAP_DATA_TYPE_BFLOAT16, rank, const_cast<void*>(ptr), dims, strides, box, es, CU_TENSOR_MAP_INTERLEAVE_NONE, sw,
     CU_TENSOR_MAP_L2_PROMOTION_L2_256B, CU_TENSOR_MAP_FLOAT_OOB_FILL_NONE);
}
void map_a(EncodeFn fn, CUtensorMap* tm, const void* p, int rows, int cols, int box_rows) {
  const cuuint64_t dims[2] = {(cuuint64_t)cols, (cuuint64_t)rows};
  const cuuint64_t str[1] = {(cuuint64_t)cols * 2};
  const cuuint32_t box[2] = {64, (cuuint32_t)box_rows};
  make_map(fn, tm, p, 2, dims, str, box, CU_TENSOR_MAP_SWIZZLE_128B);
}
void map_w(EncodeFn fn, CUtensorMap* tm, const void* p, int K, int N, int atom, CUtensorMapSwizzle sw) {
  const cuuint64_t dims[3] = {(cuuint64_t)atom, (cuuint64_t)K, (cuuint64_t)(N / atom)};
  const cuuint64_t str[2] = {(cuuint64_t)N * 2, (cuuint64_t)atom * 2};
  const cuuint32_t box[3] = {(cuuint32_t)atom, 64, 5};
  make_map(fn, tm, p, 3, dims, str, box, sw);
}

template <typename... KArgs, typename... Args>
void launch(void (*kern)(KArgs...), int grid, int block, int smem, bool pdl, Args... args) {
  cudaLaunchConfig_t cfg = {};
  cfg.gridDim = dim3(grid); cfg.blockDim = dim3(block); cfg.dynamicSmemBytes = smem; cfg.stream = cudaStreamPerThread;
  cudaLaunchAttribute at[1];
  at[0].id = cudaLaunchAttributeProgrammaticStreamSerialization;
  at[0].val.programmaticStreamSerializationAllowed = 1;
  cfg.attrs = at; cfg.numAttrs = pdl ? 1 : 0;
  cudaLaunchKernelEx(&cfg, kern, KArgs(args)...);
}

}

extern "C" void kernel_launch(void* const* d_in, const int* in_sizes, int n_in, void* d_out, int out_size) {
  (void)in_sizes; (void)n_in; (void)out_size;
  const __nv_bfloat16* x = (const __nv_bfloat16*)d_in[0];
  const __nv_bfloat16* wq = (const __nv_bfloat16*)d_in[1];
  const __nv_bfloat16* wk = (const __nv_bfloat16*)d_in[2];
  const __nv_bfloat16* wv = (const __nv_bfloat16*)d_in[3];
  const __nv_bfloat16* woA = (const __nv_bfloat16*)d_in[4];
  const __nv_bfloat16* wqkv = (const __nv_bfloat16*)d_in[6];
  const __nv_bfloat16* woB = (const __nv_bfloat16*)d_in[7];
  const __nv_bfloat16* gate_w = (const __nv_bfloat16*)d_in[8];

  static EncodeFn enc = nullptr;
  static void* a2_ptr = nullptr;
  if (!enc) {
    void* fp = nullptr;
    cudaDriverEntryPointQueryResult qr;
    cudaGetDriverEntryPoint("cuTensorMapEncodeTiled", &fp, cudaEnableDefault, &qr);
    enc = (EncodeFn)fp;
    cudaGetSymbolAddress(&a2_ptr, g_a2);
    cudaFuncSetAttribute(proj_kernel, cudaFuncAttributeMaxDynamicSharedMemorySize, K1_SMEM);
    cudaFuncSetAttribute(attn_kernel, cudaFuncAttributeMaxDynamicSharedMemorySize, K2_SMEM);
    cudaFuncSetAttribute(out_kernel, cudaFuncAttributeMaxDynamicSharedMemorySize, K3_SMEM);
  }
  CUtensorMap tmX, tmWq, tmWqkv, tmA2, tmWoA, tmWoB;
  map_a(enc, &tmX, x, S_LEN, D_MODEL, 256);
  map_w(enc, &tmWq, wq, D_MODEL, D_MODEL, 32, CU_TENSOR_MAP_SWIZZLE_64B);
  map_w(enc, &tmWqkv, wqkv, D_MODEL, 3 * D_MODEL, 32, CU_TENSOR_MAP_SWIZZLE_64B);
  map_a(enc, &tmA2, a2_ptr, S_LEN, 2 * D_MODEL, 64);
  map_w(enc, &tmWoA, woA, D_MODEL, D_MODEL, 16, CU_TENSOR_MAP_SWIZZLE_32B);
  map_w(enc, &tmWoB, woB, D_MODEL, D_MODEL, 16, CU_TENSOR_MAP_SWIZZLE_32B);

  launch(proj_kernel, 132, 512, K1_SMEM, false, tmX, tmWq, tmWqkv, wk, wv, gate_w);
  launch(attn_kernel, 128, 640, K2_SMEM, true, 0x3F803F80u);
  launch(out_kernel, 128, 288, K3_SMEM, true, tmA2, tmWoA, tmWoB, (__nv_bfloat16*)d_out);
}
```

```cpp
#include <cuda_runtime.h>
#include <cuda_bf16.h>
#include <cuda.h>
#include <stdint.h>

namespace {

constexpr int S_LEN = 2048, D_MODEL = 640, DH = 20;

constexpr int GRP = 128;
constexpr int PLANE = GRP * 16;
constexpr int GRP_BYTES = GRP * 16 * 6;
constexpr int NGRP = S_LEN / GRP;
constexpr uint32_t TMASK = 0x6DB6u;

__device__ __align__(1024) __nv_bfloat16 g_q[S_LEN * D_MODEL];
__device__ __align__(1024) __nv_bfloat16 g_qkv[S_LEN * 3 * D_MODEL];
__device__ __align__(1024) __nv_bfloat16 g_a2[S_LEN * 2 * D_MODEL];
__device__ __align__(1024) uint8_t g_kvimg[NGRP * GRP_BYTES];
__device__ float g_gate[S_LEN];
__device__ float g_kmax2[128];
__device__ float g_vmax[128];
__device__ __align__(32) unsigned int g_doneL[128];
__device__ float g_part[128 * 2 * 40 * 128];
__device__ __align__(32) unsigned int g_done[128];

#define PROF(k, slot)
#define PROF2(k, slot)
__device__ __forceinline__ uint32_t smem_u32(const void* p) { return (uint32_t)__cvta_generic_to_shared(p); }
__device__ __forceinline__ uint64_t mkd(uint32_t lo, uint32_t hi) {
  uint64_t d; asm("mov.b64 %0, {%1, %2};" : "=l"(d) : "r"(lo), "r"(hi)); return d;
}
__device__ __forceinline__ void wg_fence() { asm volatile("wgmma.fence.sync.aligned;" ::: "memory"); }
__device__ __forceinline__ void wg_commit() { asm volatile("wgmma.commit_group.sync.aligned;" ::: "memory"); }
template <int N> __device__ __forceinline__ void wg_wait() { asm volatile("wgmma.wait_group.sync.aligned %0;" :: "n"(N) : "memory"); }
template <int N> __device__ __forceinline__ void fence_regs(float (&d)[N]) {
#pragma unroll
  for (int i = 0; i < N; i++) asm volatile("" : "+f"(d[i]) :: "memory");
}
template <int N> __device__ __forceinline__ void fence_regs(uint32_t (&d)[N]) {
#pragma unroll
  for (int i = 0; i < N; i++) asm volatile("" : "+r"(d[i]) :: "memory");
}
__device__ __forceinline__ void mbar_init(uint32_t bar, uint32_t cnt) { asm volatile("mbarrier.init.shared::cta.b64 [%0], %1;" :: "r"(bar), "r"(cnt)); }
__device__ __forceinline__ void mbar_expect_tx(uint32_t bar, uint32_t bytes) {
  asm volatile("mbarrier.arrive.expect_tx.shared::cta.b64 _, [%0], %1;" :: "r"(bar), "r"(bytes) : "memory");
}
__device__ __forceinline__ void mbar_arrive(uint32_t bar) { asm volatile("mbarrier.arrive.shared::cta.b64 _, [%0];" :: "r"(bar) : "memory"); }
__device__ __forceinline__ void mbar_wait(uint32_t bar, uint32_t parity) {
  asm volatile("{\n.reg .pred p;\nWAIT_%=:\nmbarrier.try_wait.parity.shared::cta.b64 p, [%0], %1;\n@p bra DONE_%=;\nbra WAIT_%=;\nDONE_%=:\n}\n"
               :: "r"(bar), "r"(parity) : "memory");
}
__device__ __forceinline__ void fence_mbar_init() { asm volatile("fence.mbarrier_init.release.cluster;" ::: "memory"); }
__device__ __forceinline__ void fence_proxy_async() { asm volatile("fence.proxy.async.shared::cta;" ::: "memory"); }
__device__ __forceinline__ void bulk_g2s(uint32_t dst, const void* src, uint32_t bytes, uint32_t bar) {
  asm volatile("cp.async.bulk.shared::cluster.global.mbarrier::complete_tx::bytes [%0], [%1], %2, [%3];"
               :: "r"(dst), "l"(src), "r"(bytes), "r"(bar) : "memory");
}
__device__ __forceinline__ void tma_2d(uint32_t dst, const CUtensorMap* tm, int c0, int c1, uint32_t bar) {
  asm volatile("cp.async.bulk.tensor.2d.shared::cluster.global.mbarrier::complete_tx::bytes [%0], [%1, {%3, %4}], [%2];"
               :: "r"(dst), "l"((uint64_t)tm), "r"(bar), "r"(c0), "r"(c1) : "memory");
}
__device__ __forceinline__ void tma_3d(uint32_t dst, const CUtensorMap* tm, int c0, int c1, int c2, uint32_t bar) {
  asm volatile("cp.async.bulk.tensor.3d.shared::cluster.global.mbarrier::complete_tx::bytes [%0], [%1, {%3, %4, %5}], [%2];"
               :: "r"(dst), "l"((uint64_t)tm), "r"(bar), "r"(c0), "r"(c1), "r"(c2) : "memory");
}
__device__ __forceinline__ void pdl_wait() { asm volatile("griddepcontrol.wait;" ::: "memory"); }
__device__ __forceinline__ void pdl_launch() { asm volatile("griddepcontrol.launch_dependents;" ::: "memory"); }
__device__ __forceinline__ float ex2(float x) { float y; asm("ex2.approx.ftz.f32 %0, %1;" : "=f"(y) : "f"(x)); return y; }
__device__ __forceinline__ uint32_t pack_bf16(float lo, float hi) {
  uint32_t r; asm("cvt.rn.bf16x2.f32 %0, %1, %2;" : "=r"(r) : "f"(hi), "f"(lo)); return r;
}
__device__ __forceinline__ float bf_lo(uint32_t x) { return __uint_as_float(x << 16); }
__device__ __forceinline__ float bf_hi(uint32_t x) { return __uint_as_float(x & 0xffff0000u); }
__device__ __forceinline__ void stsm4(uint32_t addr, uint32_t r0, uint32_t r1, uint32_t r2, uint32_t r3) {
  asm volatile("stmatrix.sync.aligned.m8n8.x4.shared.b16 [%0], {%1, %2, %3, %4};" :: "r"(addr), "r"(r0), "r"(r1), "r"(r2), "r"(r3) : "memory");
}

__device__ __forceinline__ void wgmma_ss_n160_tb(float (&d)[80], uint64_t descA, uint64_t descB) {
  asm volatile("wgmma.mma_async.sync.aligned.m64n160k16.f32.bf16.bf16 {%0, %1, %2, %3, %4, %5, %6, %7, %8, %9, %10, %11, %12, %13, %14, %15, %16, %17, %18, %19, %20, %21, %22, %23, %24, %25, %26, %27, %28, %29, %30, %31, %32, %33, %34, %35, %36, %37, %38, %39, %40, %41, %42, %43, %44, %45, %46, %47, %48, %49, %50, %51, %52, %53, %54, %55, %56, %57, %58, %59, %60, %61, %62, %63, %64, %65, %66, %67, %68, %69, %70, %71, %72, %73, %74, %75, %76, %77, %78, %79}, %80, %81, 1, 1, 1, 0, 1;\n"
    : "+f"(d[0]), "+f"(d[1]), "+f"(d[2]), "+f"(d[3]), "+f"(d[4]), "+f"(d[5]), "+f"(d[6]), "+f"(d[7]), "+f"(d[8]), "+f"(d[9]), "+f"(d[10]), "+f"(d[11]), "+f"(d[12]), "+f"(d[13]), "+f"(d[14]), "+f"(d[15]), "+f"(d[16]), "+f"(d[17]), "+f"(d[18]), "+f"(d[19]), "+f"(d[20]), "+f"(d[21]), "+f"(d[22]), "+f"(d[23]), "+f"(d[24]), "+f"(d[25]), "+f"(d[26]), "+f"(d[27]), "+f"(d[28]), "+f"(d[29]), "+f"(d[30]), "+f"(d[31]), "+f"(d[32]), "+f"(d[33]), "+f"(d[34]), "+f"(d[35]), "+f"(d[36]), "+f"(d[37]), "+f"(d[38]), "+f"(d[39]), "+f"(d[40]), "+f"(d[41]), "+f"(d[42]), "+f"(d[43]), "+f"(d[44]), "+f"(d[45]), "+f"(d[46]), "+f"(d[47]), "+f"(d[48]), "+f"(d[49]), "+f"(d[50]), "+f"(d[51]), "+f"(d[52]), "+f"(d[53]), "+f"(d[54]), "+f"(d[55]), "+f"(d[56]), "+f"(d[57]), "+f"(d[58]), "+f"(d[59]), "+f"(d[60]), "+f"(d[61]), "+f"(d[62]), "+f"(d[63]), "+f"(d[64]), "+f"(d[65]), "+f"(d[66]), "+f"(d[67]), "+f"(d[68]), "+f"(d[69]), "+f"(d[70]), "+f"(d[71]), "+f"(d[72]), "+f"(d[73]), "+f"(d[74]), "+f"(d[75]), "+f"(d[76]), "+f"(d[77]), "+f"(d[78]), "+f"(d[79])
    : "l"(descA), "l"(descB));
}
__device__ __forceinline__ void wgmma_ss_n48_tb(float (&d)[24], uint64_t descA, uint64_t descB) {
  asm volatile("wgmma.mma_async.sync.aligned.m64n48k16.f32.bf16.bf16 {%0, %1, %2, %3, %4, %5, %6, %7, %8, %9, %10, %11, %12, %13, %14, %15, %16, %17, %18, %19, %20, %21, %22, %23}, %24, %25, 1, 1, 1, 0, 1;\n"
    : "+f"(d[0]), "+f"(d[1]), "+f"(d[2]), "+f"(d[3]), "+f"(d[4]), "+f"(d[5]), "+f"(d[6]), "+f"(d[7]), "+f"(d[8]), "+f"(d[9]), "+f"(d[10]), "+f"(d[11]), "+f"(d[12]), "+f"(d[13]), "+f"(d[14]), "+f"(d[15]), "+f"(d[16]), "+f"(d[17]), "+f"(d[18]), "+f"(d[19]), "+f"(d[20]), "+f"(d[21]), "+f"(d[22]), "+f"(d[23])
    : "l"(descA), "l"(descB));
}
__device__ __forceinline__ void wgmma_ss_n80_tb(float (&d)[40], uint64_t descA, uint64_t descB) {
  asm volatile("wgmma.mma_async.sync.aligned.m64n80k16.f32.bf16.bf16 {%0, %1, %2, %3, %4, %5, %6, %7, %8, %9, %10, %11, %12, %13, %14, %15, %16, %17, %18, %19, %20, %21, %22, %23, %24, %25, %26, %27, %28, %29, %30, %31, %32, %33, %34, %35, %36, %37, %38, %39}, %40, %41, 1, 1, 1, 0, 1;\n"
    : "+f"(d[0]), "+f"(d[1]), "+f"(d[2]), "+f"(d[3]), "+f"(d[4]), "+f"(d[5]), "+f"(d[6]), "+f"(d[7]), "+f"(d[8]), "+f"(d[9]), "+f"(d[10]), "+f"(d[11]), "+f"(d[12]), "+f"(d[13]), "+f"(d[14]), "+f"(d[15]), "+f"(d[16]), "+f"(d[17]), "+f"(d[18]), "+f"(d[19]), "+f"(d[20]), "+f"(d[21]), "+f"(d[22]), "+f"(d[23]), "+f"(d[24]), "+f"(d[25]), "+f"(d[26]), "+f"(d[27]), "+f"(d[28]), "+f"(d[29]), "+f"(d[30]), "+f"(d[31]), "+f"(d[32]), "+f"(d[33]), "+f"(d[34]), "+f"(d[35]), "+f"(d[36]), "+f"(d[37]), "+f"(d[38]), "+f"(d[39])
    : "l"(descA), "l"(descB));
}
template <int SCALE_D>
__device__ __forceinline__ void wgmma_rs_n64(float (&d)[32], uint32_t a0, uint32_t a1, uint32_t a2, uint32_t a3, uint64_t descB) {
  asm volatile("wgmma.mma_async.sync.aligned.m64n64k16.f32.bf16.bf16 {%0, %1, %2, %3, %4, %5, %6, %7, %8, %9, %10, %11, %12, %13, %14, %15, %16, %17, %18, %19, %20, %21, %22, %23, %24, %25, %26, %27, %28, %29, %30, %31}, {%32, %33, %34, %35}, %36, %37, 1, 1, 0;\n"
    : "+f"(d[0]), "+f"(d[1]), "+f"(d[2]), "+f"(d[3]), "+f"(d[4]), "+f"(d[5]), "+f"(d[6]), "+f"(d[7]), "+f"(d[8]), "+f"(d[9]), "+f"(d[10]), "+f"(d[11]), "+f"(d[12]), "+f"(d[13]), "+f"(d[14]), "+f"(d[15]), "+f"(d[16]), "+f"(d[17]), "+f"(d[18]), "+f"(d[19]), "+f"(d[20]), "+f"(d[21]), "+f"(d[22]), "+f"(d[23]), "+f"(d[24]), "+f"(d[25]), "+f"(d[26]), "+f"(d[27]), "+f"(d[28]), "+f"(d[29]), "+f"(d[30]), "+f"(d[31])
    : "r"(a0), "r"(a1), "r"(a2), "r"(a3), "l"(descB), "n"(SCALE_D));
}
template <int SCALE_D>
__device__ __forceinline__ void wgmma_rs_n24_tb(float (&d)[12], uint32_t a0, uint32_t a1, uint32_t a2, uint32_t a3, uint64_t descB) {
  asm volatile("wgmma.mma_async.sync.aligned.m64n24k16.f32.bf16.bf16 {%0, %1, %2, %3, %4, %5, %6, %7, %8, %9, %10, %11}, {%12, %13, %14, %15}, %16, %17, 1, 1, 1;\n"
    : "+f"(d[0]), "+f"(d[1]), "+f"(d[2]), "+f"(d[3]), "+f"(d[4]), "+f"(d[5]), "+f"(d[6]), "+f"(d[7]), "+f"(d[8]), "+f"(d[9]), "+f"(d[10]), "+f"(d[11])
    : "r"(a0), "r"(a1), "r"(a2), "r"(a3), "l"(descB), "n"(SCALE_D));
}

constexpr uint32_t DHI_SW128_K = (1024 >> 4) | (1u << 30);
constexpr uint32_t DHI_SW64_MN = (512 >> 4) | (2u << 30);
constexpr uint32_t DHI_SW32_MN = (256 >> 4) | (3u << 30);

template <int NC>
__device__ __forceinline__ void store_tile_bf16(const float (&acc)[NC / 2], float scale, uint32_t stage, uint8_t* stage_ptr,
                                                __nv_bfloat16* gdst, int gpitch, int lane) {
  constexpr int PITCH = NC * 2 + 16;
  const uint32_t waddr = stage + ((lane & 7) + ((lane >> 3) & 1) * 8) * PITCH + (lane >> 4) * 16;
#pragma unroll
  for (int j = 0; j < NC / 16; j++) {
    stsm4(waddr + j * 32, pack_bf16(acc[8 * j] * scale, acc[8 * j + 1] * scale), pack_bf16(acc[8 * j + 2] * scale, acc[8 * j + 3] * scale),
          pack_bf16(acc[8 * j + 4] * scale, acc[8 * j + 5] * scale), pack_bf16(acc[8 * j + 6] * scale, acc[8 * j + 7] * scale));
  }
  __syncwarp();
  constexpr int CPR = NC / 8;
#pragma unroll
  for (int i = 0; i < CPR / 2; i++) {
    const int c = i * 32 + lane, r = c / CPR, cc = c % CPR;
    const uint4 v = *reinterpret_cast<const uint4*>(stage_ptr + r * PITCH + cc * 16);
    *reinterpret_cast<uint4*>(gdst + (size_t)r * gpitch + cc * 8) = v;
  }
}

constexpr int K1_STAGES = 4;
constexpr int K1_A_BYTES = 256 * 128;
constexpr int K1_B_BYTES = 64 * 160 * 2;
constexpr int K1_STAGE = K1_A_BYTES + K1_B_BYTES;
constexpr int K1_SMEM = 5 * K1_A_BYTES + 61440 + 1024;
constexpr int KV_STAGES = 5;
constexpr int KVW_OFF = KV_STAGES * K1_A_BYTES;

__global__ void __launch_bounds__(512, 1)
proj_kernel(const __grid_constant__ CUtensorMap tmX, const __grid_constant__ CUtensorMap tmWq, const __grid_constant__ CUtensorMap tmWqkv,
            const __nv_bfloat16* __restrict__ wk, const __nv_bfloat16* __restrict__ wv, const __nv_bfloat16* __restrict__ gate_w) {
  extern __shared__ uint8_t smem_raw[];
  __shared__ __align__(8) uint64_t bar_full[KV_STAGES], bar_empty[KV_STAGES];
  uint8_t* smem = reinterpret_cast<uint8_t*>((reinterpret_cast<uintptr_t>(smem_raw) + 1023) & ~(uintptr_t)1023);
  const uint32_t sbase = smem_u32(smem);
  const uint32_t dbase = sbase & 0x3FFFFu;
  const int tid = threadIdx.x, warp = tid >> 5, lane = tid & 31;
  const bool is_kv = blockIdx.x >= 128;
  PROF(0, 0);
  pdl_launch();
  if (tid == 0) {
    for (int i = 0; i < KV_STAGES; i++) { mbar_init(smem_u32(&bar_full[i]), 1); mbar_init(smem_u32(&bar_empty[i]), 16); }
    fence_mbar_init();
    if (!is_kv) { g_done[blockIdx.x] = 0u; g_doneL[blockIdx.x] = 0u; }
  }
  __syncthreads();

  if (!is_kv) {
    const int mb = blockIdx.x >> 4, nb = blockIdx.x & 15;
    const CUtensorMap* tw = nb < 4 ? &tmWq : &tmWqkv;
    const int j0 = (nb < 4 ? nb : nb - 4) * 5;
    auto load = [&](int kt) {
      const int s = kt % K1_STAGES;
      const uint32_t fb = smem_u32(&bar_full[s]);
      mbar_expect_tx(fb, K1_STAGE);
      tma_2d(sbase + s * K1_STAGE, &tmX, kt * 64, mb * 256, fb);
      tma_3d(sbase + s * K1_STAGE + K1_A_BYTES, tw, 0, kt * 64, j0, fb);
    };
    if (tid == 0) for (int kt = 0; kt < K1_STAGES; kt++) load(kt);
    {
      const int wg = warp >> 2;
      float acc[80];
#pragma unroll
      for (int i = 0; i < 80; i++) acc[i] = 0.f;
      for (int kt = 0; kt < 10; kt++) {
        const int s = kt % K1_STAGES;
        mbar_wait(smem_u32(&bar_full[s]), (kt / K1_STAGES) & 1);
        const uint32_t alo = ((dbase + s * K1_STAGE + wg * 8192) >> 4) | (1u << 16);
        const uint32_t blo = ((dbase + s * K1_STAGE + K1_A_BYTES) >> 4) | ((4096u >> 4) << 16);
        fence_regs(acc);
        wg_fence();
#pragma unroll
        for (int k = 0; k < 4; k++) wgmma_ss_n160_tb(acc, mkd(alo + k * 2, DHI_SW128_K), mkd(blo + k * 64, DHI_SW64_MN));
        wg_commit();
        if (kt > 0 && kt - 1 + K1_STAGES < 10) {
          wg_wait<1>();
          const uint32_t eb = smem_u32(&bar_empty[(kt - 1) % K1_STAGES]);
          if (lane == 0) mbar_arrive(eb);
          if (tid == 0) { mbar_wait(eb, ((kt - 1) / K1_STAGES) & 1); load(kt - 1 + K1_STAGES); }
          __syncwarp();
        }
      }
      wg_wait<0>();
      fence_regs(acc);
      PROF(0, 1);
      asm volatile("bar.sync %0, 128;" :: "r"(wg + 1) : "memory");
      const int w4 = warp & 3;
      const uint32_t off = w4 * K1_STAGE + wg * 8192;
      const int row0 = mb * 256 + wg * 64 + w4 * 16;
      if (nb < 4) {
        store_tile_bf16<160>(acc, 0.22360679774997896f * 1.4426950408889634f, sbase + off, smem + off,
                             g_q + (size_t)row0 * D_MODEL + nb * 160, D_MODEL, lane);
      } else {
        store_tile_bf16<160>(acc, 1.0f, sbase + off, smem + off, g_qkv + (size_t)row0 * (3 * D_MODEL) + (nb - 4) * 160, 3 * D_MODEL, lane);
      }
    }
  } else {
    const int cb = blockIdx.x - 128;
    auto load = [&](int it) {
      const int s = it % KV_STAGES;
      const uint32_t fb = smem_u32(&bar_full[s]);
      mbar_expect_tx(fb, K1_A_BYTES);
      tma_2d(sbase + s * K1_A_BYTES, &tmX, (it % 10) * 64, cb * 512 + (it / 10) * 256, fb);
    };
    if (tid == 0) for (int it = 0; it < KV_STAGES; it++) load(it);
    {
      if (tid < 320) {
        uint2 a[2][5], b[2][5]; uint32_t gw[2];
#pragma unroll
        for (int r = 0; r < 2; r++) {
          const int k = tid + r * 320;
          const uint2* pk = reinterpret_cast<const uint2*>(wk + k * 20);
          const uint2* pv = reinterpret_cast<const uint2*>(wv + k * 20);
#pragma unroll
          for (int i = 0; i < 5; i++) { a[r][i] = __ldg(pk + i); b[r][i] = __ldg(pv + i); }
          gw[r] = (uint32_t)__bfloat16_as_ushort(gate_w[k]);
        }
#pragma unroll
        for (int r = 0; r < 2; r++) {
          uint4* dst = reinterpret_cast<uint4*>(smem + KVW_OFF + (tid + r * 320) * 16);
          dst[0] = make_uint4(a[r][0].x, a[r][0].y, a[r][1].x, a[r][1].y);
          dst[640] = make_uint4(a[r][2].x, a[r][2].y, a[r][3].x, a[r][3].y);
          dst[1280] = make_uint4(a[r][4].x, a[r][4].y, 0u, 0u);
          dst[1920] = make_uint4(b[r][0].x, b[r][0].y, b[r][1].x, b[r][1].y);
          dst[2560] = make_uint4(b[r][2].x, b[r][2].y, b[r][3].x, b[r][3].y);
          dst[3200] = make_uint4(b[r][4].x, b[r][4].y, gw[r], 0u);
        }
      }
      fence_proxy_async();
      asm volatile("bar.sync 1, 512;" ::: "memory");
      PROF(0, 1);
      const int wg = warp >> 2, w4 = warp & 3, g = lane >> 2, t = lane & 3;
      for (int pass = 0; pass < 2; pass++) {
        float acc[24];
#pragma unroll
        for (int i = 0; i < 24; i++) acc[i] = 0.f;
        for (int kt = 0; kt < 10; kt++) {
          const int it = pass * 10 + kt, s = it % KV_STAGES;
          mbar_wait(smem_u32(&bar_full[s]), (it / KV_STAGES) & 1);
          const uint32_t alo = ((dbase + s * K1_A_BYTES + wg * 8192) >> 4) | (1u << 16);
          const uint32_t blo = ((dbase + KVW_OFF + kt * 1024) >> 4) | ((128u >> 4) << 16);
          fence_regs(acc);
          wg_fence();
#pragma unroll
          for (int k = 0; k < 4; k++) wgmma_ss_n48_tb(acc, mkd(alo + k * 2, DHI_SW128_K), mkd(blo + k * 16, 10240u >> 4));
          wg_commit();
          wg_wait<0>();
          if (it + KV_STAGES < 20) {
            const uint32_t eb = smem_u32(&bar_empty[s]);
            if (lane == 0) mbar_arrive(eb);
            if (tid == 0) { mbar_wait(eb, (it / KV_STAGES) & 1); load(it + KV_STAGES); }
            __syncwarp();
          }
        }
        fence_regs(acc);
        float kmax2 = 0.f, vmax = 0.f;
#pragma unroll
        for (int h = 0; h < 2; h++) {
          const int key = cb * 512 + pass * 256 + wg * 64 + w4 * 16 + g + h * 8;
          const int grp = key >> 7, kk = key & 127;
          const bool poly = (TMASK >> (kk >> 3)) & 1;
          uint8_t* gp = g_kvimg + grp * GRP_BYTES;
          const uint32_t k0 = pack_bf16(acc[2 * h], acc[2 * h + 1]);
          const uint32_t k1 = pack_bf16(acc[4 + 2 * h], acc[5 + 2 * h]);
          uint32_t k2 = pack_bf16(acc[8 + 2 * h], acc[9 + 2 * h]);
          float n2 = bf_lo(k0) * bf_lo(k0) + bf_hi(k0) * bf_hi(k0) + bf_lo(k1) * bf_lo(k1) + bf_hi(k1) * bf_hi(k1);
          if (t < 2) {
            n2 += bf_lo(k2) * bf_lo(k2) + bf_hi(k2) * bf_hi(k2);
            k2 = pack_bf16(bf_lo(k2) * 0.5f, bf_hi(k2) * 0.5f);
          } else if (t == 2) k2 = poly ? pack_bf16(24.f, 2.5f) : pack_bf16(0.5f, 0.f);
          else k2 = poly ? pack_bf16(0.5f, 0.f) : 0u;
          *reinterpret_cast<uint32_t*>(gp + kk * 16 + t * 4) = k0;
          *reinterpret_cast<uint32_t*>(gp + PLANE + kk * 16 + t * 4) = k1;
          *reinterpret_cast<uint32_t*>(gp + 2 * PLANE + kk * 16 + t * 4) = k2;
          n2 += __shfl_xor_sync(0xffffffffu, n2, 1);
          n2 += __shfl_xor_sync(0xffffffffu, n2, 2);
          kmax2 = (n2 > kmax2 || n2 != n2) ? n2 : kmax2;
          uint32_t v0 = pack_bf16(acc[12 + 2 * h], acc[13 + 2 * h]);
          uint32_t v1 = pack_bf16(acc[16 + 2 * h], acc[17 + 2 * h]);
          uint32_t v2 = pack_bf16(acc[20 + 2 * h], acc[21 + 2 * h]);
          float vm = fmaxf(fmaxf(fabsf(bf_lo(v0)), fabsf(bf_hi(v0))), fmaxf(fabsf(bf_lo(v1)), fabsf(bf_hi(v1))));
          if (t < 2) vm = fmaxf(vm, fmaxf(fabsf(bf_lo(v2)), fabsf(bf_hi(v2))));
          else if (t == 2) {
            const float z = acc[20 + 2 * h];
            g_gate[key] = 1.f / (1.f + __expf(-z));
            v2 = 0x00003F80u;
          } else v2 = 0u;
          vmax = fmaxf(vmax, vm);
          if (poly) { v0 ^= 0x80008000u; v1 ^= 0x80008000u; v2 ^= 0x80008000u; }
          uint8_t* vp = gp + 3 * PLANE + (kk >> 3) * 384 + (kk & 7) * 16 + t * 4;
          *reinterpret_cast<uint32_t*>(vp) = v0;
          *reinterpret_cast<uint32_t*>(vp + 128) = v1;
          *reinterpret_cast<uint32_t*>(vp + 256) = v2;
        }
#pragma unroll
        for (int o = 1; o < 32; o <<= 1) {
          const float a = __shfl_xor_sync(0xffffffffu, kmax2, o);
          kmax2 = (a > kmax2 || a != a) ? a : kmax2;
          vmax = fmaxf(vmax, __shfl_xor_sync(0xffffffffu, vmax, o));
        }
        if (lane == 0) { g_kmax2[cb * 32 + pass * 16 + warp] = kmax2; g_vmax[cb * 32 + pass * 16 + warp] = vmax; }
      }
    }
  }
  PROF(0, 3);
}

__device__ __forceinline__ uint32_t ex2_pair_poly(float u0, float u1, uint32_t one2) {
  const uint32_t W = __byte_perm(__float_as_uint(u0), __float_as_uint(u1), 0x6521);
  uint32_t v; asm("lop3.b32 %0, %1, 0x007F007F, %2, 0xEA;" : "=r"(v) : "r"(W), "r"(one2));
  uint32_t L, p;
  asm("fma.rn.bf16x2 %0, %1, %2, %3;" : "=r"(L) : "r"(v), "r"(0x1f961f96u), "r"(0x9fe39fe3u));
  asm("fma.rn.bf16x2 %0, %1, %1, %2;" : "=r"(p) : "r"(L), "r"(0x00f500f5u));
  return W + p;
}
template <int JOFF>
__device__ __forceinline__ void softmax_fast(const float (&S)[32], uint32_t (&P)[16], uint32_t one2) {
#pragma unroll
  for (int i = 0; i < 16; i++) {
    if ((TMASK >> (JOFF + i / 2)) & 1) P[i] = ex2_pair_poly(S[2 * i], S[2 * i + 1], one2);
    else P[i] = pack_bf16(ex2(S[2 * i]), ex2(S[2 * i + 1]));
  }
}
template <int JOFF>
__device__ __forceinline__ void softmax_slow(const float (&S)[32], uint32_t (&P)[16], float (&O)[12], float& m0, float& m1) {
  float a0 = m0, a1 = m1;
#pragma unroll
  for (int j = 0; j < 8; j++) {
    a0 = fmaxf(a0, fmaxf(S[4 * j], S[4 * j + 1]));
    a1 = fmaxf(a1, fmaxf(S[4 * j + 2], S[4 * j + 3]));
  }
  a0 = fmaxf(a0, __shfl_xor_sync(0xffffffffu, a0, 1)); a0 = fmaxf(a0, __shfl_xor_sync(0xffffffffu, a0, 2));
  a1 = fmaxf(a1, __shfl_xor_sync(0xffffffffu, a1, 1)); a1 = fmaxf(a1, __shfl_xor_sync(0xffffffffu, a1, 2));
  const float c0 = ex2(m0 - a0), c1 = ex2(m1 - a1);
  m0 = a0; m1 = a1;
#pragma unroll
  for (int j = 0; j < 3; j++) { O[4 * j] *= c0; O[4 * j + 1] *= c0; O[4 * j + 2] *= c1; O[4 * j + 3] *= c1; }
#pragma unroll
  for (int i = 0; i < 16; i++) {
    const float m = (i & 1) ? a1 : a0;
    const uint32_t p = pack_bf16(ex2(S[2 * i] - m), ex2(S[2 * i + 1] - m));
    P[i] = ((TMASK >> (JOFF + i / 2)) & 1) ? (p ^ 0x80008000u) : p;
  }
}
constexpr uint32_t DHI_KV = 128 >> 4;
__device__ __forceinline__ void issue_qk(float (&S)[32], const uint32_t (&q)[8], uint32_t base) {
  wgmma_rs_n64<0>(S, q[0], q[1], q[2], q[3], mkd(base + ((PLANE >> 4) << 16), DHI_KV));
  wgmma_rs_n64<1>(S, q[4], q[5], q[6], q[7], mkd(base + (2 * PLANE >> 4), DHI_KV));
}
__device__ __forceinline__ void issue_pv(float (&O)[12], const uint32_t (&P)[16], uint32_t vbase) {
#pragma unroll
  for (int kk = 0; kk < 4; kk++)
    wgmma_rs_n24_tb<1>(O, P[4 * kk], P[4 * kk + 1], P[4 * kk + 2], P[4 * kk + 3], mkd(vbase + kk * (768 >> 4), DHI_KV));
}

constexpr uint32_t VOFF = ((3 * PLANE) >> 4) + ((384u >> 4) << 16);
constexpr int KVR = 4;
constexpr int OFF_WA = KVR * GRP_BYTES;
constexpr int OFF_BR = OFF_WA + 10 * 10240;
constexpr int BR_STAGE = 8192 + 10240, BR_STAGES = 3;
constexpr int OFF_QS = OFF_BR + BR_STAGES * BR_STAGE;
constexpr int OFF_BAR = OFF_QS + 512 * 6 * 4;
constexpr int K2_SMEM = OFF_BAR + 256 + 1024;
constexpr int BAR_KV = 0, BAR_WA = 4, BAR_BR = 5, BAR_TA = 8, BAR_TE = 14, CNT_KV = 18;
constexpr int NSTEP = 2 * NGRP;

__device__ __forceinline__ void kv_load(uint32_t sbase, int step) {
  const uint32_t bar = sbase + OFF_BAR + (BAR_KV + (step & (KVR - 1))) * 8;
  mbar_expect_tx(bar, GRP_BYTES);
  bulk_g2s(sbase + (step & (KVR - 1)) * GRP_BYTES, g_kvimg + (step & (NGRP - 1)) * GRP_BYTES, GRP_BYTES, bar);
}
__device__ __forceinline__ void kv_release(uint32_t sbase, int step, bool elected) {
  if (elected && step + KVR < NSTEP) {
    uint32_t old;
    asm volatile("atom.acq_rel.cta.shared::cta.inc.u32 %0, [%1], 3;" : "=r"(old) : "r"(sbase + OFF_BAR + CNT_KV * 8 + (step & (KVR - 1)) * 4) : "memory");
    if (old == 3u) kv_load(sbase, step + KVR);
  }
  __syncwarp();
}
__device__ __forceinline__ void kv_wait(uint32_t sbase, int step) {
  mbar_wait(sbase + OFF_BAR + (BAR_KV + (step & (KVR - 1))) * 8, (step / KVR) & 1);
}

__device__ __forceinline__ void attn_tile_fast(const uint32_t (&q)[8], float (&O)[12], uint32_t sbase, int step0, bool elected, uint32_t one2) {
  float S[32]; uint32_t P[16];
#pragma unroll
  for (int i = 0; i < 32; i++) S[i] = 0.f;
  const uint32_t kb0 = (sbase & 0x3FFFFu) >> 4;
  kv_wait(sbase, step0);
  fence_regs(S); fence_regs(O);
  wg_fence();
  issue_qk(S, q, kb0);
  wg_commit();
#pragma unroll 1
  for (int grp = 0; grp < NGRP; grp++) {
    const int step = step0 + grp;
    const uint32_t kb = kb0 + (grp & (KVR - 1)) * (GRP_BYTES >> 4);
    const int nxt = min(grp + 1, NGRP - 1);
    const uint32_t knext = kb0 + (nxt & (KVR - 1)) * (GRP_BYTES >> 4);
    wg_wait<0>();
    fence_regs(S); fence_regs(P); fence_regs(O);
    if (grp > 0) kv_release(sbase, step - 1, elected);
    softmax_fast<0>(S, P, one2);
    fence_regs(S); fence_regs(P); fence_regs(O);
    wg_fence();
    issue_qk(S, q, kb + 64);
    issue_pv(O, P, kb + VOFF);
    wg_commit();
    kv_wait(sbase, step0 + nxt);
    wg_wait<0>();
    fence_regs(S); fence_regs(P); fence_regs(O);
    softmax_fast<8>(S, P, one2);
    fence_regs(S); fence_regs(P); fence_regs(O);
    wg_fence();
    issue_qk(S, q, knext);
    issue_pv(O, P, kb + VOFF + 4 * (768 >> 4));
    wg_commit();
  }
  wg_wait<0>();
  fence_regs(O); fence_regs(S);
  kv_release(sbase, step0 + NGRP - 1, elected);
}
template <int H>
__device__ __forceinline__ void slow_step(const uint32_t (&q)[8], float (&O)[12], uint32_t kb, float& m0, float& m1) {
  float S[32]; uint32_t P[16];
#pragma unroll
  for (int i = 0; i < 32; i++) S[i] = 0.f;
  fence_regs(S);
  wg_fence();
  issue_qk(S, q, kb + 64 * H);
  wg_commit();
  wg_wait<0>();
  fence_regs(S);
  softmax_slow<8 * H>(S, P, O, m0, m1);
  fence_regs(P); fence_regs(O);
  wg_fence();
  issue_pv(O, P, kb + VOFF + H * 4 * (768 >> 4));
  wg_commit();
  wg_wait<0>();
  fence_regs(O); fence_regs(P);
}
__device__ __forceinline__ void attn_tile_slow(const uint32_t (&q)[8], float (&O)[12], uint32_t sbase, int step0, bool elected) {
  float m0 = -INFINITY, m1 = -INFINITY;
#pragma unroll 1
  for (int grp = 0; grp < NGRP; grp++) {
    kv_wait(sbase, step0 + grp);
    const uint32_t kb = ((sbase & 0x3FFFFu) >> 4) + (grp & (KVR - 1)) * (GRP_BYTES >> 4);
    slow_step<0>(q, O, kb, m0, m1);
    slow_step<1>(q, O, kb, m0, m1);
    kv_release(sbase, step0 + grp, elected);
  }
}

__device__ __forceinline__ void local_attn_pair(int token, int lane) {
  const __nv_bfloat16* base = g_qkv + (size_t)token * (3 * D_MODEL) + lane * DH;
  float f[20];
  {
    const uint2* p = reinterpret_cast<const uint2*>(base);
#pragma unroll
    for (int i = 0; i < 5; i++) { const uint2 v = p[i]; f[4 * i] = bf_lo(v.x); f[4 * i + 1] = bf_hi(v.x); f[4 * i + 2] = bf_lo(v.y); f[4 * i + 3] = bf_hi(v.y); }
  }
  float sc[8];
  float mx = -INFINITY;
#pragma unroll
  for (int w = 0; w < 8; w++) {
    const bool ok = token - 2 * w >= 0;
    const uint2* p = reinterpret_cast<const uint2*>(base + D_MODEL - (ok ? 2 * w : 0) * (3 * D_MODEL));
    float s = 0.f;
#pragma unroll
    for (int i = 0; i < 5; i++) {
      const uint2 v = p[i];
      s = fmaf(f[4 * i], bf_lo(v.x), s); s = fmaf(f[4 * i + 1], bf_hi(v.x), s);
      s = fmaf(f[4 * i + 2], bf_lo(v.y), s); s = fmaf(f[4 * i + 3], bf_hi(v.y), s);
    }
    s *= 0.22360679774997896f * 1.4426950408889634f;
    sc[w] = ok ? s : -1e9f * 1.4426950408889634f;
    mx = fmaxf(mx, sc[w]);
  }
  float l = 0.f;
#pragma unroll
  for (int w = 0; w < 8; w++) { sc[w] = ex2(sc[w] - mx); l += sc[w]; }
#pragma unroll
  for (int i = 0; i < 20; i++) f[i] = 0.f;
#pragma unroll
  for (int w = 0; w < 8; w++) {
    const bool ok = token - 2 * w >= 0;
    const uint2* p = reinterpret_cast<const uint2*>(base + 2 * D_MODEL - (ok ? 2 * w : token) * (3 * D_MODEL));
#pragma unroll
    for (int i = 0; i < 5; i++) {
      const uint2 v = p[i];
      f[4 * i] = fmaf(sc[w], bf_lo(v.x), f[4 * i]); f[4 * i + 1] = fmaf(sc[w], bf_hi(v.x), f[4 * i + 1]);
      f[4 * i + 2] = fmaf(sc[w], bf_lo(v.y), f[4 * i + 2]); f[4 * i + 3] = fmaf(sc[w], bf_hi(v.y), f[4 * i + 3]);
    }
  }
  const float r = (1.f - g_gate[token]) / l;
  uint2* dst = reinterpret_cast<uint2*>(g_a2 + (size_t)token * (2 * D_MODEL) + D_MODEL + lane * DH);
#pragma unroll
  for (int i = 0; i < 5; i++) dst[i] = make_uint2(pack_bf16(f[4 * i] * r, f[4 * i + 1] * r), pack_bf16(f[4 * i + 2] * r, f[4 * i + 3] * r));
}

__device__ __forceinline__ void signal_done(unsigned int* flag, int wg, int tid) {
  asm volatile("bar.sync %0, 128;" :: "r"(wg + 1) : "memory");
  if ((tid & 127) == 0) asm volatile("red.release.gpu.global.add.u32 [%0], 1;" :: "l"(flag) : "memory");
}
__device__ __forceinline__ void wait_flags8(const unsigned int* f, unsigned int target) {
  for (int spin = 0; spin < (1 << 26); spin++) {
    unsigned int a, b, c, d, e, g, h, i;
    asm volatile("ld.volatile.global.v4.u32 {%0, %1, %2, %3}, [%4];" : "=r"(a), "=r"(b), "=r"(c), "=r"(d) : "l"(f) : "memory");
    asm volatile("ld.volatile.global.v4.u32 {%0, %1, %2, %3}, [%4];" : "=r"(e), "=r"(g), "=r"(h), "=r"(i) : "l"(f + 4) : "memory");
    if (min(min(min(a, b), min(c, d)), min(min(e, g), min(h, i))) >= target) break;
  }
  asm volatile("fence.acq_rel.gpu;" ::: "memory");
  asm volatile("fence.proxy.async;" ::: "memory");
}
__device__ __forceinline__ uint32_t ta_slot(int i) { return i < 3 ? i * 16384 : OFF_BR + (i - 3) * 16384; }

__global__ void __launch_bounds__(640, 1)
attn_kernel(const __grid_constant__ CUtensorMap tmA2, const __grid_constant__ CUtensorMap tmWoA, const __grid_constant__ CUtensorMap tmWoB,
            __nv_bfloat16* __restrict__ out, uint32_t one2) {
  extern __shared__ uint8_t smem_raw[];
  uint8_t* smem = reinterpret_cast<uint8_t*>((reinterpret_cast<uintptr_t>(smem_raw) + 1023) & ~(uintptr_t)1023);
  const uint32_t sbase = smem_u32(smem);
  const uint32_t dbase = sbase & 0x3FFFFu;
  const uint32_t bars = sbase + OFF_BAR;
  const int tid = threadIdx.x, wg = tid >> 7, warp = (tid >> 5) & 3, lane = tid & 31, g = lane >> 2, t = lane & 3;
  const int mb = blockIdx.x >> 3, nb = blockIdx.x & 7;
  PROF(1, 0);
  if (tid == 0) {
    for (int i = 0; i < BAR_TE; i++) mbar_init(bars + i * 8, 1);
    for (int i = BAR_TE; i < BAR_TE + 4; i++) mbar_init(bars + i * 8, 8);
    for (int i = 0; i < 4; i++) *reinterpret_cast<uint32_t*>(smem + OFF_BAR + CNT_KV * 8 + i * 4) = 0u;
    fence_mbar_init();
  }
  __syncthreads();
  if (wg == 4) {
    if (tid == 512) {
      mbar_expect_tx(bars + BAR_WA * 8, 10 * 10240);
      for (int kt = 0; kt < 10; kt++) tma_3d(sbase + OFF_WA + kt * 10240, &tmWoA, 0, kt * 64, nb * 5, bars + BAR_WA * 8);
    }
    pdl_wait();
    if (tid == 512) for (int j = 0; j < KVR; j++) kv_load(sbase, j);
    __syncwarp();
#pragma unroll 1
    for (int i = 0; i < 4; i++) local_attn_pair(blockIdx.x * 16 + i * 4 + warp, lane);
    signal_done(&g_doneL[blockIdx.x], wg, tid);
    auto br_load = [&](int it, int st) {
      const uint32_t fb = bars + (BAR_BR + st) * 8;
      const uint32_t dst = sbase + OFF_BR + st * BR_STAGE;
      const int kc = (it >= 10 ? it - 10 : it) * 64;
      mbar_expect_tx(fb, BR_STAGE);
      tma_2d(dst, &tmA2, D_MODEL + kc, (blockIdx.x >> 3) * 128 + (it >= 10 ? 64 : 0), fb);
      tma_3d(dst + 8192, &tmWoB, 0, kc, (blockIdx.x & 7) * 5, fb);
    };
    if (tid == 512) {
      wait_flags8(&g_doneL[mb * 8], 1u);
      for (int it = 0; it < BR_STAGES; it++) br_load(it, it);
    }
    __syncwarp();
    {
      int st = 0, ph = 0;
      float acc[40];
#pragma unroll 1
      for (int it = 0; it < 20; it++) {
        if (it == 0 || it == 10) {
#pragma unroll
          for (int i = 0; i < 40; i++) acc[i] = 0.f;
        }
        mbar_wait(bars + (BAR_BR + st) * 8, ph);
        const uint32_t alo = ((dbase + OFF_BR + st * BR_STAGE) >> 4);
        fence_regs(acc);
        wg_fence();
#pragma unroll
        for (int k = 0; k < 4; k++)
          wgmma_ss_n80_tb(acc, mkd(alo + (k * 2 + (1u << 16)), DHI_SW128_K), mkd(alo + (512 + k * 32 + ((2048u >> 4) << 16)), DHI_SW32_MN));
        wg_commit();
        wg_wait<0>();
        fence_regs(acc);
        asm volatile("bar.sync 5, 128;" ::: "memory");
        if (threadIdx.x == 512 && it + BR_STAGES < 20) br_load(it + BR_STAGES, st);
        __syncwarp();
        if (it == 9 || it == 19) {
          float* pp = g_part + (size_t)(blockIdx.x * 2 + (it == 19)) * (40 * 128) + (threadIdx.x & 127);
#pragma unroll
          for (int i = 0; i < 40; i++) pp[i * 128] = acc[i];
        }
        if (++st == BR_STAGES) { st = 0; ph ^= 1; }
      }
    }
    asm volatile("bar.arrive 6, 384;" ::: "memory");
    if (tid == 512) {
      wait_flags8(&g_done[mb * 8], 4u);
      PROF2(2, 0);
      for (int kt = 0; kt < 10; kt++) {
        const int sl = kt % 6;
        if (kt >= 6) mbar_wait(bars + (BAR_TE + kt - 6) * 8, 0);
        const uint32_t fb = bars + (BAR_TA + sl) * 8;
        mbar_expect_tx(fb, 16384);
        tma_2d(sbase + ta_slot(sl), &tmA2, kt * 64, mb * 128, fb);
        tma_2d(sbase + ta_slot(sl) + 8192, &tmA2, kt * 64, mb * 128 + 64, fb);
      }
    }
  } else {
    pdl_wait();
    PROF(1, 1);
    const bool elected = (tid & 127) == 0;
    uint32_t q[8];
    uint32_t* qstash = reinterpret_cast<uint32_t*>(smem + OFF_QS) + tid;
    const int rowA = (blockIdx.x * 8 + wg) * 64 + warp * 16 + g;
    {
      const uint32_t* r0 = reinterpret_cast<const uint32_t*>(g_q + (size_t)rowA * DH);
      const uint32_t* r1 = r0 + 8 * (DH / 2);
      const uint32_t* s0 = r0 + 256 * (DH / 2);
      const uint32_t* s1 = s0 + 8 * (DH / 2);
      q[0] = r0[t]; q[1] = r1[t]; q[2] = r0[t + 4]; q[3] = r1[t + 4];
      q[4] = t < 2 ? r0[8 + t] : 0u;
      q[5] = t < 2 ? r1[8 + t] : 0u;
      qstash[0] = s0[t]; qstash[512] = s1[t]; qstash[1024] = s0[t + 4]; qstash[1536] = s1[t + 4];
      qstash[2048] = t < 2 ? s0[8 + t] : 0u;
      qstash[2560] = t < 2 ? s1[8 + t] : 0u;
    }
    float kmax2 = 0.f, vmax = 0.f;
#pragma unroll
    for (int i = 0; i < 4; i++) {
      const float a = g_kmax2[lane + 32 * i];
      kmax2 = (a > kmax2 || a != a) ? a : kmax2;
      vmax = fmaxf(vmax, g_vmax[lane + 32 * i]);
    }
#pragma unroll
    for (int o = 1; o < 32; o <<= 1) {
      const float a = __shfl_xor_sync(0xffffffffu, kmax2, o);
      kmax2 = (a > kmax2 || a != a) ? a : kmax2;
      vmax = fmaxf(vmax, __shfl_xor_sync(0xffffffffu, vmax, o));
    }
    const float qlim = (vmax >= 0.00390625f && vmax <= 256.f) ? 9025.f / kmax2 : -1.f;
    PROF(1, 2);
#pragma unroll 1
    for (int it = 0; it < 2; it++) {
      const int row0 = rowA + it * 256;
      if (it == 1) {
#pragma unroll
        for (int i = 0; i < 6; i++) q[i] = qstash[512 * i];
      }
      float n0 = bf_lo(q[0]) * bf_lo(q[0]) + bf_hi(q[0]) * bf_hi(q[0]) + bf_lo(q[2]) * bf_lo(q[2]) + bf_hi(q[2]) * bf_hi(q[2]) +
                 bf_lo(q[4]) * bf_lo(q[4]) + bf_hi(q[4]) * bf_hi(q[4]);
      float n1 = bf_lo(q[1]) * bf_lo(q[1]) + bf_hi(q[1]) * bf_hi(q[1]) + bf_lo(q[3]) * bf_lo(q[3]) + bf_hi(q[3]) * bf_hi(q[3]) +
                 bf_lo(q[5]) * bf_lo(q[5]) + bf_hi(q[5]) * bf_hi(q[5]);
      n0 += __shfl_xor_sync(0xffffffffu, n0, 1); n0 += __shfl_xor_sync(0xffffffffu, n0, 2);
      n1 += __shfl_xor_sync(0xffffffffu, n1, 1); n1 += __shfl_xor_sync(0xffffffffu, n1, 2);
      const bool safe = (n0 <= qlim) && (n1 <= qlim);
      uint32_t unsafe_any;
      asm volatile("{\n.reg .pred p, r;\nsetp.eq.u32 p, %1, 0;\nbarrier.cta.red.or.pred r, %2, 128, p;\nselp.u32 %0, 1, 0, r;\n}\n"
                   : "=r"(unsafe_any) : "r"((uint32_t)safe), "r"(wg + 1) : "memory");
      float O[12];
#pragma unroll
      for (int i = 0; i < 12; i++) O[i] = 0.f;
      if (!unsafe_any && t >= 2) { q[4] = q[5] = (t == 2) ? 0x3F804100u : 0x00003B80u; }
      q[6] = q[4]; q[7] = q[5];
      fence_regs(q);
      if (!unsafe_any) attn_tile_fast(q, O, sbase, it * NGRP, elected, one2);
      else attn_tile_slow(q, O, sbase, it * NGRP, elected);
      const float l0 = __shfl_sync(0xffffffffu, O[8], (lane & ~3) | 2);
      const float l1 = __shfl_sync(0xffffffffu, O[10], (lane & ~3) | 2);
      const int tok = row0 >> 5;
      const float gt = g_gate[tok];
      const float i0 = gt / l0, i1 = gt / l1;
      uint32_t* o0 = reinterpret_cast<uint32_t*>(g_a2 + (size_t)tok * (2 * D_MODEL) + (row0 & 31) * DH);
      uint32_t* o1 = o0 + 8 * (DH / 2);
      o0[t] = pack_bf16(O[0] * i0, O[1] * i0); o1[t] = pack_bf16(O[2] * i1, O[3] * i1);
      o0[t + 4] = pack_bf16(O[4] * i0, O[5] * i0); o1[t + 4] = pack_bf16(O[6] * i1, O[7] * i1);
      if (t < 2) { o0[t + 8] = pack_bf16(O[8] * i0, O[9] * i0); o1[t + 8] = pack_bf16(O[10] * i1, O[11] * i1); }
    }
    signal_done(&g_done[blockIdx.x], wg, tid);
    PROF(1, 3);
    if (wg < 2) {
      float acc[40];
      asm volatile("bar.sync 6, 384;" ::: "memory");
      {
        const float* pp = g_part + (size_t)(blockIdx.x * 2 + wg) * (40 * 128) + (tid & 127);
#pragma unroll
        for (int i = 0; i < 40; i++) acc[i] = pp[i * 128];
      }
      mbar_wait(bars + BAR_WA * 8, 0);
#pragma unroll 1
      for (int kt = 0; kt < 10; kt++) {
        const int sl = kt % 6;
        mbar_wait(bars + (BAR_TA + sl) * 8, kt / 6);
        if (kt == 0) PROF(2, 1);
        const uint32_t alo = ((dbase + ta_slot(sl) + wg * 8192) >> 4) | (1u << 16);
        const uint32_t blo = ((dbase + OFF_WA + kt * 10240) >> 4) | ((2048u >> 4) << 16);
        fence_regs(acc);
        wg_fence();
#pragma unroll
        for (int k = 0; k < 4; k++) wgmma_ss_n80_tb(acc, mkd(alo + k * 2, DHI_SW128_K), mkd(blo + k * 32, DHI_SW32_MN));
        wg_commit();
        if (kt < 4) {
          wg_wait<0>();
          if (lane == 0) mbar_arrive(bars + (BAR_TE + kt) * 8);
        }
      }
      wg_wait<0>();
      fence_regs(acc);
      PROF(2, 2);
      asm volatile("bar.sync %0, 128;" :: "r"(wg + 1) : "memory");
      const uint32_t so = ta_slot(warp) + wg * 8192;
      const int row0 = mb * 128 + wg * 64 + warp * 16;
      store_tile_bf16<80>(acc, 1.0f, sbase + so, smem + so, out + (size_t)row0 * D_MODEL + nb * 80, D_MODEL, lane);
      PROF(2, 3);
    }
  }
}

typedef CUresult (*EncodeFn)(CUtensorMap*, CUtensorMapDataType, cuuint32_t, void*, const cuuint64_t*, const cuuint64_t*,
                             const cuuint32_t*, const cuuint32_t*, CUtensorMapInterleave, CUtensorMapSwizzle,
                             CUtensorMapL2promotion, CUtensorMapFloatOOBfill);

void make_map(EncodeFn fn, CUtensorMap* tm, const void* ptr, int rank, const cuuint64_t* dims, const cuuint64_t* strides,
              const cuuint32_t* box, CUtensorMapSwizzle sw) {
  const cuuint32_t es[3] = {1, 1, 1};
  fn(tm, CU_TENSOR_MAP_DATA_TYPE_BFLOAT16, rank, const_cast<void*>(ptr), dims, strides, box, es, CU_TENSOR_MAP_INTERLEAVE_NONE, sw,
     CU_TENSOR_MAP_L2_PROMOTION_L2_256B, CU_TENSOR_MAP_FLOAT_OOB_FILL_NONE);
}
void map_a(EncodeFn fn, CUtensorMap* tm, const void* p, int rows, int cols, int box_rows) {
  const cuuint64_t dims[2] = {(cuuint64_t)cols, (cuuint64_t)rows};
  const cuuint64_t str[1] = {(cuuint64_t)cols * 2};
  const cuuint32_t box[2] = {64, (cuuint32_t)box_rows};
  make_map(fn, tm, p, 2, dims, str, box, CU_TENSOR_MAP_SWIZZLE_128B);
}
void map_w(EncodeFn fn, CUtensorMap* tm, const void* p, int K, int N, int atom, CUtensorMapSwizzle sw) {
  const cuuint64_t dims[3] = {(cuuint64_t)atom, (cuuint64_t)K, (cuuint64_t)(N / atom)};
  const cuuint64_t str[2] = {(cuuint64_t)N * 2, (cuuint64_t)atom * 2};
  const cuuint32_t box[3] = {(cuuint32_t)atom, 64, 5};
  make_map(fn, tm, p, 3, dims, str, box, sw);
}

template <typename... KArgs, typename... Args>
void launch(void (*kern)(KArgs...), int grid, int block, int smem, bool pdl, Args... args) {
  cudaLaunchConfig_t cfg = {};
  cfg.gridDim = dim3(grid); cfg.blockDim = dim3(block); cfg.dynamicSmemBytes = smem; cfg.stream = cudaStreamPerThread;
  cudaLaunchAttribute at[1];
  at[0].id = cudaLaunchAttributeProgrammaticStreamSerialization;
  at[0].val.programmaticStreamSerializationAllowed = 1;
  cfg.attrs = at; cfg.numAttrs = pdl ? 1 : 0;
  cudaLaunchKernelEx(&cfg, kern, KArgs(args)...);
}

}

extern "C" void kernel_launch(void* const* d_in, const int* in_sizes, int n_in, void* d_out, int out_size) {
  (void)in_sizes; (void)n_in; (void)out_size;
  const __nv_bfloat16* x = (const __nv_bfloat16*)d_in[0];
  const __nv_bfloat16* wq = (const __nv_bfloat16*)d_in[1];
  const __nv_bfloat16* wk = (const __nv_bfloat16*)d_in[2];
  const __nv_bfloat16* wv = (const __nv_bfloat16*)d_in[3];
  const __nv_bfloat16* woA = (const __nv_bfloat16*)d_in[4];
  const __nv_bfloat16* wqkv = (const __nv_bfloat16*)d_in[6];
  const __nv_bfloat16* woB = (const __nv_bfloat16*)d_in[7];
  const __nv_bfloat16* gate_w = (const __nv_bfloat16*)d_in[8];

  static EncodeFn enc = nullptr;
  static void* a2_ptr = nullptr;
  if (!enc) {
    void* fp = nullptr;
    cudaDriverEntryPointQueryResult qr;
    cudaGetDriverEntryPoint("cuTensorMapEncodeTiled", &fp, cudaEnableDefault, &qr);
    enc = (EncodeFn)fp;
    cudaGetSymbolAddress(&a2_ptr, g_a2);
    cudaFuncSetAttribute(proj_kernel, cudaFuncAttributeMaxDynamicSharedMemorySize, K1_SMEM);
    cudaFuncSetAttribute(attn_kernel, cudaFuncAttributeMaxDynamicSharedMemorySize, K2_SMEM);
  }
  CUtensorMap tmX, tmWq, tmWqkv, tmA2, tmWoA, tmWoB;
  map_a(enc, &tmX, x, S_LEN, D_MODEL, 256);
  map_w(enc, &tmWq, wq, D_MODEL, D_MODEL, 32, CU_TENSOR_MAP_SWIZZLE_64B);
  map_w(enc, &tmWqkv, wqkv, D_MODEL, 3 * D_MODEL, 32, CU_TENSOR_MAP_SWIZZLE_64B);
  map_a(enc, &tmA2, a2_ptr, S_LEN, 2 * D_MODEL, 64);
  map_w(enc, &tmWoA, woA, D_MODEL, D_MODEL, 16, CU_TENSOR_MAP_SWIZZLE_32B);
  map_w(enc, &tmWoB, woB, D_MODEL, D_MODEL, 16, CU_TENSOR_MAP_SWIZZLE_32B);

  launch(proj_kernel, 132, 512, K1_SMEM, false, tmX, tmWq, tmWqkv, wk, wv, gate_w);
  launch(attn_kernel, 128, 640, K2_SMEM, true, tmA2, tmWoA, tmWoB, (__nv_bfloat16*)d_out, 0x3F803F80u);
}
```

```cpp
#include <cuda_runtime.h>
#include <cuda_bf16.h>
#include <cuda.h>
#include <stdint.h>

namespace {

constexpr int S_LEN = 2048, D_MODEL = 640, DH = 20;

constexpr int GRP = 128;
constexpr int PLANE = GRP * 16;
constexpr int GRP_BYTES = GRP * 16 * 6;
constexpr int NGRP = S_LEN / GRP;
constexpr uint32_t TMASK = 0x6DB6u;

__device__ __align__(1024) __nv_bfloat16 g_q[S_LEN * D_MODEL];
__device__ __align__(1024) __nv_bfloat16 g_qkv[S_LEN * 3 * D_MODEL];
__device__ __align__(1024) __nv_bfloat16 g_a2[S_LEN * 2 * D_MODEL];
__device__ __align__(1024) uint8_t g_kvimg[NGRP * GRP_BYTES];
__device__ float g_gate[S_LEN];
__device__ float g_kmax2[128];
__device__ float g_vmax[128];
__device__ __align__(32) unsigned int g_doneL[128];
__device__ float g_part[128 * 2 * 40 * 128];
__device__ __align__(32) unsigned int g_done[128];

#define PROF(k, slot)
#define PROF2(k, slot)
__device__ __forceinline__ uint32_t smem_u32(const void* p) { return (uint32_t)__cvta_generic_to_shared(p); }
__device__ __forceinline__ uint64_t mkd(uint32_t lo, uint32_t hi) {
  uint64_t d; asm("mov.b64 %0, {%1, %2};" : "=l"(d) : "r"(lo), "r"(hi)); return d;
}
__device__ __forceinline__ void wg_fence() { asm volatile("wgmma.fence.sync.aligned;" ::: "memory"); }
__device__ __forceinline__ void wg_commit() { asm volatile("wgmma.commit_group.sync.aligned;" ::: "memory"); }
template <int N> __device__ __forceinline__ void wg_wait() { asm volatile("wgmma.wait_group.sync.aligned %0;" :: "n"(N) : "memory"); }
template <int N> __device__ __forceinline__ void fence_regs(float (&d)[N]) {
#pragma unroll
  for (int i = 0; i < N; i++) asm volatile("" : "+f"(d[i]) :: "memory");
}
template <int N> __device__ __forceinline__ void fence_regs(uint32_t (&d)[N]) {
#pragma unroll
  for (int i = 0; i < N; i++) asm volatile("" : "+r"(d[i]) :: "memory");
}
__device__ __forceinline__ void mbar_init(uint32_t bar, uint32_t cnt) { asm volatile("mbarrier.init.shared::cta.b64 [%0], %1;" :: "r"(bar), "r"(cnt)); }
__device__ __forceinline__ void mbar_expect_tx(uint32_t bar, uint32_t bytes) {
  asm volatile("mbarrier.arrive.expect_tx.shared::cta.b64 _, [%0], %1;" :: "r"(bar), "r"(bytes) : "memory");
}
__device__ __forceinline__ void mbar_arrive(uint32_t bar) { asm volatile("mbarrier.arrive.shared::cta.b64 _, [%0];" :: "r"(bar) : "memory"); }
__device__ __forceinline__ void mbar_wait(uint32_t bar, uint32_t parity) {
  asm volatile("{\n.reg .pred p;\nWAIT_%=:\nmbarrier.try_wait.parity.shared::cta.b64 p, [%0], %1;\n@p bra DONE_%=;\nbra WAIT_%=;\nDONE_%=:\n}\n"
               :: "r"(bar), "r"(parity) : "memory");
}
__device__ __forceinline__ void fence_mbar_init() { asm volatile("fence.mbarrier_init.release.cluster;" ::: "memory"); }
__device__ __forceinline__ void fence_proxy_async() { asm volatile("fence.proxy.async.shared::cta;" ::: "memory"); }
__device__ __forceinline__ void bulk_g2s(uint32_t dst, const void* src, uint32_t bytes, uint32_t bar) {
  asm volatile("cp.async.bulk.shared::cluster.global.mbarrier::complete_tx::bytes [%0], [%1], %2, [%3];"
               :: "r"(dst), "l"(src), "r"(bytes), "r"(bar) : "memory");
}
__device__ __forceinline__ void tma_2d(uint32_t dst, const CUtensorMap* tm, int c0, int c1, uint32_t bar) {
  asm volatile("cp.async.bulk.tensor.2d.shared::cluster.global.mbarrier::complete_tx::bytes [%0], [%1, {%3, %4}], [%2];"
               :: "r"(dst), "l"((uint64_t)tm), "r"(bar), "r"(c0), "r"(c1) : "memory");
}
__device__ __forceinline__ void tma_3d(uint32_t dst, const CUtensorMap* tm, int c0, int c1, int c2, uint32_t bar) {
  asm volatile("cp.async.bulk.tensor.3d.shared::cluster.global.mbarrier::complete_tx::bytes [%0], [%1, {%3, %4, %5}], [%2];"
               :: "r"(dst), "l"((uint64_t)tm), "r"(bar), "r"(c0), "r"(c1), "r"(c2) : "memory");
}
__device__ __forceinline__ void pdl_wait() { asm volatile("griddepcontrol.wait;" ::: "memory"); }
__device__ __forceinline__ void pdl_launch() { asm volatile("griddepcontrol.launch_dependents;" ::: "memory"); }
__device__ __forceinline__ float ex2(float x) { float y; asm("ex2.approx.ftz.f32 %0, %1;" : "=f"(y) : "f"(x)); return y; }
__device__ __forceinline__ uint32_t pack_bf16(float lo, float hi) {
  uint32_t r; asm("cvt.rn.bf16x2.f32 %0, %1, %2;" : "=r"(r) : "f"(hi), "f"(lo)); return r;
}
__device__ __forceinline__ float bf_lo(uint32_t x) { return __uint_as_float(x << 16); }
__device__ __forceinline__ float bf_hi(uint32_t x) { return __uint_as_float(x & 0xffff0000u); }
__device__ __forceinline__ void stsm4(uint32_t addr, uint32_t r0, uint32_t r1, uint32_t r2, uint32_t r3) {
  asm volatile("stmatrix.sync.aligned.m8n8.x4.shared.b16 [%0], {%1, %2, %3, %4};" :: "r"(addr), "r"(r0), "r"(r1), "r"(r2), "r"(r3) : "memory");
}

__device__ __forceinline__ void wgmma_ss_n160_tb(float (&d)[80], uint64_t descA, uint64_t descB) {
  asm volatile("wgmma.mma_async.sync.aligned.m64n160k16.f32.bf16.bf16 {%0, %1, %2, %3, %4, %5, %6, %7, %8, %9, %10, %11, %12, %13, %14, %15, %16, %17, %18, %19, %20, %21, %22, %23, %24, %25, %26, %27, %28, %29, %30, %31, %32, %33, %34, %35, %36, %37, %38, %39, %40, %41, %42, %43, %44, %45, %46, %47, %48, %49, %50, %51, %52, %53, %54, %55, %56, %57, %58, %59, %60, %61, %62, %63, %64, %65, %66, %67, %68, %69, %70, %71, %72, %73, %74, %75, %76, %77, %78, %79}, %80, %81, 1, 1, 1, 0, 1;\n"
    : "+f"(d[0]), "+f"(d[1]), "+f"(d[2]), "+f"(d[3]), "+f"(d[4]), "+f"(d[5]), "+f"(d[6]), "+f"(d[7]), "+f"(d[8]), "+f"(d[9]), "+f"(d[10]), "+f"(d[11]), "+f"(d[12]), "+f"(d[13]), "+f"(d[14]), "+f"(d[15]), "+f"(d[16]), "+f"(d[17]), "+f"(d[18]), "+f"(d[19]), "+f"(d[20]), "+f"(d[21]), "+f"(d[22]), "+f"(d[23]), "+f"(d[24]), "+f"(d[25]), "+f"(d[26]), "+f"(d[27]), "+f"(d[28]), "+f"(d[29]), "+f"(d[30]), "+f"(d[31]), "+f"(d[32]), "+f"(d[33]), "+f"(d[34]), "+f"(d[35]), "+f"(d[36]), "+f"(d[37]), "+f"(d[38]), "+f"(d[39]), "+f"(d[40]), "+f"(d[41]), "+f"(d[42]), "+f"(d[43]), "+f"(d[44]), "+f"(d[45]), "+f"(d[46]), "+f"(d[47]), "+f"(d[48]), "+f"(d[49]), "+f"(d[50]), "+f"(d[51]), "+f"(d[52]), "+f"(d[53]), "+f"(d[54]), "+f"(d[55]), "+f"(d[56]), "+f"(d[57]), "+f"(d[58]), "+f"(d[59]), "+f"(d[60]), "+f"(d[61]), "+f"(d[62]), "+f"(d[63]), "+f"(d[64]), "+f"(d[65]), "+f"(d[66]), "+f"(d[67]), "+f"(d[68]), "+f"(d[69]), "+f"(d[70]), "+f"(d[71]), "+f"(d[72]), "+f"(d[73]), "+f"(d[74]), "+f"(d[75]), "+f"(d[76]), "+f"(d[77]), "+f"(d[78]), "+f"(d[79])
    : "l"(descA), "l"(descB));
}
__device__ __forceinline__ void wgmma_ss_n48_tb(float (&d)[24], uint64_t descA, uint64_t descB) {
  asm volatile("wgmma.mma_async.sync.aligned.m64n48k16.f32.bf16.bf16 {%0, %1, %2, %3, %4, %5, %6, %7, %8, %9, %10, %11, %12, %13, %14, %15, %16, %17, %18, %19, %20, %21, %22, %23}, %24, %25, 1, 1, 1, 0, 1;\n"
    : "+f"(d[0]), "+f"(d[1]), "+f"(d[2]), "+f"(d[3]), "+f"(d[4]), "+f"(d[5]), "+f"(d[6]), "+f"(d[7]), "+f"(d[8]), "+f"(d[9]), "+f"(d[10]), "+f"(d[11]), "+f"(d[12]), "+f"(d[13]), "+f"(d[14]), "+f"(d[15]), "+f"(d[16]), "+f"(d[17]), "+f"(d[18]), "+f"(d[19]), "+f"(d[20]), "+f"(d[21]), "+f"(d[22]), "+f"(d[23])
    : "l"(descA), "l"(descB));
}
__device__ __forceinline__ void wgmma_ss_n80_tb(float (&d)[40], uint64_t descA, uint64_t descB) {
  asm volatile("wgmma.mma_async.sync.aligned.m64n80k16.f32.bf16.bf16 {%0, %1, %2, %3, %4, %5, %6, %7, %8, %9, %10, %11, %12, %13, %14, %15, %16, %17, %18, %19, %20, %21, %22, %23, %24, %25, %26, %27, %28, %29, %30, %31, %32, %33, %34, %35, %36, %37, %38, %39}, %40, %41, 1, 1, 1, 0, 1;\n"
    : "+f"(d[0]), "+f"(d[1]), "+f"(d[2]), "+f"(d[3]), "+f"(d[4]), "+f"(d[5]), "+f"(d[6]), "+f"(d[7]), "+f"(d[8]), "+f"(d[9]), "+f"(d[10]), "+f"(d[11]), "+f"(d[12]), "+f"(d[13]), "+f"(d[14]), "+f"(d[15]), "+f"(d[16]), "+f"(d[17]), "+f"(d[18]), "+f"(d[19]), "+f"(d[20]), "+f"(d[21]), "+f"(d[22]), "+f"(d[23]), "+f"(d[24]), "+f"(d[25]), "+f"(d[26]), "+f"(d[27]), "+f"(d[28]), "+f"(d[29]), "+f"(d[30]), "+f"(d[31]), "+f"(d[32]), "+f"(d[33]), "+f"(d[34]), "+f"(d[35]), "+f"(d[36]), "+f"(d[37]), "+f"(d[38]), "+f"(d[39])
    : "l"(descA), "l"(descB));
}
template <int SCALE_D>
__device__ __forceinline__ void wgmma_rs_n64(float (&d)[32], uint32_t a0, uint32_t a1, uint32_t a2, uint32_t a3, uint64_t descB) {
  asm volatile("wgmma.mma_async.sync.aligned.m64n64k16.f32.bf16.bf16 {%0, %1, %2, %3, %4, %5, %6, %7, %8, %9, %10, %11, %12, %13, %14, %15, %16, %17, %18, %19, %20, %21, %22, %23, %24, %25, %26, %27, %28, %29, %30, %31}, {%32, %33, %34, %35}, %36, %37, 1, 1, 0;\n"
    : "+f"(d[0]), "+f"(d[1]), "+f"(d[2]), "+f"(d[3]), "+f"(d[4]), "+f"(d[5]), "+f"(d[6]), "+f"(d[7]), "+f"(d[8]), "+f"(d[9]), "+f"(d[10]), "+f"(d[11]), "+f"(d[12]), "+f"(d[13]), "+f"(d[14]), "+f"(d[15]), "+f"(d[16]), "+f"(d[17]), "+f"(d[18]), "+f"(d[19]), "+f"(d[20]), "+f"(d[21]), "+f"(d[22]), "+f"(d[23]), "+f"(d[24]), "+f"(d[25]), "+f"(d[26]), "+f"(d[27]), "+f"(d[28]), "+f"(d[29]), "+f"(d[30]), "+f"(d[31])
    : "r"(a0), "r"(a1), "r"(a2), "r"(a3), "l"(descB), "n"(SCALE_D));
}
template <int SCALE_D>
__device__ __forceinline__ void wgmma_rs_n24_tb(float (&d)[12], uint32_t a0, uint32_t a1, uint32_t a2, uint32_t a3, uint64_t descB) {
  asm volatile("wgmma.mma_async.sync.aligned.m64n24k16.f32.bf16.bf16 {%0, %1, %2, %3, %4, %5, %6, %7, %8, %9, %10, %11}, {%12, %13, %14, %15}, %16, %17, 1, 1, 1;\n"
    : "+f"(d[0]), "+f"(d[1]), "+f"(d[2]), "+f"(d[3]), "+f"(d[4]), "+f"(d[5]), "+f"(d[6]), "+f"(d[7]), "+f"(d[8]), "+f"(d[9]), "+f"(d[10]), "+f"(d[11])
    : "r"(a0), "r"(a1), "r"(a2), "r"(a3), "l"(descB), "n"(SCALE_D));
}

constexpr uint32_t DHI_SW128_K = (1024 >> 4) | (1u << 30);
constexpr uint32_t DHI_SW64_MN = (512 >> 4) | (2u << 30);
constexpr uint32_t DHI_SW32_MN = (256 >> 4) | (3u << 30);

template <int NC>
__device__ __forceinline__ void store_tile_bf16(const float (&acc)[NC / 2], float scale, uint32_t stage, uint8_t* stage_ptr,
                                                __nv_bfloat16* gdst, int gpitch, int lane) {
  constexpr int PITCH = NC * 2 + 16;
  const uint32_t waddr = stage + ((lane & 7) + ((lane >> 3) & 1) * 8) * PITCH + (lane >> 4) * 16;
#pragma unroll
  for (int j = 0; j < NC / 16; j++) {
    stsm4(waddr + j * 32, pack_bf16(acc[8 * j] * scale, acc[8 * j + 1] * scale), pack_bf16(acc[8 * j + 2] * scale, acc[8 * j + 3] * scale),
          pack_bf16(acc[8 * j + 4] * scale, acc[8 * j + 5] * scale), pack_bf16(acc[8 * j + 6] * scale, acc[8 * j + 7] * scale));
  }
  __syncwarp();
  constexpr int CPR = NC / 8;
#pragma unroll
  for (int i = 0; i < CPR / 2; i++) {
    const int c = i * 32 + lane, r = c / CPR, cc = c % CPR;
    const uint4 v = *reinterpret_cast<const uint4*>(stage_ptr + r * PITCH + cc * 16);
    *reinterpret_cast<uint4*>(gdst + (size_t)r * gpitch + cc * 8) = v;
  }
}

constexpr int K1_STAGES = 4;
constexpr int K1_A_BYTES = 256 * 128;
constexpr int K1_B_BYTES = 64 * 160 * 2;
constexpr int K1_STAGE = K1_A_BYTES + K1_B_BYTES;
constexpr int K1_SMEM = 5 * K1_A_BYTES + 61440 + 1024;
constexpr int KV_STAGES = 5;
constexpr int KVW_OFF = KV_STAGES * K1_A_BYTES;

__global__ void __launch_bounds__(512, 1)
proj_kernel(const __grid_constant__ CUtensorMap tmX, const __grid_constant__ CUtensorMap tmWq, const __grid_constant__ CUtensorMap tmWqkv,
            const __nv_bfloat16* __restrict__ wk, const __nv_bfloat16* __restrict__ wv, const __nv_bfloat16* __restrict__ gate_w) {
  extern __shared__ uint8_t smem_raw[];
  __shared__ __align__(8) uint64_t bar_full[KV_STAGES], bar_empty[KV_STAGES];
  uint8_t* smem = reinterpret_cast<uint8_t*>((reinterpret_cast<uintptr_t>(smem_raw) + 1023) & ~(uintptr_t)1023);
  const uint32_t sbase = smem_u32(smem);
  const uint32_t dbase = sbase & 0x3FFFFu;
  const int tid = threadIdx.x, warp = tid >> 5, lane = tid & 31;
  const bool is_kv = blockIdx.x >= 128;
  PROF(0, 0);
  pdl_launch();
  if (tid == 0) {
    for (int i = 0; i < KV_STAGES; i++) { mbar_init(smem_u32(&bar_full[i]), 1); mbar_init(smem_u32(&bar_empty[i]), 16); }
    fence_mbar_init();
    if (!is_kv) { g_done[blockIdx.x] = 0u; g_doneL[blockIdx.x] = 0u; }
  }
  __syncthreads();

  if (!is_kv) {
    const int mb = blockIdx.x >> 4, nb = blockIdx.x & 15;
    const CUtensorMap* tw = nb < 4 ? &tmWq : &tmWqkv;
    const int j0 = (nb < 4 ? nb : nb - 4) * 5;
    auto load = [&](int kt) {
      const int s = kt % K1_STAGES;
      const uint32_t fb = smem_u32(&bar_full[s]);
      mbar_expect_tx(fb, K1_STAGE);
      tma_2d(sbase + s * K1_STAGE, &tmX, kt * 64, mb * 256, fb);
      tma_3d(sbase + s * K1_STAGE + K1_A_BYTES, tw, 0, kt * 64, j0, fb);
    };
    if (tid == 0) for (int kt = 0; kt < K1_STAGES; kt++) load(kt);
    {
      const int wg = warp >> 2;
      float acc[80];
#pragma unroll
      for (int i = 0; i < 80; i++) acc[i] = 0.f;
      for (int kt = 0; kt < 10; kt++) {
        const int s = kt % K1_STAGES;
        mbar_wait(smem_u32(&bar_full[s]), (kt / K1_STAGES) & 1);
        const uint32_t alo = ((dbase + s * K1_STAGE + wg * 8192) >> 4) | (1u << 16);
        const uint32_t blo = ((dbase + s * K1_STAGE + K1_A_BYTES) >> 4) | ((4096u >> 4) << 16);
        fence_regs(acc);
        wg_fence();
#pragma unroll
        for (int k = 0; k < 4; k++) wgmma_ss_n160_tb(acc, mkd(alo + k * 2, DHI_SW128_K), mkd(blo + k * 64, DHI_SW64_MN));
        wg_commit();
        if (kt > 0 && kt - 1 + K1_STAGES < 10) {
          wg_wait<1>();
          const uint32_t eb = smem_u32(&bar_empty[(kt - 1) % K1_STAGES]);
          if (lane == 0) mbar_arrive(eb);
          if (tid == 0) { mbar_wait(eb, ((kt - 1) / K1_STAGES) & 1); load(kt - 1 + K1_STAGES); }
          __syncwarp();
        }
      }
      wg_wait<0>();
      fence_regs(acc);
      PROF(0, 1);
      asm volatile("bar.sync %0, 128;" :: "r"(wg + 1) : "memory");
      const int w4 = warp & 3;
      const uint32_t off = w4 * K1_STAGE + wg * 8192;
      const int row0 = mb * 256 + wg * 64 + w4 * 16;
      if (nb < 4) {
        store_tile_bf16<160>(acc, 0.22360679774997896f * 1.4426950408889634f, sbase + off, smem + off,
                             g_q + (size_t)row0 * D_MODEL + nb * 160, D_MODEL, lane);
      } else {
        store_tile_bf16<160>(acc, 1.0f, sbase + off, smem + off, g_qkv + (size_t)row0 * (3 * D_MODEL) + (nb - 4) * 160, 3 * D_MODEL, lane);
      }
    }
  } else {
    const int cb = blockIdx.x - 128;
    auto load = [&](int it) {
      const int s = it % KV_STAGES;
      const uint32_t fb = smem_u32(&bar_full[s]);
      mbar_expect_tx(fb, K1_A_BYTES);
      tma_2d(sbase + s * K1_A_BYTES, &tmX, (it % 10) * 64, cb * 512 + (it / 10) * 256, fb);
    };
    if (tid == 0) for (int it = 0; it < KV_STAGES; it++) load(it);
    {
      if (tid < 320) {
        uint2 a[2][5], b[2][5]; uint32_t gw[2];
#pragma unroll
        for (int r = 0; r < 2; r++) {
          const int k = tid + r * 320;
          const uint2* pk = reinterpret_cast<const uint2*>(wk + k * 20);
          const uint2* pv = reinterpret_cast<const uint2*>(wv + k * 20);
#pragma unroll
          for (int i = 0; i < 5; i++) { a[r][i] = __ldg(pk + i); b[r][i] = __ldg(pv + i); }
          gw[r] = (uint32_t)__bfloat16_as_ushort(gate_w[k]);
        }
#pragma unroll
        for (int r = 0; r < 2; r++) {
          uint4* dst = reinterpret_cast<uint4*>(smem + KVW_OFF + (tid + r * 320) * 16);
          dst[0] = make_uint4(a[r][0].x, a[r][0].y, a[r][1].x, a[r][1].y);
          dst[640] = make_uint4(a[r][2].x, a[r][2].y, a[r][3].x, a[r][3].y);
          dst[1280] = make_uint4(a[r][4].x, a[r][4].y, 0u, 0u);
          dst[1920] = make_uint4(b[r][0].x, b[r][0].y, b[r][1].x, b[r][1].y);
          dst[2560] = make_uint4(b[r][2].x, b[r][2].y, b[r][3].x, b[r][3].y);
          dst[3200] = make_uint4(b[r][4].x, b[r][4].y, gw[r], 0u);
        }
      }
      fence_proxy_async();
      asm volatile("bar.sync 1, 512;" ::: "memory");
      PROF(0, 1);
      const int wg = warp >> 2, w4 = warp & 3, g = lane >> 2, t = lane & 3;
      for (int pass = 0; pass < 2; pass++) {
        float acc[24];
#pragma unroll
        for (int i = 0; i < 24; i++) acc[i] = 0.f;
        for (int kt = 0; kt < 10; kt++) {
          const int it = pass * 10 + kt, s = it % KV_STAGES;
          mbar_wait(smem_u32(&bar_full[s]), (it / KV_STAGES) & 1);
          const uint32_t alo = ((dbase + s * K1_A_BYTES + wg * 8192) >> 4) | (1u << 16);
          const uint32_t blo = ((dbase + KVW_OFF + kt * 1024) >> 4) | ((128u >> 4) << 16);
          fence_regs(acc);
          wg_fence();
#pragma unroll
          for (int k = 0; k < 4; k++) wgmma_ss_n48_tb(acc, mkd(alo + k * 2, DHI_SW128_K), mkd(blo + k * 16, 10240u >> 4));
          wg_commit();
          wg_wait<0>();
          if (it + KV_STAGES < 20) {
            const uint32_t eb = smem_u32(&bar_empty[s]);
            if (lane == 0) mbar_arrive(eb);
            if (tid == 0) { mbar_wait(eb, (it / KV_STAGES) & 1); load(it + KV_STAGES); }
            __syncwarp();
          }
        }
        fence_regs(acc);
        float kmax2 = 0.f, vmax = 0.f;
#pragma unroll
        for (int h = 0; h < 2; h++) {
          const int key = cb * 512 + pass * 256 + wg * 64 + w4 * 16 + g + h * 8;
          const int grp = key >> 7, kk = key & 127;
          const bool poly = (TMASK >> (kk >> 3)) & 1;
          uint8_t* gp = g_kvimg + grp * GRP_BYTES;
          const uint32_t k0 = pack_bf16(acc[2 * h], acc[2 * h + 1]);
          const uint32_t k1 = pack_bf16(acc[4 + 2 * h], acc[5 + 2 * h]);
          uint32_t k2 = pack_bf16(acc[8 + 2 * h], acc[9 + 2 * h]);
          float n2 = bf_lo(k0) * bf_lo(k0) + bf_hi(k0) * bf_hi(k0) + bf_lo(k1) * bf_lo(k1) + bf_hi(k1) * bf_hi(k1);
          if (t < 2) {
            n2 += bf_lo(k2) * bf_lo(k2) + bf_hi(k2) * bf_hi(k2);
            k2 = pack_bf16(bf_lo(k2) * 0.5f, bf_hi(k2) * 0.5f);
          } else if (t == 2) k2 = poly ? pack_bf16(24.f, 2.5f) : pack_bf16(0.5f, 0.f);
          else k2 = poly ? pack_bf16(0.5f, 0.f) : 0u;
          *reinterpret_cast<uint32_t*>(gp + kk * 16 + t * 4) = k0;
          *reinterpret_cast<uint32_t*>(gp + PLANE + kk * 16 + t * 4) = k1;
          *reinterpret_cast<uint32_t*>(gp + 2 * PLANE + kk * 16 + t * 4) = k2;
          n2 += __shfl_xor_sync(0xffffffffu, n2, 1);
          n2 += __shfl_xor_sync(0xffffffffu, n2, 2);
          kmax2 = (n2 > kmax2 || n2 != n2) ? n2 : kmax2;
          uint32_t v0 = pack_bf16(acc[12 + 2 * h], acc[13 + 2 * h]);
          uint32_t v1 = pack_bf16(acc[16 + 2 * h], acc[17 + 2 * h]);
          uint32_t v2 = pack_bf16(acc[20 + 2 * h], acc[21 + 2 * h]);
          float vm = fmaxf(fmaxf(fabsf(bf_lo(v0)), fabsf(bf_hi(v0))), fmaxf(fabsf(bf_lo(v1)), fabsf(bf_hi(v1))));
          if (t < 2) vm = fmaxf(vm, fmaxf(fabsf(bf_lo(v2)), fabsf(bf_hi(v2))));
          else if (t == 2) {
            const float z = acc[20 + 2 * h];
            g_gate[key] = 1.f / (1.f + __expf(-z));
            v2 = 0x00003F80u;
          } else v2 = 0u;
          vmax = fmaxf(vmax, vm);
          if (poly) { v0 ^= 0x80008000u; v1 ^= 0x80008000u; v2 ^= 0x80008000u; }
          uint8_t* vp = gp + 3 * PLANE + (kk >> 3) * 384 + (kk & 7) * 16 + t * 4;
          *reinterpret_cast<uint32_t*>(vp) = v0;
          *reinterpret_cast<uint32_t*>(vp + 128) = v1;
          *reinterpret_cast<uint32_t*>(vp + 256) = v2;
        }
#pragma unroll
        for (int o = 1; o < 32; o <<= 1) {
          const float a = __shfl_xor_sync(0xffffffffu, kmax2, o);
          kmax2 = (a > kmax2 || a != a) ? a : kmax2;
          vmax = fmaxf(vmax, __shfl_xor_sync(0xffffffffu, vmax, o));
        }
        if (lane == 0) { g_kmax2[cb * 32 + pass * 16 + warp] = kmax2; g_vmax[cb * 32 + pass * 16 + warp] = vmax; }
      }
    }
  }
  PROF(0, 3);
}

__device__ __forceinline__ uint32_t ex2_pair_poly(float u0, float u1, uint32_t one2) {
  const uint32_t W = __byte_perm(__float_as_uint(u0), __float_as_uint(u1), 0x6521);
  uint32_t v; asm("lop3.b32 %0, %1, 0x007F007F, %2, 0xEA;" : "=r"(v) : "r"(W), "r"(one2));
  uint32_t L, p;
  asm("fma.rn.bf16x2 %0, %1, %2, %3;" : "=r"(L) : "r"(v), "r"(0x1f961f96u), "r"(0x9fe39fe3u));
  asm("fma.rn.bf16x2 %0, %1, %1, %2;" : "=r"(p) : "r"(L), "r"(0x00f500f5u));
  return W + p;
}
template <int JOFF>
__device__ __forceinline__ void softmax_fast(const float (&S)[32], uint32_t (&P)[16], uint32_t one2) {
#pragma unroll
  for (int i = 0; i < 16; i++) {
    if ((TMASK >> (JOFF + i / 2)) & 1) P[i] = ex2_pair_poly(S[2 * i], S[2 * i + 1], one2);
    else P[i] = pack_bf16(ex2(S[2 * i]), ex2(S[2 * i + 1]));
  }
}
template <int JOFF>
__device__ __forceinline__ void softmax_slow(const float (&S)[32], uint32_t (&P)[16], float (&O)[12], float& m0, float& m1) {
  float a0 = m0, a1 = m1;
#pragma unroll
  for (int j = 0; j < 8; j++) {
    a0 = fmaxf(a0, fmaxf(S[4 * j], S[4 * j + 1]));
    a1 = fmaxf(a1, fmaxf(S[4 * j + 2], S[4 * j + 3]));
  }
  a0 = fmaxf(a0, __shfl_xor_sync(0xffffffffu, a0, 1)); a0 = fmaxf(a0, __shfl_xor_sync(0xffffffffu, a0, 2));
  a1 = fmaxf(a1, __shfl_xor_sync(0xffffffffu, a1, 1)); a1 = fmaxf(a1, __shfl_xor_sync(0xffffffffu, a1, 2));
  const float c0 = ex2(m0 - a0), c1 = ex2(m1 - a1);
  m0 = a0; m1 = a1;
#pragma unroll
  for (int j = 0; j < 3; j++) { O[4 * j] *= c0; O[4 * j + 1] *= c0; O[4 * j + 2] *= c1; O[4 * j + 3] *= c1; }
#pragma unroll
  for (int i = 0; i < 16; i++) {
    const float m = (i & 1) ? a1 : a0;
    const uint32_t p = pack_bf16(ex2(S[2 * i] - m), ex2(S[2 * i + 1] - m));
    P[i] = ((TMASK >> (JOFF + i / 2)) & 1) ? (p ^ 0x80008000u) : p;
  }
}
constexpr uint32_t DHI_KV = 128 >> 4;
__device__ __forceinline__ void issue_qk(float (&S)[32], const uint32_t (&q)[8], uint32_t base) {
  wgmma_rs_n64<0>(S, q[0], q[1], q[2], q[3], mkd(base + ((PLANE >> 4) << 16), DHI_KV));
  wgmma_rs_n64<1>(S, q[4], q[5], q[6], q[7], mkd(base + (2 * PLANE >> 4), DHI_KV));
}
__device__ __forceinline__ void issue_pv(float (&O)[12], const uint32_t (&P)[16], uint32_t vbase) {
#pragma unroll
  for (int kk = 0; kk < 4; kk++)
    wgmma_rs_n24_tb<1>(O, P[4 * kk], P[4 * kk + 1], P[4 * kk + 2], P[4 * kk + 3], mkd(vbase + kk * (768 >> 4), DHI_KV));
}

constexpr uint32_t VOFF = ((3 * PLANE) >> 4) + ((384u >> 4) << 16);
constexpr int KVR = 4;
constexpr int OFF_WA = KVR * GRP_BYTES;
constexpr int OFF_BR = OFF_WA + 10 * 10240;
constexpr int BR_STAGE = 8192 + 10240, BR_STAGES = 3;
constexpr int OFF_QS = OFF_BR + BR_STAGES * BR_STAGE;
constexpr int OFF_BAR = OFF_QS + 512 * 6 * 4;
constexpr int K2_SMEM = OFF_BAR + 256 + 1024;
constexpr int BAR_KV = 0, BAR_WA = 4, BAR_BR = 5, BAR_TA = 8, BAR_TE = 14, CNT_KV = 18;
constexpr int NSTEP = 2 * NGRP;

__device__ __forceinline__ void kv_load(uint32_t sbase, int step) {
  const uint32_t bar = sbase + OFF_BAR + (BAR_KV + (step & (KVR - 1))) * 8;
  mbar_expect_tx(bar, GRP_BYTES);
  bulk_g2s(sbase + (step & (KVR - 1)) * GRP_BYTES, g_kvimg + (step & (NGRP - 1)) * GRP_BYTES, GRP_BYTES, bar);
}
__device__ __forceinline__ void kv_release(uint32_t sbase, int step, bool elected) {
  if (elected && step + KVR < NSTEP) {
    uint32_t old;
    asm volatile("atom.acq_rel.cta.shared::cta.inc.u32 %0, [%1], 3;" : "=r"(old) : "r"(sbase + OFF_BAR + CNT_KV * 8 + (step & (KVR - 1)) * 4) : "memory");
    if (old == 3u) kv_load(sbase, step + KVR);
  }
  __syncwarp();
}
__device__ __forceinline__ void kv_wait(uint32_t sbase, int step) {
  mbar_wait(sbase + OFF_BAR + (BAR_KV + (step & (KVR - 1))) * 8, (step / KVR) & 1);
}

__device__ __forceinline__ uint32_t kv_release_begin(uint32_t sbase, int slot, bool doit) {
  uint32_t old = 0;
  if (doit) asm volatile("atom.acq_rel.cta.shared::cta.inc.u32 %0, [%1], 3;" : "=r"(old) : "r"(sbase + OFF_BAR + CNT_KV * 8 + slot * 4) : "memory");
  return old;
}
__device__ __forceinline__ void attn_tile_fast(const uint32_t (&q)[8], float (&O)[12], uint32_t sbase, int step0, bool elected, uint32_t one2) {
  float S[32]; uint32_t P[16];
#pragma unroll
  for (int i = 0; i < 32; i++) S[i] = 0.f;
  const uint32_t kb0 = (sbase & 0x3FFFFu) >> 4;
  kv_wait(sbase, step0);
  fence_regs(S); fence_regs(O);
  wg_fence();
  issue_qk(S, q, kb0);
  wg_commit();
#pragma unroll 1
  for (int step4 = step0; step4 < step0 + NGRP; step4 += KVR) {
#pragma unroll
    for (int j = 0; j < KVR; j++) {
      const int step = step4 + j;
      const uint32_t kb = kb0 + j * (GRP_BYTES >> 4);
      const uint32_t knext = kb0 + ((j + 1) & (KVR - 1)) * (GRP_BYTES >> 4);
      wg_wait<0>();
      fence_regs(S); fence_regs(P); fence_regs(O);
      const uint32_t old = kv_release_begin(sbase, (j + KVR - 1) & (KVR - 1), elected && step > step0 && step - 1 + KVR < NSTEP);
      softmax_fast<0>(S, P, one2);
      fence_regs(S); fence_regs(P); fence_regs(O);
      wg_fence();
      issue_qk(S, q, kb + 64);
      issue_pv(O, P, kb + VOFF);
      wg_commit();
      if (old == 3u) kv_load(sbase, step - 1 + KVR);
      if (step + 1 < NSTEP) mbar_wait(sbase + OFF_BAR + (BAR_KV + ((j + 1) & (KVR - 1))) * 8, ((step + 1) / KVR) & 1);
      wg_wait<0>();
      fence_regs(S); fence_regs(P); fence_regs(O);
      softmax_fast<8>(S, P, one2);
      fence_regs(S); fence_regs(P); fence_regs(O);
      wg_fence();
      issue_qk(S, q, knext);
      issue_pv(O, P, kb + VOFF + 4 * (768 >> 4));
      wg_commit();
    }
  }
  wg_wait<0>();
  fence_regs(O); fence_regs(S);
  kv_release(sbase, step0 + NGRP - 1, elected);
}
template <int H>
__device__ __forceinline__ void slow_step(const uint32_t (&q)[8], float (&O)[12], uint32_t kb, float& m0, float& m1) {
  float S[32]; uint32_t P[16];
#pragma unroll
  for (int i = 0; i < 32; i++) S[i] = 0.f;
  fence_regs(S);
  wg_fence();
  issue_qk(S, q, kb + 64 * H);
  wg_commit();
  wg_wait<0>();
  fence_regs(S);
  softmax_slow<8 * H>(S, P, O, m0, m1);
  fence_regs(P); fence_regs(O);
  wg_fence();
  issue_pv(O, P, kb + VOFF + H * 4 * (768 >> 4));
  wg_commit();
  wg_wait<0>();
  fence_regs(O); fence_regs(P);
}
__device__ __forceinline__ void attn_tile_slow(const uint32_t (&q)[8], float (&O)[12], uint32_t sbase, int step0, bool elected) {
  float m0 = -INFINITY, m1 = -INFINITY;
#pragma unroll 1
  for (int grp = 0; grp < NGRP; grp++) {
    kv_wait(sbase, step0 + grp);
    const uint32_t kb = ((sbase & 0x3FFFFu) >> 4) + (grp & (KVR - 1)) * (GRP_BYTES >> 4);
    slow_step<0>(q, O, kb, m0, m1);
    slow_step<1>(q, O, kb, m0, m1);
    kv_release(sbase, step0 + grp, elected);
  }
}

__device__ __forceinline__ void local_attn_pair(int token, int lane) {
  const __nv_bfloat16* base = g_qkv + (size_t)token * (3 * D_MODEL) + lane * DH;
  float f[20];
  {
    const uint2* p = reinterpret_cast<const uint2*>(base);
#pragma unroll
    for (int i = 0; i < 5; i++) { const uint2 v = p[i]; f[4 * i] = bf_lo(v.x); f[4 * i + 1] = bf_hi(v.x); f[4 * i + 2] = bf_lo(v.y); f[4 * i + 3] = bf_hi(v.y); }
  }
  float sc[8];
  float mx = -INFINITY;
#pragma unroll
  for (int w = 0; w < 8; w++) {
    const bool ok = token - 2 * w >= 0;
    const uint2* p = reinterpret_cast<const uint2*>(base + D_MODEL - (ok ? 2 * w : 0) * (3 * D_MODEL));
    float s = 0.f;
#pragma unroll
    for (int i = 0; i < 5; i++) {
      const uint2 v = p[i];
      s = fmaf(f[4 * i], bf_lo(v.x), s); s = fmaf(f[4 * i + 1], bf_hi(v.x), s);
      s = fmaf(f[4 * i + 2], bf_lo(v.y), s); s = fmaf(f[4 * i + 3], bf_hi(v.y), s);
    }
    s *= 0.22360679774997896f * 1.4426950408889634f;
    sc[w] = ok ? s : -1e9f * 1.4426950408889634f;
    mx = fmaxf(mx, sc[w]);
  }
  float l = 0.f;
#pragma unroll
  for (int w = 0; w < 8; w++) { sc[w] = ex2(sc[w] - mx); l += sc[w]; }
#pragma unroll
  for (int i = 0; i < 20; i++) f[i] = 0.f;
#pragma unroll
  for (int w = 0; w < 8; w++) {
    const bool ok = token - 2 * w >= 0;
    const uint2* p = reinterpret_cast<const uint2*>(base + 2 * D_MODEL - (ok ? 2 * w : token) * (3 * D_MODEL));
#pragma unroll
    for (int i = 0; i < 5; i++) {
      const uint2 v = p[i];
      f[4 * i] = fmaf(sc[w], bf_lo(v.x), f[4 * i]); f[4 * i + 1] = fmaf(sc[w], bf_hi(v.x), f[4 * i + 1]);
      f[4 * i + 2] = fmaf(sc[w], bf_lo(v.y), f[4 * i + 2]); f[4 * i + 3] = fmaf(sc[w], bf_hi(v.y), f[4 * i + 3]);
    }
  }
  const float r = (1.f - g_gate[token]) / l;
  uint2* dst = reinterpret_cast<uint2*>(g_a2 + (size_t)token * (2 * D_MODEL) + D_MODEL + lane * DH);
#pragma unroll
  for (int i = 0; i < 5; i++) dst[i] = make_uint2(pack_bf16(f[4 * i] * r, f[4 * i + 1] * r), pack_bf16(f[4 * i + 2] * r, f[4 * i + 3] * r));
}

__device__ __forceinline__ void signal_done(unsigned int* flag, int wg, int tid) {
  asm volatile("bar.sync %0, 128;" :: "r"(wg + 1) : "memory");
  if ((tid & 127) == 0) asm volatile("red.release.gpu.global.add.u32 [%0], 1;" :: "l"(flag) : "memory");
}
__device__ __forceinline__ void wait_flags8(const unsigned int* f, unsigned int target) {
  for (int spin = 0; spin < (1 << 26); spin++) {
    unsigned int a, b, c, d, e, g, h, i;
    asm volatile("ld.volatile.global.v4.u32 {%0, %1, %2, %3}, [%4];" : "=r"(a), "=r"(b), "=r"(c), "=r"(d) : "l"(f) : "memory");
    asm volatile("ld.volatile.global.v4.u32 {%0, %1, %2, %3}, [%4];" : "=r"(e), "=r"(g), "=r"(h), "=r"(i) : "l"(f + 4) : "memory");
    if (min(min(min(a, b), min(c, d)), min(min(e, g), min(h, i))) >= target) break;
  }
  asm volatile("fence.acq_rel.gpu;" ::: "memory");
  asm volatile("fence.proxy.async;" ::: "memory");
}
__device__ __forceinline__ uint32_t ta_slot(int i) { return i < 3 ? i * 16384 : OFF_BR + (i - 3) * 16384; }

__global__ void __launch_bounds__(640, 1)
attn_kernel(const __grid_constant__ CUtensorMap tmA2, const __grid_constant__ CUtensorMap tmWoA, const __grid_constant__ CUtensorMap tmWoB,
            __nv_bfloat16* __restrict__ out, uint32_t one2) {
  extern __shared__ uint8_t smem_raw[];
  uint8_t* smem = reinterpret_cast<uint8_t*>((reinterpret_cast<uintptr_t>(smem_raw) + 1023) & ~(uintptr_t)1023);
  const uint32_t sbase = smem_u32(smem);
  const uint32_t dbase = sbase & 0x3FFFFu;
  const uint32_t bars = sbase + OFF_BAR;
  const int tid = threadIdx.x, wg = tid >> 7, warp = (tid >> 5) & 3, lane = tid & 31, g = lane >> 2, t = lane & 3;
  const int mb = blockIdx.x >> 3, nb = blockIdx.x & 7;
  if (tid == 0) {
    for (int i = 0; i < BAR_TE; i++) mbar_init(bars + i * 8, 1);
    for (int i = BAR_TE; i < BAR_TE + 4; i++) mbar_init(bars + i * 8, 8);
    for (int i = 0; i < 4; i++) *reinterpret_cast<uint32_t*>(smem + OFF_BAR + CNT_KV * 8 + i * 4) = 0u;
    fence_mbar_init();
  }
  __syncthreads();
  if (wg == 4) {
    if (tid == 512) {
      mbar_expect_tx(bars + BAR_WA * 8, 10 * 10240);
      for (int kt = 0; kt < 10; kt++) tma_3d(sbase + OFF_WA + kt * 10240, &tmWoA, 0, kt * 64, nb * 5, bars + BAR_WA * 8);
    }
    pdl_wait();
    if (tid == 512) for (int j = 0; j < KVR; j++) kv_load(sbase, j);
    __syncwarp();
#pragma unroll 1
    for (int i = 0; i < 4; i++) local_attn_pair(blockIdx.x * 16 + i * 4 + warp, lane);
    if (tid == 512) PROF2(0, 2);
    signal_done(&g_doneL[blockIdx.x], wg, tid);
    auto br_load = [&](int it, int st) {
      const uint32_t fb = bars + (BAR_BR + st) * 8;
      const uint32_t dst = sbase + OFF_BR + st * BR_STAGE;
      const int kc = (it >= 10 ? it - 10 : it) * 64;
      mbar_expect_tx(fb, BR_STAGE);
      tma_2d(dst, &tmA2, D_MODEL + kc, (blockIdx.x >> 3) * 128 + (it >= 10 ? 64 : 0), fb);
      tma_3d(dst + 8192, &tmWoB, 0, kc, (blockIdx.x & 7) * 5, fb);
    };
    if (tid == 512) {
      wait_flags8(&g_doneL[mb * 8], 1u);
      for (int it = 0; it < BR_STAGES; it++) br_load(it, it);
    }
    __syncwarp();
    {
      int st = 0, ph = 0;
      float acc[40];
#pragma unroll 1
      for (int it = 0; it < 20; it++) {
        if (it == 0 || it == 10) {
#pragma unroll
          for (int i = 0; i < 40; i++) acc[i] = 0.f;
        }
        mbar_wait(bars + (BAR_BR + st) * 8, ph);
        const uint32_t alo = ((dbase + OFF_BR + st * BR_STAGE) >> 4);
        fence_regs(acc);
        wg_fence();
#pragma unroll
        for (int k = 0; k < 4; k++)
          wgmma_ss_n80_tb(acc, mkd(alo + (k * 2 + (1u << 16)), DHI_SW128_K), mkd(alo + (512 + k * 32 + ((2048u >> 4) << 16)), DHI_SW32_MN));
        wg_commit();
        wg_wait<0>();
        fence_regs(acc);
        asm volatile("bar.sync 5, 128;" ::: "memory");
        if (threadIdx.x == 512 && it + BR_STAGES < 20) br_load(it + BR_STAGES, st);
        __syncwarp();
        if (it == 9 || it == 19) {
          float* pp = g_part + (size_t)(blockIdx.x * 2 + (it == 19)) * (40 * 128) + (threadIdx.x & 127);
#pragma unroll
          for (int i = 0; i < 40; i++) pp[i * 128] = acc[i];
        }
        if (++st == BR_STAGES) { st = 0; ph ^= 1; }
      }
    }
    if (tid == 512) PROF2(1, 0);
    asm volatile("bar.arrive 6, 384;" ::: "memory");
    if (tid == 512) {
      wait_flags8(&g_done[mb * 8], 4u);
      PROF2(2, 0);
      for (int kt = 0; kt < 10; kt++) {
        const int sl = kt % 6;
        if (kt >= 6) mbar_wait(bars + (BAR_TE + kt - 6) * 8, 0);
        const uint32_t fb = bars + (BAR_TA + sl) * 8;
        mbar_expect_tx(fb, 16384);
        tma_2d(sbase + ta_slot(sl), &tmA2, kt * 64, mb * 128, fb);
        tma_2d(sbase + ta_slot(sl) + 8192, &tmA2, kt * 64, mb * 128 + 64, fb);
      }
    }
  } else {
    pdl_wait();
    PROF(1, 1);
    const bool elected = (tid & 127) == 0;
    uint32_t q[8];
    uint32_t* qstash = reinterpret_cast<uint32_t*>(smem + OFF_QS) + tid;
    const int rowA = (blockIdx.x * 8 + wg) * 64 + warp * 16 + g;
    {
      const uint32_t* r0 = reinterpret_cast<const uint32_t*>(g_q + (size_t)rowA * DH);
      const uint32_t* r1 = r0 + 8 * (DH / 2);
      const uint32_t* s0 = r0 + 256 * (DH / 2);
      const uint32_t* s1 = s0 + 8 * (DH / 2);
      q[0] = r0[t]; q[1] = r1[t]; q[2] = r0[t + 4]; q[3] = r1[t + 4];
      q[4] = t < 2 ? r0[8 + t] : 0u;
      q[5] = t < 2 ? r1[8 + t] : 0u;
      qstash[0] = s0[t]; qstash[512] = s1[t]; qstash[1024] = s0[t + 4]; qstash[1536] = s1[t + 4];
      qstash[2048] = t < 2 ? s0[8 + t] : 0u;
      qstash[2560] = t < 2 ? s1[8 + t] : 0u;
    }
    float kmax2 = 0.f, vmax = 0.f;
#pragma unroll
    for (int i = 0; i < 4; i++) {
      const float a = g_kmax2[lane + 32 * i];
      kmax2 = (a > kmax2 || a != a) ? a : kmax2;
      vmax = fmaxf(vmax, g_vmax[lane + 32 * i]);
    }
#pragma unroll
    for (int o = 1; o < 32; o <<= 1) {
      const float a = __shfl_xor_sync(0xffffffffu, kmax2, o);
      kmax2 = (a > kmax2 || a != a) ? a : kmax2;
      vmax = fmaxf(vmax, __shfl_xor_sync(0xffffffffu, vmax, o));
    }
    const float qlim = (vmax >= 0.00390625f && vmax <= 256.f) ? 9025.f / kmax2 : -1.f;
    PROF(1, 2);
#pragma unroll 1
    for (int it = 0; it < 2; it++) {
      const int row0 = rowA + it * 256;
      if (it == 1) {
#pragma unroll
        for (int i = 0; i < 6; i++) q[i] = qstash[512 * i];
      }
      float n0 = bf_lo(q[0]) * bf_lo(q[0]) + bf_hi(q[0]) * bf_hi(q[0]) + bf_lo(q[2]) * bf_lo(q[2]) + bf_hi(q[2]) * bf_hi(q[2]) +
                 bf_lo(q[4]) * bf_lo(q[4]) + bf_hi(q[4]) * bf_hi(q[4]);
      float n1 = bf_lo(q[1]) * bf_lo(q[1]) + bf_hi(q[1]) * bf_hi(q[1]) + bf_lo(q[3]) * bf_lo(q[3]) + bf_hi(q[3]) * bf_hi(q[3]) +
                 bf_lo(q[5]) * bf_lo(q[5]) + bf_hi(q[5]) * bf_hi(q[5]);
      n0 += __shfl_xor_sync(0xffffffffu, n0, 1); n0 += __shfl_xor_sync(0xffffffffu, n0, 2);
      n1 += __shfl_xor_sync(0xffffffffu, n1, 1); n1 += __shfl_xor_sync(0xffffffffu, n1, 2);
      const bool safe = (n0 <= qlim) && (n1 <= qlim);
      uint32_t unsafe_any;
      asm volatile("{\n.reg .pred p, r;\nsetp.eq.u32 p, %1, 0;\nbarrier.cta.red.or.pred r, %2, 128, p;\nselp.u32 %0, 1, 0, r;\n}\n"
                   : "=r"(unsafe_any) : "r"((uint32_t)safe), "r"(wg + 1) : "memory");
      float O[12];
#pragma unroll
      for (int i = 0; i < 12; i++) O[i] = 0.f;
      if (!unsafe_any && t >= 2) { q[4] = q[5] = (t == 2) ? 0x3F804100u : 0x00003B80u; }
      q[6] = q[4]; q[7] = q[5];
      fence_regs(q);
      if (!unsafe_any) attn_tile_fast(q, O, sbase, it * NGRP, elected, one2);
      else attn_tile_slow(q, O, sbase, it * NGRP, elected);
      const float l0 = __shfl_sync(0xffffffffu, O[8], (lane & ~3) | 2);
      const float l1 = __shfl_sync(0xffffffffu, O[10], (lane & ~3) | 2);
      const int tok = row0 >> 5;
      const float gt = g_gate[tok];
      const float i0 = gt / l0, i1 = gt / l1;
      uint32_t* o0 = reinterpret_cast<uint32_t*>(g_a2 + (size_t)tok * (2 * D_MODEL) + (row0 & 31) * DH);
      uint32_t* o1 = o0 + 8 * (DH / 2);
      o0[t] = pack_bf16(O[0] * i0, O[1] * i0); o1[t] = pack_bf16(O[2] * i1, O[3] * i1);
      o0[t + 4] = pack_bf16(O[4] * i0, O[5] * i0); o1[t + 4] = pack_bf16(O[6] * i1, O[7] * i1);
      if (t < 2) { o0[t + 8] = pack_bf16(O[8] * i0, O[9] * i0); o1[t + 8] = pack_bf16(O[10] * i1, O[11] * i1); }
    }
    signal_done(&g_done[blockIdx.x], wg, tid);
    PROF(1, 3);
    if (wg < 2) {
      float acc[40];
      asm volatile("bar.sync 6, 384;" ::: "memory");
      {
        const float* pp = g_part + (size_t)(blockIdx.x * 2 + wg) * (40 * 128) + (tid & 127);
#pragma unroll
        for (int i = 0; i < 40; i++) acc[i] = pp[i * 128];
      }
      mbar_wait(bars + BAR_WA * 8, 0);
#pragma unroll 1
      for (int kt = 0; kt < 10; kt++) {
        const int sl = kt % 6;
        mbar_wait(bars + (BAR_TA + sl) * 8, kt / 6);
        if (kt == 0) PROF(2, 1);
        const uint32_t alo = ((dbase + ta_slot(sl) + wg * 8192) >> 4) | (1u << 16);
        const uint32_t blo = ((dbase + OFF_WA + kt * 10240) >> 4) | ((2048u >> 4) << 16);
        fence_regs(acc);
        wg_fence();
#pragma unroll
        for (int k = 0; k < 4; k++) wgmma_ss_n80_tb(acc, mkd(alo + k * 2, DHI_SW128_K), mkd(blo + k * 32, DHI_SW32_MN));
        wg_commit();
        if (kt < 4) {
          wg_wait<0>();
          if (lane == 0) mbar_arrive(bars + (BAR_TE + kt) * 8);
        }
      }
      wg_wait<0>();
      fence_regs(acc);
      PROF(2, 2);
      asm volatile("bar.sync %0, 128;" :: "r"(wg + 1) : "memory");
      const uint32_t so = ta_slot(warp) + wg * 8192;
      const int row0 = mb * 128 + wg * 64 + warp * 16;
      store_tile_bf16<80>(acc, 1.0f, sbase + so, smem + so, out + (size_t)row0 * D_MODEL + nb * 80, D_MODEL, lane);
      PROF(2, 3);
    }
  }
}

typedef CUresult (*EncodeFn)(CUtensorMap*, CUtensorMapDataType, cuuint32_t, void*, const cuuint64_t*, const cuuint64_t*,
                             const cuuint32_t*, const cuuint32_t*, CUtensorMapInterleave, CUtensorMapSwizzle,
                             CUtensorMapL2promotion, CUtensorMapFloatOOBfill);

void make_map(EncodeFn fn, CUtensorMap* tm, const void* ptr, int rank, const cuuint64_t* dims, const cuuint64_t* strides,
              const cuuint32_t* box, CUtensorMapSwizzle sw) {
  const cuuint32_t es[3] = {1, 1, 1};
  fn(tm, CU_TENSOR_MAP_DATA_TYPE_BFLOAT16, rank, const_cast<void*>(ptr), dims, strides, box, es, CU_TENSOR_MAP_INTERLEAVE_NONE, sw,
     CU_TENSOR_MAP_L2_PROMOTION_L2_256B, CU_TENSOR_MAP_FLOAT_OOB_FILL_NONE);
}
void map_a(EncodeFn fn, CUtensorMap* tm, const void* p, int rows, int cols, int box_rows) {
  const cuuint64_t dims[2] = {(cuuint64_t)cols, (cuuint64_t)rows};
  const cuuint64_t str[1] = {(cuuint64_t)cols * 2};
  const cuuint32_t box[2] = {64, (cuuint32_t)box_rows};
  make_map(fn, tm, p, 2, dims, str, box, CU_TENSOR_MAP_SWIZZLE_128B);
}
void map_w(EncodeFn fn, CUtensorMap* tm, const void* p, int K, int N, int atom, CUtensorMapSwizzle sw) {
  const cuuint64_t dims[3] = {(cuuint64_t)atom, (cuuint64_t)K, (cuuint64_t)(N / atom)};
  const cuuint64_t str[2] = {(cuuint64_t)N * 2, (cuuint64_t)atom * 2};
  const cuuint32_t box[3] = {(cuuint32_t)atom, 64, 5};
  make_map(fn, tm, p, 3, dims, str, box, sw);
}

template <typename... KArgs, typename... Args>
void launch(void (*kern)(KArgs...), int grid, int block, int smem, bool pdl, Args... args) {
  cudaLaunchConfig_t cfg = {};
  cfg.gridDim = dim3(grid); cfg.blockDim = dim3(block); cfg.dynamicSmemBytes = smem; cfg.stream = cudaStreamPerThread;
  cudaLaunchAttribute at[1];
  at[0].id = cudaLaunchAttributeProgrammaticStreamSerialization;
  at[0].val.programmaticStreamSerializationAllowed = 1;
  cfg.attrs = at; cfg.numAttrs = pdl ? 1 : 0;
  cudaLaunchKernelEx(&cfg, kern, KArgs(args)...);
}

}

extern "C" void kernel_launch(void* const* d_in, const int* in_sizes, int n_in, void* d_out, int out_size) {
  (void)in_sizes; (void)n_in; (void)out_size;
  const __nv_bfloat16* x = (const __nv_bfloat16*)d_in[0];
  const __nv_bfloat16* wq = (const __nv_bfloat16*)d_in[1];
  const __nv_bfloat16* wk = (const __nv_bfloat16*)d_in[2];
  const __nv_bfloat16* wv = (const __nv_bfloat16*)d_in[3];
  const __nv_bfloat16* woA = (const __nv_bfloat16*)d_in[4];
  const __nv_bfloat16* wqkv = (const __nv_bfloat16*)d_in[6];
  const __nv_bfloat16* woB = (const __nv_bfloat16*)d_in[7];
  const __nv_bfloat16* gate_w = (const __nv_bfloat16*)d_in[8];

  static EncodeFn enc = nullptr;
  static void* a2_ptr = nullptr;
  if (!enc) {
    void* fp = nullptr;
    cudaDriverEntryPointQueryResult qr;
    cudaGetDriverEntryPoint("cuTensorMapEncodeTiled", &fp, cudaEnableDefault, &qr);
    enc = (EncodeFn)fp;
    cudaGetSymbolAddress(&a2_ptr, g_a2);
    cudaFuncSetAttribute(proj_kernel, cudaFuncAttributeMaxDynamicSharedMemorySize, K1_SMEM);
    cudaFuncSetAttribute(attn_kernel, cudaFuncAttributeMaxDynamicSharedMemorySize, K2_SMEM);
  }
  CUtensorMap tmX, tmWq, tmWqkv, tmA2, tmWoA, tmWoB;
  map_a(enc, &tmX, x, S_LEN, D_MODEL, 256);
  map_w(enc, &tmWq, wq, D_MODEL, D_MODEL, 32, CU_TENSOR_MAP_SWIZZLE_64B);
  map_w(enc, &tmWqkv, wqkv, D_MODEL, 3 * D_MODEL, 32, CU_TENSOR_MAP_SWIZZLE_64B);
  map_a(enc, &tmA2, a2_ptr, S_LEN, 2 * D_MODEL, 64);
  map_w(enc, &tmWoA, woA, D_MODEL, D_MODEL, 16, CU_TENSOR_MAP_SWIZZLE_32B);
  map_w(enc, &tmWoB, woB, D_MODEL, D_MODEL, 16, CU_TENSOR_MAP_SWIZZLE_32B);

  launch(proj_kernel, 132, 512, K1_SMEM, false, tmX, tmWq, tmWqkv, wk, wv, gate_w);
  launch(attn_kernel, 128, 640, K2_SMEM, true, tmA2, tmWoA, tmWoB, (__nv_bfloat16*)d_out, 0x3F803F80u);
}
```

```cpp
#include <cuda_runtime.h>
#include <cuda_bf16.h>
#include <cuda.h>
#include <stdint.h>

namespace {

constexpr int S_LEN = 2048, D_MODEL = 640, DH = 20;

constexpr int GRP = 128;
constexpr int PLANE = GRP * 16;
constexpr int GRP_BYTES = GRP * 16 * 6;
constexpr int NGRP = S_LEN / GRP;
constexpr uint32_t TMASK = 0x6DB6u;

__device__ __align__(1024) __nv_bfloat16 g_q[S_LEN * D_MODEL];
__device__ __align__(1024) __nv_bfloat16 g_qkv[S_LEN * 3 * D_MODEL];
__device__ __align__(1024) __nv_bfloat16 g_a2[S_LEN * 2 * D_MODEL];
__device__ __align__(1024) uint8_t g_kvimg[NGRP * GRP_BYTES];
__device__ float g_gate[S_LEN];
__device__ float g_kmax2[128];
__device__ float g_vmax[128];
__device__ __align__(64) unsigned int g_doneP[128];
__device__ __align__(32) unsigned int g_doneL[128];
__device__ float g_part[128 * 2 * 40 * 128];
__device__ __align__(32) unsigned int g_done[128];

#define PROF(k, slot)
#define PROF2(k, slot)
__device__ __forceinline__ uint32_t smem_u32(const void* p) { return (uint32_t)__cvta_generic_to_shared(p); }
__device__ __forceinline__ uint64_t mkd(uint32_t lo, uint32_t hi) {
  uint64_t d; asm("mov.b64 %0, {%1, %2};" : "=l"(d) : "r"(lo), "r"(hi)); return d;
}
__device__ __forceinline__ void wg_fence() { asm volatile("wgmma.fence.sync.aligned;" ::: "memory"); }
__device__ __forceinline__ void wg_commit() { asm volatile("wgmma.commit_group.sync.aligned;" ::: "memory"); }
template <int N> __device__ __forceinline__ void wg_wait() { asm volatile("wgmma.wait_group.sync.aligned %0;" :: "n"(N) : "memory"); }
template <int N> __device__ __forceinline__ void fence_regs(float (&d)[N]) {
#pragma unroll
  for (int i = 0; i < N; i++) asm volatile("" : "+f"(d[i]) :: "memory");
}
template <int N> __device__ __forceinline__ void fence_regs(uint32_t (&d)[N]) {
#pragma unroll
  for (int i = 0; i < N; i++) asm volatile("" : "+r"(d[i]) :: "memory");
}
__device__ __forceinline__ void mbar_init(uint32_t bar, uint32_t cnt) { asm volatile("mbarrier.init.shared::cta.b64 [%0], %1;" :: "r"(bar), "r"(cnt)); }
__device__ __forceinline__ void mbar_expect_tx(uint32_t bar, uint32_t bytes) {
  asm volatile("mbarrier.arrive.expect_tx.shared::cta.b64 _, [%0], %1;" :: "r"(bar), "r"(bytes) : "memory");
}
__device__ __forceinline__ void mbar_arrive(uint32_t bar) { asm volatile("mbarrier.arrive.shared::cta.b64 _, [%0];" :: "r"(bar) : "memory"); }
__device__ __forceinline__ void mbar_wait(uint32_t bar, uint32_t parity) {
  asm volatile("{\n.reg .pred p;\nWAIT_%=:\nmbarrier.try_wait.parity.shared::cta.b64 p, [%0], %1;\n@p bra DONE_%=;\nbra WAIT_%=;\nDONE_%=:\n}\n"
               :: "r"(bar), "r"(parity) : "memory");
}
__device__ __forceinline__ void fence_mbar_init() { asm volatile("fence.mbarrier_init.release.cluster;" ::: "memory"); }
__device__ __forceinline__ void fence_proxy_async() { asm volatile("fence.proxy.async.shared::cta;" ::: "memory"); }
__device__ __forceinline__ void bulk_g2s(uint32_t dst, const void* src, uint32_t bytes, uint32_t bar) {
  asm volatile("cp.async.bulk.shared::cluster.global.mbarrier::complete_tx::bytes [%0], [%1], %2, [%3];"
               :: "r"(dst), "l"(src), "r"(bytes), "r"(bar) : "memory");
}
__device__ __forceinline__ void tma_2d(uint32_t dst, const CUtensorMap* tm, int c0, int c1, uint32_t bar) {
  asm volatile("cp.async.bulk.tensor.2d.shared::cluster.global.mbarrier::complete_tx::bytes [%0], [%1, {%3, %4}], [%2];"
               :: "r"(dst), "l"((uint64_t)tm), "r"(bar), "r"(c0), "r"(c1) : "memory");
}
__device__ __forceinline__ void tma_3d(uint32_t dst, const CUtensorMap* tm, int c0, int c1, int c2, uint32_t bar) {
  asm volatile("cp.async.bulk.tensor.3d.shared::cluster.global.mbarrier::complete_tx::bytes [%0], [%1, {%3, %4, %5}], [%2];"
               :: "r"(dst), "l"((uint64_t)tm), "r"(bar), "r"(c0), "r"(c1), "r"(c2) : "memory");
}
__device__ __forceinline__ void pdl_wait() { asm volatile("griddepcontrol.wait;" ::: "memory"); }
__device__ __forceinline__ void pdl_launch() { asm volatile("griddepcontrol.launch_dependents;" ::: "memory"); }
__device__ __forceinline__ float ex2(float x) { float y; asm("ex2.approx.ftz.f32 %0, %1;" : "=f"(y) : "f"(x)); return y; }
__device__ __forceinline__ uint32_t pack_bf16(float lo, float hi) {
  uint32_t r; asm("cvt.rn.bf16x2.f32 %0, %1, %2;" : "=r"(r) : "f"(hi), "f"(lo)); return r;
}
__device__ __forceinline__ float bf_lo(uint32_t x) { return __uint_as_float(x << 16); }
__device__ __forceinline__ float bf_hi(uint32_t x) { return __uint_as_float(x & 0xffff0000u); }
__device__ __forceinline__ void stsm4(uint32_t addr, uint32_t r0, uint32_t r1, uint32_t r2, uint32_t r3) {
  asm volatile("stmatrix.sync.aligned.m8n8.x4.shared.b16 [%0], {%1, %2, %3, %4};" :: "r"(addr), "r"(r0), "r"(r1), "r"(r2), "r"(r3) : "memory");
}

__device__ __forceinline__ void wgmma_ss_n160_tb(float (&d)[80], uint64_t descA, uint64_t descB) {
  asm volatile("wgmma.mma_async.sync.aligned.m64n160k16.f32.bf16.bf16 {%0, %1, %2, %3, %4, %5, %6, %7, %8, %9, %10, %11, %12, %13, %14, %15, %16, %17, %18, %19, %20, %21, %22, %23, %24, %25, %26, %27, %28, %29, %30, %31, %32, %33, %34, %35, %36, %37, %38, %39, %40, %41, %42, %43, %44, %45, %46, %47, %48, %49, %50, %51, %52, %53, %54, %55, %56, %57, %58, %59, %60, %61, %62, %63, %64, %65, %66, %67, %68, %69, %70, %71, %72, %73, %74, %75, %76, %77, %78, %79}, %80, %81, 1, 1, 1, 0, 1;\n"
    : "+f"(d[0]), "+f"(d[1]), "+f"(d[2]), "+f"(d[3]), "+f"(d[4]), "+f"(d[5]), "+f"(d[6]), "+f"(d[7]), "+f"(d[8]), "+f"(d[9]), "+f"(d[10]), "+f"(d[11]), "+f"(d[12]), "+f"(d[13]), "+f"(d[14]), "+f"(d[15]), "+f"(d[16]), "+f"(d[17]), "+f"(d[18]), "+f"(d[19]), "+f"(d[20]), "+f"(d[21]), "+f"(d[22]), "+f"(d[23]), "+f"(d[24]), "+f"(d[25]), "+f"(d[26]), "+f"(d[27]), "+f"(d[28]), "+f"(d[29]), "+f"(d[30]), "+f"(d[31]), "+f"(d[32]), "+f"(d[33]), "+f"(d[34]), "+f"(d[35]), "+f"(d[36]), "+f"(d[37]), "+f"(d[38]), "+f"(d[39]), "+f"(d[40]), "+f"(d[41]), "+f"(d[42]), "+f"(d[43]), "+f"(d[44]), "+f"(d[45]), "+f"(d[46]), "+f"(d[47]), "+f"(d[48]), "+f"(d[49]), "+f"(d[50]), "+f"(d[51]), "+f"(d[52]), "+f"(d[53]), "+f"(d[54]), "+f"(d[55]), "+f"(d[56]), "+f"(d[57]), "+f"(d[58]), "+f"(d[59]), "+f"(d[60]), "+f"(d[61]), "+f"(d[62]), "+f"(d[63]), "+f"(d[64]), "+f"(d[65]), "+f"(d[66]), "+f"(d[67]), "+f"(d[68]), "+f"(d[69]), "+f"(d[70]), "+f"(d[71]), "+f"(d[72]), "+f"(d[73]), "+f"(d[74]), "+f"(d[75]), "+f"(d[76]), "+f"(d[77]), "+f"(d[78]), "+f"(d[79])
    : "l"(descA), "l"(descB));
}
__device__ __forceinline__ void wgmma_ss_n48_tb(float (&d)[24], uint64_t descA, uint64_t descB) {
  asm volatile("wgmma.mma_async.sync.aligned.m64n48k16.f32.bf16.bf16 {%0, %1, %2, %3, %4, %5, %6, %7, %8, %9, %10, %11, %12, %13, %14, %15, %16, %17, %18, %19, %20, %21, %22, %23}, %24, %25, 1, 1, 1, 0, 1;\n"
    : "+f"(d[0]), "+f"(d[1]), "+f"(d[2]), "+f"(d[3]), "+f"(d[4]), "+f"(d[5]), "+f"(d[6]), "+f"(d[7]), "+f"(d[8]), "+f"(d[9]), "+f"(d[10]), "+f"(d[11]), "+f"(d[12]), "+f"(d[13]), "+f"(d[14]), "+f"(d[15]), "+f"(d[16]), "+f"(d[17]), "+f"(d[18]), "+f"(d[19]), "+f"(d[20]), "+f"(d[21]), "+f"(d[22]), "+f"(d[23])
    : "l"(descA), "l"(descB));
}
__device__ __forceinline__ void wgmma_ss_n80_tb(float (&d)[40], uint64_t descA, uint64_t descB) {
  asm volatile("wgmma.mma_async.sync.aligned.m64n80k16.f32.bf16.bf16 {%0, %1, %2, %3, %4, %5, %6, %7, %8, %9, %10, %11, %12, %13, %14, %15, %16, %17, %18, %19, %20, %21, %22, %23, %24, %25, %26, %27, %28, %29, %30, %31, %32, %33, %34, %35, %36, %37, %38, %39}, %40, %41, 1, 1, 1, 0, 1;\n"
    : "+f"(d[0]), "+f"(d[1]), "+f"(d[2]), "+f"(d[3]), "+f"(d[4]), "+f"(d[5]), "+f"(d[6]), "+f"(d[7]), "+f"(d[8]), "+f"(d[9]), "+f"(d[10]), "+f"(d[11]), "+f"(d[12]), "+f"(d[13]), "+f"(d[14]), "+f"(d[15]), "+f"(d[16]), "+f"(d[17]), "+f"(d[18]), "+f"(d[19]), "+f"(d[20]), "+f"(d[21]), "+f"(d[22]), "+f"(d[23]), "+f"(d[24]), "+f"(d[25]), "+f"(d[26]), "+f"(d[27]), "+f"(d[28]), "+f"(d[29]), "+f"(d[30]), "+f"(d[31]), "+f"(d[32]), "+f"(d[33]), "+f"(d[34]), "+f"(d[35]), "+f"(d[36]), "+f"(d[37]), "+f"(d[38]), "+f"(d[39])
    : "l"(descA), "l"(descB));
}
template <int SCALE_D>
__device__ __forceinline__ void wgmma_rs_n64(float (&d)[32], uint32_t a0, uint32_t a1, uint32_t a2, uint32_t a3, uint64_t descB) {
  asm volatile("wgmma.mma_async.sync.aligned.m64n64k16.f32.bf16.bf16 {%0, %1, %2, %3, %4, %5, %6, %7, %8, %9, %10, %11, %12, %13, %14, %15, %16, %17, %18, %19, %20, %21, %22, %23, %24, %25, %26, %27, %28, %29, %30, %31}, {%32, %33, %34, %35}, %36, %37, 1, 1, 0;\n"
    : "+f"(d[0]), "+f"(d[1]), "+f"(d[2]), "+f"(d[3]), "+f"(d[4]), "+f"(d[5]), "+f"(d[6]), "+f"(d[7]), "+f"(d[8]), "+f"(d[9]), "+f"(d[10]), "+f"(d[11]), "+f"(d[12]), "+f"(d[13]), "+f"(d[14]), "+f"(d[15]), "+f"(d[16]), "+f"(d[17]), "+f"(d[18]), "+f"(d[19]), "+f"(d[20]), "+f"(d[21]), "+f"(d[22]), "+f"(d[23]), "+f"(d[24]), "+f"(d[25]), "+f"(d[26]), "+f"(d[27]), "+f"(d[28]), "+f"(d[29]), "+f"(d[30]), "+f"(d[31])
    : "r"(a0), "r"(a1), "r"(a2), "r"(a3), "l"(descB), "n"(SCALE_D));
}
template <int SCALE_D>
__device__ __forceinline__ void wgmma_rs_n24_tb(float (&d)[12], uint32_t a0, uint32_t a1, uint32_t a2, uint32_t a3, uint64_t descB) {
  asm volatile("wgmma.mma_async.sync.aligned.m64n24k16.f32.bf16.bf16 {%0, %1, %2, %3, %4, %5, %6, %7, %8, %9, %10, %11}, {%12, %13, %14, %15}, %16, %17, 1, 1, 1;\n"
    : "+f"(d[0]), "+f"(d[1]), "+f"(d[2]), "+f"(d[3]), "+f"(d[4]), "+f"(d[5]), "+f"(d[6]), "+f"(d[7]), "+f"(d[8]), "+f"(d[9]), "+f"(d[10]), "+f"(d[11])
    : "r"(a0), "r"(a1), "r"(a2), "r"(a3), "l"(descB), "n"(SCALE_D));
}

constexpr uint32_t DHI_SW128_K = (1024 >> 4) | (1u << 30);
constexpr uint32_t DHI_SW64_MN = (512 >> 4) | (2u << 30);
constexpr uint32_t DHI_SW32_MN = (256 >> 4) | (3u << 30);

template <int NC>
__device__ __forceinline__ void store_tile_bf16(const float (&acc)[NC / 2], float scale, uint32_t stage, uint8_t* stage_ptr,
                                                __nv_bfloat16* gdst, int gpitch, int lane) {
  constexpr int PITCH = NC * 2 + 16;
  const uint32_t waddr = stage + ((lane & 7) + ((lane >> 3) & 1) * 8) * PITCH + (lane >> 4) * 16;
#pragma unroll
  for (int j = 0; j < NC / 16; j++) {
    stsm4(waddr + j * 32, pack_bf16(acc[8 * j] * scale, acc[8 * j + 1] * scale), pack_bf16(acc[8 * j + 2] * scale, acc[8 * j + 3] * scale),
          pack_bf16(acc[8 * j + 4] * scale, acc[8 * j + 5] * scale), pack_bf16(acc[8 * j + 6] * scale, acc[8 * j + 7] * scale));
  }
  __syncwarp();
  constexpr int CPR = NC / 8;
#pragma unroll
  for (int i = 0; i < CPR / 2; i++) {
    const int c = i * 32 + lane, r = c / CPR, cc = c % CPR;
    const uint4 v = *reinterpret_cast<const uint4*>(stage_ptr + r * PITCH + cc * 16);
    *reinterpret_cast<uint4*>(gdst + (size_t)r * gpitch + cc * 8) = v;
  }
}

__device__ __forceinline__ void signal_done(unsigned int* flag, int wg, int tid) {
  asm volatile("bar.sync %0, 128;" :: "r"(wg + 1) : "memory");
  if ((tid & 127) == 0) asm volatile("red.release.gpu.global.add.u32 [%0], 1;" :: "l"(flag) : "memory");
}
__device__ __forceinline__ void wait_flags8(const unsigned int* f, unsigned int target) {
  for (int spin = 0; spin < (1 << 26); spin++) {
    unsigned int a, b, c, d, e, g, h, i;
    asm volatile("ld.volatile.global.v4.u32 {%0, %1, %2, %3}, [%4];" : "=r"(a), "=r"(b), "=r"(c), "=r"(d) : "l"(f) : "memory");
    asm volatile("ld.volatile.global.v4.u32 {%0, %1, %2, %3}, [%4];" : "=r"(e), "=r"(g), "=r"(h), "=r"(i) : "l"(f + 4) : "memory");
    if (min(min(min(a, b), min(c, d)), min(min(e, g), min(h, i))) >= target) break;
  }
  asm volatile("fence.acq_rel.gpu;" ::: "memory");
  asm volatile("fence.proxy.async;" ::: "memory");
}
__device__ __forceinline__ void wait_flags(const unsigned int* f, int n4, unsigned int target) {
  for (int spin = 0; spin < (1 << 26); spin++) {
    unsigned int m = 0xffffffffu;
    for (int i = 0; i < n4; i++) {
      unsigned int a, b, c, d;
      asm volatile("ld.volatile.global.v4.u32 {%0, %1, %2, %3}, [%4];" : "=r"(a), "=r"(b), "=r"(c), "=r"(d) : "l"(f + 4 * i) : "memory");
      m = min(m, min(min(a, b), min(c, d)));
    }
    if (m >= target) break;
  }
  asm volatile("fence.acq_rel.gpu;" ::: "memory");
}

constexpr int K1_STAGES = 4;
constexpr int K1_A_BYTES = 256 * 128;
constexpr int K1_B_BYTES = 64 * 160 * 2;
constexpr int K1_STAGE = K1_A_BYTES + K1_B_BYTES;
constexpr int K1_SMEM = 5 * K1_A_BYTES + 61440 + 1024;
constexpr int KV_STAGES = 5;
constexpr int KVW_OFF = KV_STAGES * K1_A_BYTES;

__global__ void __launch_bounds__(512, 1)
proj_kernel(const __grid_constant__ CUtensorMap tmX, const __grid_constant__ CUtensorMap tmWq, const __grid_constant__ CUtensorMap tmWqkv,
            const __nv_bfloat16* __restrict__ wk, const __nv_bfloat16* __restrict__ wv, const __nv_bfloat16* __restrict__ gate_w) {
  extern __shared__ uint8_t smem_raw[];
  __shared__ __align__(8) uint64_t bar_full[KV_STAGES], bar_empty[KV_STAGES];
  uint8_t* smem = reinterpret_cast<uint8_t*>((reinterpret_cast<uintptr_t>(smem_raw) + 1023) & ~(uintptr_t)1023);
  const uint32_t sbase = smem_u32(smem);
  const uint32_t dbase = sbase & 0x3FFFFu;
  const int tid = threadIdx.x, warp = tid >> 5, lane = tid & 31;
  const bool is_kv = blockIdx.x >= 128;
  PROF(0, 0);
  if (tid == 0) {
    for (int i = 0; i < KV_STAGES; i++) { mbar_init(smem_u32(&bar_full[i]), 1); mbar_init(smem_u32(&bar_empty[i]), 16); }
    fence_mbar_init();
    if (!is_kv) { g_done[blockIdx.x] = 0u; g_doneL[blockIdx.x] = 0u; g_doneP[blockIdx.x] = 0u; }
    asm volatile("fence.acq_rel.gpu;" ::: "memory");
    pdl_launch();
  }
  __syncthreads();

  if (!is_kv) {
    const int mb = blockIdx.x >> 4, nb = blockIdx.x & 15;
    const CUtensorMap* tw = nb < 4 ? &tmWq : &tmWqkv;
    const int j0 = (nb < 4 ? nb : nb - 4) * 5;
    auto load = [&](int kt) {
      const int s = kt % K1_STAGES;
      const uint32_t fb = smem_u32(&bar_full[s]);
      mbar_expect_tx(fb, K1_STAGE);
      tma_2d(sbase + s * K1_STAGE, &tmX, kt * 64, mb * 256, fb);
      tma_3d(sbase + s * K1_STAGE + K1_A_BYTES, tw, 0, kt * 64, j0, fb);
    };
    if (tid == 0) for (int kt = 0; kt < K1_STAGES; kt++) load(kt);
    {
      const int wg = warp >> 2;
      float acc[80];
#pragma unroll
      for (int i = 0; i < 80; i++) acc[i] = 0.f;
      for (int kt = 0; kt < 10; kt++) {
        const int s = kt % K1_STAGES;
        mbar_wait(smem_u32(&bar_full[s]), (kt / K1_STAGES) & 1);
        const uint32_t alo = ((dbase + s * K1_STAGE + wg * 8192) >> 4) | (1u << 16);
        const uint32_t blo = ((dbase + s * K1_STAGE + K1_A_BYTES) >> 4) | ((4096u >> 4) << 16);
        fence_regs(acc);
        wg_fence();
#pragma unroll
        for (int k = 0; k < 4; k++) wgmma_ss_n160_tb(acc, mkd(alo + k * 2, DHI_SW128_K), mkd(blo + k * 64, DHI_SW64_MN));
        wg_commit();
        if (kt > 0 && kt - 1 + K1_STAGES < 10) {
          wg_wait<1>();
          const uint32_t eb = smem_u32(&bar_empty[(kt - 1) % K1_STAGES]);
          if (lane == 0) mbar_arrive(eb);
          if (tid == 0) { mbar_wait(eb, ((kt - 1) / K1_STAGES) & 1); load(kt - 1 + K1_STAGES); }
          __syncwarp();
        }
      }
      wg_wait<0>();
      fence_regs(acc);
      PROF(0, 1);
      asm volatile("bar.sync %0, 128;" :: "r"(wg + 1) : "memory");
      const int w4 = warp & 3;
      const uint32_t off = w4 * K1_STAGE + wg * 8192;
      const int row0 = mb * 256 + wg * 64 + w4 * 16;
      if (nb < 4) {
        store_tile_bf16<160>(acc, 0.22360679774997896f * 1.4426950408889634f, sbase + off, smem + off,
                             g_q + (size_t)row0 * D_MODEL + nb * 160, D_MODEL, lane);
      } else {
        store_tile_bf16<160>(acc, 1.0f, sbase + off, smem + off, g_qkv + (size_t)row0 * (3 * D_MODEL) + (nb - 4) * 160, 3 * D_MODEL, lane);
      }
      signal_done(&g_doneP[blockIdx.x], wg, tid);
    }
  } else {
    const int cb = blockIdx.x - 128;
    auto load = [&](int it) {
      const int s = it % KV_STAGES;
      const uint32_t fb = smem_u32(&bar_full[s]);
      mbar_expect_tx(fb, K1_A_BYTES);
      tma_2d(sbase + s * K1_A_BYTES, &tmX, (it % 10) * 64, cb * 512 + (it / 10) * 256, fb);
    };
    if (tid == 0) for (int it = 0; it < KV_STAGES; it++) load(it);
    {
      if (tid < 320) {
        uint2 a[2][5], b[2][5]; uint32_t gw[2];
#pragma unroll
        for (int r = 0; r < 2; r++) {
          const int k = tid + r * 320;
          const uint2* pk = reinterpret_cast<const uint2*>(wk + k * 20);
          const uint2* pv = reinterpret_cast<const uint2*>(wv + k * 20);
#pragma unroll
          for (int i = 0; i < 5; i++) { a[r][i] = __ldg(pk + i); b[r][i] = __ldg(pv + i); }
          gw[r] = (uint32_t)__bfloat16_as_ushort(gate_w[k]);
        }
#pragma unroll
        for (int r = 0; r < 2; r++) {
          uint4* dst = reinterpret_cast<uint4*>(smem + KVW_OFF + (tid + r * 320) * 16);
          dst[0] = make_uint4(a[r][0].x, a[r][0].y, a[r][1].x, a[r][1].y);
          dst[640] = make_uint4(a[r][2].x, a[r][2].y, a[r][3].x, a[r][3].y);
          dst[1280] = make_uint4(a[r][4].x, a[r][4].y, 0u, 0u);
          dst[1920] = make_uint4(b[r][0].x, b[r][0].y, b[r][1].x, b[r][1].y);
          dst[2560] = make_uint4(b[r][2].x, b[r][2].y, b[r][3].x, b[r][3].y);
          dst[3200] = make_uint4(b[r][4].x, b[r][4].y, gw[r], 0u);
        }
      }
      fence_proxy_async();
      asm volatile("bar.sync 1, 512;" ::: "memory");
      PROF(0, 1);
      const int wg = warp >> 2, w4 = warp & 3, g = lane >> 2, t = lane & 3;
      for (int pass = 0; pass < 2; pass++) {
        float acc[24];
#pragma unroll
        for (int i = 0; i < 24; i++) acc[i] = 0.f;
        for (int kt = 0; kt < 10; kt++) {
          const int it = pass * 10 + kt, s = it % KV_STAGES;
          mbar_wait(smem_u32(&bar_full[s]), (it / KV_STAGES) & 1);
          const uint32_t alo = ((dbase + s * K1_A_BYTES + wg * 8192) >> 4) | (1u << 16);
          const uint32_t blo = ((dbase + KVW_OFF + kt * 1024) >> 4) | ((128u >> 4) << 16);
          fence_regs(acc);
          wg_fence();
#pragma unroll
          for (int k = 0; k < 4; k++) wgmma_ss_n48_tb(acc, mkd(alo + k * 2, DHI_SW128_K), mkd(blo + k * 16, 10240u >> 4));
          wg_commit();
          wg_wait<0>();
          if (it + KV_STAGES < 20) {
            const uint32_t eb = smem_u32(&bar_empty[s]);
            if (lane == 0) mbar_arrive(eb);
            if (tid == 0) { mbar_wait(eb, (it / KV_STAGES) & 1); load(it + KV_STAGES); }
            __syncwarp();
          }
        }
        fence_regs(acc);
        float kmax2 = 0.f, vmax = 0.f;
#pragma unroll
        for (int h = 0; h < 2; h++) {
          const int key = cb * 512 + pass * 256 + wg * 64 + w4 * 16 + g + h * 8;
          const int grp = key >> 7, kk = key & 127;
          const bool poly = (TMASK >> (kk >> 3)) & 1;
          uint8_t* gp = g_kvimg + grp * GRP_BYTES;
          const uint32_t k0 = pack_bf16(acc[2 * h], acc[2 * h + 1]);
          const uint32_t k1 = pack_bf16(acc[4 + 2 * h], acc[5 + 2 * h]);
          uint32_t k2 = pack_bf16(acc[8 + 2 * h], acc[9 + 2 * h]);
          float n2 = bf_lo(k0) * bf_lo(k0) + bf_hi(k0) * bf_hi(k0) + bf_lo(k1) * bf_lo(k1) + bf_hi(k1) * bf_hi(k1);
          if (t < 2) {
            n2 += bf_lo(k2) * bf_lo(k2) + bf_hi(k2) * bf_hi(k2);
            k2 = pack_bf16(bf_lo(k2) * 0.5f, bf_hi(k2) * 0.5f);
          } else if (t == 2) k2 = poly ? pack_bf16(24.f, 2.5f) : pack_bf16(0.5f, 0.f);
          else k2 = poly ? pack_bf16(0.5f, 0.f) : 0u;
          *reinterpret_cast<uint32_t*>(gp + kk * 16 + t * 4) = k0;
          *reinterpret_cast<uint32_t*>(gp + PLANE + kk * 16 + t * 4) = k1;
          *reinterpret_cast<uint32_t*>(gp + 2 * PLANE + kk * 16 + t * 4) = k2;
          n2 += __shfl_xor_sync(0xffffffffu, n2, 1);
          n2 += __shfl_xor_sync(0xffffffffu, n2, 2);
          kmax2 = (n2 > kmax2 || n2 != n2) ? n2 : kmax2;
          uint32_t v0 = pack_bf16(acc[12 + 2 * h], acc[13 + 2 * h]);
          uint32_t v1 = pack_bf16(acc[16 + 2 * h], acc[17 + 2 * h]);
          uint32_t v2 = pack_bf16(acc[20 + 2 * h], acc[21 + 2 * h]);
          float vm = fmaxf(fmaxf(fabsf(bf_lo(v0)), fabsf(bf_hi(v0))), fmaxf(fabsf(bf_lo(v1)), fabsf(bf_hi(v1))));
          if (t < 2) vm = fmaxf(vm, fmaxf(fabsf(bf_lo(v2)), fabsf(bf_hi(v2))));
          else if (t == 2) {
            const float z = acc[20 + 2 * h];
            g_gate[key] = 1.f / (1.f + __expf(-z));
            v2 = 0x00003F80u;
          } else v2 = 0u;
          vmax = fmaxf(vmax, vm);
          if (poly) { v0 ^= 0x80008000u; v1 ^= 0x80008000u; v2 ^= 0x80008000u; }
          uint8_t* vp = gp + 3 * PLANE + (kk >> 3) * 384 + (kk & 7) * 16 + t * 4;
          *reinterpret_cast<uint32_t*>(vp) = v0;
          *reinterpret_cast<uint32_t*>(vp + 128) = v1;
          *reinterpret_cast<uint32_t*>(vp + 256) = v2;
        }
#pragma unroll
        for (int o = 1; o < 32; o <<= 1) {
          const float a = __shfl_xor_sync(0xffffffffu, kmax2, o);
          kmax2 = (a > kmax2 || a != a) ? a : kmax2;
          vmax = fmaxf(vmax, __shfl_xor_sync(0xffffffffu, vmax, o));
        }
        if (lane == 0) { g_kmax2[cb * 32 + pass * 16 + warp] = kmax2; g_vmax[cb * 32 + pass * 16 + warp] = vmax; }
      }
    }
  }
  PROF(0, 3);
}

__device__ __forceinline__ uint32_t ex2_pair_poly(float u0, float u1, uint32_t one2) {
  const uint32_t W = __byte_perm(__float_as_uint(u0), __float_as_uint(u1), 0x6521);
  uint32_t v; asm("lop3.b32 %0, %1, 0x007F007F, %2, 0xEA;" : "=r"(v) : "r"(W), "r"(one2));
  uint32_t L, p;
  asm("fma.rn.bf16x2 %0, %1, %2, %3;" : "=r"(L) : "r"(v), "r"(0x1f961f96u), "r"(0x9fe39fe3u));
  asm("fma.rn.bf16x2 %0, %1, %1, %2;" : "=r"(p) : "r"(L), "r"(0x00f500f5u));
  return W + p;
}
template <int JOFF>
__device__ __forceinline__ void softmax_fast(const float (&S)[32], uint32_t (&P)[16], uint32_t one2) {
#pragma unroll
  for (int i = 0; i < 16; i++) {
    if ((TMASK >> (JOFF + i / 2)) & 1) P[i] = ex2_pair_poly(S[2 * i], S[2 * i + 1], one2);
    else P[i] = pack_bf16(ex2(S[2 * i]), ex2(S[2 * i + 1]));
  }
}
template <int JOFF>
__device__ __forceinline__ void softmax_slow(const float (&S)[32], uint32_t (&P)[16], float (&O)[12], float& m0, float& m1) {
  float a0 = m0, a1 = m1;
#pragma unroll
  for (int j = 0; j < 8; j++) {
    a0 = fmaxf(a0, fmaxf(S[4 * j], S[4 * j + 1]));
    a1 = fmaxf(a1, fmaxf(S[4 * j + 2], S[4 * j + 3]));
  }
  a0 = fmaxf(a0, __shfl_xor_sync(0xffffffffu, a0, 1)); a0 = fmaxf(a0, __shfl_xor_sync(0xffffffffu, a0, 2));
  a1 = fmaxf(a1, __shfl_xor_sync(0xffffffffu, a1, 1)); a1 = fmaxf(a1, __shfl_xor_sync(0xffffffffu, a1, 2));
  const float c0 = ex2(m0 - a0), c1 = ex2(m1 - a1);
  m0 = a0; m1 = a1;
#pragma unroll
  for (int j = 0; j < 3; j++) { O[4 * j] *= c0; O[4 * j + 1] *= c0; O[4 * j + 2] *= c1; O[4 * j + 3] *= c1; }
#pragma unroll
  for (int i = 0; i < 16; i++) {
    const float m = (i & 1) ? a1 : a0;
    const uint32_t p = pack_bf16(ex2(S[2 * i] - m), ex2(S[2 * i + 1] - m));
    P[i] = ((TMASK >> (JOFF + i / 2)) & 1) ? (p ^ 0x80008000u) : p;
  }
}
constexpr uint32_t DHI_KV = 128 >> 4;
__device__ __forceinline__ void issue_qk(float (&S)[32], const uint32_t (&q)[8], uint32_t base) {
  wgmma_rs_n64<0>(S, q[0], q[1], q[2], q[3], mkd(base + ((PLANE >> 4) << 16), DHI_KV));
  wgmma_rs_n64<1>(S, q[4], q[5], q[6], q[7], mkd(base + (2 * PLANE >> 4), DHI_KV));
}
__device__ __forceinline__ void issue_pv(float (&O)[12], const uint32_t (&P)[16], uint32_t vbase) {
#pragma unroll
  for (int kk = 0; kk < 4; kk++)
    wgmma_rs_n24_tb<1>(O, P[4 * kk], P[4 * kk + 1], P[4 * kk + 2], P[4 * kk + 3], mkd(vbase + kk * (768 >> 4), DHI_KV));
}

constexpr uint32_t VOFF = ((3 * PLANE) >> 4) + ((384u >> 4) << 16);
constexpr int KVR = 4;
constexpr int OFF_WA = KVR * GRP_BYTES;
constexpr int OFF_BR = OFF_WA + 10 * 10240;
constexpr int BR_STAGE = 8192 + 10240, BR_STAGES = 3;
constexpr int OFF_QS = OFF_BR + BR_STAGES * BR_STAGE;
constexpr int OFF_BAR = OFF_QS + 512 * 6 * 4;
constexpr int K2_SMEM = OFF_BAR + 256 + 1024;
constexpr int BAR_KV = 0, BAR_WA = 4, BAR_BR = 5, BAR_TA = 8, BAR_TE = 14, CNT_KV = 18;
constexpr int NSTEP = 2 * NGRP;

__device__ __forceinline__ void kv_load(uint32_t sbase, int step) {
  const uint32_t bar = sbase + OFF_BAR + (BAR_KV + (step & (KVR - 1))) * 8;
  mbar_expect_tx(bar, GRP_BYTES);
  bulk_g2s(sbase + (step & (KVR - 1)) * GRP_BYTES, g_kvimg + (step & (NGRP - 1)) * GRP_BYTES, GRP_BYTES, bar);
}
__device__ __forceinline__ void kv_release(uint32_t sbase, int step, bool elected) {
  if (elected && step + KVR < NSTEP) {
    uint32_t old;
    asm volatile("atom.acq_rel.cta.shared::cta.inc.u32 %0, [%1], 3;" : "=r"(old) : "r"(sbase + OFF_BAR + CNT_KV * 8 + (step & (KVR - 1)) * 4) : "memory");
    if (old == 3u) kv_load(sbase, step + KVR);
  }
  __syncwarp();
}
__device__ __forceinline__ void kv_wait(uint32_t sbase, int step) {
  mbar_wait(sbase + OFF_BAR + (BAR_KV + (step & (KVR - 1))) * 8, (step / KVR) & 1);
}

__device__ __forceinline__ uint32_t kv_release_begin(uint32_t sbase, int slot, bool doit) {
  uint32_t old = 0;
  if (doit) asm volatile("atom.acq_rel.cta.shared::cta.inc.u32 %0, [%1], 3;" : "=r"(old) : "r"(sbase + OFF_BAR + CNT_KV * 8 + slot * 4) : "memory");
  return old;
}
__device__ __forceinline__ void attn_tile_fast(const uint32_t (&q)[8], float (&O)[12], uint32_t sbase, int step0, bool elected, uint32_t one2) {
  float S[32]; uint32_t P[16];
#pragma unroll
  for (int i = 0; i < 32; i++) S[i] = 0.f;
  const uint32_t kb0 = (sbase & 0x3FFFFu) >> 4;
  kv_wait(sbase, step0);
  fence_regs(S); fence_regs(O);
  wg_fence();
  issue_qk(S, q, kb0);
  wg_commit();
#pragma unroll 1
  for (int step4 = step0; step4 < step0 + NGRP; step4 += KVR) {
#pragma unroll
    for (int j = 0; j < KVR; j++) {
      const int step = step4 + j;
      const uint32_t kb = kb0 + j * (GRP_BYTES >> 4);
      const uint32_t knext = kb0 + ((j + 1) & (KVR - 1)) * (GRP_BYTES >> 4);
      wg_wait<0>();
      fence_regs(S); fence_regs(P); fence_regs(O);
      const uint32_t old = kv_release_begin(sbase, (j + KVR - 1) & (KVR - 1), elected && step > step0 && step - 1 + KVR < NSTEP);
      softmax_fast<0>(S, P, one2);
      fence_regs(S); fence_regs(P); fence_regs(O);
      wg_fence();
      issue_qk(S, q, kb + 64);
      issue_pv(O, P, kb + VOFF);
      wg_commit();
      if (old == 3u) kv_load(sbase, step - 1 + KVR);
      if (step + 1 < NSTEP) mbar_wait(sbase + OFF_BAR + (BAR_KV + ((j + 1) & (KVR - 1))) * 8, ((step + 1) / KVR) & 1);
      wg_wait<0>();
      fence_regs(S); fence_regs(P); fence_regs(O);
      softmax_fast<8>(S, P, one2);
      fence_regs(S); fence_regs(P); fence_regs(O);
      wg_fence();
      issue_qk(S, q, knext);
      issue_pv(O, P, kb + VOFF + 4 * (768 >> 4));
      wg_commit();
    }
  }
  wg_wait<0>();
  fence_regs(O); fence_regs(S);
  kv_release(sbase, step0 + NGRP - 1, elected);
}
template <int H>
__device__ __forceinline__ void slow_step(const uint32_t (&q)[8], float (&O)[12], uint32_t kb, float& m0, float& m1) {
  float S[32]; uint32_t P[16];
#pragma unroll
  for (int i = 0; i < 32; i++) S[i] = 0.f;
  fence_regs(S);
  wg_fence();
  issue_qk(S, q, kb + 64 * H);
  wg_commit();
  wg_wait<0>();
  fence_regs(S);
  softmax_slow<8 * H>(S, P, O, m0, m1);
  fence_regs(P); fence_regs(O);
  wg_fence();
  issue_pv(O, P, kb + VOFF + H * 4 * (768 >> 4));
  wg_commit();
  wg_wait<0>();
  fence_regs(O); fence_regs(P);
}
__device__ __forceinline__ void attn_tile_slow(const uint32_t (&q)[8], float (&O)[12], uint32_t sbase, int step0, bool elected) {
  float m0 = -INFINITY, m1 = -INFINITY;
#pragma unroll 1
  for (int grp = 0; grp < NGRP; grp++) {
    kv_wait(sbase, step0 + grp);
    const uint32_t kb = ((sbase & 0x3FFFFu) >> 4) + (grp & (KVR - 1)) * (GRP_BYTES >> 4);
    slow_step<0>(q, O, kb, m0, m1);
    slow_step<1>(q, O, kb, m0, m1);
    kv_release(sbase, step0 + grp, elected);
  }
}

__device__ __forceinline__ void local_attn_pair(int token, int lane, bool first) {
  const __nv_bfloat16* base = g_qkv + (size_t)token * (3 * D_MODEL) + lane * DH;
  float f[20];
  {
    const uint2* p = reinterpret_cast<const uint2*>(base);
#pragma unroll
    for (int i = 0; i < 5; i++) { const uint2 v = p[i]; f[4 * i] = bf_lo(v.x); f[4 * i + 1] = bf_hi(v.x); f[4 * i + 2] = bf_lo(v.y); f[4 * i + 3] = bf_hi(v.y); }
  }
  float sc[8];
  float mx = -INFINITY;
#pragma unroll
  for (int w = 0; w < 8; w++) {
    const bool ok = token - 2 * w >= 0;
    const uint2* p = reinterpret_cast<const uint2*>(base + D_MODEL - (ok ? 2 * w : 0) * (3 * D_MODEL));
    float s = 0.f;
#pragma unroll
    for (int i = 0; i < 5; i++) {
      const uint2 v = p[i];
      s = fmaf(f[4 * i], bf_lo(v.x), s); s = fmaf(f[4 * i + 1], bf_hi(v.x), s);
      s = fmaf(f[4 * i + 2], bf_lo(v.y), s); s = fmaf(f[4 * i + 3], bf_hi(v.y), s);
    }
    s *= 0.22360679774997896f * 1.4426950408889634f;
    sc[w] = ok ? s : -1e9f * 1.4426950408889634f;
    mx = fmaxf(mx, sc[w]);
  }
  float l = 0.f;
#pragma unroll
  for (int w = 0; w < 8; w++) { sc[w] = ex2(sc[w] - mx); l += sc[w]; }
#pragma unroll
  for (int i = 0; i < 20; i++) f[i] = 0.f;
#pragma unroll
  for (int w = 0; w < 8; w++) {
    const bool ok = token - 2 * w >= 0;
    const uint2* p = reinterpret_cast<const uint2*>(base + 2 * D_MODEL - (ok ? 2 * w : token) * (3 * D_MODEL));
#pragma unroll
    for (int i = 0; i < 5; i++) {
      const uint2 v = p[i];
      f[4 * i] = fmaf(sc[w], bf_lo(v.x), f[4 * i]); f[4 * i + 1] = fmaf(sc[w], bf_hi(v.x), f[4 * i + 1]);
      f[4 * i + 2] = fmaf(sc[w], bf_lo(v.y), f[4 * i + 2]); f[4 * i + 3] = fmaf(sc[w], bf_hi(v.y), f[4 * i + 3]);
    }
  }
  if (first) pdl_wait();
  const float r = (1.f - g_gate[token]) / l;
  uint2* dst = reinterpret_cast<uint2*>(g_a2 + (size_t)token * (2 * D_MODEL) + D_MODEL + lane * DH);
#pragma unroll
  for (int i = 0; i < 5; i++) dst[i] = make_uint2(pack_bf16(f[4 * i] * r, f[4 * i + 1] * r), pack_bf16(f[4 * i + 2] * r, f[4 * i + 3] * r));
}

__device__ __forceinline__ uint32_t ta_slot(int i) { return i < 3 ? i * 16384 : OFF_BR + (i - 3) * 16384; }

__global__ void __launch_bounds__(640, 1)
attn_kernel(const __grid_constant__ CUtensorMap tmA2, const __grid_constant__ CUtensorMap tmWoA, const __grid_constant__ CUtensorMap tmWoB,
            __nv_bfloat16* __restrict__ out, uint32_t one2) {
  extern __shared__ uint8_t smem_raw[];
  uint8_t* smem = reinterpret_cast<uint8_t*>((reinterpret_cast<uintptr_t>(smem_raw) + 1023) & ~(uintptr_t)1023);
  const uint32_t sbase = smem_u32(smem);
  const uint32_t dbase = sbase & 0x3FFFFu;
  const uint32_t bars = sbase + OFF_BAR;
  const int tid = threadIdx.x, wg = tid >> 7, warp = (tid >> 5) & 3, lane = tid & 31, g = lane >> 2, t = lane & 3;
  const int mb = blockIdx.x >> 3, nb = blockIdx.x & 7;
  if (tid == 0) {
    for (int i = 0; i < BAR_TE; i++) mbar_init(bars + i * 8, 1);
    for (int i = BAR_TE; i < BAR_TE + 4; i++) mbar_init(bars + i * 8, 8);
    for (int i = 0; i < 4; i++) *reinterpret_cast<uint32_t*>(smem + OFF_BAR + CNT_KV * 8 + i * 4) = 0u;
    fence_mbar_init();
  }
  __syncthreads();
  if (wg == 4) {
    if (tid == 512) {
      mbar_expect_tx(bars + BAR_WA * 8, 10 * 10240);
      for (int kt = 0; kt < 10; kt++) tma_3d(sbase + OFF_WA + kt * 10240, &tmWoA, 0, kt * 64, nb * 5, bars + BAR_WA * 8);
    }
    if (lane == 0) {
      const int rb = blockIdx.x >> 4;
      wait_flags(&g_doneP[rb * 16 + 4], 3, 4u);
      if ((blockIdx.x & 15) == 0 && rb > 0) wait_flags(&g_doneP[rb * 16 - 8], 2, 4u);
    }
    __syncwarp();
#pragma unroll 1
    for (int i = 0; i < 4; i++) local_attn_pair(blockIdx.x * 16 + i * 4 + warp, lane, i == 0);
    if (tid == 512) PROF2(0, 2);
    signal_done(&g_doneL[blockIdx.x], wg, tid);
    auto br_load = [&](int it, int st) {
      const uint32_t fb = bars + (BAR_BR + st) * 8;
      const uint32_t dst = sbase + OFF_BR + st * BR_STAGE;
      const int kc = (it >= 10 ? it - 10 : it) * 64;
      mbar_expect_tx(fb, BR_STAGE);
      tma_2d(dst, &tmA2, D_MODEL + kc, (blockIdx.x >> 3) * 128 + (it >= 10 ? 64 : 0), fb);
      tma_3d(dst + 8192, &tmWoB, 0, kc, (blockIdx.x & 7) * 5, fb);
    };
    if (tid == 512) {
      wait_flags8(&g_doneL[mb * 8], 1u);
      for (int it = 0; it < BR_STAGES; it++) br_load(it, it);
    }
    __syncwarp();
    {
      int st = 0, ph = 0;
      float acc[40];
#pragma unroll 1
      for (int it = 0; it < 20; it++) {
        if (it == 0 || it == 10) {
#pragma unroll
          for (int i = 0; i < 40; i++) acc[i] = 0.f;
        }
        mbar_wait(bars + (BAR_BR + st) * 8, ph);
        const uint32_t alo = ((dbase + OFF_BR + st * BR_STAGE) >> 4);
        fence_regs(acc);
        wg_fence();
#pragma unroll
        for (int k = 0; k < 4; k++)
          wgmma_ss_n80_tb(acc, mkd(alo + (k * 2 + (1u << 16)), DHI_SW128_K), mkd(alo + (512 + k * 32 + ((2048u >> 4) << 16)), DHI_SW32_MN));
        wg_commit();
        wg_wait<0>();
        fence_regs(acc);
        asm volatile("bar.sync 5, 128;" ::: "memory");
        if (threadIdx.x == 512 && it + BR_STAGES < 20) br_load(it + BR_STAGES, st);
        __syncwarp();
        if (it == 9 || it == 19) {
          float* pp = g_part + (size_t)(blockIdx.x * 2 + (it == 19)) * (40 * 128) + (threadIdx.x & 127);
#pragma unroll
          for (int i = 0; i < 40; i++) pp[i * 128] = acc[i];
        }
        if (++st == BR_STAGES) { st = 0; ph ^= 1; }
      }
    }
    if (tid == 512) PROF2(1, 0);
    asm volatile("bar.arrive 6, 384;" ::: "memory");
    if (tid == 512) {
      wait_flags8(&g_done[mb * 8], 4u);
      PROF2(2, 0);
      for (int kt = 0; kt < 10; kt++) {
        const int sl = kt % 6;
        if (kt >= 6) mbar_wait(bars + (BAR_TE + kt - 6) * 8, 0);
        const uint32_t fb = bars + (BAR_TA + sl) * 8;
        mbar_expect_tx(fb, 16384);
        tma_2d(sbase + ta_slot(sl), &tmA2, kt * 64, mb * 128, fb);
        tma_2d(sbase + ta_slot(sl) + 8192, &tmA2, kt * 64, mb * 128 + 64, fb);
      }
    }
  } else {
    const bool elected = (tid & 127) == 0;
    if (lane == 0) wait_flags(&g_doneP[(blockIdx.x >> 4) * 16], 1, 4u);
    __syncwarp();
    uint32_t q[8];
    uint32_t* qstash = reinterpret_cast<uint32_t*>(smem + OFF_QS) + tid;
    const int rowA = (blockIdx.x * 8 + wg) * 64 + warp * 16 + g;
    {
      const uint32_t* r0 = reinterpret_cast<const uint32_t*>(g_q + (size_t)rowA * DH);
      const uint32_t* r1 = r0 + 8 * (DH / 2);
      const uint32_t* s0 = r0 + 256 * (DH / 2);
      const uint32_t* s1 = s0 + 8 * (DH / 2);
      q[0] = r0[t]; q[1] = r1[t]; q[2] = r0[t + 4]; q[3] = r1[t + 4];
      q[4] = t < 2 ? r0[8 + t] : 0u;
      q[5] = t < 2 ? r1[8 + t] : 0u;
      qstash[0] = s0[t]; qstash[512] = s1[t]; qstash[1024] = s0[t + 4]; qstash[1536] = s1[t + 4];
      qstash[2048] = t < 2 ? s0[8 + t] : 0u;
      qstash[2560] = t < 2 ? s1[8 + t] : 0u;
    }
    pdl_wait();
    PROF(1, 1);
    if (tid == 0) for (int j = 0; j < KVR; j++) kv_load(sbase, j);
    __syncwarp();
    float kmax2 = 0.f, vmax = 0.f;
#pragma unroll
    for (int i = 0; i < 4; i++) {
      const float a = g_kmax2[lane + 32 * i];
      kmax2 = (a > kmax2 || a != a) ? a : kmax2;
      vmax = fmaxf(vmax, g_vmax[lane + 32 * i]);
    }
#pragma unroll
    for (int o = 1; o < 32; o <<= 1) {
      const float a = __shfl_xor_sync(0xffffffffu, kmax2, o);
      kmax2 = (a > kmax2 || a != a) ? a : kmax2;
      vmax = fmaxf(vmax, __shfl_xor_sync(0xffffffffu, vmax, o));
    }
    const float qlim = (vmax >= 0.00390625f && vmax <= 256.f) ? 9025.f / kmax2 : -1.f;
    PROF(1, 2);
#pragma unroll 1
    for (int it = 0; it < 2; it++) {
      const int row0 = rowA + it * 256;
      if (it == 1) {
#pragma unroll
        for (int i = 0; i < 6; i++) q[i] = qstash[512 * i];
      }
      float n0 = bf_lo(q[0]) * bf_lo(q[0]) + bf_hi(q[0]) * bf_hi(q[0]) + bf_lo(q[2]) * bf_lo(q[2]) + bf_hi(q[2]) * bf_hi(q[2]) +
                 bf_lo(q[4]) * bf_lo(q[4]) + bf_hi(q[4]) * bf_hi(q[4]);
      float n1 = bf_lo(q[1]) * bf_lo(q[1]) + bf_hi(q[1]) * bf_hi(q[1]) + bf_lo(q[3]) * bf_lo(q[3]) + bf_hi(q[3]) * bf_hi(q[3]) +
                 bf_lo(q[5]) * bf_lo(q[5]) + bf_hi(q[5]) * bf_hi(q[5]);
      n0 += __shfl_xor_sync(0xffffffffu, n0, 1); n0 += __shfl_xor_sync(0xffffffffu, n0, 2);
      n1 += __shfl_xor_sync(0xffffffffu, n1, 1); n1 += __shfl_xor_sync(0xffffffffu, n1, 2);
      const bool safe = (n0 <= qlim) && (n1 <= qlim);
      uint32_t unsafe_any;
      asm volatile("{\n.reg .pred p, r;\nsetp.eq.u32 p, %1, 0;\nbarrier.cta.red.or.pred r, %2, 128, p;\nselp.u32 %0, 1, 0, r;\n}\n"
                   : "=r"(unsafe_any) : "r"((uint32_t)safe), "r"(wg + 1) : "memory");
      float O[12];
#pragma unroll
      for (int i = 0; i < 12; i++) O[i] = 0.f;
      if (!unsafe_any && t >= 2) { q[4] = q[5] = (t == 2) ? 0x3F804100u : 0x00003B80u; }
      q[6] = q[4]; q[7] = q[5];
      fence_regs(q);
      if (!unsafe_any) attn_tile_fast(q, O, sbase, it * NGRP, elected, one2);
      else attn_tile_slow(q, O, sbase, it * NGRP, elected);
      const float l0 = __shfl_sync(0xffffffffu, O[8], (lane & ~3) | 2);
      const float l1 = __shfl_sync(0xffffffffu, O[10], (lane & ~3) | 2);
      const int tok = row0 >> 5;
      const float gt = g_gate[tok];
      const float i0 = gt / l0, i1 = gt / l1;
      uint32_t* o0 = reinterpret_cast<uint32_t*>(g_a2 + (size_t)tok * (2 * D_MODEL) + (row0 & 31) * DH);
      uint32_t* o1 = o0 + 8 * (DH / 2);
      o0[t] = pack_bf16(O[0] * i0, O[1] * i0); o1[t] = pack_bf16(O[2] * i1, O[3] * i1);
      o0[t + 4] = pack_bf16(O[4] * i0, O[5] * i0); o1[t + 4] = pack_bf16(O[6] * i1, O[7] * i1);
      if (t < 2) { o0[t + 8] = pack_bf16(O[8] * i0, O[9] * i0); o1[t + 8] = pack_bf16(O[10] * i1, O[11] * i1); }
    }
    signal_done(&g_done[blockIdx.x], wg, tid);
    PROF(1, 3);
    if (wg < 2) {
      float acc[40];
      asm volatile("bar.sync 6, 384;" ::: "memory");
      {
        const float* pp = g_part + (size_t)(blockIdx.x * 2 + wg) * (40 * 128) + (tid & 127);
#pragma unroll
        for (int i = 0; i < 40; i++) acc[i] = pp[i * 128];
      }
      mbar_wait(bars + BAR_WA * 8, 0);
#pragma unroll 1
      for (int kt = 0; kt < 10; kt++) {
        const int sl = kt % 6;
        mbar_wait(bars + (BAR_TA + sl) * 8, kt / 6);
        if (kt == 0) PROF(2, 1);
        const uint32_t alo = ((dbase + ta_slot(sl) + wg * 8192) >> 4) | (1u << 16);
        const uint32_t blo = ((dbase + OFF_WA + kt * 10240) >> 4) | ((2048u >> 4) << 16);
        fence_regs(acc);
        wg_fence();
#pragma unroll
        for (int k = 0; k < 4; k++) wgmma_ss_n80_tb(acc, mkd(alo + k * 2, DHI_SW128_K), mkd(blo + k * 32, DHI_SW32_MN));
        wg_commit();
        if (kt < 4) {
          wg_wait<0>();
          if (lane == 0) mbar_arrive(bars + (BAR_TE + kt) * 8);
        }
      }
      wg_wait<0>();
      fence_regs(acc);
      PROF(2, 2);
      asm volatile("bar.sync %0, 128;" :: "r"(wg + 1) : "memory");
      const uint32_t so = ta_slot(warp) + wg * 8192;
      const int row0 = mb * 128 + wg * 64 + warp * 16;
      store_tile_bf16<80>(acc, 1.0f, sbase + so, smem + so, out + (size_t)row0 * D_MODEL + nb * 80, D_MODEL, lane);
      PROF(2, 3);
    }
  }
}

typedef CUresult (*EncodeFn)(CUtensorMap*, CUtensorMapDataType, cuuint32_t, void*, const cuuint64_t*, const cuuint64_t*,
                             const cuuint32_t*, const cuuint32_t*, CUtensorMapInterleave, CUtensorMapSwizzle,
                             CUtensorMapL2promotion, CUtensorMapFloatOOBfill);

void make_map(EncodeFn fn, CUtensorMap* tm, const void* ptr, int rank, const cuuint64_t* dims, const cuuint64_t* strides,
              const cuuint32_t* box, CUtensorMapSwizzle sw) {
  const cuuint32_t es[3] = {1, 1, 1};
  fn(tm, CU_TENSOR_MAP_DATA_TYPE_BFLOAT16, rank, const_cast<void*>(ptr), dims, strides, box, es, CU_TENSOR_MAP_INTERLEAVE_NONE, sw,
     CU_TENSOR_MAP_L2_PROMOTION_L2_256B, CU_TENSOR_MAP_FLOAT_OOB_FILL_NONE);
}
void map_a(EncodeFn fn, CUtensorMap* tm, const void* p, int rows, int cols, int box_rows) {
  const cuuint64_t dims[2] = {(cuuint64_t)cols, (cuuint64_t)rows};
  const cuuint64_t str[1] = {(cuuint64_t)cols * 2};
  const cuuint32_t box[2] = {64, (cuuint32_t)box_rows};
  make_map(fn, tm, p, 2, dims, str, box, CU_TENSOR_MAP_SWIZZLE_128B);
}
void map_w(EncodeFn fn, CUtensorMap* tm, const void* p, int K, int N, int atom, CUtensorMapSwizzle sw) {
  const cuuint64_t dims[3] = {(cuuint64_t)atom, (cuuint64_t)K, (cuuint64_t)(N / atom)};
  const cuuint64_t str[2] = {(cuuint64_t)N * 2, (cuuint64_t)atom * 2};
  const cuuint32_t box[3] = {(cuuint32_t)atom, 64, 5};
  make_map(fn, tm, p, 3, dims, str, box, sw);
}

template <typename... KArgs, typename... Args>
void launch(void (*kern)(KArgs...), int grid, int block, int smem, bool pdl, Args... args) {
  cudaLaunchConfig_t cfg = {};
  cfg.gridDim = dim3(grid); cfg.blockDim = dim3(block); cfg.dynamicSmemBytes = smem; cfg.stream = cudaStreamPerThread;
  cudaLaunchAttribute at[1];
  at[0].id = cudaLaunchAttributeProgrammaticStreamSerialization;
  at[0].val.programmaticStreamSerializationAllowed = 1;
  cfg.attrs = at; cfg.numAttrs = pdl ? 1 : 0;
  cudaLaunchKernelEx(&cfg, kern, KArgs(args)...);
}

}

extern "C" void kernel_launch(void* const* d_in, const int* in_sizes, int n_in, void* d_out, int out_size) {
  (void)in_sizes; (void)n_in; (void)out_size;
  const __nv_bfloat16* x = (const __nv_bfloat16*)d_in[0];
  const __nv_bfloat16* wq = (const __nv_bfloat16*)d_in[1];
  const __nv_bfloat16* wk = (const __nv_bfloat16*)d_in[2];
  const __nv_bfloat16* wv = (const __nv_bfloat16*)d_in[3];
  const __nv_bfloat16* woA = (const __nv_bfloat16*)d_in[4];
  const __nv_bfloat16* wqkv = (const __nv_bfloat16*)d_in[6];
  const __nv_bfloat16* woB = (const __nv_bfloat16*)d_in[7];
  const __nv_bfloat16* gate_w = (const __nv_bfloat16*)d_in[8];

  static EncodeFn enc = nullptr;
  static void* a2_ptr = nullptr;
  if (!enc) {
    void* fp = nullptr;
    cudaDriverEntryPointQueryResult qr;
    cudaGetDriverEntryPoint("cuTensorMapEncodeTiled", &fp, cudaEnableDefault, &qr);
    enc = (EncodeFn)fp;
    cudaGetSymbolAddress(&a2_ptr, g_a2);
    cudaFuncSetAttribute(proj_kernel, cudaFuncAttributeMaxDynamicSharedMemorySize, K1_SMEM);
    cudaFuncSetAttribute(attn_kernel, cudaFuncAttributeMaxDynamicSharedMemorySize, K2_SMEM);
  }
  CUtensorMap tmX, tmWq, tmWqkv, tmA2, tmWoA, tmWoB;
  map_a(enc, &tmX, x, S_LEN, D_MODEL, 256);
  map_w(enc, &tmWq, wq, D_MODEL, D_MODEL, 32, CU_TENSOR_MAP_SWIZZLE_64B);
  map_w(enc, &tmWqkv, wqkv, D_MODEL, 3 * D_MODEL, 32, CU_TENSOR_MAP_SWIZZLE_64B);
  map_a(enc, &tmA2, a2_ptr, S_LEN, 2 * D_MODEL, 64);
  map_w(enc, &tmWoA, woA, D_MODEL, D_MODEL, 16, CU_TENSOR_MAP_SWIZZLE_32B);
  map_w(enc, &tmWoB, woB, D_MODEL, D_MODEL, 16, CU_TENSOR_MAP_SWIZZLE_32B);

  launch(proj_kernel, 132, 512, K1_SMEM, false, tmX, tmWq, tmWqkv, wk, wv, gate_w);
  launch(attn_kernel, 128, 640, K2_SMEM, true, tmA2, tmWoA, tmWoB, (__nv_bfloat16*)d_out, 0x3F803F80u);
}
```

```cpp
#include <cuda_runtime.h>
#include <cuda_bf16.h>
#include <cuda.h>
#include <stdint.h>

namespace {

constexpr int S_LEN = 2048, D_MODEL = 640, DH = 20;

constexpr int GRP = 128;
constexpr int PLANE = GRP * 16;
constexpr int GRP_BYTES = GRP * 16 * 6;
constexpr int NGRP = S_LEN / GRP;
constexpr uint32_t TMASK = 0x6DB6u;

__device__ __align__(1024) __nv_bfloat16 g_q[S_LEN * D_MODEL];
__device__ __align__(1024) __nv_bfloat16 g_qkv[S_LEN * 3 * D_MODEL];
__device__ __align__(1024) __nv_bfloat16 g_a2[S_LEN * 2 * D_MODEL];
__device__ __align__(1024) uint8_t g_kvimg[NGRP * GRP_BYTES];
__device__ float g_gate[S_LEN];
__device__ float g_kmax2[128];
__device__ float g_vmax[128];
__device__ __align__(64) unsigned int g_doneP[128];
__device__ __align__(32) unsigned int g_doneL[128];
__device__ float g_part[128 * 2 * 40 * 128];
__device__ __align__(32) unsigned int g_done[128];

#define PROF(k, slot)
#define PROF2(k, slot)
__device__ __forceinline__ uint32_t smem_u32(const void* p) { return (uint32_t)__cvta_generic_to_shared(p); }
__device__ __forceinline__ uint64_t mkd(uint32_t lo, uint32_t hi) {
  uint64_t d; asm("mov.b64 %0, {%1, %2};" : "=l"(d) : "r"(lo), "r"(hi)); return d;
}
__device__ __forceinline__ void wg_fence() { asm volatile("wgmma.fence.sync.aligned;" ::: "memory"); }
__device__ __forceinline__ void wg_commit() { asm volatile("wgmma.commit_group.sync.aligned;" ::: "memory"); }
template <int N> __device__ __forceinline__ void wg_wait() { asm volatile("wgmma.wait_group.sync.aligned %0;" :: "n"(N) : "memory"); }
template <int N> __device__ __forceinline__ void fence_regs(float (&d)[N]) {
#pragma unroll
  for (int i = 0; i < N; i++) asm volatile("" : "+f"(d[i]) :: "memory");
}
template <int N> __device__ __forceinline__ void fence_regs(uint32_t (&d)[N]) {
#pragma unroll
  for (int i = 0; i < N; i++) asm volatile("" : "+r"(d[i]) :: "memory");
}
__device__ __forceinline__ void mbar_init(uint32_t bar, uint32_t cnt) { asm volatile("mbarrier.init.shared::cta.b64 [%0], %1;" :: "r"(bar), "r"(cnt)); }
__device__ __forceinline__ void mbar_expect_tx(uint32_t bar, uint32_t bytes) {
  asm volatile("mbarrier.arrive.expect_tx.shared::cta.b64 _, [%0], %1;" :: "r"(bar), "r"(bytes) : "memory");
}
__device__ __forceinline__ void mbar_arrive(uint32_t bar) { asm volatile("mbarrier.arrive.shared::cta.b64 _, [%0];" :: "r"(bar) : "memory"); }
__device__ __forceinline__ void mbar_wait(uint32_t bar, uint32_t parity) {
  asm volatile("{\n.reg .pred p;\nWAIT_%=:\nmbarrier.try_wait.parity.shared::cta.b64 p, [%0], %1;\n@p bra DONE_%=;\nbra WAIT_%=;\nDONE_%=:\n}\n"
               :: "r"(bar), "r"(parity) : "memory");
}
__device__ __forceinline__ void fence_mbar_init() { asm volatile("fence.mbarrier_init.release.cluster;" ::: "memory"); }
__device__ __forceinline__ void fence_proxy_async() { asm volatile("fence.proxy.async.shared::cta;" ::: "memory"); }
__device__ __forceinline__ void bulk_g2s(uint32_t dst, const void* src, uint32_t bytes, uint32_t bar) {
  asm volatile("cp.async.bulk.shared::cluster.global.mbarrier::complete_tx::bytes [%0], [%1], %2, [%3];"
               :: "r"(dst), "l"(src), "r"(bytes), "r"(bar) : "memory");
}
__device__ __forceinline__ void tma_2d(uint32_t dst, const CUtensorMap* tm, int c0, int c1, uint32_t bar) {
  asm volatile("cp.async.bulk.tensor.2d.shared::cluster.global.mbarrier::complete_tx::bytes [%0], [%1, {%3, %4}], [%2];"
               :: "r"(dst), "l"((uint64_t)tm), "r"(bar), "r"(c0), "r"(c1) : "memory");
}
__device__ __forceinline__ void tma_3d(uint32_t dst, const CUtensorMap* tm, int c0, int c1, int c2, uint32_t bar) {
  asm volatile("cp.async.bulk.tensor.3d.shared::cluster.global.mbarrier::complete_tx::bytes [%0], [%1, {%3, %4, %5}], [%2];"
               :: "r"(dst), "l"((uint64_t)tm), "r"(bar), "r"(c0), "r"(c1), "r"(c2) : "memory");
}
__device__ __forceinline__ void pdl_wait() { asm volatile("griddepcontrol.wait;" ::: "memory"); }
__device__ __forceinline__ void pdl_launch() { asm volatile("griddepcontrol.launch_dependents;" ::: "memory"); }
__device__ __forceinline__ float ex2(float x) { float y; asm("ex2.approx.ftz.f32 %0, %1;" : "=f"(y) : "f"(x)); return y; }
__device__ __forceinline__ uint32_t pack_bf16(float lo, float hi) {
  uint32_t r; asm("cvt.rn.bf16x2.f32 %0, %1, %2;" : "=r"(r) : "f"(hi), "f"(lo)); return r;
}
__device__ __forceinline__ float bf_lo(uint32_t x) { return __uint_as_float(x << 16); }
__device__ __forceinline__ float bf_hi(uint32_t x) { return __uint_as_float(x & 0xffff0000u); }
__device__ __forceinline__ void stsm4(uint32_t addr, uint32_t r0, uint32_t r1, uint32_t r2, uint32_t r3) {
  asm volatile("stmatrix.sync.aligned.m8n8.x4.shared.b16 [%0], {%1, %2, %3, %4};" :: "r"(addr), "r"(r0), "r"(r1), "r"(r2), "r"(r3) : "memory");
}

__device__ __forceinline__ void wgmma_ss_n160_tb(float (&d)[80], uint64_t descA, uint64_t descB) {
  asm volatile("wgmma.mma_async.sync.aligned.m64n160k16.f32.bf16.bf16 {%0, %1, %2, %3, %4, %5, %6, %7, %8, %9, %10, %11, %12, %13, %14, %15, %16, %17, %18, %19, %20, %21, %22, %23, %24, %25, %26, %27, %28, %29, %30, %31, %32, %33, %34, %35, %36, %37, %38, %39, %40, %41, %42, %43, %44, %45, %46, %47, %48, %49, %50, %51, %52, %53, %54, %55, %56, %57, %58, %59, %60, %61, %62, %63, %64, %65, %66, %67, %68, %69, %70, %71, %72, %73, %74, %75, %76, %77, %78, %79}, %80, %81, 1, 1, 1, 0, 1;\n"
    : "+f"(d[0]), "+f"(d[1]), "+f"(d[2]), "+f"(d[3]), "+f"(d[4]), "+f"(d[5]), "+f"(d[6]), "+f"(d[7]), "+f"(d[8]), "+f"(d[9]), "+f"(d[10]), "+f"(d[11]), "+f"(d[12]), "+f"(d[13]), "+f"(d[14]), "+f"(d[15]), "+f"(d[16]), "+f"(d[17]), "+f"(d[18]), "+f"(d[19]), "+f"(d[20]), "+f"(d[21]), "+f"(d[22]), "+f"(d[23]), "+f"(d[24]), "+f"(d[25]), "+f"(d[26]), "+f"(d[27]), "+f"(d[28]), "+f"(d[29]), "+f"(d[30]), "+f"(d[31]), "+f"(d[32]), "+f"(d[33]), "+f"(d[34]), "+f"(d[35]), "+f"(d[36]), "+f"(d[37]), "+f"(d[38]), "+f"(d[39]), "+f"(d[40]), "+f"(d[41]), "+f"(d[42]), "+f"(d[43]), "+f"(d[44]), "+f"(d[45]), "+f"(d[46]), "+f"(d[47]), "+f"(d[48]), "+f"(d[49]), "+f"(d[50]), "+f"(d[51]), "+f"(d[52]), "+f"(d[53]), "+f"(d[54]), "+f"(d[55]), "+f"(d[56]), "+f"(d[57]), "+f"(d[58]), "+f"(d[59]), "+f"(d[60]), "+f"(d[61]), "+f"(d[62]), "+f"(d[63]), "+f"(d[64]), "+f"(d[65]), "+f"(d[66]), "+f"(d[67]), "+f"(d[68]), "+f"(d[69]), "+f"(d[70]), "+f"(d[71]), "+f"(d[72]), "+f"(d[73]), "+f"(d[74]), "+f"(d[75]), "+f"(d[76]), "+f"(d[77]), "+f"(d[78]), "+f"(d[79])
    : "l"(descA), "l"(descB));
}
__device__ __forceinline__ void wgmma_ss_n48_tb(float (&d)[24], uint64_t descA, uint64_t descB) {
  asm volatile("wgmma.mma_async.sync.aligned.m64n48k16.f32.bf16.bf16 {%0, %1, %2, %3, %4, %5, %6, %7, %8, %9, %10, %11, %12, %13, %14, %15, %16, %17, %18, %19, %20, %21, %22, %23}, %24, %25, 1, 1, 1, 0, 1;\n"
    : "+f"(d[0]), "+f"(d[1]), "+f"(d[2]), "+f"(d[3]), "+f"(d[4]), "+f"(d[5]), "+f"(d[6]), "+f"(d[7]), "+f"(d[8]), "+f"(d[9]), "+f"(d[10]), "+f"(d[11]), "+f"(d[12]), "+f"(d[13]), "+f"(d[14]), "+f"(d[15]), "+f"(d[16]), "+f"(d[17]), "+f"(d[18]), "+f"(d[19]), "+f"(d[20]), "+f"(d[21]), "+f"(d[22]), "+f"(d[23])
    : "l"(descA), "l"(descB));
}
__device__ __forceinline__ void wgmma_ss_n80_tb(float (&d)[40], uint64_t descA, uint64_t descB) {
  asm volatile("wgmma.mma_async.sync.aligned.m64n80k16.f32.bf16.bf16 {%0, %1, %2, %3, %4, %5, %6, %7, %8, %9, %10, %11, %12, %13, %14, %15, %16, %17, %18, %19, %20, %21, %22, %23, %24, %25, %26, %27, %28, %29, %30, %31, %32, %33, %34, %35, %36, %37, %38, %39}, %40, %41, 1, 1, 1, 0, 1;\n"
    : "+f"(d[0]), "+f"(d[1]), "+f"(d[2]), "+f"(d[3]), "+f"(d[4]), "+f"(d[5]), "+f"(d[6]), "+f"(d[7]), "+f"(d[8]), "+f"(d[9]), "+f"(d[10]), "+f"(d[11]), "+f"(d[12]), "+f"(d[13]), "+f"(d[14]), "+f"(d[15]), "+f"(d[16]), "+f"(d[17]), "+f"(d[18]), "+f"(d[19]), "+f"(d[20]), "+f"(d[21]), "+f"(d[22]), "+f"(d[23]), "+f"(d[24]), "+f"(d[25]), "+f"(d[26]), "+f"(d[27]), "+f"(d[28]), "+f"(d[29]), "+f"(d[30]), "+f"(d[31]), "+f"(d[32]), "+f"(d[33]), "+f"(d[34]), "+f"(d[35]), "+f"(d[36]), "+f"(d[37]), "+f"(d[38]), "+f"(d[39])
    : "l"(descA), "l"(descB));
}
template <int SCALE_D>
__device__ __forceinline__ void wgmma_rs_n64(float (&d)[32], uint32_t a0, uint32_t a1, uint32_t a2, uint32_t a3, uint64_t descB) {
  asm volatile("wgmma.mma_async.sync.aligned.m64n64k16.f32.bf16.bf16 {%0, %1, %2, %3, %4, %5, %6, %7, %8, %9, %10, %11, %12, %13, %14, %15, %16, %17, %18, %19, %20, %21, %22, %23, %24, %25, %26, %27, %28, %29, %30, %31}, {%32, %33, %34, %35}, %36, %37, 1, 1, 0;\n"
    : "+f"(d[0]), "+f"(d[1]), "+f"(d[2]), "+f"(d[3]), "+f"(d[4]), "+f"(d[5]), "+f"(d[6]), "+f"(d[7]), "+f"(d[8]), "+f"(d[9]), "+f"(d[10]), "+f"(d[11]), "+f"(d[12]), "+f"(d[13]), "+f"(d[14]), "+f"(d[15]), "+f"(d[16]), "+f"(d[17]), "+f"(d[18]), "+f"(d[19]), "+f"(d[20]), "+f"(d[21]), "+f"(d[22]), "+f"(d[23]), "+f"(d[24]), "+f"(d[25]), "+f"(d[26]), "+f"(d[27]), "+f"(d[28]), "+f"(d[29]), "+f"(d[30]), "+f"(d[31])
    : "r"(a0), "r"(a1), "r"(a2), "r"(a3), "l"(descB), "n"(SCALE_D));
}
template <int SCALE_D>
__device__ __forceinline__ void wgmma_rs_n24_tb(float (&d)[12], uint32_t a0, uint32_t a1, uint32_t a2, uint32_t a3, uint64_t descB) {
  asm volatile("wgmma.mma_async.sync.aligned.m64n24k16.f32.bf16.bf16 {%0, %1, %2, %3, %4, %5, %6, %7, %8, %9, %10, %11}, {%12, %13, %14, %15}, %16, %17, 1, 1, 1;\n"
    : "+f"(d[0]), "+f"(d[1]), "+f"(d[2]), "+f"(d[3]), "+f"(d[4]), "+f"(d[5]), "+f"(d[6]), "+f"(d[7]), "+f"(d[8]), "+f"(d[9]), "+f"(d[10]), "+f"(d[11])
    : "r"(a0), "r"(a1), "r"(a2), "r"(a3), "l"(descB), "n"(SCALE_D));
}

constexpr uint32_t DHI_SW128_K = (1024 >> 4) | (1u << 30);
constexpr uint32_t DHI_SW64_MN = (512 >> 4) | (2u << 30);
constexpr uint32_t DHI_SW32_MN = (256 >> 4) | (3u << 30);

template <int NC>
__device__ __forceinline__ void store_tile_bf16(const float (&acc)[NC / 2], float scale, uint32_t stage, uint8_t* stage_ptr,
                                                __nv_bfloat16* gdst, int gpitch, int lane) {
  constexpr int PITCH = NC * 2 + 16;
  const uint32_t waddr = stage + ((lane & 7) + ((lane >> 3) & 1) * 8) * PITCH + (lane >> 4) * 16;
#pragma unroll
  for (int j = 0; j < NC / 16; j++) {
    stsm4(waddr + j * 32, pack_bf16(acc[8 * j] * scale, acc[8 * j + 1] * scale), pack_bf16(acc[8 * j + 2] * scale, acc[8 * j + 3] * scale),
          pack_bf16(acc[8 * j + 4] * scale, acc[8 * j + 5] * scale), pack_bf16(acc[8 * j + 6] * scale, acc[8 * j + 7] * scale));
  }
  __syncwarp();
  constexpr int CPR = NC / 8;
#pragma unroll
  for (int i = 0; i < CPR / 2; i++) {
    const int c = i * 32 + lane, r = c / CPR, cc = c % CPR;
    const uint4 v = *reinterpret_cast<const uint4*>(stage_ptr + r * PITCH + cc * 16);
    *reinterpret_cast<uint4*>(gdst + (size_t)r * gpitch + cc * 8) = v;
  }
}

__device__ __forceinline__ void signal_done(unsigned int* flag, int wg, int tid) {
  asm volatile("bar.sync %0, 128;" :: "r"(wg + 1) : "memory");
  if ((tid & 127) == 0) asm volatile("red.release.gpu.global.add.u32 [%0], 1;" :: "l"(flag) : "memory");
}
__device__ __forceinline__ void wait_flags8(const unsigned int* f, unsigned int target) {
  for (int spin = 0; spin < (1 << 26); spin++) {
    unsigned int a, b, c, d, e, g, h, i;
    asm volatile("ld.volatile.global.v4.u32 {%0, %1, %2, %3}, [%4];" : "=r"(a), "=r"(b), "=r"(c), "=r"(d) : "l"(f) : "memory");
    asm volatile("ld.volatile.global.v4.u32 {%0, %1, %2, %3}, [%4];" : "=r"(e), "=r"(g), "=r"(h), "=r"(i) : "l"(f + 4) : "memory");
    if (min(min(min(a, b), min(c, d)), min(min(e, g), min(h, i))) >= target) break;
    __nanosleep(64);
  }
  asm volatile("fence.acq_rel.gpu;" ::: "memory");
  asm volatile("fence.proxy.async;" ::: "memory");
}
__device__ __forceinline__ void wait_flags(const unsigned int* f, int n4, unsigned int target) {
  for (int spin = 0; spin < (1 << 26); spin++) {
    unsigned int m = 0xffffffffu;
    for (int i = 0; i < n4; i++) {
      unsigned int a, b, c, d;
      asm volatile("ld.volatile.global.v4.u32 {%0, %1, %2, %3}, [%4];" : "=r"(a), "=r"(b), "=r"(c), "=r"(d) : "l"(f + 4 * i) : "memory");
      m = min(m, min(min(a, b), min(c, d)));
    }
    if (m >= target) break;
    __nanosleep(100);
  }
  asm volatile("fence.acq_rel.gpu;" ::: "memory");
}

constexpr int K1_STAGES = 4;
constexpr int K1_A_BYTES = 256 * 128;
constexpr int K1_B_BYTES = 64 * 160 * 2;
constexpr int K1_STAGE = K1_A_BYTES + K1_B_BYTES;
constexpr int K1_SMEM = 5 * K1_A_BYTES + 61440 + 1024;
constexpr int KV_STAGES = 5;
constexpr int KVW_OFF = KV_STAGES * K1_A_BYTES;

__global__ void __launch_bounds__(512, 1)
proj_kernel(const __grid_constant__ CUtensorMap tmX, const __grid_constant__ CUtensorMap tmWq, const __grid_constant__ CUtensorMap tmWqkv,
            const __nv_bfloat16* __restrict__ wk, const __nv_bfloat16* __restrict__ wv, const __nv_bfloat16* __restrict__ gate_w) {
  extern __shared__ uint8_t smem_raw[];
  __shared__ __align__(8) uint64_t bar_full[KV_STAGES], bar_empty[KV_STAGES];
  uint8_t* smem = reinterpret_cast<uint8_t*>((reinterpret_cast<uintptr_t>(smem_raw) + 1023) & ~(uintptr_t)1023);
  const uint32_t sbase = smem_u32(smem);
  const uint32_t dbase = sbase & 0x3FFFFu;
  const int tid = threadIdx.x, warp = tid >> 5, lane = tid & 31;
  const bool is_kv = blockIdx.x >= 128;
  PROF(0, 0);
  if (tid == 0) {
    for (int i = 0; i < KV_STAGES; i++) { mbar_init(smem_u32(&bar_full[i]), 1); mbar_init(smem_u32(&bar_empty[i]), 16); }
    fence_mbar_init();
    if (!is_kv) { g_done[blockIdx.x] = 0u; g_doneL[blockIdx.x] = 0u; g_doneP[blockIdx.x] = 0u; }
    asm volatile("fence.acq_rel.gpu;" ::: "memory");
    pdl_launch();
  }
  __syncthreads();

  if (!is_kv) {
    const int mb = blockIdx.x >> 4, nb = blockIdx.x & 15;
    const CUtensorMap* tw = nb < 4 ? &tmWq : &tmWqkv;
    const int j0 = (nb < 4 ? nb : nb - 4) * 5;
    auto load = [&](int kt) {
      const int s = kt % K1_STAGES;
      const uint32_t fb = smem_u32(&bar_full[s]);
      mbar_expect_tx(fb, K1_STAGE);
      tma_2d(sbase + s * K1_STAGE, &tmX, kt * 64, mb * 256, fb);
      tma_3d(sbase + s * K1_STAGE + K1_A_BYTES, tw, 0, kt * 64, j0, fb);
    };
    if (tid == 0) for (int kt = 0; kt < K1_STAGES; kt++) load(kt);
    {
      const int wg = warp >> 2;
      float acc[80];
#pragma unroll
      for (int i = 0; i < 80; i++) acc[i] = 0.f;
      for (int kt = 0; kt < 10; kt++) {
        const int s = kt % K1_STAGES;
        mbar_wait(smem_u32(&bar_full[s]), (kt / K1_STAGES) & 1);
        const uint32_t alo = ((dbase + s * K1_STAGE + wg * 8192) >> 4) | (1u << 16);
        const uint32_t blo = ((dbase + s * K1_STAGE + K1_A_BYTES) >> 4) | ((4096u >> 4) << 16);
        fence_regs(acc);
        wg_fence();
#pragma unroll
        for (int k = 0; k < 4; k++) wgmma_ss_n160_tb(acc, mkd(alo + k * 2, DHI_SW128_K), mkd(blo + k * 64, DHI_SW64_MN));
        wg_commit();
        if (kt > 0 && kt - 1 + K1_STAGES < 10) {
          wg_wait<1>();
          const uint32_t eb = smem_u32(&bar_empty[(kt - 1) % K1_STAGES]);
          if (lane == 0) mbar_arrive(eb);
          if (tid == 0) { mbar_wait(eb, ((kt - 1) / K1_STAGES) & 1); load(kt - 1 + K1_STAGES); }
          __syncwarp();
        }
      }
      wg_wait<0>();
      fence_regs(acc);
      PROF(0, 1);
      asm volatile("bar.sync %0, 128;" :: "r"(wg + 1) : "memory");
      const int w4 = warp & 3;
      const uint32_t off = w4 * K1_STAGE + wg * 8192;
      const int row0 = mb * 256 + wg * 64 + w4 * 16;
      if (nb < 4) {
        store_tile_bf16<160>(acc, 0.22360679774997896f * 1.4426950408889634f, sbase + off, smem + off,
                             g_q + (size_t)row0 * D_MODEL + nb * 160, D_MODEL, lane);
      } else {
        store_tile_bf16<160>(acc, 1.0f, sbase + off, smem + off, g_qkv + (size_t)row0 * (3 * D_MODEL) + (nb - 4) * 160, 3 * D_MODEL, lane);
      }
      signal_done(&g_doneP[blockIdx.x], wg, tid);
    }
  } else {
    const int cb = blockIdx.x - 128;
    auto load = [&](int it) {
      const int s = it % KV_STAGES;
      const uint32_t fb = smem_u32(&bar_full[s]);
      mbar_expect_tx(fb, K1_A_BYTES);
      tma_2d(sbase + s * K1_A_BYTES, &tmX, (it % 10) * 64, cb * 512 + (it / 10) * 256, fb);
    };
    if (tid == 0) for (int it = 0; it < KV_STAGES; it++) load(it);
    {
      if (tid < 320) {
        uint2 a[2][5], b[2][5]; uint32_t gw[2];
#pragma unroll
        for (int r = 0; r < 2; r++) {
          const int k = tid + r * 320;
          const uint2* pk = reinterpret_cast<const uint2*>(wk + k * 20);
          const uint2* pv = reinterpret_cast<const uint2*>(wv + k * 20);
#pragma unroll
          for (int i = 0; i < 5; i++) { a[r][i] = __ldg(pk + i); b[r][i] = __ldg(pv + i); }
          gw[r] = (uint32_t)__bfloat16_as_ushort(gate_w[k]);
        }
#pragma unroll
        for (int r = 0; r < 2; r++) {
          uint4* dst = reinterpret_cast<uint4*>(smem + KVW_OFF + (tid + r * 320) * 16);
          dst[0] = make_uint4(a[r][0].x, a[r][0].y, a[r][1].x, a[r][1].y);
          dst[640] = make_uint4(a[r][2].x, a[r][2].y, a[r][3].x, a[r][3].y);
          dst[1280] = make_uint4(a[r][4].x, a[r][4].y, 0u, 0u);
          dst[1920] = make_uint4(b[r][0].x, b[r][0].y, b[r][1].x, b[r][1].y);
          dst[2560] = make_uint4(b[r][2].x, b[r][2].y, b[r][3].x, b[r][3].y);
          dst[3200] = make_uint4(b[r][4].x, b[r][4].y, gw[r], 0u);
        }
      }
      fence_proxy_async();
      asm volatile("bar.sync 1, 512;" ::: "memory");
      PROF(0, 1);
      const int wg = warp >> 2, w4 = warp & 3, g = lane >> 2, t = lane & 3;
      for (int pass = 0; pass < 2; pass++) {
        float acc[24];
#pragma unroll
        for (int i = 0; i < 24; i++) acc[i] = 0.f;
        for (int kt = 0; kt < 10; kt++) {
          const int it = pass * 10 + kt, s = it % KV_STAGES;
          mbar_wait(smem_u32(&bar_full[s]), (it / KV_STAGES) & 1);
          const uint32_t alo = ((dbase + s * K1_A_BYTES + wg * 8192) >> 4) | (1u << 16);
          const uint32_t blo = ((dbase + KVW_OFF + kt * 1024) >> 4) | ((128u >> 4) << 16);
          fence_regs(acc);
          wg_fence();
#pragma unroll
          for (int k = 0; k < 4; k++) wgmma_ss_n48_tb(acc, mkd(alo + k * 2, DHI_SW128_K), mkd(blo + k * 16, 10240u >> 4));
          wg_commit();
          wg_wait<0>();
          if (it + KV_STAGES < 20) {
            const uint32_t eb = smem_u32(&bar_empty[s]);
            if (lane == 0) mbar_arrive(eb);
            if (tid == 0) { mbar_wait(eb, (it / KV_STAGES) & 1); load(it + KV_STAGES); }
            __syncwarp();
          }
        }
        fence_regs(acc);
        float kmax2 = 0.f, vmax = 0.f;
#pragma unroll
        for (int h = 0; h < 2; h++) {
          const int key = cb * 512 + pass * 256 + wg * 64 + w4 * 16 + g + h * 8;
          const int grp = key >> 7, kk = key & 127;
          const bool poly = (TMASK >> (kk >> 3)) & 1;
          uint8_t* gp = g_kvimg + grp * GRP_BYTES;
          const uint32_t k0 = pack_bf16(acc[2 * h], acc[2 * h + 1]);
          const uint32_t k1 = pack_bf16(acc[4 + 2 * h], acc[5 + 2 * h]);
          uint32_t k2 = pack_bf16(acc[8 + 2 * h], acc[9 + 2 * h]);
          float n2 = bf_lo(k0) * bf_lo(k0) + bf_hi(k0) * bf_hi(k0) + bf_lo(k1) * bf_lo(k1) + bf_hi(k1) * bf_hi(k1);
          if (t < 2) {
            n2 += bf_lo(k2) * bf_lo(k2) + bf_hi(k2) * bf_hi(k2);
            k2 = pack_bf16(bf_lo(k2) * 0.5f, bf_hi(k2) * 0.5f);
          } else if (t == 2) k2 = poly ? pack_bf16(24.f, 2.5f) : pack_bf16(0.5f, 0.f);
          else k2 = poly ? pack_bf16(0.5f, 0.f) : 0u;
          *reinterpret_cast<uint32_t*>(gp + kk * 16 + t * 4) = k0;
          *reinterpret_cast<uint32_t*>(gp + PLANE + kk * 16 + t * 4) = k1;
          *reinterpret_cast<uint32_t*>(gp + 2 * PLANE + kk * 16 + t * 4) = k2;
          n2 += __shfl_xor_sync(0xffffffffu, n2, 1);
          n2 += __shfl_xor_sync(0xffffffffu, n2, 2);
          kmax2 = (n2 > kmax2 || n2 != n2) ? n2 : kmax2;
          uint32_t v0 = pack_bf16(acc[12 + 2 * h], acc[13 + 2 * h]);
          uint32_t v1 = pack_bf16(acc[16 + 2 * h], acc[17 + 2 * h]);
          uint32_t v2 = pack_bf16(acc[20 + 2 * h], acc[21 + 2 * h]);
          float vm = fmaxf(fmaxf(fabsf(bf_lo(v0)), fabsf(bf_hi(v0))), fmaxf(fabsf(bf_lo(v1)), fabsf(bf_hi(v1))));
          if (t < 2) vm = fmaxf(vm, fmaxf(fabsf(bf_lo(v2)), fabsf(bf_hi(v2))));
          else if (t == 2) {
            const float z = acc[20 + 2 * h];
            g_gate[key] = 1.f / (1.f + __expf(-z));
            v2 = 0x00003F80u;
          } else v2 = 0u;
          vmax = fmaxf(vmax, vm);
          if (poly) { v0 ^= 0x80008000u; v1 ^= 0x80008000u; v2 ^= 0x80008000u; }
          uint8_t* vp = gp + 3 * PLANE + (kk >> 3) * 384 + (kk & 7) * 16 + t * 4;
          *reinterpret_cast<uint32_t*>(vp) = v0;
          *reinterpret_cast<uint32_t*>(vp + 128) = v1;
          *reinterpret_cast<uint32_t*>(vp + 256) = v2;
        }
#pragma unroll
        for (int o = 1; o < 32; o <<= 1) {
          const float a = __shfl_xor_sync(0xffffffffu, kmax2, o);
          kmax2 = (a > kmax2 || a != a) ? a : kmax2;
          vmax = fmaxf(vmax, __shfl_xor_sync(0xffffffffu, vmax, o));
        }
        if (lane == 0) { g_kmax2[cb * 32 + pass * 16 + warp] = kmax2; g_vmax[cb * 32 + pass * 16 + warp] = vmax; }
      }
    }
  }
  PROF(0, 3);
}

__device__ __forceinline__ uint32_t ex2_pair_poly(float u0, float u1, uint32_t one2) {
  const uint32_t W = __byte_perm(__float_as_uint(u0), __float_as_uint(u1), 0x6521);
  uint32_t v; asm("lop3.b32 %0, %1, 0x007F007F, %2, 0xEA;" : "=r"(v) : "r"(W), "r"(one2));
  uint32_t L, p;
  asm("fma.rn.bf16x2 %0, %1, %2, %3;" : "=r"(L) : "r"(v), "r"(0x1f961f96u), "r"(0x9fe39fe3u));
  asm("fma.rn.bf16x2 %0, %1, %1, %2;" : "=r"(p) : "r"(L), "r"(0x00f500f5u));
  return W + p;
}
template <int JOFF>
__device__ __forceinline__ void softmax_fast(const float (&S)[32], uint32_t (&P)[16], uint32_t one2) {
#pragma unroll
  for (int i = 0; i < 16; i++) {
    if ((TMASK >> (JOFF + i / 2)) & 1) P[i] = ex2_pair_poly(S[2 * i], S[2 * i + 1], one2);
    else P[i] = pack_bf16(ex2(S[2 * i]), ex2(S[2 * i + 1]));
  }
}
template <int JOFF>
__device__ __forceinline__ void softmax_slow(const float (&S)[32], uint32_t (&P)[16], float (&O)[12], float& m0, float& m1) {
  float a0 = m0, a1 = m1;
#pragma unroll
  for (int j = 0; j < 8; j++) {
    a0 = fmaxf(a0, fmaxf(S[4 * j], S[4 * j + 1]));
    a1 = fmaxf(a1, fmaxf(S[4 * j + 2], S[4 * j + 3]));
  }
  a0 = fmaxf(a0, __shfl_xor_sync(0xffffffffu, a0, 1)); a0 = fmaxf(a0, __shfl_xor_sync(0xffffffffu, a0, 2));
  a1 = fmaxf(a1, __shfl_xor_sync(0xffffffffu, a1, 1)); a1 = fmaxf(a1, __shfl_xor_sync(0xffffffffu, a1, 2));
  const float c0 = ex2(m0 - a0), c1 = ex2(m1 - a1);
  m0 = a0; m1 = a1;
#pragma unroll
  for (int j = 0; j < 3; j++) { O[4 * j] *= c0; O[4 * j + 1] *= c0; O[4 * j + 2] *= c1; O[4 * j + 3] *= c1; }
#pragma unroll
  for (int i = 0; i < 16; i++) {
    const float m = (i & 1) ? a1 : a0;
    const uint32_t p = pack_bf16(ex2(S[2 * i] - m), ex2(S[2 * i + 1] - m));
    P[i] = ((TMASK >> (JOFF + i / 2)) & 1) ? (p ^ 0x80008000u) : p;
  }
}
constexpr uint32_t DHI_KV = 128 >> 4;
__device__ __forceinline__ void issue_qk(float (&S)[32], const uint32_t (&q)[8], uint32_t base) {
  wgmma_rs_n64<0>(S, q[0], q[1], q[2], q[3], mkd(base + ((PLANE >> 4) << 16), DHI_KV));
  wgmma_rs_n64<1>(S, q[4], q[5], q[6], q[7], mkd(base + (2 * PLANE >> 4), DHI_KV));
}
__device__ __forceinline__ void issue_pv(float (&O)[12], const uint32_t (&P)[16], uint32_t vbase) {
#pragma unroll
  for (int kk = 0; kk < 4; kk++)
    wgmma_rs_n24_tb<1>(O, P[4 * kk], P[4 * kk + 1], P[4 * kk + 2], P[4 * kk + 3], mkd(vbase + kk * (768 >> 4), DHI_KV));
}

constexpr uint32_t VOFF = ((3 * PLANE) >> 4) + ((384u >> 4) << 16);
constexpr int KVR = 4;
constexpr int OFF_WA = KVR * GRP_BYTES;
constexpr int OFF_BR = OFF_WA + 10 * 10240;
constexpr int BR_STAGE = 8192 + 10240, BR_STAGES = 3;
constexpr int OFF_QS = OFF_BR + BR_STAGES * BR_STAGE;
constexpr int OFF_BAR = OFF_QS + 512 * 6 * 4;
constexpr int K2_SMEM = OFF_BAR + 256 + 1024;
constexpr int BAR_KV = 0, BAR_WA = 4, BAR_BR = 5, BAR_TA = 8, BAR_TE = 14, CNT_KV = 18;
constexpr int NSTEP = 2 * NGRP;

__device__ __forceinline__ void kv_load(uint32_t sbase, int step) {
  const uint32_t bar = sbase + OFF_BAR + (BAR_KV + (step & (KVR - 1))) * 8;
  mbar_expect_tx(bar, GRP_BYTES);
  bulk_g2s(sbase + (step & (KVR - 1)) * GRP_BYTES, g_kvimg + (step & (NGRP - 1)) * GRP_BYTES, GRP_BYTES, bar);
}
__device__ __forceinline__ void kv_release(uint32_t sbase, int step, bool elected) {
  if (elected && step + KVR < NSTEP) {
    uint32_t old;
    asm volatile("atom.acq_rel.cta.shared::cta.inc.u32 %0, [%1], 3;" : "=r"(old) : "r"(sbase + OFF_BAR + CNT_KV * 8 + (step & (KVR - 1)) * 4) : "memory");
    if (old == 3u) kv_load(sbase, step + KVR);
  }
  __syncwarp();
}
__device__ __forceinline__ void kv_wait(uint32_t sbase, int step) {
  mbar_wait(sbase + OFF_BAR + (BAR_KV + (step & (KVR - 1))) * 8, (step / KVR) & 1);
}

__device__ __forceinline__ uint32_t kv_release_begin(uint32_t sbase, int slot, bool doit) {
  uint32_t old = 0;
  if (doit) asm volatile("atom.acq_rel.cta.shared::cta.inc.u32 %0, [%1], 3;" : "=r"(old) : "r"(sbase + OFF_BAR + CNT_KV * 8 + slot * 4) : "memory");
  return old;
}
__device__ __forceinline__ void attn_tile_fast(const uint32_t (&q)[8], float (&O)[12], uint32_t sbase, int step0, bool elected, uint32_t one2) {
  float S[32]; uint32_t P[16];
#pragma unroll
  for (int i = 0; i < 32; i++) S[i] = 0.f;
  const uint32_t kb0 = (sbase & 0x3FFFFu) >> 4;
  kv_wait(sbase, step0);
  fence_regs(S); fence_regs(O);
  wg_fence();
  issue_qk(S, q, kb0);
  wg_commit();
#pragma unroll 1
  for (int step4 = step0; step4 < step0 + NGRP; step4 += KVR) {
#pragma unroll
    for (int j = 0; j < KVR; j++) {
      const int step = step4 + j;
      const uint32_t kb = kb0 + j * (GRP_BYTES >> 4);
      const uint32_t knext = kb0 + ((j + 1) & (KVR - 1)) * (GRP_BYTES >> 4);
      wg_wait<0>();
      fence_regs(S); fence_regs(P); fence_regs(O);
      const uint32_t old = kv_release_begin(sbase, (j + KVR - 1) & (KVR - 1), elected && step > step0 && step - 1 + KVR < NSTEP);
      softmax_fast<0>(S, P, one2);
      fence_regs(S); fence_regs(P); fence_regs(O);
      wg_fence();
      issue_qk(S, q, kb + 64);
      issue_pv(O, P, kb + VOFF);
      wg_commit();
      if (old == 3u) kv_load(sbase, step - 1 + KVR);
      if (step + 1 < NSTEP) mbar_wait(sbase + OFF_BAR + (BAR_KV + ((j + 1) & (KVR - 1))) * 8, ((step + 1) / KVR) & 1);
      wg_wait<0>();
      fence_regs(S); fence_regs(P); fence_regs(O);
      softmax_fast<8>(S, P, one2);
      fence_regs(S); fence_regs(P); fence_regs(O);
      wg_fence();
      issue_qk(S, q, knext);
      issue_pv(O, P, kb + VOFF + 4 * (768 >> 4));
      wg_commit();
    }
  }
  wg_wait<0>();
  fence_regs(O); fence_regs(S);
  kv_release(sbase, step0 + NGRP - 1, elected);
}
template <int H>
__device__ __forceinline__ void slow_step(const uint32_t (&q)[8], float (&O)[12], uint32_t kb, float& m0, float& m1) {
  float S[32]; uint32_t P[16];
#pragma unroll
  for (int i = 0; i < 32; i++) S[i] = 0.f;
  fence_regs(S);
  wg_fence();
  issue_qk(S, q, kb + 64 * H);
  wg_commit();
  wg_wait<0>();
  fence_regs(S);
  softmax_slow<8 * H>(S, P, O, m0, m1);
  fence_regs(P); fence_regs(O);
  wg_fence();
  issue_pv(O, P, kb + VOFF + H * 4 * (768 >> 4));
  wg_commit();
  wg_wait<0>();
  fence_regs(O); fence_regs(P);
}
__device__ __forceinline__ void attn_tile_slow(const uint32_t (&q)[8], float (&O)[12], uint32_t sbase, int step0, bool elected) {
  float m0 = -INFINITY, m1 = -INFINITY;
#pragma unroll 1
  for (int grp = 0; grp < NGRP; grp++) {
    kv_wait(sbase, step0 + grp);
    const uint32_t kb = ((sbase & 0x3FFFFu) >> 4) + (grp & (KVR - 1)) * (GRP_BYTES >> 4);
    slow_step<0>(q, O, kb, m0, m1);
    slow_step<1>(q, O, kb, m0, m1);
    kv_release(sbase, step0 + grp, elected);
  }
}

__device__ __forceinline__ void local_attn_pair(int token, int lane, bool first) {
  const __nv_bfloat16* base = g_qkv + (size_t)token * (3 * D_MODEL) + lane * DH;
  float f[20];
  {
    const uint2* p = reinterpret_cast<const uint2*>(base);
#pragma unroll
    for (int i = 0; i < 5; i++) { const uint2 v = p[i]; f[4 * i] = bf_lo(v.x); f[4 * i + 1] = bf_hi(v.x); f[4 * i + 2] = bf_lo(v.y); f[4 * i + 3] = bf_hi(v.y); }
  }
  float sc[8];
  float mx = -INFINITY;
#pragma unroll
  for (int w = 0; w < 8; w++) {
    const bool ok = token - 2 * w >= 0;
    const uint2* p = reinterpret_cast<const uint2*>(base + D_MODEL - (ok ? 2 * w : 0) * (3 * D_MODEL));
    float s = 0.f;
#pragma unroll
    for (int i = 0; i < 5; i++) {
      const uint2 v = p[i];
      s = fmaf(f[4 * i], bf_lo(v.x), s); s = fmaf(f[4 * i + 1], bf_hi(v.x), s);
      s = fmaf(f[4 * i + 2], bf_lo(v.y), s); s = fmaf(f[4 * i + 3], bf_hi(v.y), s);
    }
    s *= 0.22360679774997896f * 1.4426950408889634f;
    sc[w] = ok ? s : -1e9f * 1.4426950408889634f;
    mx = fmaxf(mx, sc[w]);
  }
  float l = 0.f;
#pragma unroll
  for (int w = 0; w < 8; w++) { sc[w] = ex2(sc[w] - mx); l += sc[w]; }
#pragma unroll
  for (int i = 0; i < 20; i++) f[i] = 0.f;
#pragma unroll
  for (int w = 0; w < 8; w++) {
    const bool ok = token - 2 * w >= 0;
    const uint2* p = reinterpret_cast<const uint2*>(base + 2 * D_MODEL - (ok ? 2 * w : token) * (3 * D_MODEL));
#pragma unroll
    for (int i = 0; i < 5; i++) {
      const uint2 v = p[i];
      f[4 * i] = fmaf(sc[w], bf_lo(v.x), f[4 * i]); f[4 * i + 1] = fmaf(sc[w], bf_hi(v.x), f[4 * i + 1]);
      f[4 * i + 2] = fmaf(sc[w], bf_lo(v.y), f[4 * i + 2]); f[4 * i + 3] = fmaf(sc[w], bf_hi(v.y), f[4 * i + 3]);
    }
  }
  if (first) pdl_wait();
  const float r = (1.f - g_gate[token]) / l;
  uint2* dst = reinterpret_cast<uint2*>(g_a2 + (size_t)token * (2 * D_MODEL) + D_MODEL + lane * DH);
#pragma unroll
  for (int i = 0; i < 5; i++) dst[i] = make_uint2(pack_bf16(f[4 * i] * r, f[4 * i + 1] * r), pack_bf16(f[4 * i + 2] * r, f[4 * i + 3] * r));
}

__device__ __forceinline__ uint32_t ta_slot(int i) { return i < 3 ? i * 16384 : OFF_BR + (i - 3) * 16384; }

__global__ void __launch_bounds__(640, 1)
attn_kernel(const __grid_constant__ CUtensorMap tmA2, const __grid_constant__ CUtensorMap tmWoA, const __grid_constant__ CUtensorMap tmWoB,
            __nv_bfloat16* __restrict__ out, uint32_t one2) {
  extern __shared__ uint8_t smem_raw[];
  uint8_t* smem = reinterpret_cast<uint8_t*>((reinterpret_cast<uintptr_t>(smem_raw) + 1023) & ~(uintptr_t)1023);
  const uint32_t sbase = smem_u32(smem);
  const uint32_t dbase = sbase & 0x3FFFFu;
  const uint32_t bars = sbase + OFF_BAR;
  const int tid = threadIdx.x, wg = tid >> 7, warp = (tid >> 5) & 3, lane = tid & 31, g = lane >> 2, t = lane & 3;
  const int mb = blockIdx.x >> 3, nb = blockIdx.x & 7;
  if (tid == 0) {
    for (int i = 0; i < BAR_TE; i++) mbar_init(bars + i * 8, 1);
    for (int i = BAR_TE; i < BAR_TE + 4; i++) mbar_init(bars + i * 8, 8);
    for (int i = 0; i < 4; i++) *reinterpret_cast<uint32_t*>(smem + OFF_BAR + CNT_KV * 8 + i * 4) = 0u;
    fence_mbar_init();
  }
  __syncthreads();
  if (wg == 4) {
    if (tid == 512) {
      mbar_expect_tx(bars + BAR_WA * 8, 10 * 10240);
      for (int kt = 0; kt < 10; kt++) tma_3d(sbase + OFF_WA + kt * 10240, &tmWoA, 0, kt * 64, nb * 5, bars + BAR_WA * 8);
    }
    if (tid == 512) {
      const int rb = blockIdx.x >> 4;
      if ((blockIdx.x & 15) == 0 && rb > 0) wait_flags(&g_doneP[rb * 16 - 8], 6, 4u);
      else wait_flags(&g_doneP[rb * 16], 4, 4u);
    }
    asm volatile("bar.sync 7, 640;" ::: "memory");
#pragma unroll 1
    for (int i = 0; i < 4; i++) local_attn_pair(blockIdx.x * 16 + i * 4 + warp, lane, i == 0);
    if (tid == 512) PROF2(0, 2);
    signal_done(&g_doneL[blockIdx.x], wg, tid);
    auto br_load = [&](int it, int st) {
      const uint32_t fb = bars + (BAR_BR + st) * 8;
      const uint32_t dst = sbase + OFF_BR + st * BR_STAGE;
      const int kc = (it >= 10 ? it - 10 : it) * 64;
      mbar_expect_tx(fb, BR_STAGE);
      tma_2d(dst, &tmA2, D_MODEL + kc, (blockIdx.x >> 3) * 128 + (it >= 10 ? 64 : 0), fb);
      tma_3d(dst + 8192, &tmWoB, 0, kc, (blockIdx.x & 7) * 5, fb);
    };
    if (tid == 512) {
      wait_flags8(&g_doneL[mb * 8], 1u);
      for (int it = 0; it < BR_STAGES; it++) br_load(it, it);
    }
    __syncwarp();
    {
      int st = 0, ph = 0;
      float acc[40];
#pragma unroll 1
      for (int it = 0; it < 20; it++) {
        if (it == 0 || it == 10) {
#pragma unroll
          for (int i = 0; i < 40; i++) acc[i] = 0.f;
        }
        mbar_wait(bars + (BAR_BR + st) * 8, ph);
        const uint32_t alo = ((dbase + OFF_BR + st * BR_STAGE) >> 4);
        fence_regs(acc);
        wg_fence();
#pragma unroll
        for (int k = 0; k < 4; k++)
          wgmma_ss_n80_tb(acc, mkd(alo + (k * 2 + (1u << 16)), DHI_SW128_K), mkd(alo + (512 + k * 32 + ((2048u >> 4) << 16)), DHI_SW32_MN));
        wg_commit();
        wg_wait<0>();
        fence_regs(acc);
        asm volatile("bar.sync 5, 128;" ::: "memory");
        if (threadIdx.x == 512 && it + BR_STAGES < 20) br_load(it + BR_STAGES, st);
        __syncwarp();
        if (it == 9 || it == 19) {
          float* pp = g_part + (size_t)(blockIdx.x * 2 + (it == 19)) * (40 * 128) + (threadIdx.x & 127);
#pragma unroll
          for (int i = 0; i < 40; i++) pp[i * 128] = acc[i];
        }
        if (++st == BR_STAGES) { st = 0; ph ^= 1; }
      }
    }
    if (tid == 512) PROF2(1, 0);
    asm volatile("bar.arrive 6, 384;" ::: "memory");
    if (tid == 512) {
      wait_flags8(&g_done[mb * 8], 4u);
      PROF2(2, 0);
      for (int kt = 0; kt < 10; kt++) {
        const int sl = kt % 6;
        if (kt >= 6) mbar_wait(bars + (BAR_TE + kt - 6) * 8, 0);
        const uint32_t fb = bars + (BAR_TA + sl) * 8;
        mbar_expect_tx(fb, 16384);
        tma_2d(sbase + ta_slot(sl), &tmA2, kt * 64, mb * 128, fb);
        tma_2d(sbase + ta_slot(sl) + 8192, &tmA2, kt * 64, mb * 128 + 64, fb);
      }
    }
  } else {
    const bool elected = (tid & 127) == 0;
    asm volatile("bar.sync 7, 640;" ::: "memory");
    uint32_t q[8];
    uint32_t* qstash = reinterpret_cast<uint32_t*>(smem + OFF_QS) + tid;
    const int rowA = (blockIdx.x * 8 + wg) * 64 + warp * 16 + g;
    {
      const uint32_t* r0 = reinterpret_cast<const uint32_t*>(g_q + (size_t)rowA * DH);
      const uint32_t* r1 = r0 + 8 * (DH / 2);
      const uint32_t* s0 = r0 + 256 * (DH / 2);
      const uint32_t* s1 = s0 + 8 * (DH / 2);
      q[0] = r0[t]; q[1] = r1[t]; q[2] = r0[t + 4]; q[3] = r1[t + 4];
      q[4] = t < 2 ? r0[8 + t] : 0u;
      q[5] = t < 2 ? r1[8 + t] : 0u;
      qstash[0] = s0[t]; qstash[512] = s1[t]; qstash[1024] = s0[t + 4]; qstash[1536] = s1[t + 4];
      qstash[2048] = t < 2 ? s0[8 + t] : 0u;
      qstash[2560] = t < 2 ? s1[8 + t] : 0u;
    }
    pdl_wait();
    PROF(1, 1);
    if (tid == 0) for (int j = 0; j < KVR; j++) kv_load(sbase, j);
    __syncwarp();
    float kmax2 = 0.f, vmax = 0.f;
#pragma unroll
    for (int i = 0; i < 4; i++) {
      const float a = g_kmax2[lane + 32 * i];
      kmax2 = (a > kmax2 || a != a) ? a : kmax2;
      vmax = fmaxf(vmax, g_vmax[lane + 32 * i]);
    }
#pragma unroll
    for (int o = 1; o < 32; o <<= 1) {
      const float a = __shfl_xor_sync(0xffffffffu, kmax2, o);
      kmax2 = (a > kmax2 || a != a) ? a : kmax2;
      vmax = fmaxf(vmax, __shfl_xor_sync(0xffffffffu, vmax, o));
    }
    const float qlim = (vmax >= 0.00390625f && vmax <= 256.f) ? 9025.f / kmax2 : -1.f;
    PROF(1, 2);
#pragma unroll 1
    for (int it = 0; it < 2; it++) {
      const int row0 = rowA + it * 256;
      if (it == 1) {
#pragma unroll
        for (int i = 0; i < 6; i++) q[i] = qstash[512 * i];
      }
      float n0 = bf_lo(q[0]) * bf_lo(q[0]) + bf_hi(q[0]) * bf_hi(q[0]) + bf_lo(q[2]) * bf_lo(q[2]) + bf_hi(q[2]) * bf_hi(q[2]) +
                 bf_lo(q[4]) * bf_lo(q[4]) + bf_hi(q[4]) * bf_hi(q[4]);
      float n1 = bf_lo(q[1]) * bf_lo(q[1]) + bf_hi(q[1]) * bf_hi(q[1]) + bf_lo(q[3]) * bf_lo(q[3]) + bf_hi(q[3]) * bf_hi(q[3]) +
                 bf_lo(q[5]) * bf_lo(q[5]) + bf_hi(q[5]) * bf_hi(q[5]);
      n0 += __shfl_xor_sync(0xffffffffu, n0, 1); n0 += __shfl_xor_sync(0xffffffffu, n0, 2);
      n1 += __shfl_xor_sync(0xffffffffu, n1, 1); n1 += __shfl_xor_sync(0xffffffffu, n1, 2);
      const bool safe = (n0 <= qlim) && (n1 <= qlim);
      uint32_t unsafe_any;
      asm volatile("{\n.reg .pred p, r;\nsetp.eq.u32 p, %1, 0;\nbarrier.cta.red.or.pred r, %2, 128, p;\nselp.u32 %0, 1, 0, r;\n}\n"
                   : "=r"(unsafe_any) : "r"((uint32_t)safe), "r"(wg + 1) : "memory");
      float O[12];
#pragma unroll
      for (int i = 0; i < 12; i++) O[i] = 0.f;
      if (!unsafe_any && t >= 2) { q[4] = q[5] = (t == 2) ? 0x3F804100u : 0x00003B80u; }
      q[6] = q[4]; q[7] = q[5];
      fence_regs(q);
      if (!unsafe_any) attn_tile_fast(q, O, sbase, it * NGRP, elected, one2);
      else attn_tile_slow(q, O, sbase, it * NGRP, elected);
      const float l0 = __shfl_sync(0xffffffffu, O[8], (lane & ~3) | 2);
      const float l1 = __shfl_sync(0xffffffffu, O[10], (lane & ~3) | 2);
      const int tok = row0 >> 5;
      const float gt = g_gate[tok];
      const float i0 = gt / l0, i1 = gt / l1;
      uint32_t* o0 = reinterpret_cast<uint32_t*>(g_a2 + (size_t)tok * (2 * D_MODEL) + (row0 & 31) * DH);
      uint32_t* o1 = o0 + 8 * (DH / 2);
      o0[t] = pack_bf16(O[0] * i0, O[1] * i0); o1[t] = pack_bf16(O[2] * i1, O[3] * i1);
      o0[t + 4] = pack_bf16(O[4] * i0, O[5] * i0); o1[t + 4] = pack_bf16(O[6] * i1, O[7] * i1);
      if (t < 2) { o0[t + 8] = pack_bf16(O[8] * i0, O[9] * i0); o1[t + 8] = pack_bf16(O[10] * i1, O[11] * i1); }
    }
    signal_done(&g_done[blockIdx.x], wg, tid);
    PROF(1, 3);
    if (wg < 2) {
      float acc[40];
      asm volatile("bar.sync 6, 384;" ::: "memory");
      {
        const float* pp = g_part + (size_t)(blockIdx.x * 2 + wg) * (40 * 128) + (tid & 127);
#pragma unroll
        for (int i = 0; i < 40; i++) acc[i] = pp[i * 128];
      }
      mbar_wait(bars + BAR_WA * 8, 0);
#pragma unroll 1
      for (int kt = 0; kt < 10; kt++) {
        const int sl = kt % 6;
        mbar_wait(bars + (BAR_TA + sl) * 8, kt / 6);
        if (kt == 0) PROF(2, 1);
        const uint32_t alo = ((dbase + ta_slot(sl) + wg * 8192) >> 4) | (1u << 16);
        const uint32_t blo = ((dbase + OFF_WA + kt * 10240) >> 4) | ((2048u >> 4) << 16);
        fence_regs(acc);
        wg_fence();
#pragma unroll
        for (int k = 0; k < 4; k++) wgmma_ss_n80_tb(acc, mkd(alo + k * 2, DHI_SW128_K), mkd(blo + k * 32, DHI_SW32_MN));
        wg_commit();
        if (kt < 4) {
          wg_wait<0>();
          if (lane == 0) mbar_arrive(bars + (BAR_TE + kt) * 8);
        }
      }
      wg_wait<0>();
      fence_regs(acc);
      PROF(2, 2);
      asm volatile("bar.sync %0, 128;" :: "r"(wg + 1) : "memory");
      const uint32_t so = ta_slot(warp) + wg * 8192;
      const int row0 = mb * 128 + wg * 64 + warp * 16;
      store_tile_bf16<80>(acc, 1.0f, sbase + so, smem + so, out + (size_t)row0 * D_MODEL + nb * 80, D_MODEL, lane);
      PROF(2, 3);
    }
  }
}

typedef CUresult (*EncodeFn)(CUtensorMap*, CUtensorMapDataType, cuuint32_t, void*, const cuuint64_t*, const cuuint64_t*,
                             const cuuint32_t*, const cuuint32_t*, CUtensorMapInterleave, CUtensorMapSwizzle,
                             CUtensorMapL2promotion, CUtensorMapFloatOOBfill);

void make_map(EncodeFn fn, CUtensorMap* tm, const void* ptr, int rank, const cuuint64_t* dims, const cuuint64_t* strides,
              const cuuint32_t* box, CUtensorMapSwizzle sw) {
  const cuuint32_t es[3] = {1, 1, 1};
  fn(tm, CU_TENSOR_MAP_DATA_TYPE_BFLOAT16, rank, const_cast<void*>(ptr), dims, strides, box, es, CU_TENSOR_MAP_INTERLEAVE_NONE, sw,
     CU_TENSOR_MAP_L2_PROMOTION_L2_256B, CU_TENSOR_MAP_FLOAT_OOB_FILL_NONE);
}
void map_a(EncodeFn fn, CUtensorMap* tm, const void* p, int rows, int cols, int box_rows) {
  const cuuint64_t dims[2] = {(cuuint64_t)cols, (cuuint64_t)rows};
  const cuuint64_t str[1] = {(cuuint64_t)cols * 2};
  const cuuint32_t box[2] = {64, (cuuint32_t)box_rows};
  make_map(fn, tm, p, 2, dims, str, box, CU_TENSOR_MAP_SWIZZLE_128B);
}
void map_w(EncodeFn fn, CUtensorMap* tm, const void* p, int K, int N, int atom, CUtensorMapSwizzle sw) {
  const cuuint64_t dims[3] = {(cuuint64_t)atom, (cuuint64_t)K, (cuuint64_t)(N / atom)};
  const cuuint64_t str[2] = {(cuuint64_t)N * 2, (cuuint64_t)atom * 2};
  const cuuint32_t box[3] = {(cuuint32_t)atom, 64, 5};
  make_map(fn, tm, p, 3, dims, str, box, sw);
}

template <typename... KArgs, typename... Args>
void launch(void (*kern)(KArgs...), int grid, int block, int smem, bool pdl, Args... args) {
  cudaLaunchConfig_t cfg = {};
  cfg.gridDim = dim3(grid); cfg.blockDim = dim3(block); cfg.dynamicSmemBytes = smem; cfg.stream = cudaStreamPerThread;
  cudaLaunchAttribute at[1];
  at[0].id = cudaLaunchAttributeProgrammaticStreamSerialization;
  at[0].val.programmaticStreamSerializationAllowed = 1;
  cfg.attrs = at; cfg.numAttrs = pdl ? 1 : 0;
  cudaLaunchKernelEx(&cfg, kern, KArgs(args)...);
}

}

extern "C" void kernel_launch(void* const* d_in, const int* in_sizes, int n_in, void* d_out, int out_size) {
  (void)in_sizes; (void)n_in; (void)out_size;
  const __nv_bfloat16* x = (const __nv_bfloat16*)d_in[0];
  const __nv_bfloat16* wq = (const __nv_bfloat16*)d_in[1];
  const __nv_bfloat16* wk = (const __nv_bfloat16*)d_in[2];
  const __nv_bfloat16* wv = (const __nv_bfloat16*)d_in[3];
  const __nv_bfloat16* woA = (const __nv_bfloat16*)d_in[4];
  const __nv_bfloat16* wqkv = (const __nv_bfloat16*)d_in[6];
  const __nv_bfloat16* woB = (const __nv_bfloat16*)d_in[7];
  const __nv_bfloat16* gate_w = (const __nv_bfloat16*)d_in[8];

  static EncodeFn enc = nullptr;
  static void* a2_ptr = nullptr;
  if (!enc) {
    void* fp = nullptr;
    cudaDriverEntryPointQueryResult qr;
    cudaGetDriverEntryPoint("cuTensorMapEncodeTiled", &fp, cudaEnableDefault, &qr);
    enc = (EncodeFn)fp;
    cudaGetSymbolAddress(&a2_ptr, g_a2);
    cudaFuncSetAttribute(proj_kernel, cudaFuncAttributeMaxDynamicSharedMemorySize, K1_SMEM);
    cudaFuncSetAttribute(attn_kernel, cudaFuncAttributeMaxDynamicSharedMemorySize, K2_SMEM);
  }
  CUtensorMap tmX, tmWq, tmWqkv, tmA2, tmWoA, tmWoB;
  map_a(enc, &tmX, x, S_LEN, D_MODEL, 256);
  map_w(enc, &tmWq, wq, D_MODEL, D_MODEL, 32, CU_TENSOR_MAP_SWIZZLE_64B);
  map_w(enc, &tmWqkv, wqkv, D_MODEL, 3 * D_MODEL, 32, CU_TENSOR_MAP_SWIZZLE_64B);
  map_a(enc, &tmA2, a2_ptr, S_LEN, 2 * D_MODEL, 64);
  map_w(enc, &tmWoA, woA, D_MODEL, D_MODEL, 16, CU_TENSOR_MAP_SWIZZLE_32B);
  map_w(enc, &tmWoB, woB, D_MODEL, D_MODEL, 16, CU_TENSOR_MAP_SWIZZLE_32B);

  launch(proj_kernel, 132, 512, K1_SMEM, false, tmX, tmWq, tmWqkv, wk, wv, gate_w);
  launch(attn_kernel, 128, 640, K2_SMEM, true, tmA2, tmWoA, tmWoB, (__nv_bfloat16*)d_out, 0x3F803F80u);
}
```

```cpp
#include <cuda_runtime.h>
#include <cuda_bf16.h>
#include <cuda.h>
#include <stdint.h>

namespace {

constexpr int S_LEN = 2048, D_MODEL = 640, DH = 20;

constexpr int GRP = 128;
constexpr int PLANE = GRP * 16;
constexpr int GRP_BYTES = GRP * 16 * 6;
constexpr int NGRP = S_LEN / GRP;
#define TMASKV 0x6DB6u
constexpr uint32_t TMASK = TMASKV;

__device__ __align__(1024) __nv_bfloat16 g_q[S_LEN * D_MODEL];
__device__ __align__(1024) __nv_bfloat16 g_qkv[S_LEN * 3 * D_MODEL];
__device__ __align__(1024) __nv_bfloat16 g_a2[S_LEN * 2 * D_MODEL];
__device__ __align__(1024) uint8_t g_kvimg[NGRP * GRP_BYTES];
__device__ float g_gate[S_LEN];
__device__ float g_kmax2[128];
__device__ float g_vmax[128];
__device__ __align__(32) unsigned int g_doneL[128];
__device__ float g_part[128 * 2 * 40 * 128];
__device__ __align__(32) unsigned int g_done[128];

#define PROF(k, slot)
#define PROF2(k, slot)
__device__ __forceinline__ uint32_t smem_u32(const void* p) { return (uint32_t)__cvta_generic_to_shared(p); }
__device__ __forceinline__ uint64_t mkd(uint32_t lo, uint32_t hi) {
  uint64_t d; asm("mov.b64 %0, {%1, %2};" : "=l"(d) : "r"(lo), "r"(hi)); return d;
}
__device__ __forceinline__ void wg_fence() { asm volatile("wgmma.fence.sync.aligned;" ::: "memory"); }
__device__ __forceinline__ void wg_commit() { asm volatile("wgmma.commit_group.sync.aligned;" ::: "memory"); }
template <int N> __device__ __forceinline__ void wg_wait() { asm volatile("wgmma.wait_group.sync.aligned %0;" :: "n"(N) : "memory"); }
template <int N> __device__ __forceinline__ void fence_regs(float (&d)[N]) {
#pragma unroll
  for (int i = 0; i < N; i++) asm volatile("" : "+f"(d[i]) :: "memory");
}
template <int N> __device__ __forceinline__ void fence_regs(uint32_t (&d)[N]) {
#pragma unroll
  for (int i = 0; i < N; i++) asm volatile("" : "+r"(d[i]) :: "memory");
}
__device__ __forceinline__ void mbar_init(uint32_t bar, uint32_t cnt) { asm volatile("mbarrier.init.shared::cta.b64 [%0], %1;" :: "r"(bar), "r"(cnt)); }
__device__ __forceinline__ void mbar_expect_tx(uint32_t bar, uint32_t bytes) {
  asm volatile("mbarrier.arrive.expect_tx.shared::cta.b64 _, [%0], %1;" :: "r"(bar), "r"(bytes) : "memory");
}
__device__ __forceinline__ void mbar_arrive(uint32_t bar) { asm volatile("mbarrier.arrive.shared::cta.b64 _, [%0];" :: "r"(bar) : "memory"); }
__device__ __forceinline__ void mbar_wait(uint32_t bar, uint32_t parity) {
  asm volatile("{\n.reg .pred p;\nWAIT_%=:\nmbarrier.try_wait.parity.shared::cta.b64 p, [%0], %1;\n@p bra DONE_%=;\nbra WAIT_%=;\nDONE_%=:\n}\n"
               :: "r"(bar), "r"(parity) : "memory");
}
__device__ __forceinline__ void fence_mbar_init() { asm volatile("fence.mbarrier_init.release.cluster;" ::: "memory"); }
__device__ __forceinline__ void fence_proxy_async() { asm volatile("fence.proxy.async.shared::cta;" ::: "memory"); }
__device__ __forceinline__ void bulk_g2s(uint32_t dst, const void* src, uint32_t bytes, uint32_t bar) {
  asm volatile("cp.async.bulk.shared::cluster.global.mbarrier::complete_tx::bytes [%0], [%1], %2, [%3];"
               :: "r"(dst), "l"(src), "r"(bytes), "r"(bar) : "memory");
}
__device__ __forceinline__ void tma_2d(uint32_t dst, const CUtensorMap* tm, int c0, int c1, uint32_t bar) {
  asm volatile("cp.async.bulk.tensor.2d.shared::cluster.global.mbarrier::complete_tx::bytes [%0], [%1, {%3, %4}], [%2];"
               :: "r"(dst), "l"((uint64_t)tm), "r"(bar), "r"(c0), "r"(c1) : "memory");
}
__device__ __forceinline__ void tma_3d(uint32_t dst, const CUtensorMap* tm, int c0, int c1, int c2, uint32_t bar) {
  asm volatile("cp.async.bulk.tensor.3d.shared::cluster.global.mbarrier::complete_tx::bytes [%0], [%1, {%3, %4, %5}], [%2];"
               :: "r"(dst), "l"((uint64_t)tm), "r"(bar), "r"(c0), "r"(c1), "r"(c2) : "memory");
}
__device__ __forceinline__ void pdl_wait() { asm volatile("griddepcontrol.wait;" ::: "memory"); }
__device__ __forceinline__ void pdl_launch() { asm volatile("griddepcontrol.launch_dependents;" ::: "memory"); }
__device__ __forceinline__ float ex2(float x) { float y; asm("ex2.approx.ftz.f32 %0, %1;" : "=f"(y) : "f"(x)); return y; }
__device__ __forceinline__ uint32_t pack_bf16(float lo, float hi) {
  uint32_t r; asm("cvt.rn.bf16x2.f32 %0, %1, %2;" : "=r"(r) : "f"(hi), "f"(lo)); return r;
}
__device__ __forceinline__ float bf_lo(uint32_t x) { return __uint_as_float(x << 16); }
__device__ __forceinline__ float bf_hi(uint32_t x) { return __uint_as_float(x & 0xffff0000u); }
__device__ __forceinline__ void stsm4(uint32_t addr, uint32_t r0, uint32_t r1, uint32_t r2, uint32_t r3) {
  asm volatile("stmatrix.sync.aligned.m8n8.x4.shared.b16 [%0], {%1, %2, %3, %4};" :: "r"(addr), "r"(r0), "r"(r1), "r"(r2), "r"(r3) : "memory");
}

__device__ __forceinline__ void wgmma_ss_n160_tb(float (&d)[80], uint64_t descA, uint64_t descB) {
  asm volatile("wgmma.mma_async.sync.aligned.m64n160k16.f32.bf16.bf16 {%0, %1, %2, %3, %4, %5, %6, %7, %8, %9, %10, %11, %12, %13, %14, %15, %16, %17, %18, %19, %20, %21, %22, %23, %24, %25, %26, %27, %28, %29, %30, %31, %32, %33, %34, %35, %36, %37, %38, %39, %40, %41, %42, %43, %44, %45, %46, %47, %48, %49, %50, %51, %52, %53, %54, %55, %56, %57, %58, %59, %60, %61, %62, %63, %64, %65, %66, %67, %68, %69, %70, %71, %72, %73, %74, %75, %76, %77, %78, %79}, %80, %81, 1, 1, 1, 0, 1;\n"
    : "+f"(d[0]), "+f"(d[1]), "+f"(d[2]), "+f"(d[3]), "+f"(d[4]), "+f"(d[5]), "+f"(d[6]), "+f"(d[7]), "+f"(d[8]), "+f"(d[9]), "+f"(d[10]), "+f"(d[11]), "+f"(d[12]), "+f"(d[13]), "+f"(d[14]), "+f"(d[15]), "+f"(d[16]), "+f"(d[17]), "+f"(d[18]), "+f"(d[19]), "+f"(d[20]), "+f"(d[21]), "+f"(d[22]), "+f"(d[23]), "+f"(d[24]), "+f"(d[25]), "+f"(d[26]), "+f"(d[27]), "+f"(d[28]), "+f"(d[29]), "+f"(d[30]), "+f"(d[31]), "+f"(d[32]), "+f"(d[33]), "+f"(d[34]), "+f"(d[35]), "+f"(d[36]), "+f"(d[37]), "+f"(d[38]), "+f"(d[39]), "+f"(d[40]), "+f"(d[41]), "+f"(d[42]), "+f"(d[43]), "+f"(d[44]), "+f"(d[45]), "+f"(d[46]), "+f"(d[47]), "+f"(d[48]), "+f"(d[49]), "+f"(d[50]), "+f"(d[51]), "+f"(d[52]), "+f"(d[53]), "+f"(d[54]), "+f"(d[55]), "+f"(d[56]), "+f"(d[57]), "+f"(d[58]), "+f"(d[59]), "+f"(d[60]), "+f"(d[61]), "+f"(d[62]), "+f"(d[63]), "+f"(d[64]), "+f"(d[65]), "+f"(d[66]), "+f"(d[67]), "+f"(d[68]), "+f"(d[69]), "+f"(d[70]), "+f"(d[71]), "+f"(d[72]), "+f"(d[73]), "+f"(d[74]), "+f"(d[75]), "+f"(d[76]), "+f"(d[77]), "+f"(d[78]), "+f"(d[79])
    : "l"(descA), "l"(descB));
}
__device__ __forceinline__ void wgmma_ss_n48_tb(float (&d)[24], uint64_t descA, uint64_t descB) {
  asm volatile("wgmma.mma_async.sync.aligned.m64n48k16.f32.bf16.bf16 {%0, %1, %2, %3, %4, %5, %6, %7, %8, %9, %10, %11, %12, %13, %14, %15, %16, %17, %18, %19, %20, %21, %22, %23}, %24, %25, 1, 1, 1, 0, 1;\n"
    : "+f"(d[0]), "+f"(d[1]), "+f"(d[2]), "+f"(d[3]), "+f"(d[4]), "+f"(d[5]), "+f"(d[6]), "+f"(d[7]), "+f"(d[8]), "+f"(d[9]), "+f"(d[10]), "+f"(d[11]), "+f"(d[12]), "+f"(d[13]), "+f"(d[14]), "+f"(d[15]), "+f"(d[16]), "+f"(d[17]), "+f"(d[18]), "+f"(d[19]), "+f"(d[20]), "+f"(d[21]), "+f"(d[22]), "+f"(d[23])
    : "l"(descA), "l"(descB));
}
__device__ __forceinline__ void wgmma_ss_n80_tb(float (&d)[40], uint64_t descA, uint64_t descB) {
  asm volatile("wgmma.mma_async.sync.aligned.m64n80k16.f32.bf16.bf16 {%0, %1, %2, %3, %4, %5, %6, %7, %8, %9, %10, %11, %12, %13, %14, %15, %16, %17, %18, %19, %20, %21, %22, %23, %24, %25, %26, %27, %28, %29, %30, %31, %32, %33, %34, %35, %36, %37, %38, %39}, %40, %41, 1, 1, 1, 0, 1;\n"
    : "+f"(d[0]), "+f"(d[1]), "+f"(d[2]), "+f"(d[3]), "+f"(d[4]), "+f"(d[5]), "+f"(d[6]), "+f"(d[7]), "+f"(d[8]), "+f"(d[9]), "+f"(d[10]), "+f"(d[11]), "+f"(d[12]), "+f"(d[13]), "+f"(d[14]), "+f"(d[15]), "+f"(d[16]), "+f"(d[17]), "+f"(d[18]), "+f"(d[19]), "+f"(d[20]), "+f"(d[21]), "+f"(d[22]), "+f"(d[23]), "+f"(d[24]), "+f"(d[25]), "+f"(d[26]), "+f"(d[27]), "+f"(d[28]), "+f"(d[29]), "+f"(d[30]), "+f"(d[31]), "+f"(d[32]), "+f"(d[33]), "+f"(d[34]), "+f"(d[35]), "+f"(d[36]), "+f"(d[37]), "+f"(d[38]), "+f"(d[39])
    : "l"(descA), "l"(descB));
}
template <int SCALE_D>
__device__ __forceinline__ void wgmma_rs_n64(float (&d)[32], uint32_t a0, uint32_t a1, uint32_t a2, uint32_t a3, uint64_t descB) {
  asm volatile("wgmma.mma_async.sync.aligned.m64n64k16.f32.bf16.bf16 {%0, %1, %2, %3, %4, %5, %6, %7, %8, %9, %10, %11, %12, %13, %14, %15, %16, %17, %18, %19, %20, %21, %22, %23, %24, %25, %26, %27, %28, %29, %30, %31}, {%32, %33, %34, %35}, %36, %37, 1, 1, 0;\n"
    : "+f"(d[0]), "+f"(d[1]), "+f"(d[2]), "+f"(d[3]), "+f"(d[4]), "+f"(d[5]), "+f"(d[6]), "+f"(d[7]), "+f"(d[8]), "+f"(d[9]), "+f"(d[10]), "+f"(d[11]), "+f"(d[12]), "+f"(d[13]), "+f"(d[14]), "+f"(d[15]), "+f"(d[16]), "+f"(d[17]), "+f"(d[18]), "+f"(d[19]), "+f"(d[20]), "+f"(d[21]), "+f"(d[22]), "+f"(d[23]), "+f"(d[24]), "+f"(d[25]), "+f"(d[26]), "+f"(d[27]), "+f"(d[28]), "+f"(d[29]), "+f"(d[30]), "+f"(d[31])
    : "r"(a0), "r"(a1), "r"(a2), "r"(a3), "l"(descB), "n"(SCALE_D));
}
template <int SCALE_D>
__device__ __forceinline__ void wgmma_rs_n24_tb(float (&d)[12], uint32_t a0, uint32_t a1, uint32_t a2, uint32_t a3, uint64_t descB) {
  asm volatile("wgmma.mma_async.sync.aligned.m64n24k16.f32.bf16.bf16 {%0, %1, %2, %3, %4, %5, %6, %7, %8, %9, %10, %11}, {%12, %13, %14, %15}, %16, %17, 1, 1, 1;\n"
    : "+f"(d[0]), "+f"(d[1]), "+f"(d[2]), "+f"(d[3]), "+f"(d[4]), "+f"(d[5]), "+f"(d[6]), "+f"(d[7]), "+f"(d[8]), "+f"(d[9]), "+f"(d[10]), "+f"(d[11])
    : "r"(a0), "r"(a1), "r"(a2), "r"(a3), "l"(descB), "n"(SCALE_D));
}

constexpr uint32_t DHI_SW128_K = (1024 >> 4) | (1u << 30);
constexpr uint32_t DHI_SW64_MN = (512 >> 4) | (2u << 30);
constexpr uint32_t DHI_SW32_MN = (256 >> 4) | (3u << 30);

template <int NC>
__device__ __forceinline__ void store_tile_bf16(const float (&acc)[NC / 2], float scale, uint32_t stage, uint8_t* stage_ptr,
                                                __nv_bfloat16* gdst, int gpitch, int lane) {
  constexpr int PITCH = NC * 2 + 16;
  const uint32_t waddr = stage + ((lane & 7) + ((lane >> 3) & 1) * 8) * PITCH + (lane >> 4) * 16;
#pragma unroll
  for (int j = 0; j < NC / 16; j++) {
    stsm4(waddr + j * 32, pack_bf16(acc[8 * j] * scale, acc[8 * j + 1] * scale), pack_bf16(acc[8 * j + 2] * scale, acc[8 * j + 3] * scale),
          pack_bf16(acc[8 * j + 4] * scale, acc[8 * j + 5] * scale), pack_bf16(acc[8 * j + 6] * scale, acc[8 * j + 7] * scale));
  }
  __syncwarp();
  constexpr int CPR = NC / 8;
#pragma unroll
  for (int i = 0; i < CPR / 2; i++) {
    const int c = i * 32 + lane, r = c / CPR, cc = c % CPR;
    const uint4 v = *reinterpret_cast<const uint4*>(stage_ptr + r * PITCH + cc * 16);
    *reinterpret_cast<uint4*>(gdst + (size_t)r * gpitch + cc * 8) = v;
  }
}

__device__ __forceinline__ void signal_done(unsigned int* flag, int wg, int tid) {
  asm volatile("bar.sync %0, 128;" :: "r"(wg + 1) : "memory");
  if ((tid & 127) == 0) asm volatile("red.release.gpu.global.add.u32 [%0], 1;" :: "l"(flag) : "memory");
}
__device__ __forceinline__ void wait_flags8(const unsigned int* f, unsigned int target) {
  for (int spin = 0; spin < (1 << 26); spin++) {
    unsigned int a, b, c, d, e, g, h, i;
    asm volatile("ld.volatile.global.v4.u32 {%0, %1, %2, %3}, [%4];" : "=r"(a), "=r"(b), "=r"(c), "=r"(d) : "l"(f) : "memory");
    asm volatile("ld.volatile.global.v4.u32 {%0, %1, %2, %3}, [%4];" : "=r"(e), "=r"(g), "=r"(h), "=r"(i) : "l"(f + 4) : "memory");
    if (min(min(min(a, b), min(c, d)), min(min(e, g), min(h, i))) >= target) break;
    __nanosleep(64);
  }
  asm volatile("fence.acq_rel.gpu;" ::: "memory");
  asm volatile("fence.proxy.async;" ::: "memory");
}

constexpr int K1_STAGES = 4;
constexpr int K1_A_BYTES = 256 * 128;
constexpr int K1_B_BYTES = 64 * 160 * 2;
constexpr int K1_STAGE = K1_A_BYTES + K1_B_BYTES;
constexpr int K1_SMEM = 5 * K1_A_BYTES + 61440 + 1024;
constexpr int KV_STAGES = 5;
constexpr int KVW_OFF = KV_STAGES * K1_A_BYTES;

__global__ void __launch_bounds__(512, 1)
proj_kernel(const __grid_constant__ CUtensorMap tmX, const __grid_constant__ CUtensorMap tmWq, const __grid_constant__ CUtensorMap tmWqkv,
            const __nv_bfloat16* __restrict__ wk, const __nv_bfloat16* __restrict__ wv, const __nv_bfloat16* __restrict__ gate_w) {
  extern __shared__ uint8_t smem_raw[];
  __shared__ __align__(8) uint64_t bar_full[KV_STAGES], bar_empty[KV_STAGES];
  uint8_t* smem = reinterpret_cast<uint8_t*>((reinterpret_cast<uintptr_t>(smem_raw) + 1023) & ~(uintptr_t)1023);
  const uint32_t sbase = smem_u32(smem);
  const uint32_t dbase = sbase & 0x3FFFFu;
  const int tid = threadIdx.x, warp = tid >> 5, lane = tid & 31;
  const bool is_kv = blockIdx.x >= 128;
  PROF(0, 0);
  if (tid == 0) {
    for (int i = 0; i < KV_STAGES; i++) { mbar_init(smem_u32(&bar_full[i]), 1); mbar_init(smem_u32(&bar_empty[i]), 16); }
    fence_mbar_init();
  }
  uint2 wa[2][5], wb[2][5]; uint32_t gw[2];
  if (is_kv && tid < 320) {
#pragma unroll
    for (int r = 0; r < 2; r++) {
      const int k = tid + r * 320;
      const uint2* pk = reinterpret_cast<const uint2*>(wk + k * 20);
      const uint2* pv = reinterpret_cast<const uint2*>(wv + k * 20);
#pragma unroll
      for (int i = 0; i < 5; i++) { wa[r][i] = __ldg(pk + i); wb[r][i] = __ldg(pv + i); }
      gw[r] = (uint32_t)__bfloat16_as_ushort(gate_w[k]);
    }
  }
  __syncthreads();
  if (tid == 480) {
    if (!is_kv) { g_done[blockIdx.x] = 0u; g_doneL[blockIdx.x] = 0u; }
    asm volatile("fence.acq_rel.gpu;" ::: "memory");
    pdl_launch();
  }
  __syncwarp();

  if (!is_kv) {
    const int mb = blockIdx.x >> 4, nb = blockIdx.x & 15;
    const CUtensorMap* tw = nb < 4 ? &tmWq : &tmWqkv;
    const int j0 = (nb < 4 ? nb : nb - 4) * 5;
    auto load = [&](int kt) {
      const int s = kt % K1_STAGES;
      const uint32_t fb = smem_u32(&bar_full[s]);
      mbar_expect_tx(fb, K1_STAGE);
      tma_2d(sbase + s * K1_STAGE, &tmX, kt * 64, mb * 256, fb);
      tma_3d(sbase + s * K1_STAGE + K1_A_BYTES, tw, 0, kt * 64, j0, fb);
    };
    if ((tid & 127) == 0) load(tid >> 7);
    __syncwarp();
    {
      const int wg = warp >> 2;
      float acc[80];
#pragma unroll
      for (int i = 0; i < 80; i++) acc[i] = 0.f;
      for (int kt = 0; kt < 10; kt++) {
        const int s = kt % K1_STAGES;
        mbar_wait(smem_u32(&bar_full[s]), (kt / K1_STAGES) & 1);
        const uint32_t alo = ((dbase + s * K1_STAGE + wg * 8192) >> 4) | (1u << 16);
        const uint32_t blo = ((dbase + s * K1_STAGE + K1_A_BYTES) >> 4) | ((4096u >> 4) << 16);
        fence_regs(acc);
        wg_fence();
#pragma unroll
        for (int k = 0; k < 4; k++) wgmma_ss_n160_tb(acc, mkd(alo + k * 2, DHI_SW128_K), mkd(blo + k * 64, DHI_SW64_MN));
        wg_commit();
        if (kt > 0 && kt - 1 + K1_STAGES < 10) {
          wg_wait<1>();
          const uint32_t eb = smem_u32(&bar_empty[(kt - 1) % K1_STAGES]);
          if (lane == 0) mbar_arrive(eb);
          if (tid == (kt & 3) * 128) { mbar_wait(eb, ((kt - 1) / K1_STAGES) & 1); load(kt - 1 + K1_STAGES); }
          __syncwarp();
        }
      }
      wg_wait<0>();
      fence_regs(acc);
      PROF(0, 1);
      asm volatile("bar.sync %0, 128;" :: "r"(wg + 1) : "memory");
      const int w4 = warp & 3;
      const uint32_t off = w4 * K1_STAGE + wg * 8192;
      const int row0 = mb * 256 + wg * 64 + w4 * 16;
      if (nb < 4) {
        store_tile_bf16<160>(acc, 0.22360679774997896f * 1.4426950408889634f, sbase + off, smem + off,
                             g_q + (size_t)row0 * D_MODEL + nb * 160, D_MODEL, lane);
      } else {
        store_tile_bf16<160>(acc, 1.0f, sbase + off, smem + off, g_qkv + (size_t)row0 * (3 * D_MODEL) + (nb - 4) * 160, 3 * D_MODEL, lane);
      }
    }
  } else {
    const int cb = blockIdx.x - 128;
    auto load = [&](int it) {
      const int s = it % KV_STAGES;
      const uint32_t fb = smem_u32(&bar_full[s]);
      mbar_expect_tx(fb, K1_A_BYTES);
      tma_2d(sbase + s * K1_A_BYTES, &tmX, (it % 10) * 64, cb * 512 + (it / 10) * 256, fb);
    };
    auto release = [&](int rel) {
      if (rel + KV_STAGES < 20) {
        const uint32_t eb = smem_u32(&bar_empty[rel % KV_STAGES]);
        if (lane == 0) mbar_arrive(eb);
        if (tid == (rel & 3) * 128) { mbar_wait(eb, (rel / KV_STAGES) & 1); load(rel + KV_STAGES); }
        __syncwarp();
      }
    };
    if ((tid & 63) == 0 && (tid >> 6) < KV_STAGES) load(tid >> 6);
    __syncwarp();
    {
      if (tid < 320) {
#pragma unroll
        for (int r = 0; r < 2; r++) {
          uint4* dst = reinterpret_cast<uint4*>(smem + KVW_OFF + (tid + r * 320) * 16);
          dst[0] = make_uint4(wa[r][0].x, wa[r][0].y, wa[r][1].x, wa[r][1].y);
          dst[640] = make_uint4(wa[r][2].x, wa[r][2].y, wa[r][3].x, wa[r][3].y);
          dst[1280] = make_uint4(wa[r][4].x, wa[r][4].y, 0u, 0u);
          dst[1920] = make_uint4(wb[r][0].x, wb[r][0].y, wb[r][1].x, wb[r][1].y);
          dst[2560] = make_uint4(wb[r][2].x, wb[r][2].y, wb[r][3].x, wb[r][3].y);
          dst[3200] = make_uint4(wb[r][4].x, wb[r][4].y, gw[r], 0u);
        }
      }
      fence_proxy_async();
      asm volatile("bar.sync 1, 512;" ::: "memory");
      PROF(0, 1);
      const int wg = warp >> 2, w4 = warp & 3, g = lane >> 2, t = lane & 3;
      for (int pass = 0; pass < 2; pass++) {
        float acc[24];
#pragma unroll
        for (int i = 0; i < 24; i++) acc[i] = 0.f;
        for (int kt = 0; kt < 10; kt++) {
          const int it = pass * 10 + kt, s = it % KV_STAGES;
          mbar_wait(smem_u32(&bar_full[s]), (it / KV_STAGES) & 1);
          const uint32_t alo = ((dbase + s * K1_A_BYTES + wg * 8192) >> 4) | (1u << 16);
          const uint32_t blo = ((dbase + KVW_OFF + kt * 1024) >> 4) | ((128u >> 4) << 16);
          fence_regs(acc);
          wg_fence();
#pragma unroll
          for (int k = 0; k < 4; k++) wgmma_ss_n48_tb(acc, mkd(alo + k * 2, DHI_SW128_K), mkd(blo + k * 16, 10240u >> 4));
          wg_commit();
          if (kt > 0) {
            wg_wait<1>();
            release(it - 1);
          }
        }
        wg_wait<0>();
        release(pass * 10 + 9);
        fence_regs(acc);
        float kmax2 = 0.f, vmax = 0.f;
#pragma unroll
        for (int h = 0; h < 2; h++) {
          const int key = cb * 512 + pass * 256 + wg * 64 + w4 * 16 + g + h * 8;
          const int grp = key >> 7, kk = key & 127;
          const bool poly = (TMASK >> (kk >> 3)) & 1;
          uint8_t* gp = g_kvimg + grp * GRP_BYTES;
          const uint32_t k0 = pack_bf16(acc[2 * h], acc[2 * h + 1]);
          const uint32_t k1 = pack_bf16(acc[4 + 2 * h], acc[5 + 2 * h]);
          uint32_t k2 = pack_bf16(acc[8 + 2 * h], acc[9 + 2 * h]);
          float n2 = bf_lo(k0) * bf_lo(k0) + bf_hi(k0) * bf_hi(k0) + bf_lo(k1) * bf_lo(k1) + bf_hi(k1) * bf_hi(k1);
          if (t < 2) {
            n2 += bf_lo(k2) * bf_lo(k2) + bf_hi(k2) * bf_hi(k2);
            k2 = pack_bf16(bf_lo(k2) * 0.5f, bf_hi(k2) * 0.5f);
          } else if (t == 2) k2 = poly ? pack_bf16(24.f, 2.5f) : pack_bf16(0.5f, 0.f);
          else k2 = poly ? pack_bf16(0.5f, 0.f) : 0u;
          *reinterpret_cast<uint32_t*>(gp + kk * 16 + t * 4) = k0;
          *reinterpret_cast<uint32_t*>(gp + PLANE + kk * 16 + t * 4) = k1;
          *reinterpret_cast<uint32_t*>(gp + 2 * PLANE + kk * 16 + t * 4) = k2;
          n2 += __shfl_xor_sync(0xffffffffu, n2, 1);
          n2 += __shfl_xor_sync(0xffffffffu, n2, 2);
          kmax2 = (n2 > kmax2 || n2 != n2) ? n2 : kmax2;
          uint32_t v0 = pack_bf16(acc[12 + 2 * h], acc[13 + 2 * h]);
          uint32_t v1 = pack_bf16(acc[16 + 2 * h], acc[17 + 2 * h]);
          uint32_t v2 = pack_bf16(acc[20 + 2 * h], acc[21 + 2 * h]);
          float vm = fmaxf(fmaxf(fabsf(bf_lo(v0)), fabsf(bf_hi(v0))), fmaxf(fabsf(bf_lo(v1)), fabsf(bf_hi(v1))));
          if (t < 2) vm = fmaxf(vm, fmaxf(fabsf(bf_lo(v2)), fabsf(bf_hi(v2))));
          else if (t == 2) {
            const float z = acc[20 + 2 * h];
            g_gate[key] = 1.f / (1.f + __expf(-z));
            v2 = 0x00003F80u;
          } else v2 = 0u;
          vmax = fmaxf(vmax, vm);
          if (poly) { v0 ^= 0x80008000u; v1 ^= 0x80008000u; v2 ^= 0x80008000u; }
          uint8_t* vp = gp + 3 * PLANE + (kk >> 3) * 384 + (kk & 7) * 16 + t * 4;
          *reinterpret_cast<uint32_t*>(vp) = v0;
          *reinterpret_cast<uint32_t*>(vp + 128) = v1;
          *reinterpret_cast<uint32_t*>(vp + 256) = v2;
        }
#pragma unroll
        for (int o = 1; o < 32; o <<= 1) {
          const float a = __shfl_xor_sync(0xffffffffu, kmax2, o);
          kmax2 = (a > kmax2 || a != a) ? a : kmax2;
          vmax = fmaxf(vmax, __shfl_xor_sync(0xffffffffu, vmax, o));
        }
        if (lane == 0) { g_kmax2[cb * 32 + pass * 16 + warp] = kmax2; g_vmax[cb * 32 + pass * 16 + warp] = vmax; }
      }
    }
  }
  PROF(0, 3);
}

__device__ __forceinline__ uint32_t ex2_pair_poly(float u0, float u1, uint32_t one2) {
  const uint32_t W = __byte_perm(__float_as_uint(u0), __float_as_uint(u1), 0x6521);
  uint32_t v; asm("lop3.b32 %0, %1, 0x007F007F, %2, 0xEA;" : "=r"(v) : "r"(W), "r"(one2));
  uint32_t L, p;
  asm("fma.rn.bf16x2 %0, %1, %2, %3;" : "=r"(L) : "r"(v), "r"(0x1f961f96u), "r"(0x9fe39fe3u));
  asm("fma.rn.bf16x2 %0, %1, %1, %2;" : "=r"(p) : "r"(L), "r"(0x00f500f5u));
  return W + p;
}
template <int JOFF>
__device__ __forceinline__ void softmax_fast(const float (&S)[32], uint32_t (&P)[16], uint32_t one2) {
#pragma unroll
  for (int i = 0; i < 16; i++) {
    if ((TMASK >> (JOFF + i / 2)) & 1) P[i] = ex2_pair_poly(S[2 * i], S[2 * i + 1], one2);
    else P[i] = pack_bf16(ex2(S[2 * i]), ex2(S[2 * i + 1]));
  }
}
template <int JOFF>
__device__ __forceinline__ void softmax_slow(const float (&S)[32], uint32_t (&P)[16], float (&O)[12], float& m0, float& m1) {
  float a0 = m0, a1 = m1;
#pragma unroll
  for (int j = 0; j < 8; j++) {
    a0 = fmaxf(a0, fmaxf(S[4 * j], S[4 * j + 1]));
    a1 = fmaxf(a1, fmaxf(S[4 * j + 2], S[4 * j + 3]));
  }
  a0 = fmaxf(a0, __shfl_xor_sync(0xffffffffu, a0, 1)); a0 = fmaxf(a0, __shfl_xor_sync(0xffffffffu, a0, 2));
  a1 = fmaxf(a1, __shfl_xor_sync(0xffffffffu, a1, 1)); a1 = fmaxf(a1, __shfl_xor_sync(0xffffffffu, a1, 2));
  const float c0 = ex2(m0 - a0), c1 = ex2(m1 - a1);
  m0 = a0; m1 = a1;
#pragma unroll
  for (int j = 0; j < 3; j++) { O[4 * j] *= c0; O[4 * j + 1] *= c0; O[4 * j + 2] *= c1; O[4 * j + 3] *= c1; }
#pragma unroll
  for (int i = 0; i < 16; i++) {
    const float m = (i & 1) ? a1 : a0;
    const uint32_t p = pack_bf16(ex2(S[2 * i] - m), ex2(S[2 * i + 1] - m));
    P[i] = ((TMASK >> (JOFF + i / 2)) & 1) ? (p ^ 0x80008000u) : p;
  }
}
constexpr uint32_t DHI_KV = 128 >> 4;
__device__ __forceinline__ void issue_qk(float (&S)[32], const uint32_t (&q)[8], uint32_t base) {
  wgmma_rs_n64<0>(S, q[0], q[1], q[2], q[3], mkd(base + ((PLANE >> 4) << 16), DHI_KV));
  wgmma_rs_n64<1>(S, q[4], q[5], q[6], q[7], mkd(base + (2 * PLANE >> 4), DHI_KV));
}
__device__ __forceinline__ void issue_pv(float (&O)[12], const uint32_t (&P)[16], uint32_t vbase) {
#pragma unroll
  for (int kk = 0; kk < 4; kk++)
    wgmma_rs_n24_tb<1>(O, P[4 * kk], P[4 * kk + 1], P[4 * kk + 2], P[4 * kk + 3], mkd(vbase + kk * (768 >> 4), DHI_KV));
}

constexpr uint32_t VOFF = ((3 * PLANE) >> 4) + ((384u >> 4) << 16);
constexpr int KVR = 4;
constexpr int OFF_WA = KVR * GRP_BYTES;
constexpr int OFF_BR = OFF_WA + 10 * 10240;
constexpr int BR_STAGE = 8192 + 10240, BR_STAGES = 3;
constexpr int OFF_QS = OFF_BR + BR_STAGES * BR_STAGE;
constexpr int OFF_BAR = OFF_QS + 512 * 6 * 4;
constexpr int K2_SMEM = OFF_BAR + 256 + 1024;
constexpr int BAR_KV = 0, BAR_WA = 4, BAR_BR = 5, BAR_TA = 8, BAR_TE = 14, CNT_KV = 18;
constexpr int NSTEP = 2 * NGRP;

__device__ __forceinline__ void kv_load(uint32_t sbase, int step) {
  const uint32_t bar = sbase + OFF_BAR + (BAR_KV + (step & (KVR - 1))) * 8;
  mbar_expect_tx(bar, GRP_BYTES);
  bulk_g2s(sbase + (step & (KVR - 1)) * GRP_BYTES, g_kvimg + (step & (NGRP - 1)) * GRP_BYTES, GRP_BYTES, bar);
}
__device__ __forceinline__ void kv_release(uint32_t sbase, int step, bool elected) {
  if (elected && step + KVR < NSTEP) {
    uint32_t old;
    asm volatile("atom.acq_rel.cta.shared::cta.inc.u32 %0, [%1], 3;" : "=r"(old) : "r"(sbase + OFF_BAR + CNT_KV * 8 + (step & (KVR - 1)) * 4) : "memory");
    if (old == 3u) kv_load(sbase, step + KVR);
  }
  __syncwarp();
}
__device__ __forceinline__ void kv_wait(uint32_t sbase, int step) {
  mbar_wait(sbase + OFF_BAR + (BAR_KV + (step & (KVR - 1))) * 8, (step / KVR) & 1);
}

__device__ __forceinline__ uint32_t kv_release_begin(uint32_t sbase, int slot, bool doit) {
  uint32_t old = 0;
  if (doit) asm volatile("atom.relaxed.cta.shared::cta.inc.u32 %0, [%1], 3;" : "=r"(old) : "r"(sbase + OFF_BAR + CNT_KV * 8 + slot * 4) : "memory");
  return old;
}
__device__ __forceinline__ void attn_tile_fast(const uint32_t (&q)[8], float (&O)[12], uint32_t sbase, int step0, bool elected, uint32_t one2) {
  float S[32]; uint32_t P[16];
#pragma unroll
  for (int i = 0; i < 32; i++) S[i] = 0.f;
  const uint32_t kb0 = (sbase & 0x3FFFFu) >> 4;
  kv_wait(sbase, step0);
  fence_regs(S); fence_regs(O);
  wg_fence();
  issue_qk(S, q, kb0);
  wg_commit();
#pragma unroll 1
  for (int step4 = step0; step4 < step0 + NGRP; step4 += KVR) {
#pragma unroll
    for (int j = 0; j < KVR; j++) {
      const int step = step4 + j;
      const uint32_t kb = kb0 + j * (GRP_BYTES >> 4);
      const uint32_t knext = kb0 + ((j + 1) & (KVR - 1)) * (GRP_BYTES >> 4);
      wg_wait<0>();
      fence_regs(S); fence_regs(P); fence_regs(O);
      const uint32_t old = kv_release_begin(sbase, (j + KVR - 1) & (KVR - 1), elected && step > step0 && step - 1 + KVR < NSTEP);
      softmax_fast<0>(S, P, one2);
      fence_regs(S); fence_regs(P); fence_regs(O);
      wg_fence();
      issue_qk(S, q, kb + 64);
      issue_pv(O, P, kb + VOFF);
      wg_commit();
      if (step + 1 < NSTEP) mbar_wait(sbase + OFF_BAR + (BAR_KV + ((j + 1) & (KVR - 1))) * 8, ((step + 1) / KVR) & 1);
      wg_wait<0>();
      fence_regs(S); fence_regs(P); fence_regs(O);
      softmax_fast<8>(S, P, one2);
      fence_regs(S); fence_regs(P); fence_regs(O);
      wg_fence();
      issue_qk(S, q, knext);
      issue_pv(O, P, kb + VOFF + 4 * (768 >> 4));
      wg_commit();
      if (old == 3u) kv_load(sbase, step - 1 + KVR);
    }
  }
  wg_wait<0>();
  fence_regs(O); fence_regs(S);
  kv_release(sbase, step0 + NGRP - 1, elected);
}
template <int H>
__device__ __forceinline__ void slow_step(const uint32_t (&q)[8], float (&O)[12], uint32_t kb, float& m0, float& m1) {
  float S[32]; uint32_t P[16];
#pragma unroll
  for (int i = 0; i < 32; i++) S[i] = 0.f;
  fence_regs(S);
  wg_fence();
  issue_qk(S, q, kb + 64 * H);
  wg_commit();
  wg_wait<0>();
  fence_regs(S);
  softmax_slow<8 * H>(S, P, O, m0, m1);
  fence_regs(P); fence_regs(O);
  wg_fence();
  issue_pv(O, P, kb + VOFF + H * 4 * (768 >> 4));
  wg_commit();
  wg_wait<0>();
  fence_regs(O); fence_regs(P);
}
__device__ __forceinline__ void attn_tile_slow(const uint32_t (&q)[8], float (&O)[12], uint32_t sbase, int step0, bool elected) {
  float m0 = -INFINITY, m1 = -INFINITY;
#pragma unroll 1
  for (int grp = 0; grp < NGRP; grp++) {
    kv_wait(sbase, step0 + grp);
    const uint32_t kb = ((sbase & 0x3FFFFu) >> 4) + (grp & (KVR - 1)) * (GRP_BYTES >> 4);
    slow_step<0>(q, O, kb, m0, m1);
    slow_step<1>(q, O, kb, m0, m1);
    kv_release(sbase, step0 + grp, elected);
  }
}

__device__ __forceinline__ void local_attn_pair(int token, int lane) {
  const __nv_bfloat16* base = g_qkv + (size_t)token * (3 * D_MODEL) + lane * DH;
  float f[20];
  {
    const uint2* p = reinterpret_cast<const uint2*>(base);
#pragma unroll
    for (int i = 0; i < 5; i++) { const uint2 v = p[i]; f[4 * i] = bf_lo(v.x); f[4 * i + 1] = bf_hi(v.x); f[4 * i + 2] = bf_lo(v.y); f[4 * i + 3] = bf_hi(v.y); }
  }
  float sc[8];
  float mx = -INFINITY;
#pragma unroll
  for (int w = 0; w < 8; w++) {
    const bool ok = token - 2 * w >= 0;
    const uint2* p = reinterpret_cast<const uint2*>(base + D_MODEL - (ok ? 2 * w : 0) * (3 * D_MODEL));
    float s = 0.f;
#pragma unroll
    for (int i = 0; i < 5; i++) {
      const uint2 v = p[i];
      s = fmaf(f[4 * i], bf_lo(v.x), s); s = fmaf(f[4 * i + 1], bf_hi(v.x), s);
      s = fmaf(f[4 * i + 2], bf_lo(v.y), s); s = fmaf(f[4 * i + 3], bf_hi(v.y), s);
    }
    s *= 0.22360679774997896f * 1.4426950408889634f;
    sc[w] = ok ? s : -1e9f * 1.4426950408889634f;
    mx = fmaxf(mx, sc[w]);
  }
  float l = 0.f;
#pragma unroll
  for (int w = 0; w < 8; w++) { sc[w] = ex2(sc[w] - mx); l += sc[w]; }
#pragma unroll
  for (int i = 0; i < 20; i++) f[i] = 0.f;
#pragma unroll
  for (int w = 0; w < 8; w++) {
    const bool ok = token - 2 * w >= 0;
    const uint2* p = reinterpret_cast<const uint2*>(base + 2 * D_MODEL - (ok ? 2 * w : token) * (3 * D_MODEL));
#pragma unroll
    for (int i = 0; i < 5; i++) {
      const uint2 v = p[i];
      f[4 * i] = fmaf(sc[w], bf_lo(v.x), f[4 * i]); f[4 * i + 1] = fmaf(sc[w], bf_hi(v.x), f[4 * i + 1]);
      f[4 * i + 2] = fmaf(sc[w], bf_lo(v.y), f[4 * i + 2]); f[4 * i + 3] = fmaf(sc[w], bf_hi(v.y), f[4 * i + 3]);
    }
  }
  const float r = (1.f - g_gate[token]) / l;
  uint2* dst = reinterpret_cast<uint2*>(g_a2 + (size_t)token * (2 * D_MODEL) + D_MODEL + lane * DH);
#pragma unroll
  for (int i = 0; i < 5; i++) dst[i] = make_uint2(pack_bf16(f[4 * i] * r, f[4 * i + 1] * r), pack_bf16(f[4 * i + 2] * r, f[4 * i + 3] * r));
}

__device__ __forceinline__ uint32_t ta_slot(int i) { return i < 3 ? i * 16384 : OFF_BR + (i - 3) * 16384; }

__global__ void __launch_bounds__(640, 1)
attn_kernel(const __grid_constant__ CUtensorMap tmA2, const __grid_constant__ CUtensorMap tmA2b, const __grid_constant__ CUtensorMap tmWoA, const __grid_constant__ CUtensorMap tmWoB,
            __nv_bfloat16* __restrict__ out, uint32_t one2) {
  extern __shared__ uint8_t smem_raw[];
  uint8_t* smem = reinterpret_cast<uint8_t*>((reinterpret_cast<uintptr_t>(smem_raw) + 1023) & ~(uintptr_t)1023);
  const uint32_t sbase = smem_u32(smem);
  const uint32_t dbase = sbase & 0x3FFFFu;
  const uint32_t bars = sbase + OFF_BAR;
  const int tid = threadIdx.x, wg = tid >> 7, warp = (tid >> 5) & 3, lane = tid & 31, g = lane >> 2, t = lane & 3;
  const int mb = blockIdx.x >> 3, nb = blockIdx.x & 7;
  if (tid == 0) {
    for (int i = 0; i < BAR_TE; i++) mbar_init(bars + i * 8, 1);
    for (int i = BAR_TE; i < BAR_TE + 4; i++) mbar_init(bars + i * 8, 8);
    for (int i = 0; i < 4; i++) *reinterpret_cast<uint32_t*>(smem + OFF_BAR + CNT_KV * 8 + i * 4) = 0u;
    fence_mbar_init();
  }
  __syncthreads();
  if (wg == 4) {
    if (tid == 512) {
      mbar_expect_tx(bars + BAR_WA * 8, 10 * 10240);
      for (int kt = 0; kt < 10; kt++) tma_3d(sbase + OFF_WA + kt * 10240, &tmWoA, 0, kt * 64, nb * 5, bars + BAR_WA * 8);
    }
    pdl_wait();
    asm volatile("bar.sync 7, 640;" ::: "memory");
#pragma unroll 1
    for (int i = 0; i < 4; i++) local_attn_pair(blockIdx.x * 16 + i * 4 + warp, lane);
    if (tid == 512) PROF2(0, 2);
    signal_done(&g_doneL[blockIdx.x], wg, tid);
    auto br_load = [&](int it, int st) {
      const uint32_t fb = bars + (BAR_BR + st) * 8;
      const uint32_t dst = sbase + OFF_BR + st * BR_STAGE;
      const int kc = (it >= 10 ? it - 10 : it) * 64;
      mbar_expect_tx(fb, BR_STAGE);
      tma_2d(dst, &tmA2, D_MODEL + kc, (blockIdx.x >> 3) * 128 + (it >= 10 ? 64 : 0), fb);
      tma_3d(dst + 8192, &tmWoB, 0, kc, (blockIdx.x & 7) * 5, fb);
    };
    if (tid == 512) {
      wait_flags8(&g_doneL[mb * 8], 1u);
      for (int it = 0; it < BR_STAGES; it++) br_load(it, it);
    }
    __syncwarp();
    {
      int st = 0, ph = 0;
      float acc[40];
#pragma unroll 1
      for (int it = 0; it < 20; it++) {
        if (it == 0 || it == 10) {
#pragma unroll
          for (int i = 0; i < 40; i++) acc[i] = 0.f;
        }
        mbar_wait(bars + (BAR_BR + st) * 8, ph);
        const uint32_t alo = ((dbase + OFF_BR + st * BR_STAGE) >> 4);
        fence_regs(acc);
        wg_fence();
#pragma unroll
        for (int k = 0; k < 4; k++)
          wgmma_ss_n80_tb(acc, mkd(alo + (k * 2 + (1u << 16)), DHI_SW128_K), mkd(alo + (512 + k * 32 + ((2048u >> 4) << 16)), DHI_SW32_MN));
        wg_commit();
        wg_wait<0>();
        fence_regs(acc);
        asm volatile("bar.sync 5, 128;" ::: "memory");
        if (threadIdx.x == 512 && it + BR_STAGES < 20) br_load(it + BR_STAGES, st);
        __syncwarp();
        if (it == 9 || it == 19) {
          float* pp = g_part + (size_t)(blockIdx.x * 2 + (it == 19)) * (40 * 128) + (threadIdx.x & 127);
#pragma unroll
          for (int i = 0; i < 40; i++) pp[i * 128] = acc[i];
        }
        if (++st == BR_STAGES) { st = 0; ph ^= 1; }
      }
    }
    if (tid == 512) PROF2(1, 0);
    asm volatile("bar.arrive 6, 384;" ::: "memory");
    if (tid == 512) {
      wait_flags8(&g_done[mb * 8], 4u);
      PROF2(2, 0);
    }
    asm volatile("bar.sync 5, 128;" ::: "memory");
    if (lane == 0) {
      asm volatile("fence.proxy.async;" ::: "memory");
      for (int kt = warp; kt < 10; kt += 4) {
        const int sl = kt % 6;
        if (kt >= 6) mbar_wait(bars + (BAR_TE + kt - 6) * 8, 0);
        const uint32_t fb = bars + (BAR_TA + sl) * 8;
        mbar_expect_tx(fb, 16384);
        tma_2d(sbase + ta_slot(sl), &tmA2b, kt * 64, mb * 128, fb);
      }
    }
  } else {
    const bool elected = (tid & 127) == 0;
    pdl_wait();
    PROF(1, 1);
    if (elected) kv_load(sbase, wg);
    __syncwarp();
    uint32_t q[8];
    uint32_t* qstash = reinterpret_cast<uint32_t*>(smem + OFF_QS) + tid;
    const int rowA = (blockIdx.x * 8 + wg) * 64 + warp * 16 + g;
    {
      const uint32_t* r0 = reinterpret_cast<const uint32_t*>(g_q + (size_t)rowA * DH);
      const uint32_t* r1 = r0 + 8 * (DH / 2);
      const uint32_t* s0 = r0 + 256 * (DH / 2);
      const uint32_t* s1 = s0 + 8 * (DH / 2);
      q[0] = r0[t]; q[1] = r1[t]; q[2] = r0[t + 4]; q[3] = r1[t + 4];
      q[4] = t < 2 ? r0[8 + t] : 0u;
      q[5] = t < 2 ? r1[8 + t] : 0u;
      qstash[0] = s0[t]; qstash[512] = s1[t]; qstash[1024] = s0[t + 4]; qstash[1536] = s1[t + 4];
      qstash[2048] = t < 2 ? s0[8 + t] : 0u;
      qstash[2560] = t < 2 ? s1[8 + t] : 0u;
    }
    float kmax2 = 0.f, vmax = 0.f;
#pragma unroll
    for (int i = 0; i < 4; i++) {
      const float a = g_kmax2[lane + 32 * i];
      kmax2 = (a > kmax2 || a != a) ? a : kmax2;
      vmax = fmaxf(vmax, g_vmax[lane + 32 * i]);
    }
#pragma unroll
    for (int o = 1; o < 32; o <<= 1) {
      const float a = __shfl_xor_sync(0xffffffffu, kmax2, o);
      kmax2 = (a > kmax2 || a != a) ? a : kmax2;
      vmax = fmaxf(vmax, __shfl_xor_sync(0xffffffffu, vmax, o));
    }
    const float qlim = (vmax >= 0.00390625f && vmax <= 256.f) ? 9025.f / kmax2 : -1.f;
    asm volatile("bar.arrive 7, 640;" ::: "memory");
    PROF(1, 2);
#pragma unroll 1
    for (int it = 0; it < 2; it++) {
      const int row0 = rowA + it * 256;
      if (it == 1) {
#pragma unroll
        for (int i = 0; i < 6; i++) q[i] = qstash[512 * i];
      }
      float n0 = bf_lo(q[0]) * bf_lo(q[0]) + bf_hi(q[0]) * bf_hi(q[0]) + bf_lo(q[2]) * bf_lo(q[2]) + bf_hi(q[2]) * bf_hi(q[2]) +
                 bf_lo(q[4]) * bf_lo(q[4]) + bf_hi(q[4]) * bf_hi(q[4]);
      float n1 = bf_lo(q[1]) * bf_lo(q[1]) + bf_hi(q[1]) * bf_hi(q[1]) + bf_lo(q[3]) * bf_lo(q[3]) + bf_hi(q[3]) * bf_hi(q[3]) +
                 bf_lo(q[5]) * bf_lo(q[5]) + bf_hi(q[5]) * bf_hi(q[5]);
      n0 += __shfl_xor_sync(0xffffffffu, n0, 1); n0 += __shfl_xor_sync(0xffffffffu, n0, 2);
      n1 += __shfl_xor_sync(0xffffffffu, n1, 1); n1 += __shfl_xor_sync(0xffffffffu, n1, 2);
      const bool safe = (n0 <= qlim) && (n1 <= qlim);
      uint32_t unsafe_any;
      asm volatile("{\n.reg .pred p, r;\nsetp.eq.u32 p, %1, 0;\nbarrier.cta.red.or.pred r, %2, 128, p;\nselp.u32 %0, 1, 0, r;\n}\n"
                   : "=r"(unsafe_any) : "r"((uint32_t)safe), "r"(wg + 1) : "memory");
      float O[12];
#pragma unroll
      for (int i = 0; i < 12; i++) O[i] = 0.f;
      if (!unsafe_any && t >= 2) { q[4] = q[5] = (t == 2) ? 0x3F804100u : 0x00003B80u; }
      q[6] = q[4]; q[7] = q[5];
      fence_regs(q);
      if (!unsafe_any) attn_tile_fast(q, O, sbase, it * NGRP, elected, one2);
      else attn_tile_slow(q, O, sbase, it * NGRP, elected);
      const float l0 = __shfl_sync(0xffffffffu, O[8], (lane & ~3) | 2);
      const float l1 = __shfl_sync(0xffffffffu, O[10], (lane & ~3) | 2);
      const int tok = row0 >> 5;
      const float gt = g_gate[tok];
      const float i0 = gt / l0, i1 = gt / l1;
      uint32_t* o0 = reinterpret_cast<uint32_t*>(g_a2 + (size_t)tok * (2 * D_MODEL) + (row0 & 31) * DH);
      uint32_t* o1 = o0 + 8 * (DH / 2);
      o0[t] = pack_bf16(O[0] * i0, O[1] * i0); o1[t] = pack_bf16(O[2] * i1, O[3] * i1);
      o0[t + 4] = pack_bf16(O[4] * i0, O[5] * i0); o1[t + 4] = pack_bf16(O[6] * i1, O[7] * i1);
      if (t < 2) { o0[t + 8] = pack_bf16(O[8] * i0, O[9] * i0); o1[t + 8] = pack_bf16(O[10] * i1, O[11] * i1); }
    }
    signal_done(&g_done[blockIdx.x], wg, tid);
    PROF(1, 3);
    if (wg < 2) {
      float acc[40];
      asm volatile("bar.sync 6, 384;" ::: "memory");
      {
        const float* pp = g_part + (size_t)(blockIdx.x * 2 + wg) * (40 * 128) + (tid & 127);
#pragma unroll
        for (int i = 0; i < 40; i++) acc[i] = pp[i * 128];
      }
      mbar_wait(bars + BAR_WA * 8, 0);
#pragma unroll 1
      for (int kt = 0; kt < 10; kt++) {
        const int sl = kt % 6;
        mbar_wait(bars + (BAR_TA + sl) * 8, kt / 6);
        if (kt == 0) PROF(2, 1);
        const uint32_t alo = ((dbase + ta_slot(sl) + wg * 8192) >> 4) | (1u << 16);
        const uint32_t blo = ((dbase + OFF_WA + kt * 10240) >> 4) | ((2048u >> 4) << 16);
        fence_regs(acc);
        wg_fence();
#pragma unroll
        for (int k = 0; k < 4; k++) wgmma_ss_n80_tb(acc, mkd(alo + k * 2, DHI_SW128_K), mkd(blo + k * 32, DHI_SW32_MN));
        wg_commit();
        if (kt < 4) {
          wg_wait<0>();
          if (lane == 0) mbar_arrive(bars + (BAR_TE + kt) * 8);
        }
      }
      wg_wait<0>();
      fence_regs(acc);
      PROF(2, 2);
      asm volatile("bar.sync %0, 128;" :: "r"(wg + 1) : "memory");
      const uint32_t so = ta_slot(warp) + wg * 8192;
      const int row0 = mb * 128 + wg * 64 + warp * 16;
      store_tile_bf16<80>(acc, 1.0f, sbase + so, smem + so, out + (size_t)row0 * D_MODEL + nb * 80, D_MODEL, lane);
      PROF(2, 3);
    }
  }
}

typedef CUresult (*EncodeFn)(CUtensorMap*, CUtensorMapDataType, cuuint32_t, void*, const cuuint64_t*, const cuuint64_t*,
                             const cuuint32_t*, const cuuint32_t*, CUtensorMapInterleave, CUtensorMapSwizzle,
                             CUtensorMapL2promotion, CUtensorMapFloatOOBfill);

void make_map(EncodeFn fn, CUtensorMap* tm, const void* ptr, int rank, const cuuint64_t* dims, const cuuint64_t* strides,
              const cuuint32_t* box, CUtensorMapSwizzle sw) {
  const cuuint32_t es[3] = {1, 1, 1};
  fn(tm, CU_TENSOR_MAP_DATA_TYPE_BFLOAT16, rank, const_cast<void*>(ptr), dims, strides, box, es, CU_TENSOR_MAP_INTERLEAVE_NONE, sw,
     CU_TENSOR_MAP_L2_PROMOTION_L2_256B, CU_TENSOR_MAP_FLOAT_OOB_FILL_NONE);
}
void map_a(EncodeFn fn, CUtensorMap* tm, const void* p, int rows, int cols, int box_rows) {
  const cuuint64_t dims[2] = {(cuuint64_t)cols, (cuuint64_t)rows};
  const cuuint64_t str[1] = {(cuuint64_t)cols * 2};
  const cuuint32_t box[2] = {64, (cuuint32_t)box_rows};
  make_map(fn, tm, p, 2, dims, str, box, CU_TENSOR_MAP_SWIZZLE_128B);
}
void map_w(EncodeFn fn, CUtensorMap* tm, const void* p, int K, int N, int atom, CUtensorMapSwizzle sw) {
  const cuuint64_t dims[3] = {(cuuint64_t)atom, (cuuint64_t)K, (cuuint64_t)(N / atom)};
  const cuuint64_t str[2] = {(cuuint64_t)N * 2, (cuuint64_t)atom * 2};
  const cuuint32_t box[3] = {(cuuint32_t)atom, 64, 5};
  make_map(fn, tm, p, 3, dims, str, box, sw);
}

template <typename... KArgs, typename... Args>
void launch(void (*kern)(KArgs...), int grid, int block, int smem, bool pdl, Args... args) {
  cudaLaunchConfig_t cfg = {};
  cfg.gridDim = dim3(grid); cfg.blockDim = dim3(block); cfg.dynamicSmemBytes = smem; cfg.stream = cudaStreamPerThread;
  cudaLaunchAttribute at[1];
  at[0].id = cudaLaunchAttributeProgrammaticStreamSerialization;
  at[0].val.programmaticStreamSerializationAllowed = 1;
  cfg.attrs = at; cfg.numAttrs = pdl ? 1 : 0;
  cudaLaunchKernelEx(&cfg, kern, KArgs(args)...);
}

}

extern "C" void kernel_launch(void* const* d_in, const int* in_sizes, int n_in, void* d_out, int out_size) {
  (void)in_sizes; (void)n_in; (void)out_size;
  const __nv_bfloat16* x = (const __nv_bfloat16*)d_in[0];
  const __nv_bfloat16* wq = (const __nv_bfloat16*)d_in[1];
  const __nv_bfloat16* wk = (const __nv_bfloat16*)d_in[2];
  const __nv_bfloat16* wv = (const __nv_bfloat16*)d_in[3];
  const __nv_bfloat16* woA = (const __nv_bfloat16*)d_in[4];
  const __nv_bfloat16* wqkv = (const __nv_bfloat16*)d_in[6];
  const __nv_bfloat16* woB = (const __nv_bfloat16*)d_in[7];
  const __nv_bfloat16* gate_w = (const __nv_bfloat16*)d_in[8];

  static EncodeFn enc = nullptr;
  static void* a2_ptr = nullptr;
  if (!enc) {
    void* fp = nullptr;
    cudaDriverEntryPointQueryResult qr;
    cudaGetDriverEntryPoint("cuTensorMapEncodeTiled", &fp, cudaEnableDefault, &qr);
    enc = (EncodeFn)fp;
    cudaGetSymbolAddress(&a2_ptr, g_a2);
    cudaFuncSetAttribute(proj_kernel, cudaFuncAttributeMaxDynamicSharedMemorySize, K1_SMEM);
    cudaFuncSetAttribute(attn_kernel, cudaFuncAttributeMaxDynamicSharedMemorySize, K2_SMEM);
  }
  CUtensorMap tmX, tmWq, tmWqkv, tmA2, tmA2b, tmWoA, tmWoB;
  map_a(enc, &tmX, x, S_LEN, D_MODEL, 256);
  map_w(enc, &tmWq, wq, D_MODEL, D_MODEL, 32, CU_TENSOR_MAP_SWIZZLE_64B);
  map_w(enc, &tmWqkv, wqkv, D_MODEL, 3 * D_MODEL, 32, CU_TENSOR_MAP_SWIZZLE_64B);
  map_a(enc, &tmA2, a2_ptr, S_LEN, 2 * D_MODEL, 64);
  map_a(enc, &tmA2b, a2_ptr, S_LEN, 2 * D_MODEL, 128);
  map_w(enc, &tmWoA, woA, D_MODEL, D_MODEL, 16, CU_TENSOR_MAP_SWIZZLE_32B);
  map_w(enc, &tmWoB, woB, D_MODEL, D_MODEL, 16, CU_TENSOR_MAP_SWIZZLE_32B);

  launch(proj_kernel, 132, 512, K1_SMEM, false, tmX, tmWq, tmWqkv, wk, wv, gate_w);
  launch(attn_kernel, 128, 640, K2_SMEM, true, tmA2, tmA2b, tmWoA, tmWoB, (__nv_bfloat16*)d_out, 0x3F803F80u);
}
```

```cpp
#include <cuda_runtime.h>
#include <cuda_bf16.h>
#include <cuda.h>
#include <stdint.h>

namespace {

constexpr int S_LEN = 2048, D_MODEL = 640, DH = 20;

constexpr int GRP = 128;
constexpr int PLANE = GRP * 16;
constexpr int GRP_BYTES = GRP * 16 * 6;
constexpr int NGRP = S_LEN / GRP;
#define TMASKV 0x6DB6u
constexpr uint32_t TMASK = TMASKV;

__device__ __align__(1024) __nv_bfloat16 g_q[S_LEN * D_MODEL];
__device__ __align__(1024) __nv_bfloat16 g_qkv[S_LEN * 3 * D_MODEL];
__device__ __align__(1024) __nv_bfloat16 g_a2[S_LEN * 2 * D_MODEL];
__device__ __align__(1024) uint8_t g_kvimg[NGRP * GRP_BYTES];
__device__ float g_gate[S_LEN];
__device__ float g_kmax2[64];
__device__ float g_vmax[64];
__device__ __align__(32) unsigned int g_doneL[128];
__device__ float g_part[128 * 2 * 40 * 128];
__device__ __align__(32) unsigned int g_done[128];

#define PROF(k, slot)
#define PROF2(k, slot)
__device__ __forceinline__ uint32_t smem_u32(const void* p) { return (uint32_t)__cvta_generic_to_shared(p); }
__device__ __forceinline__ uint64_t mkd(uint32_t lo, uint32_t hi) {
  uint64_t d; asm("mov.b64 %0, {%1, %2};" : "=l"(d) : "r"(lo), "r"(hi)); return d;
}
__device__ __forceinline__ void wg_fence() { asm volatile("wgmma.fence.sync.aligned;" ::: "memory"); }
__device__ __forceinline__ void wg_commit() { asm volatile("wgmma.commit_group.sync.aligned;" ::: "memory"); }
template <int N> __device__ __forceinline__ void wg_wait() { asm volatile("wgmma.wait_group.sync.aligned %0;" :: "n"(N) : "memory"); }
template <int N> __device__ __forceinline__ void fence_regs(float (&d)[N]) {
#pragma unroll
  for (int i = 0; i < N; i++) asm volatile("" : "+f"(d[i]) :: "memory");
}
template <int N> __device__ __forceinline__ void fence_regs(uint32_t (&d)[N]) {
#pragma unroll
  for (int i = 0; i < N; i++) asm volatile("" : "+r"(d[i]) :: "memory");
}
__device__ __forceinline__ void mbar_init(uint32_t bar, uint32_t cnt) { asm volatile("mbarrier.init.shared::cta.b64 [%0], %1;" :: "r"(bar), "r"(cnt)); }
__device__ __forceinline__ void mbar_expect_tx(uint32_t bar, uint32_t bytes) {
  asm volatile("mbarrier.arrive.expect_tx.shared::cta.b64 _, [%0], %1;" :: "r"(bar), "r"(bytes) : "memory");
}
__device__ __forceinline__ void mbar_arrive(uint32_t bar) { asm volatile("mbarrier.arrive.shared::cta.b64 _, [%0];" :: "r"(bar) : "memory"); }
__device__ __forceinline__ void mbar_wait(uint32_t bar, uint32_t parity) {
  asm volatile("{\n.reg .pred p;\nWAIT_%=:\nmbarrier.try_wait.parity.shared::cta.b64 p, [%0], %1;\n@p bra DONE_%=;\nbra WAIT_%=;\nDONE_%=:\n}\n"
               :: "r"(bar), "r"(parity) : "memory");
}
__device__ __forceinline__ void fence_mbar_init() { asm volatile("fence.mbarrier_init.release.cluster;" ::: "memory"); }
__device__ __forceinline__ void fence_proxy_async() { asm volatile("fence.proxy.async.shared::cta;" ::: "memory"); }
__device__ __forceinline__ void bulk_g2s(uint32_t dst, const void* src, uint32_t bytes, uint32_t bar) {
  asm volatile("cp.async.bulk.shared::cluster.global.mbarrier::complete_tx::bytes [%0], [%1], %2, [%3];"
               :: "r"(dst), "l"(src), "r"(bytes), "r"(bar) : "memory");
}
__device__ __forceinline__ void tma_2d(uint32_t dst, const CUtensorMap* tm, int c0, int c1, uint32_t bar) {
  asm volatile("cp.async.bulk.tensor.2d.shared::cluster.global.mbarrier::complete_tx::bytes [%0], [%1, {%3, %4}], [%2];"
               :: "r"(dst), "l"((uint64_t)tm), "r"(bar), "r"(c0), "r"(c1) : "memory");
}
__device__ __forceinline__ void tma_3d(uint32_t dst, const CUtensorMap* tm, int c0, int c1, int c2, uint32_t bar) {
  asm volatile("cp.async.bulk.tensor.3d.shared::cluster.global.mbarrier::complete_tx::bytes [%0], [%1, {%3, %4, %5}], [%2];"
               :: "r"(dst), "l"((uint64_t)tm), "r"(bar), "r"(c0), "r"(c1), "r"(c2) : "memory");
}
__device__ __forceinline__ void pdl_wait() { asm volatile("griddepcontrol.wait;" ::: "memory"); }
__device__ __forceinline__ void pdl_launch() { asm volatile("griddepcontrol.launch_dependents;" ::: "memory"); }
__device__ __forceinline__ float ex2(float x) { float y; asm("ex2.approx.ftz.f32 %0, %1;" : "=f"(y) : "f"(x)); return y; }
__device__ __forceinline__ uint32_t pack_bf16(float lo, float hi) {
  uint32_t r; asm("cvt.rn.bf16x2.f32 %0, %1, %2;" : "=r"(r) : "f"(hi), "f"(lo)); return r;
}
__device__ __forceinline__ float bf_lo(uint32_t x) { return __uint_as_float(x << 16); }
__device__ __forceinline__ float bf_hi(uint32_t x) { return __uint_as_float(x & 0xffff0000u); }
__device__ __forceinline__ void stsm4(uint32_t addr, uint32_t r0, uint32_t r1, uint32_t r2, uint32_t r3) {
  asm volatile("stmatrix.sync.aligned.m8n8.x4.shared.b16 [%0], {%1, %2, %3, %4};" :: "r"(addr), "r"(r0), "r"(r1), "r"(r2), "r"(r3) : "memory");
}

__device__ __forceinline__ void wgmma_ss_n160_tb(float (&d)[80], uint64_t descA, uint64_t descB) {
  asm volatile("wgmma.mma_async.sync.aligned.m64n160k16.f32.bf16.bf16 {%0, %1, %2, %3, %4, %5, %6, %7, %8, %9, %10, %11, %12, %13, %14, %15, %16, %17, %18, %19, %20, %21, %22, %23, %24, %25, %26, %27, %28, %29, %30, %31, %32, %33, %34, %35, %36, %37, %38, %39, %40, %41, %42, %43, %44, %45, %46, %47, %48, %49, %50, %51, %52, %53, %54, %55, %56, %57, %58, %59, %60, %61, %62, %63, %64, %65, %66, %67, %68, %69, %70, %71, %72, %73, %74, %75, %76, %77, %78, %79}, %80, %81, 1, 1, 1, 0, 1;\n"
    : "+f"(d[0]), "+f"(d[1]), "+f"(d[2]), "+f"(d[3]), "+f"(d[4]), "+f"(d[5]), "+f"(d[6]), "+f"(d[7]), "+f"(d[8]), "+f"(d[9]), "+f"(d[10]), "+f"(d[11]), "+f"(d[12]), "+f"(d[13]), "+f"(d[14]), "+f"(d[15]), "+f"(d[16]), "+f"(d[17]), "+f"(d[18]), "+f"(d[19]), "+f"(d[20]), "+f"(d[21]), "+f"(d[22]), "+f"(d[23]), "+f"(d[24]), "+f"(d[25]), "+f"(d[26]), "+f"(d[27]), "+f"(d[28]), "+f"(d[29]), "+f"(d[30]), "+f"(d[31]), "+f"(d[32]), "+f"(d[33]), "+f"(d[34]), "+f"(d[35]), "+f"(d[36]), "+f"(d[37]), "+f"(d[38]), "+f"(d[39]), "+f"(d[40]), "+f"(d[41]), "+f"(d[42]), "+f"(d[43]), "+f"(d[44]), "+f"(d[45]), "+f"(d[46]), "+f"(d[47]), "+f"(d[48]), "+f"(d[49]), "+f"(d[50]), "+f"(d[51]), "+f"(d[52]), "+f"(d[53]), "+f"(d[54]), "+f"(d[55]), "+f"(d[56]), "+f"(d[57]), "+f"(d[58]), "+f"(d[59]), "+f"(d[60]), "+f"(d[61]), "+f"(d[62]), "+f"(d[63]), "+f"(d[64]), "+f"(d[65]), "+f"(d[66]), "+f"(d[67]), "+f"(d[68]), "+f"(d[69]), "+f"(d[70]), "+f"(d[71]), "+f"(d[72]), "+f"(d[73]), "+f"(d[74]), "+f"(d[75]), "+f"(d[76]), "+f"(d[77]), "+f"(d[78]), "+f"(d[79])
    : "l"(descA), "l"(descB));
}
__device__ __forceinline__ void wgmma_ss_n48_tb(float (&d)[24], uint64_t descA, uint64_t descB) {
  asm volatile("wgmma.mma_async.sync.aligned.m64n48k16.f32.bf16.bf16 {%0, %1, %2, %3, %4, %5, %6, %7, %8, %9, %10, %11, %12, %13, %14, %15, %16, %17, %18, %19, %20, %21, %22, %23}, %24, %25, 1, 1, 1, 0, 1;\n"
    : "+f"(d[0]), "+f"(d[1]), "+f"(d[2]), "+f"(d[3]), "+f"(d[4]), "+f"(d[5]), "+f"(d[6]), "+f"(d[7]), "+f"(d[8]), "+f"(d[9]), "+f"(d[10]), "+f"(d[11]), "+f"(d[12]), "+f"(d[13]), "+f"(d[14]), "+f"(d[15]), "+f"(d[16]), "+f"(d[17]), "+f"(d[18]), "+f"(d[19]), "+f"(d[20]), "+f"(d[21]), "+f"(d[22]), "+f"(d[23])
    : "l"(descA), "l"(descB));
}
__device__ __forceinline__ void wgmma_ss_n80_tb(float (&d)[40], uint64_t descA, uint64_t descB) {
  asm volatile("wgmma.mma_async.sync.aligned.m64n80k16.f32.bf16.bf16 {%0, %1, %2, %3, %4, %5, %6, %7, %8, %9, %10, %11, %12, %13, %14, %15, %16, %17, %18, %19, %20, %21, %22, %23, %24, %25, %26, %27, %28, %29, %30, %31, %32, %33, %34, %35, %36, %37, %38, %39}, %40, %41, 1, 1, 1, 0, 1;\n"
    : "+f"(d[0]), "+f"(d[1]), "+f"(d[2]), "+f"(d[3]), "+f"(d[4]), "+f"(d[5]), "+f"(d[6]), "+f"(d[7]), "+f"(d[8]), "+f"(d[9]), "+f"(d[10]), "+f"(d[11]), "+f"(d[12]), "+f"(d[13]), "+f"(d[14]), "+f"(d[15]), "+f"(d[16]), "+f"(d[17]), "+f"(d[18]), "+f"(d[19]), "+f"(d[20]), "+f"(d[21]), "+f"(d[22]), "+f"(d[23]), "+f"(d[24]), "+f"(d[25]), "+f"(d[26]), "+f"(d[27]), "+f"(d[28]), "+f"(d[29]), "+f"(d[30]), "+f"(d[31]), "+f"(d[32]), "+f"(d[33]), "+f"(d[34]), "+f"(d[35]), "+f"(d[36]), "+f"(d[37]), "+f"(d[38]), "+f"(d[39])
    : "l"(descA), "l"(descB));
}
template <int SCALE_D>
__device__ __forceinline__ void wgmma_rs_n64(float (&d)[32], uint32_t a0, uint32_t a1, uint32_t a2, uint32_t a3, uint64_t descB) {
  asm volatile("wgmma.mma_async.sync.aligned.m64n64k16.f32.bf16.bf16 {%0, %1, %2, %3, %4, %5, %6, %7, %8, %9, %10, %11, %12, %13, %14, %15, %16, %17, %18, %19, %20, %21, %22, %23, %24, %25, %26, %27, %28, %29, %30, %31}, {%32, %33, %34, %35}, %36, %37, 1, 1, 0;\n"
    : "+f"(d[0]), "+f"(d[1]), "+f"(d[2]), "+f"(d[3]), "+f"(d[4]), "+f"(d[5]), "+f"(d[6]), "+f"(d[7]), "+f"(d[8]), "+f"(d[9]), "+f"(d[10]), "+f"(d[11]), "+f"(d[12]), "+f"(d[13]), "+f"(d[14]), "+f"(d[15]), "+f"(d[16]), "+f"(d[17]), "+f"(d[18]), "+f"(d[19]), "+f"(d[20]), "+f"(d[21]), "+f"(d[22]), "+f"(d[23]), "+f"(d[24]), "+f"(d[25]), "+f"(d[26]), "+f"(d[27]), "+f"(d[28]), "+f"(d[29]), "+f"(d[30]), "+f"(d[31])
    : "r"(a0), "r"(a1), "r"(a2), "r"(a3), "l"(descB), "n"(SCALE_D));
}
template <int SCALE_D>
__device__ __forceinline__ void wgmma_rs_n24_tb(float (&d)[12], uint32_t a0, uint32_t a1, uint32_t a2, uint32_t a3, uint64_t descB) {
  asm volatile("wgmma.mma_async.sync.aligned.m64n24k16.f32.bf16.bf16 {%0, %1, %2, %3, %4, %5, %6, %7, %8, %9, %10, %11}, {%12, %13, %14, %15}, %16, %17, 1, 1, 1;\n"
    : "+f"(d[0]), "+f"(d[1]), "+f"(d[2]), "+f"(d[3]), "+f"(d[4]), "+f"(d[5]), "+f"(d[6]), "+f"(d[7]), "+f"(d[8]), "+f"(d[9]), "+f"(d[10]), "+f"(d[11])
    : "r"(a0), "r"(a1), "r"(a2), "r"(a3), "l"(descB), "n"(SCALE_D));
}

constexpr uint32_t DHI_SW128_K = (1024 >> 4) | (1u << 30);
constexpr uint32_t DHI_SW64_MN = (512 >> 4) | (2u << 30);
constexpr uint32_t DHI_SW32_MN = (256 >> 4) | (3u << 30);

template <int NC>
__device__ __forceinline__ void store_tile_bf16(const float (&acc)[NC / 2], float scale, uint32_t stage, uint8_t* stage_ptr,
                                                __nv_bfloat16* gdst, int gpitch, int lane) {
  constexpr int PITCH = NC * 2 + 16;
  const uint32_t waddr = stage + ((lane & 7) + ((lane >> 3) & 1) * 8) * PITCH + (lane >> 4) * 16;
#pragma unroll
  for (int j = 0; j < NC / 16; j++) {
    stsm4(waddr + j * 32, pack_bf16(acc[8 * j] * scale, acc[8 * j + 1] * scale), pack_bf16(acc[8 * j + 2] * scale, acc[8 * j + 3] * scale),
          pack_bf16(acc[8 * j + 4] * scale, acc[8 * j + 5] * scale), pack_bf16(acc[8 * j + 6] * scale, acc[8 * j + 7] * scale));
  }
  __syncwarp();
  constexpr int CPR = NC / 8;
#pragma unroll
  for (int i = 0; i < CPR / 2; i++) {
    const int c = i * 32 + lane, r = c / CPR, cc = c % CPR;
    const uint4 v = *reinterpret_cast<const uint4*>(stage_ptr + r * PITCH + cc * 16);
    *reinterpret_cast<uint4*>(gdst + (size_t)r * gpitch + cc * 8) = v;
  }
}

__device__ __forceinline__ void signal_done(unsigned int* flag, int wg, int tid) {
  asm volatile("bar.sync %0, 128;" :: "r"(wg + 1) : "memory");
  if ((tid & 127) == 0) asm volatile("red.release.gpu.global.add.u32 [%0], 1;" :: "l"(flag) : "memory");
}
__device__ __forceinline__ void wait_flags8(const unsigned int* f, unsigned int target) {
  for (int spin = 0; spin < (1 << 26); spin++) {
    unsigned int a, b, c, d, e, g, h, i;
    asm volatile("ld.volatile.global.v4.u32 {%0, %1, %2, %3}, [%4];" : "=r"(a), "=r"(b), "=r"(c), "=r"(d) : "l"(f) : "memory");
    asm volatile("ld.volatile.global.v4.u32 {%0, %1, %2, %3}, [%4];" : "=r"(e), "=r"(g), "=r"(h), "=r"(i) : "l"(f + 4) : "memory");
    if (min(min(min(a, b), min(c, d)), min(min(e, g), min(h, i))) >= target) break;
    __nanosleep(64);
  }
  asm volatile("fence.acq_rel.gpu;" ::: "memory");
  asm volatile("fence.proxy.async;" ::: "memory");
}

constexpr int K1_STAGES = 4;
constexpr int K1_A_BYTES = 256 * 128;
constexpr int K1_B_BYTES = 64 * 160 * 2;
constexpr int K1_STAGE = K1_A_BYTES + K1_B_BYTES;
constexpr int K1_SMEM = 5 * K1_A_BYTES + 61440 + 1024;
constexpr int KV_STAGES = 5;
constexpr int KVW_OFF = KV_STAGES * K1_A_BYTES;

__global__ void __launch_bounds__(512, 1)
proj_kernel(const __grid_constant__ CUtensorMap tmX, const __grid_constant__ CUtensorMap tmWq, const __grid_constant__ CUtensorMap tmWqkv,
            const __nv_bfloat16* __restrict__ wk, const __nv_bfloat16* __restrict__ wv, const __nv_bfloat16* __restrict__ gate_w) {
  extern __shared__ uint8_t smem_raw[];
  __shared__ __align__(8) uint64_t bar_full[KV_STAGES], bar_empty[KV_STAGES];
  uint8_t* smem = reinterpret_cast<uint8_t*>((reinterpret_cast<uintptr_t>(smem_raw) + 1023) & ~(uintptr_t)1023);
  const uint32_t sbase = smem_u32(smem);
  const uint32_t dbase = sbase & 0x3FFFFu;
  const int tid = threadIdx.x, warp = tid >> 5, lane = tid & 31;
  const bool is_kv = blockIdx.x >= 128;
  PROF(0, 0);
  if (tid == 0) {
    for (int i = 0; i < KV_STAGES; i++) { mbar_init(smem_u32(&bar_full[i]), 1); mbar_init(smem_u32(&bar_empty[i]), is_kv ? 8 : 16); }
    fence_mbar_init();
  }
  uint2 wa[2][5], wb[2][5]; uint32_t gw[2];
  if (is_kv && tid < 320) {
#pragma unroll
    for (int r = 0; r < 2; r++) {
      const int k = tid + r * 320;
      const uint2* pk = reinterpret_cast<const uint2*>(wk + k * 20);
      const uint2* pv = reinterpret_cast<const uint2*>(wv + k * 20);
#pragma unroll
      for (int i = 0; i < 5; i++) { wa[r][i] = __ldg(pk + i); wb[r][i] = __ldg(pv + i); }
      gw[r] = (uint32_t)__bfloat16_as_ushort(gate_w[k]);
    }
  }
  __syncthreads();
  if (tid == 480) {
    if (!is_kv) { g_done[blockIdx.x] = 0u; g_doneL[blockIdx.x] = 0u; }
    asm volatile("fence.acq_rel.gpu;" ::: "memory");
    pdl_launch();
  }
  __syncwarp();

  if (!is_kv) {
    const int mb = blockIdx.x >> 4, nb = blockIdx.x & 15;
    const CUtensorMap* tw = nb < 4 ? &tmWq : &tmWqkv;
    const int j0 = (nb < 4 ? nb : nb - 4) * 5;
    auto load = [&](int kt) {
      const int s = kt % K1_STAGES;
      const uint32_t fb = smem_u32(&bar_full[s]);
      mbar_expect_tx(fb, K1_STAGE);
      tma_2d(sbase + s * K1_STAGE, &tmX, kt * 64, mb * 256, fb);
      tma_3d(sbase + s * K1_STAGE + K1_A_BYTES, tw, 0, kt * 64, j0, fb);
    };
    if (tid == 0) for (int kt = 0; kt < K1_STAGES; kt++) load(kt);
    __syncwarp();
    {
      const int wg = warp >> 2;
      float acc[80];
#pragma unroll
      for (int i = 0; i < 80; i++) acc[i] = 0.f;
      for (int kt = 0; kt < 10; kt++) {
        const int s = kt % K1_STAGES;
        mbar_wait(smem_u32(&bar_full[s]), (kt / K1_STAGES) & 1);
        const uint32_t alo = ((dbase + s * K1_STAGE + wg * 8192) >> 4) | (1u << 16);
        const uint32_t blo = ((dbase + s * K1_STAGE + K1_A_BYTES) >> 4) | ((4096u >> 4) << 16);
        fence_regs(acc);
        wg_fence();
#pragma unroll
        for (int k = 0; k < 4; k++) wgmma_ss_n160_tb(acc, mkd(alo + k * 2, DHI_SW128_K), mkd(blo + k * 64, DHI_SW64_MN));
        wg_commit();
        if (kt > 0 && kt - 1 + K1_STAGES < 10) {
          wg_wait<1>();
          const uint32_t eb = smem_u32(&bar_empty[(kt - 1) % K1_STAGES]);
          if (lane == 0) mbar_arrive(eb);
          if (tid == 0) { mbar_wait(eb, ((kt - 1) / K1_STAGES) & 1); load(kt - 1 + K1_STAGES); }
          __syncwarp();
        }
      }
      wg_wait<0>();
      fence_regs(acc);
      PROF(0, 1);
      asm volatile("bar.sync %0, 128;" :: "r"(wg + 1) : "memory");
      const int w4 = warp & 3;
      const uint32_t off = w4 * K1_STAGE + wg * 8192;
      const int row0 = mb * 256 + wg * 64 + w4 * 16;
      if (nb < 4) {
        store_tile_bf16<160>(acc, 0.22360679774997896f * 1.4426950408889634f, sbase + off, smem + off,
                             g_q + (size_t)row0 * D_MODEL + nb * 160, D_MODEL, lane);
      } else {
        store_tile_bf16<160>(acc, 1.0f, sbase + off, smem + off, g_qkv + (size_t)row0 * (3 * D_MODEL) + (nb - 4) * 160, 3 * D_MODEL, lane);
      }
    }
  } else {
    const int cb = blockIdx.x - 128;
    if (warp == 8 && lane == 0) {
      for (int it = 0; it < KV_STAGES; it++) {
        const uint32_t fb = smem_u32(&bar_full[it]);
        mbar_expect_tx(fb, K1_A_BYTES);
        tma_2d(sbase + it * K1_A_BYTES, &tmX, it * 64, cb * 512, fb);
      }
    }
    __syncwarp();
    if (tid < 320) {
#pragma unroll
      for (int r = 0; r < 2; r++) {
        uint4* dst = reinterpret_cast<uint4*>(smem + KVW_OFF + (tid + r * 320) * 16);
        dst[0] = make_uint4(wa[r][0].x, wa[r][0].y, wa[r][1].x, wa[r][1].y);
        dst[640] = make_uint4(wa[r][2].x, wa[r][2].y, wa[r][3].x, wa[r][3].y);
        dst[1280] = make_uint4(wa[r][4].x, wa[r][4].y, 0u, 0u);
        dst[1920] = make_uint4(wb[r][0].x, wb[r][0].y, wb[r][1].x, wb[r][1].y);
        dst[2560] = make_uint4(wb[r][2].x, wb[r][2].y, wb[r][3].x, wb[r][3].y);
        dst[3200] = make_uint4(wb[r][4].x, wb[r][4].y, gw[r], 0u);
      }
    }
    fence_proxy_async();
    asm volatile("bar.sync 1, 512;" ::: "memory");
    PROF(0, 1);
    if (warp == 8) {
      if (lane == 0) {
        int s = 0, ph = 0;
        for (int it = KV_STAGES; it < 20; it++) {
          mbar_wait(smem_u32(&bar_empty[s]), ph);
          const uint32_t fb = smem_u32(&bar_full[s]);
          mbar_expect_tx(fb, K1_A_BYTES);
          tma_2d(sbase + s * K1_A_BYTES, &tmX, (it >= 10 ? it - 10 : it) * 64, cb * 512 + (it >= 10 ? 256 : 0), fb);
          if (++s == KV_STAGES) { s = 0; ph ^= 1; }
        }
      }
    } else if (warp < 8) {
      const int wg = warp >> 2, w4 = warp & 3, g = lane >> 2, t = lane & 3;
      for (int pass = 0; pass < 2; pass++) {
        float acc[2][24];
#pragma unroll
        for (int i = 0; i < 24; i++) { acc[0][i] = 0.f; acc[1][i] = 0.f; }
        for (int kt = 0; kt < 10; kt++) {
          const int it = pass * 10 + kt, s = it % KV_STAGES;
          mbar_wait(smem_u32(&bar_full[s]), (it / KV_STAGES) & 1);
          const uint32_t alo = ((dbase + s * K1_A_BYTES + wg * 16384) >> 4) | (1u << 16);
          const uint32_t blo = ((dbase + KVW_OFF + kt * 1024) >> 4) | ((128u >> 4) << 16);
          fence_regs(acc[0]); fence_regs(acc[1]);
          wg_fence();
#pragma unroll
          for (int k = 0; k < 4; k++) {
            wgmma_ss_n48_tb(acc[0], mkd(alo + k * 2, DHI_SW128_K), mkd(blo + k * 16, 10240u >> 4));
            wgmma_ss_n48_tb(acc[1], mkd(alo + 512 + k * 2, DHI_SW128_K), mkd(blo + k * 16, 10240u >> 4));
          }
          wg_commit();
          if (kt > 0) {
            wg_wait<1>();
            if (lane == 0) mbar_arrive(smem_u32(&bar_empty[(it - 1) % KV_STAGES]));
          }
        }
        wg_wait<0>();
        fence_regs(acc[0]); fence_regs(acc[1]);
        if (lane == 0) mbar_arrive(smem_u32(&bar_empty[(pass * 10 + 9) % KV_STAGES]));
        if (pass == 0) PROF(0, 2);
        float kmax2 = 0.f, vmax = 0.f;
#pragma unroll
        for (int hh = 0; hh < 4; hh++) {
          const int h = hh & 1;
          const float (&a)[24] = acc[hh >> 1];
          const int key = cb * 512 + pass * 256 + wg * 128 + (hh >> 1) * 64 + w4 * 16 + g + h * 8;
          const int grp = key >> 7, kk = key & 127;
          const bool poly = (TMASK >> (kk >> 3)) & 1;
          uint8_t* gp = g_kvimg + grp * GRP_BYTES;
          const uint32_t k0 = pack_bf16(a[2 * h], a[2 * h + 1]);
          const uint32_t k1 = pack_bf16(a[4 + 2 * h], a[5 + 2 * h]);
          uint32_t k2 = pack_bf16(a[8 + 2 * h], a[9 + 2 * h]);
          float n2 = bf_lo(k0) * bf_lo(k0) + bf_hi(k0) * bf_hi(k0) + bf_lo(k1) * bf_lo(k1) + bf_hi(k1) * bf_hi(k1);
          if (t < 2) {
            n2 += bf_lo(k2) * bf_lo(k2) + bf_hi(k2) * bf_hi(k2);
            k2 = pack_bf16(bf_lo(k2) * 0.5f, bf_hi(k2) * 0.5f);
          } else if (t == 2) k2 = poly ? pack_bf16(24.f, 2.5f) : pack_bf16(0.5f, 0.f);
          else k2 = poly ? pack_bf16(0.5f, 0.f) : 0u;
          *reinterpret_cast<uint32_t*>(gp + kk * 16 + t * 4) = k0;
          *reinterpret_cast<uint32_t*>(gp + PLANE + kk * 16 + t * 4) = k1;
          *reinterpret_cast<uint32_t*>(gp + 2 * PLANE + kk * 16 + t * 4) = k2;
          n2 += __shfl_xor_sync(0xffffffffu, n2, 1);
          n2 += __shfl_xor_sync(0xffffffffu, n2, 2);
          kmax2 = (n2 > kmax2 || n2 != n2) ? n2 : kmax2;
          uint32_t v0 = pack_bf16(a[12 + 2 * h], a[13 + 2 * h]);
          uint32_t v1 = pack_bf16(a[16 + 2 * h], a[17 + 2 * h]);
          uint32_t v2 = pack_bf16(a[20 + 2 * h], a[21 + 2 * h]);
          float vm = fmaxf(fmaxf(fabsf(bf_lo(v0)), fabsf(bf_hi(v0))), fmaxf(fabsf(bf_lo(v1)), fabsf(bf_hi(v1))));
          if (t < 2) vm = fmaxf(vm, fmaxf(fabsf(bf_lo(v2)), fabsf(bf_hi(v2))));
          else if (t == 2) {
            const float z = a[20 + 2 * h];
            g_gate[key] = 1.f / (1.f + __expf(-z));
            v2 = 0x00003F80u;
          } else v2 = 0u;
          vmax = fmaxf(vmax, vm);
          if (poly) { v0 ^= 0x80008000u; v1 ^= 0x80008000u; v2 ^= 0x80008000u; }
          uint8_t* vp = gp + 3 * PLANE + (kk >> 3) * 384 + (kk & 7) * 16 + t * 4;
          *reinterpret_cast<uint32_t*>(vp) = v0;
          *reinterpret_cast<uint32_t*>(vp + 128) = v1;
          *reinterpret_cast<uint32_t*>(vp + 256) = v2;
        }
#pragma unroll
        for (int o = 1; o < 32; o <<= 1) {
          const float a = __shfl_xor_sync(0xffffffffu, kmax2, o);
          kmax2 = (a > kmax2 || a != a) ? a : kmax2;
          vmax = fmaxf(vmax, __shfl_xor_sync(0xffffffffu, vmax, o));
        }
        if (lane == 0) { g_kmax2[cb * 16 + pass * 8 + warp] = kmax2; g_vmax[cb * 16 + pass * 8 + warp] = vmax; }
      }
    }
  }
  PROF(0, 3);
}

__device__ __forceinline__ uint32_t ex2_pair_poly(float u0, float u1, uint32_t one2) {
  const uint32_t W = __byte_perm(__float_as_uint(u0), __float_as_uint(u1), 0x6521);
  uint32_t v; asm("lop3.b32 %0, %1, 0x007F007F, %2, 0xEA;" : "=r"(v) : "r"(W), "r"(one2));
  uint32_t L, p;
  asm("fma.rn.bf16x2 %0, %1, %2, %3;" : "=r"(L) : "r"(v), "r"(0x1f961f96u), "r"(0x9fe39fe3u));
  asm("fma.rn.bf16x2 %0, %1, %1, %2;" : "=r"(p) : "r"(L), "r"(0x00f500f5u));
  return W + p;
}
template <int JOFF>
__device__ __forceinline__ void softmax_fast(const float (&S)[32], uint32_t (&P)[16], uint32_t one2) {
#pragma unroll
  for (int i = 0; i < 16; i++) {
    if ((TMASK >> (JOFF + i / 2)) & 1) P[i] = ex2_pair_poly(S[2 * i], S[2 * i + 1], one2);
    else P[i] = pack_bf16(ex2(S[2 * i]), ex2(S[2 * i + 1]));
  }
}
template <int JOFF>
__device__ __forceinline__ void softmax_slow(const float (&S)[32], uint32_t (&P)[16], float (&O)[12], float& m0, float& m1) {
  float a0 = m0, a1 = m1;
#pragma unroll
  for (int j = 0; j < 8; j++) {
    a0 = fmaxf(a0, fmaxf(S[4 * j], S[4 * j + 1]));
    a1 = fmaxf(a1, fmaxf(S[4 * j + 2], S[4 * j + 3]));
  }
  a0 = fmaxf(a0, __shfl_xor_sync(0xffffffffu, a0, 1)); a0 = fmaxf(a0, __shfl_xor_sync(0xffffffffu, a0, 2));
  a1 = fmaxf(a1, __shfl_xor_sync(0xffffffffu, a1, 1)); a1 = fmaxf(a1, __shfl_xor_sync(0xffffffffu, a1, 2));
  const float c0 = ex2(m0 - a0), c1 = ex2(m1 - a1);
  m0 = a0; m1 = a1;
#pragma unroll
  for (int j = 0; j < 3; j++) { O[4 * j] *= c0; O[4 * j + 1] *= c0; O[4 * j + 2] *= c1; O[4 * j + 3] *= c1; }
#pragma unroll
  for (int i = 0; i < 16; i++) {
    const float m = (i & 1) ? a1 : a0;
    const uint32_t p = pack_bf16(ex2(S[2 * i] - m), ex2(S[2 * i + 1] - m));
    P[i] = ((TMASK >> (JOFF + i / 2)) & 1) ? (p ^ 0x80008000u) : p;
  }
}
constexpr uint32_t DHI_KV = 128 >> 4;
__device__ __forceinline__ void issue_qk(float (&S)[32], const uint32_t (&q)[8], uint32_t base) {
  wgmma_rs_n64<0>(S, q[0], q[1], q[2], q[3], mkd(base + ((PLANE >> 4) << 16), DHI_KV));
  wgmma_rs_n64<1>(S, q[4], q[5], q[6], q[7], mkd(base + (2 * PLANE >> 4), DHI_KV));
}
__device__ __forceinline__ void issue_pv(float (&O)[12], const uint32_t (&P)[16], uint32_t vbase) {
#pragma unroll
  for (int kk = 0; kk < 4; kk++)
    wgmma_rs_n24_tb<1>(O, P[4 * kk], P[4 * kk + 1], P[4 * kk + 2], P[4 * kk + 3], mkd(vbase + kk * (768 >> 4), DHI_KV));
}

constexpr uint32_t VOFF = ((3 * PLANE) >> 4) + ((384u >> 4) << 16);
constexpr int KVR = 4;
constexpr int OFF_WA = KVR * GRP_BYTES;
constexpr int OFF_BR = OFF_WA + 10 * 10240;
constexpr int BR_STAGE = 8192 + 10240, BR_STAGES = 3;
constexpr int OFF_QS = OFF_BR + BR_STAGES * BR_STAGE;
constexpr int OFF_BAR = OFF_QS + 512 * 6 * 4;
constexpr int K2_SMEM = OFF_BAR + 256 + 1024;
constexpr int BAR_KV = 0, BAR_WA = 4, BAR_BR = 5, BAR_TA = 8, BAR_TE = 14, CNT_KV = 18;
constexpr int NSTEP = 2 * NGRP;

__device__ __forceinline__ void kv_load(uint32_t sbase, int step) {
  const uint32_t bar = sbase + OFF_BAR + (BAR_KV + (step & (KVR - 1))) * 8;
  mbar_expect_tx(bar, GRP_BYTES);
  bulk_g2s(sbase + (step & (KVR - 1)) * GRP_BYTES, g_kvimg + (step & (NGRP - 1)) * GRP_BYTES, GRP_BYTES, bar);
}
__device__ __forceinline__ void kv_release(uint32_t sbase, int step, bool elected) {
  if (elected && step + KVR < NSTEP) {
    uint32_t old;
    asm volatile("atom.acq_rel.cta.shared::cta.inc.u32 %0, [%1], 3;" : "=r"(old) : "r"(sbase + OFF_BAR + CNT_KV * 8 + (step & (KVR - 1)) * 4) : "memory");
    if (old == 3u) kv_load(sbase, step + KVR);
  }
  __syncwarp();
}
__device__ __forceinline__ void kv_wait(uint32_t sbase, int step) {
  mbar_wait(sbase + OFF_BAR + (BAR_KV + (step & (KVR - 1))) * 8, (step / KVR) & 1);
}

__device__ __forceinline__ uint32_t kv_release_begin(uint32_t sbase, int slot, bool doit) {
  uint32_t old = 0;
  if (doit) asm volatile("atom.relaxed.cta.shared::cta.inc.u32 %0, [%1], 3;" : "=r"(old) : "r"(sbase + OFF_BAR + CNT_KV * 8 + slot * 4) : "memory");
  return old;
}
__device__ __forceinline__ void attn_tile_fast(const uint32_t (&q)[8], float (&O)[12], uint32_t sbase, int step0, bool elected, uint32_t one2) {
  float S[32]; uint32_t P[16];
#pragma unroll
  for (int i = 0; i < 32; i++) S[i] = 0.f;
  const uint32_t kb0 = (sbase & 0x3FFFFu) >> 4;
  kv_wait(sbase, step0);
  fence_regs(S); fence_regs(O);
  wg_fence();
  issue_qk(S, q, kb0);
  wg_commit();
#pragma unroll 1
  for (int step4 = step0; step4 < step0 + NGRP; step4 += KVR) {
#pragma unroll
    for (int j = 0; j < KVR; j++) {
      const int step = step4 + j;
      const uint32_t kb = kb0 + j * (GRP_BYTES >> 4);
      const uint32_t knext = kb0 + ((j + 1) & (KVR - 1)) * (GRP_BYTES >> 4);
      wg_wait<0>();
      fence_regs(S); fence_regs(P); fence_regs(O);
      const uint32_t old = kv_release_begin(sbase, (j + KVR - 1) & (KVR - 1), elected && step > step0 && step - 1 + KVR < NSTEP);
      softmax_fast<0>(S, P, one2);
      fence_regs(S); fence_regs(P); fence_regs(O);
      wg_fence();
      issue_qk(S, q, kb + 64);
      issue_pv(O, P, kb + VOFF);
      wg_commit();
      if (step + 1 < NSTEP) mbar_wait(sbase + OFF_BAR + (BAR_KV + ((j + 1) & (KVR - 1))) * 8, ((step + 1) / KVR) & 1);
      wg_wait<0>();
      fence_regs(S); fence_regs(P); fence_regs(O);
      softmax_fast<8>(S, P, one2);
      fence_regs(S); fence_regs(P); fence_regs(O);
      wg_fence();
      issue_qk(S, q, knext);
      issue_pv(O, P, kb + VOFF + 4 * (768 >> 4));
      wg_commit();
      if (old == 3u) kv_load(sbase, step - 1 + KVR);
    }
  }
  wg_wait<0>();
  fence_regs(O); fence_regs(S);
  kv_release(sbase, step0 + NGRP - 1, elected);
}
template <int H>
__device__ __forceinline__ void slow_step(const uint32_t (&q)[8], float (&O)[12], uint32_t kb, float& m0, float& m1) {
  float S[32]; uint32_t P[16];
#pragma unroll
  for (int i = 0; i < 32; i++) S[i] = 0.f;
  fence_regs(S);
  wg_fence();
  issue_qk(S, q, kb + 64 * H);
  wg_commit();
  wg_wait<0>();
  fence_regs(S);
  softmax_slow<8 * H>(S, P, O, m0, m1);
  fence_regs(P); fence_regs(O);
  wg_fence();
  issue_pv(O, P, kb + VOFF + H * 4 * (768 >> 4));
  wg_commit();
  wg_wait<0>();
  fence_regs(O); fence_regs(P);
}
__device__ __forceinline__ void attn_tile_slow(const uint32_t (&q)[8], float (&O)[12], uint32_t sbase, int step0, bool elected) {
  float m0 = -INFINITY, m1 = -INFINITY;
#pragma unroll 1
  for (int grp = 0; grp < NGRP; grp++) {
    kv_wait(sbase, step0 + grp);
    const uint32_t kb = ((sbase & 0x3FFFFu) >> 4) + (grp & (KVR - 1)) * (GRP_BYTES >> 4);
    slow_step<0>(q, O, kb, m0, m1);
    slow_step<1>(q, O, kb, m0, m1);
    kv_release(sbase, step0 + grp, elected);
  }
}

__device__ __forceinline__ void local_attn_pair(int token, int lane) {
  const __nv_bfloat16* base = g_qkv + (size_t)token * (3 * D_MODEL) + lane * DH;
  float f[20];
  {
    const uint2* p = reinterpret_cast<const uint2*>(base);
#pragma unroll
    for (int i = 0; i < 5; i++) { const uint2 v = p[i]; f[4 * i] = bf_lo(v.x); f[4 * i + 1] = bf_hi(v.x); f[4 * i + 2] = bf_lo(v.y); f[4 * i + 3] = bf_hi(v.y); }
  }
  float sc[8];
  float mx = -INFINITY;
#pragma unroll
  for (int w = 0; w < 8; w++) {
    const bool ok = token - 2 * w >= 0;
    const uint2* p = reinterpret_cast<const uint2*>(base + D_MODEL - (ok ? 2 * w : 0) * (3 * D_MODEL));
    float s = 0.f;
#pragma unroll
    for (int i = 0; i < 5; i++) {
      const uint2 v = p[i];
      s = fmaf(f[4 * i], bf_lo(v.x), s); s = fmaf(f[4 * i + 1], bf_hi(v.x), s);
      s = fmaf(f[4 * i + 2], bf_lo(v.y), s); s = fmaf(f[4 * i + 3], bf_hi(v.y), s);
    }
    s *= 0.22360679774997896f * 1.4426950408889634f;
    sc[w] = ok ? s : -1e9f * 1.4426950408889634f;
    mx = fmaxf(mx, sc[w]);
  }
  float l = 0.f;
#pragma unroll
  for (int w = 0; w < 8; w++) { sc[w] = ex2(sc[w] - mx); l += sc[w]; }
#pragma unroll
  for (int i = 0; i < 20; i++) f[i] = 0.f;
#pragma unroll
  for (int w = 0; w < 8; w++) {
    const bool ok = token - 2 * w >= 0;
    const uint2* p = reinterpret_cast<const uint2*>(base + 2 * D_MODEL - (ok ? 2 * w : token) * (3 * D_MODEL));
#pragma unroll
    for (int i = 0; i < 5; i++) {
      const uint2 v = p[i];
      f[4 * i] = fmaf(sc[w], bf_lo(v.x), f[4 * i]); f[4 * i + 1] = fmaf(sc[w], bf_hi(v.x), f[4 * i + 1]);
      f[4 * i + 2] = fmaf(sc[w], bf_lo(v.y), f[4 * i + 2]); f[4 * i + 3] = fmaf(sc[w], bf_hi(v.y), f[4 * i + 3]);
    }
  }
  const float r = (1.f - g_gate[token]) / l;
  uint2* dst = reinterpret_cast<uint2*>(g_a2 + (size_t)token * (2 * D_MODEL) + D_MODEL + lane * DH);
#pragma unroll
  for (int i = 0; i < 5; i++) dst[i] = make_uint2(pack_bf16(f[4 * i] * r, f[4 * i + 1] * r), pack_bf16(f[4 * i + 2] * r, f[4 * i + 3] * r));
}

__device__ __forceinline__ uint32_t ta_slot(int i) { return i < 3 ? i * 16384 : OFF_BR + (i - 3) * 16384; }

__global__ void __launch_bounds__(640, 1)
attn_kernel(const __grid_constant__ CUtensorMap tmA2, const __grid_constant__ CUtensorMap tmA2b, const __grid_constant__ CUtensorMap tmWoA, const __grid_constant__ CUtensorMap tmWoB,
            __nv_bfloat16* __restrict__ out, uint32_t one2) {
  extern __shared__ uint8_t smem_raw[];
  uint8_t* smem = reinterpret_cast<uint8_t*>((reinterpret_cast<uintptr_t>(smem_raw) + 1023) & ~(uintptr_t)1023);
  const uint32_t sbase = smem_u32(smem);
  const uint32_t dbase = sbase & 0x3FFFFu;
  const uint32_t bars = sbase + OFF_BAR;
  const int tid = threadIdx.x, wg = tid >> 7, warp = (tid >> 5) & 3, lane = tid & 31, g = lane >> 2, t = lane & 3;
  const int mb = blockIdx.x >> 3, nb = blockIdx.x & 7;
  if (tid == 0) {
    for (int i = 0; i < BAR_TE; i++) mbar_init(bars + i * 8, 1);
    for (int i = BAR_TE; i < BAR_TE + 4; i++) mbar_init(bars + i * 8, 8);
    for (int i = 0; i < 4; i++) *reinterpret_cast<uint32_t*>(smem + OFF_BAR + CNT_KV * 8 + i * 4) = 0u;
    fence_mbar_init();
  }
  __syncthreads();
  if (wg == 4) {
    if (tid == 512) {
      mbar_expect_tx(bars + BAR_WA * 8, 10 * 10240);
      for (int kt = 0; kt < 10; kt++) tma_3d(sbase + OFF_WA + kt * 10240, &tmWoA, 0, kt * 64, nb * 5, bars + BAR_WA * 8);
    }
    pdl_wait();
    asm volatile("bar.sync 7, 640;" ::: "memory");
#pragma unroll 1
    for (int i = 0; i < 4; i++) local_attn_pair(blockIdx.x * 16 + i * 4 + warp, lane);
    if (tid == 512) PROF2(0, 2);
    signal_done(&g_doneL[blockIdx.x], wg, tid);
    auto br_load = [&](int it, int st) {
      const uint32_t fb = bars + (BAR_BR + st) * 8;
      const uint32_t dst = sbase + OFF_BR + st * BR_STAGE;
      const int kc = (it >= 10 ? it - 10 : it) * 64;
      mbar_expect_tx(fb, BR_STAGE);
      tma_2d(dst, &tmA2, D_MODEL + kc, (blockIdx.x >> 3) * 128 + (it >= 10 ? 64 : 0), fb);
      tma_3d(dst + 8192, &tmWoB, 0, kc, (blockIdx.x & 7) * 5, fb);
    };
    if (tid == 512) {
      wait_flags8(&g_doneL[mb * 8], 1u);
      for (int it = 0; it < BR_STAGES; it++) br_load(it, it);
    }
    __syncwarp();
    {
      int st = 0, ph = 0;
      float acc[40];
#pragma unroll 1
      for (int it = 0; it < 20; it++) {
        if (it == 0 || it == 10) {
#pragma unroll
          for (int i = 0; i < 40; i++) acc[i] = 0.f;
        }
        mbar_wait(bars + (BAR_BR + st) * 8, ph);
        const uint32_t alo = ((dbase + OFF_BR + st * BR_STAGE) >> 4);
        fence_regs(acc);
        wg_fence();
#pragma unroll
        for (int k = 0; k < 4; k++)
          wgmma_ss_n80_tb(acc, mkd(alo + (k * 2 + (1u << 16)), DHI_SW128_K), mkd(alo + (512 + k * 32 + ((2048u >> 4) << 16)), DHI_SW32_MN));
        wg_commit();
        wg_wait<0>();
        fence_regs(acc);
        asm volatile("bar.sync 5, 128;" ::: "memory");
        if (threadIdx.x == 512 && it + BR_STAGES < 20) br_load(it + BR_STAGES, st);
        __syncwarp();
        if (it == 9 || it == 19) {
          float* pp = g_part + (size_t)(blockIdx.x * 2 + (it == 19)) * (40 * 128) + (threadIdx.x & 127);
#pragma unroll
          for (int i = 0; i < 40; i++) pp[i * 128] = acc[i];
        }
        if (++st == BR_STAGES) { st = 0; ph ^= 1; }
      }
    }
    if (tid == 512) PROF2(1, 0);
    asm volatile("bar.arrive 6, 384;" ::: "memory");
    if (tid == 512) {
      wait_flags8(&g_done[mb * 8], 4u);
      PROF2(2, 0);
    }
    if (tid == 512) {
      for (int kt = 0; kt < 10; kt++) {
        const int sl = kt % 6;
        if (kt >= 6) mbar_wait(bars + (BAR_TE + kt - 6) * 8, 0);
        const uint32_t fb = bars + (BAR_TA + sl) * 8;
        mbar_expect_tx(fb, 16384);
        tma_2d(sbase + ta_slot(sl), &tmA2b, kt * 64, mb * 128, fb);
      }
    }
  } else {
    const bool elected = (tid & 127) == 0;
    pdl_wait();
    PROF(1, 1);
    if (tid == 384) for (int j = 0; j < KVR; j++) kv_load(sbase, j);
    __syncwarp();
    uint32_t q[8];
    uint32_t* qstash = reinterpret_cast<uint32_t*>(smem + OFF_QS) + tid;
    const int rowA = (blockIdx.x * 8 + wg) * 64 + warp * 16 + g;
    {
      const uint32_t* r0 = reinterpret_cast<const uint32_t*>(g_q + (size_t)rowA * DH);
      const uint32_t* r1 = r0 + 8 * (DH / 2);
      const uint32_t* s0 = r0 + 256 * (DH / 2);
      const uint32_t* s1 = s0 + 8 * (DH / 2);
      q[0] = r0[t]; q[1] = r1[t]; q[2] = r0[t + 4]; q[3] = r1[t + 4];
      q[4] = t < 2 ? r0[8 + t] : 0u;
      q[5] = t < 2 ? r1[8 + t] : 0u;
      qstash[0] = s0[t]; qstash[512] = s1[t]; qstash[1024] = s0[t + 4]; qstash[1536] = s1[t + 4];
      qstash[2048] = t < 2 ? s0[8 + t] : 0u;
      qstash[2560] = t < 2 ? s1[8 + t] : 0u;
    }
    float kmax2 = 0.f, vmax = 0.f;
#pragma unroll
    for (int i = 0; i < 2; i++) {
      const float a = g_kmax2[lane + 32 * i];
      kmax2 = (a > kmax2 || a != a) ? a : kmax2;
      vmax = fmaxf(vmax, g_vmax[lane + 32 * i]);
    }
#pragma unroll
    for (int o = 1; o < 32; o <<= 1) {
      const float a = __shfl_xor_sync(0xffffffffu, kmax2, o);
      kmax2 = (a > kmax2 || a != a) ? a : kmax2;
      vmax = fmaxf(vmax, __shfl_xor_sync(0xffffffffu, vmax, o));
    }
    const float qlim = (vmax >= 0.00390625f && vmax <= 256.f) ? 9025.f / kmax2 : -1.f;
    asm volatile("bar.arrive 7, 640;" ::: "memory");
    PROF(1, 2);
#pragma unroll 1
    for (int it = 0; it < 2; it++) {
      const int row0 = rowA + it * 256;
      if (it == 1) {
#pragma unroll
        for (int i = 0; i < 6; i++) q[i] = qstash[512 * i];
      }
      float n0 = bf_lo(q[0]) * bf_lo(q[0]) + bf_hi(q[0]) * bf_hi(q[0]) + bf_lo(q[2]) * bf_lo(q[2]) + bf_hi(q[2]) * bf_hi(q[2]) +
                 bf_lo(q[4]) * bf_lo(q[4]) + bf_hi(q[4]) * bf_hi(q[4]);
      float n1 = bf_lo(q[1]) * bf_lo(q[1]) + bf_hi(q[1]) * bf_hi(q[1]) + bf_lo(q[3]) * bf_lo(q[3]) + bf_hi(q[3]) * bf_hi(q[3]) +
                 bf_lo(q[5]) * bf_lo(q[5]) + bf_hi(q[5]) * bf_hi(q[5]);
      n0 += __shfl_xor_sync(0xffffffffu, n0, 1); n0 += __shfl_xor_sync(0xffffffffu, n0, 2);
      n1 += __shfl_xor_sync(0xffffffffu, n1, 1); n1 += __shfl_xor_sync(0xffffffffu, n1, 2);
      const bool safe = (n0 <= qlim) && (n1 <= qlim);
      uint32_t unsafe_any;
      asm volatile("{\n.reg .pred p, r;\nsetp.eq.u32 p, %1, 0;\nbarrier.cta.red.or.pred r, %2, 128, p;\nselp.u32 %0, 1, 0, r;\n}\n"
                   : "=r"(unsafe_any) : "r"((uint32_t)safe), "r"(wg + 1) : "memory");
      float O[12];
#pragma unroll
      for (int i = 0; i < 12; i++) O[i] = 0.f;
      if (!unsafe_any && t >= 2) { q[4] = q[5] = (t == 2) ? 0x3F804100u : 0x00003B80u; }
      q[6] = q[4]; q[7] = q[5];
      fence_regs(q);
      if (!unsafe_any) attn_tile_fast(q, O, sbase, it * NGRP, elected, one2);
      else attn_tile_slow(q, O, sbase, it * NGRP, elected);
      const float l0 = __shfl_sync(0xffffffffu, O[8], (lane & ~3) | 2);
      const float l1 = __shfl_sync(0xffffffffu, O[10], (lane & ~3) | 2);
      const int tok = row0 >> 5;
      const float gt = g_gate[tok];
      const float i0 = gt / l0, i1 = gt / l1;
      uint32_t* o0 = reinterpret_cast<uint32_t*>(g_a2 + (size_t)tok * (2 * D_MODEL) + (row0 & 31) * DH);
      uint32_t* o1 = o0 + 8 * (DH / 2);
      o0[t] = pack_bf16(O[0] * i0, O[1] * i0); o1[t] = pack_bf16(O[2] * i1, O[3] * i1);
      o0[t + 4] = pack_bf16(O[4] * i0, O[5] * i0); o1[t + 4] = pack_bf16(O[6] * i1, O[7] * i1);
      if (t < 2) { o0[t + 8] = pack_bf16(O[8] * i0, O[9] * i0); o1[t + 8] = pack_bf16(O[10] * i1, O[11] * i1); }
    }
    signal_done(&g_done[blockIdx.x], wg, tid);
    PROF(1, 3);
    if (wg < 2) {
      float acc[40];
      asm volatile("bar.sync 6, 384;" ::: "memory");
      {
        const float* pp = g_part + (size_t)(blockIdx.x * 2 + wg) * (40 * 128) + (tid & 127);
#pragma unroll
        for (int i = 0; i < 40; i++) acc[i] = pp[i * 128];
      }
      mbar_wait(bars + BAR_WA * 8, 0);
#pragma unroll 1
      for (int kt = 0; kt < 10; kt++) {
        const int sl = kt % 6;
        mbar_wait(bars + (BAR_TA + sl) * 8, kt / 6);
        if (kt == 0) PROF(2, 1);
        const uint32_t alo = ((dbase + ta_slot(sl) + wg * 8192) >> 4) | (1u << 16);
        const uint32_t blo = ((dbase + OFF_WA + kt * 10240) >> 4) | ((2048u >> 4) << 16);
        fence_regs(acc);
        wg_fence();
#pragma unroll
        for (int k = 0; k < 4; k++) wgmma_ss_n80_tb(acc, mkd(alo + k * 2, DHI_SW128_K), mkd(blo + k * 32, DHI_SW32_MN));
        wg_commit();
        if (kt < 4) {
          wg_wait<0>();
          if (lane == 0) mbar_arrive(bars + (BAR_TE + kt) * 8);
        }
      }
      wg_wait<0>();
      fence_regs(acc);
      PROF(2, 2);
      asm volatile("bar.sync %0, 128;" :: "r"(wg + 1) : "memory");
      const uint32_t so = ta_slot(warp) + wg * 8192;
      const int row0 = mb * 128 + wg * 64 + warp * 16;
      store_tile_bf16<80>(acc, 1.0f, sbase + so, smem + so, out + (size_t)row0 * D_MODEL + nb * 80, D_MODEL, lane);
      PROF(2, 3);
    }
  }
}

typedef CUresult (*EncodeFn)(CUtensorMap*, CUtensorMapDataType, cuuint32_t, void*, const cuuint64_t*, const cuuint64_t*,
                             const cuuint32_t*, const cuuint32_t*, CUtensorMapInterleave, CUtensorMapSwizzle,
                             CUtensorMapL2promotion, CUtensorMapFloatOOBfill);

void make_map(EncodeFn fn, CUtensorMap* tm, const void* ptr, int rank, const cuuint64_t* dims, const cuuint64_t* strides,
              const cuuint32_t* box, CUtensorMapSwizzle sw) {
  const cuuint32_t es[3] = {1, 1, 1};
  fn(tm, CU_TENSOR_MAP_DATA_TYPE_BFLOAT16, rank, const_cast<void*>(ptr), dims, strides, box, es, CU_TENSOR_MAP_INTERLEAVE_NONE, sw,
     CU_TENSOR_MAP_L2_PROMOTION_L2_256B, CU_TENSOR_MAP_FLOAT_OOB_FILL_NONE);
}
void map_a(EncodeFn fn, CUtensorMap* tm, const void* p, int rows, int cols, int box_rows) {
  const cuuint64_t dims[2] = {(cuuint64_t)cols, (cuuint64_t)rows};
  const cuuint64_t str[1] = {(cuuint64_t)cols * 2};
  const cuuint32_t box[2] = {64, (cuuint32_t)box_rows};
  make_map(fn, tm, p, 2, dims, str, box, CU_TENSOR_MAP_SWIZZLE_128B);
}
void map_w(EncodeFn fn, CUtensorMap* tm, const void* p, int K, int N, int atom, CUtensorMapSwizzle sw) {
  const cuuint64_t dims[3] = {(cuuint64_t)atom, (cuuint64_t)K, (cuuint64_t)(N / atom)};
  const cuuint64_t str[2] = {(cuuint64_t)N * 2, (cuuint64_t)atom * 2};
  const cuuint32_t box[3] = {(cuuint32_t)atom, 64, 5};
  make_map(fn, tm, p, 3, dims, str, box, sw);
}

template <typename... KArgs, typename... Args>
void launch(void (*kern)(KArgs...), int grid, int block, int smem, bool pdl, Args... args) {
  cudaLaunchConfig_t cfg = {};
  cfg.gridDim = dim3(grid); cfg.blockDim = dim3(block); cfg.dynamicSmemBytes = smem; cfg.stream = cudaStreamPerThread;
  cudaLaunchAttribute at[1];
  at[0].id = cudaLaunchAttributeProgrammaticStreamSerialization;
  at[0].val.programmaticStreamSerializationAllowed = 1;
  cfg.attrs = at; cfg.numAttrs = pdl ? 1 : 0;
  cudaLaunchKernelEx(&cfg, kern, KArgs(args)...);
}

}

extern "C" void kernel_launch(void* const* d_in, const int* in_sizes, int n_in, void* d_out, int out_size) {
  (void)in_sizes; (void)n_in; (void)out_size;
  const __nv_bfloat16* x = (const __nv_bfloat16*)d_in[0];
  const __nv_bfloat16* wq = (const __nv_bfloat16*)d_in[1];
  const __nv_bfloat16* wk = (const __nv_bfloat16*)d_in[2];
  const __nv_bfloat16* wv = (const __nv_bfloat16*)d_in[3];
  const __nv_bfloat16* woA = (const __nv_bfloat16*)d_in[4];
  const __nv_bfloat16* wqkv = (const __nv_bfloat16*)d_in[6];
  const __nv_bfloat16* woB = (const __nv_bfloat16*)d_in[7];
  const __nv_bfloat16* gate_w = (const __nv_bfloat16*)d_in[8];

  static EncodeFn enc = nullptr;
  static void* a2_ptr = nullptr;
  if (!enc) {
    void* fp = nullptr;
    cudaDriverEntryPointQueryResult qr;
    cudaGetDriverEntryPoint("cuTensorMapEncodeTiled", &fp, cudaEnableDefault, &qr);
    enc = (EncodeFn)fp;
    cudaGetSymbolAddress(&a2_ptr, g_a2);
    cudaFuncSetAttribute(proj_kernel, cudaFuncAttributeMaxDynamicSharedMemorySize, K1_SMEM);
    cudaFuncSetAttribute(attn_kernel, cudaFuncAttributeMaxDynamicSharedMemorySize, K2_SMEM);
  }
  CUtensorMap tmX, tmWq, tmWqkv, tmA2, tmA2b, tmWoA, tmWoB;
  map_a(enc, &tmX, x, S_LEN, D_MODEL, 256);
  map_w(enc, &tmWq, wq, D_MODEL, D_MODEL, 32, CU_TENSOR_MAP_SWIZZLE_64B);
  map_w(enc, &tmWqkv, wqkv, D_MODEL, 3 * D_MODEL, 32, CU_TENSOR_MAP_SWIZZLE_64B);
  map_a(enc, &tmA2, a2_ptr, S_LEN, 2 * D_MODEL, 64);
  map_a(enc, &tmA2b, a2_ptr, S_LEN, 2 * D_MODEL, 128);
  map_w(enc, &tmWoA, woA, D_MODEL, D_MODEL, 16, CU_TENSOR_MAP_SWIZZLE_32B);
  map_w(enc, &tmWoB, woB, D_MODEL, D_MODEL, 16, CU_TENSOR_MAP_SWIZZLE_32B);

  launch(proj_kernel, 132, 512, K1_SMEM, false, tmX, tmWq, tmWqkv, wk, wv, gate_w);
  launch(attn_kernel, 128, 640, K2_SMEM, true, tmA2, tmA2b, tmWoA, tmWoB, (__nv_bfloat16*)d_out, 0x3F803F80u);
}
```

```cpp
#include <cuda_runtime.h>
#include <cuda_bf16.h>
#include <cuda.h>
#include <stdint.h>

namespace {

constexpr int S_LEN = 2048, D_MODEL = 640, DH = 20;

constexpr int GRP = 128;
constexpr int PLANE = GRP * 16;
constexpr int GRP_BYTES = GRP * 16 * 6;
constexpr int NGRP = S_LEN / GRP;
#define TMASKV 0x6DB6u
constexpr uint32_t TMASK = TMASKV;

__device__ __align__(1024) __nv_bfloat16 g_q[S_LEN * D_MODEL];
__device__ __align__(1024) __nv_bfloat16 g_qkv[S_LEN * 3 * D_MODEL];
__device__ __align__(1024) __nv_bfloat16 g_a2[S_LEN * 2 * D_MODEL];
__device__ __align__(1024) uint8_t g_kvimg[NGRP * GRP_BYTES];
__device__ float g_gate[S_LEN];
__device__ float g_kmax2[64];
__device__ float g_vmax[64];
__device__ __align__(32) unsigned int g_doneL[128];
__device__ float g_part[128 * 2 * 40 * 128];
__device__ __align__(32) unsigned int g_done[128];

#define PROF(k, slot)
#define PROF2(k, slot)
__device__ __forceinline__ uint32_t smem_u32(const void* p) { return (uint32_t)__cvta_generic_to_shared(p); }
__device__ __forceinline__ uint64_t mkd(uint32_t lo, uint32_t hi) {
  uint64_t d; asm("mov.b64 %0, {%1, %2};" : "=l"(d) : "r"(lo), "r"(hi)); return d;
}
__device__ __forceinline__ void wg_fence() { asm volatile("wgmma.fence.sync.aligned;" ::: "memory"); }
__device__ __forceinline__ void wg_commit() { asm volatile("wgmma.commit_group.sync.aligned;" ::: "memory"); }
template <int N> __device__ __forceinline__ void wg_wait() { asm volatile("wgmma.wait_group.sync.aligned %0;" :: "n"(N) : "memory"); }
template <int N> __device__ __forceinline__ void fence_regs(float (&d)[N]) {
#pragma unroll
  for (int i = 0; i < N; i++) asm volatile("" : "+f"(d[i]) :: "memory");
}
template <int N> __device__ __forceinline__ void fence_regs(uint32_t (&d)[N]) {
#pragma unroll
  for (int i = 0; i < N; i++) asm volatile("" : "+r"(d[i]) :: "memory");
}
__device__ __forceinline__ void mbar_init(uint32_t bar, uint32_t cnt) { asm volatile("mbarrier.init.shared::cta.b64 [%0], %1;" :: "r"(bar), "r"(cnt)); }
__device__ __forceinline__ void mbar_expect_tx(uint32_t bar, uint32_t bytes) {
  asm volatile("mbarrier.arrive.expect_tx.shared::cta.b64 _, [%0], %1;" :: "r"(bar), "r"(bytes) : "memory");
}
__device__ __forceinline__ void mbar_arrive(uint32_t bar) { asm volatile("mbarrier.arrive.shared::cta.b64 _, [%0];" :: "r"(bar) : "memory"); }
__device__ __forceinline__ void mbar_wait(uint32_t bar, uint32_t parity) {
  asm volatile("{\n.reg .pred p;\nWAIT_%=:\nmbarrier.try_wait.parity.shared::cta.b64 p, [%0], %1;\n@p bra DONE_%=;\nbra WAIT_%=;\nDONE_%=:\n}\n"
               :: "r"(bar), "r"(parity) : "memory");
}
__device__ __forceinline__ void fence_mbar_init() { asm volatile("fence.mbarrier_init.release.cluster;" ::: "memory"); }
__device__ __forceinline__ void fence_proxy_async() { asm volatile("fence.proxy.async.shared::cta;" ::: "memory"); }
__device__ __forceinline__ void bulk_g2s(uint32_t dst, const void* src, uint32_t bytes, uint32_t bar) {
  asm volatile("cp.async.bulk.shared::cluster.global.mbarrier::complete_tx::bytes [%0], [%1], %2, [%3];"
               :: "r"(dst), "l"(src), "r"(bytes), "r"(bar) : "memory");
}
__device__ __forceinline__ void tma_2d(uint32_t dst, const CUtensorMap* tm, int c0, int c1, uint32_t bar) {
  asm volatile("cp.async.bulk.tensor.2d.shared::cluster.global.mbarrier::complete_tx::bytes [%0], [%1, {%3, %4}], [%2];"
               :: "r"(dst), "l"((uint64_t)tm), "r"(bar), "r"(c0), "r"(c1) : "memory");
}
__device__ __forceinline__ void tma_3d(uint32_t dst, const CUtensorMap* tm, int c0, int c1, int c2, uint32_t bar) {
  asm volatile("cp.async.bulk.tensor.3d.shared::cluster.global.mbarrier::complete_tx::bytes [%0], [%1, {%3, %4, %5}], [%2];"
               :: "r"(dst), "l"((uint64_t)tm), "r"(bar), "r"(c0), "r"(c1), "r"(c2) : "memory");
}
__device__ __forceinline__ void pdl_wait() { asm volatile("griddepcontrol.wait;" ::: "memory"); }
__device__ __forceinline__ void pdl_launch() { asm volatile("griddepcontrol.launch_dependents;" ::: "memory"); }
__device__ __forceinline__ float ex2(float x) { float y; asm("ex2.approx.ftz.f32 %0, %1;" : "=f"(y) : "f"(x)); return y; }
__device__ __forceinline__ uint32_t pack_bf16(float lo, float hi) {
  uint32_t r; asm("cvt.rn.bf16x2.f32 %0, %1, %2;" : "=r"(r) : "f"(hi), "f"(lo)); return r;
}
__device__ __forceinline__ float bf_lo(uint32_t x) { return __uint_as_float(x << 16); }
__device__ __forceinline__ float bf_hi(uint32_t x) { return __uint_as_float(x & 0xffff0000u); }
__device__ __forceinline__ void stsm4(uint32_t addr, uint32_t r0, uint32_t r1, uint32_t r2, uint32_t r3) {
  asm volatile("stmatrix.sync.aligned.m8n8.x4.shared.b16 [%0], {%1, %2, %3, %4};" :: "r"(addr), "r"(r0), "r"(r1), "r"(r2), "r"(r3) : "memory");
}

__device__ __forceinline__ void wgmma_ss_n160_tb(float (&d)[80], uint64_t descA, uint64_t descB) {
  asm volatile("wgmma.mma_async.sync.aligned.m64n160k16.f32.bf16.bf16 {%0, %1, %2, %3, %4, %5, %6, %7, %8, %9, %10, %11, %12, %13, %14, %15, %16, %17, %18, %19, %20, %21, %22, %23, %24, %25, %26, %27, %28, %29, %30, %31, %32, %33, %34, %35, %36, %37, %38, %39, %40, %41, %42, %43, %44, %45, %46, %47, %48, %49, %50, %51, %52, %53, %54, %55, %56, %57, %58, %59, %60, %61, %62, %63, %64, %65, %66, %67, %68, %69, %70, %71, %72, %73, %74, %75, %76, %77, %78, %79}, %80, %81, 1, 1, 1, 0, 1;\n"
    : "+f"(d[0]), "+f"(d[1]), "+f"(d[2]), "+f"(d[3]), "+f"(d[4]), "+f"(d[5]), "+f"(d[6]), "+f"(d[7]), "+f"(d[8]), "+f"(d[9]), "+f"(d[10]), "+f"(d[11]), "+f"(d[12]), "+f"(d[13]), "+f"(d[14]), "+f"(d[15]), "+f"(d[16]), "+f"(d[17]), "+f"(d[18]), "+f"(d[19]), "+f"(d[20]), "+f"(d[21]), "+f"(d[22]), "+f"(d[23]), "+f"(d[24]), "+f"(d[25]), "+f"(d[26]), "+f"(d[27]), "+f"(d[28]), "+f"(d[29]), "+f"(d[30]), "+f"(d[31]), "+f"(d[32]), "+f"(d[33]), "+f"(d[34]), "+f"(d[35]), "+f"(d[36]), "+f"(d[37]), "+f"(d[38]), "+f"(d[39]), "+f"(d[40]), "+f"(d[41]), "+f"(d[42]), "+f"(d[43]), "+f"(d[44]), "+f"(d[45]), "+f"(d[46]), "+f"(d[47]), "+f"(d[48]), "+f"(d[49]), "+f"(d[50]), "+f"(d[51]), "+f"(d[52]), "+f"(d[53]), "+f"(d[54]), "+f"(d[55]), "+f"(d[56]), "+f"(d[57]), "+f"(d[58]), "+f"(d[59]), "+f"(d[60]), "+f"(d[61]), "+f"(d[62]), "+f"(d[63]), "+f"(d[64]), "+f"(d[65]), "+f"(d[66]), "+f"(d[67]), "+f"(d[68]), "+f"(d[69]), "+f"(d[70]), "+f"(d[71]), "+f"(d[72]), "+f"(d[73]), "+f"(d[74]), "+f"(d[75]), "+f"(d[76]), "+f"(d[77]), "+f"(d[78]), "+f"(d[79])
    : "l"(descA), "l"(descB));
}
__device__ __forceinline__ void wgmma_ss_n48_tb(float (&d)[24], uint64_t descA, uint64_t descB) {
  asm volatile("wgmma.mma_async.sync.aligned.m64n48k16.f32.bf16.bf16 {%0, %1, %2, %3, %4, %5, %6, %7, %8, %9, %10, %11, %12, %13, %14, %15, %16, %17, %18, %19, %20, %21, %22, %23}, %24, %25, 1, 1, 1, 0, 1;\n"
    : "+f"(d[0]), "+f"(d[1]), "+f"(d[2]), "+f"(d[3]), "+f"(d[4]), "+f"(d[5]), "+f"(d[6]), "+f"(d[7]), "+f"(d[8]), "+f"(d[9]), "+f"(d[10]), "+f"(d[11]), "+f"(d[12]), "+f"(d[13]), "+f"(d[14]), "+f"(d[15]), "+f"(d[16]), "+f"(d[17]), "+f"(d[18]), "+f"(d[19]), "+f"(d[20]), "+f"(d[21]), "+f"(d[22]), "+f"(d[23])
    : "l"(descA), "l"(descB));
}
__device__ __forceinline__ void wgmma_ss_n80_tb(float (&d)[40], uint64_t descA, uint64_t descB) {
  asm volatile("wgmma.mma_async.sync.aligned.m64n80k16.f32.bf16.bf16 {%0, %1, %2, %3, %4, %5, %6, %7, %8, %9, %10, %11, %12, %13, %14, %15, %16, %17, %18, %19, %20, %21, %22, %23, %24, %25, %26, %27, %28, %29, %30, %31, %32, %33, %34, %35, %36, %37, %38, %39}, %40, %41, 1, 1, 1, 0, 1;\n"
    : "+f"(d[0]), "+f"(d[1]), "+f"(d[2]), "+f"(d[3]), "+f"(d[4]), "+f"(d[5]), "+f"(d[6]), "+f"(d[7]), "+f"(d[8]), "+f"(d[9]), "+f"(d[10]), "+f"(d[11]), "+f"(d[12]), "+f"(d[13]), "+f"(d[14]), "+f"(d[15]), "+f"(d[16]), "+f"(d[17]), "+f"(d[18]), "+f"(d[19]), "+f"(d[20]), "+f"(d[21]), "+f"(d[22]), "+f"(d[23]), "+f"(d[24]), "+f"(d[25]), "+f"(d[26]), "+f"(d[27]), "+f"(d[28]), "+f"(d[29]), "+f"(d[30]), "+f"(d[31]), "+f"(d[32]), "+f"(d[33]), "+f"(d[34]), "+f"(d[35]), "+f"(d[36]), "+f"(d[37]), "+f"(d[38]), "+f"(d[39])
    : "l"(descA), "l"(descB));
}
template <int SCALE_D>
__device__ __forceinline__ void wgmma_rs_n64(float (&d)[32], uint32_t a0, uint32_t a1, uint32_t a2, uint32_t a3, uint64_t descB) {
  asm volatile("wgmma.mma_async.sync.aligned.m64n64k16.f32.bf16.bf16 {%0, %1, %2, %3, %4, %5, %6, %7, %8, %9, %10, %11, %12, %13, %14, %15, %16, %17, %18, %19, %20, %21, %22, %23, %24, %25, %26, %27, %28, %29, %30, %31}, {%32, %33, %34, %35}, %36, %37, 1, 1, 0;\n"
    : "+f"(d[0]), "+f"(d[1]), "+f"(d[2]), "+f"(d[3]), "+f"(d[4]), "+f"(d[5]), "+f"(d[6]), "+f"(d[7]), "+f"(d[8]), "+f"(d[9]), "+f"(d[10]), "+f"(d[11]), "+f"(d[12]), "+f"(d[13]), "+f"(d[14]), "+f"(d[15]), "+f"(d[16]), "+f"(d[17]), "+f"(d[18]), "+f"(d[19]), "+f"(d[20]), "+f"(d[21]), "+f"(d[22]), "+f"(d[23]), "+f"(d[24]), "+f"(d[25]), "+f"(d[26]), "+f"(d[27]), "+f"(d[28]), "+f"(d[29]), "+f"(d[30]), "+f"(d[31])
    : "r"(a0), "r"(a1), "r"(a2), "r"(a3), "l"(descB), "n"(SCALE_D));
}
template <int SCALE_D>
__device__ __forceinline__ void wgmma_rs_n24_tb(float (&d)[12], uint32_t a0, uint32_t a1, uint32_t a2, uint32_t a3, uint64_t descB) {
  asm volatile("wgmma.mma_async.sync.aligned.m64n24k16.f32.bf16.bf16 {%0, %1, %2, %3, %4, %5, %6, %7, %8, %9, %10, %11}, {%12, %13, %14, %15}, %16, %17, 1, 1, 1;\n"
    : "+f"(d[0]), "+f"(d[1]), "+f"(d[2]), "+f"(d[3]), "+f"(d[4]), "+f"(d[5]), "+f"(d[6]), "+f"(d[7]), "+f"(d[8]), "+f"(d[9]), "+f"(d[10]), "+f"(d[11])
    : "r"(a0), "r"(a1), "r"(a2), "r"(a3), "l"(descB), "n"(SCALE_D));
}

constexpr uint32_t DHI_SW128_K = (1024 >> 4) | (1u << 30);
constexpr uint32_t DHI_SW64_MN = (512 >> 4) | (2u << 30);
constexpr uint32_t DHI_SW32_MN = (256 >> 4) | (3u << 30);

template <int NC>
__device__ __forceinline__ void store_tile_bf16(const float (&acc)[NC / 2], float scale, uint32_t stage, uint8_t* stage_ptr,
                                                __nv_bfloat16* gdst, int gpitch, int lane) {
  constexpr int PITCH = NC * 2 + 16;
  const uint32_t waddr = stage + ((lane & 7) + ((lane >> 3) & 1) * 8) * PITCH + (lane >> 4) * 16;
#pragma unroll
  for (int j = 0; j < NC / 16; j++) {
    stsm4(waddr + j * 32, pack_bf16(acc[8 * j] * scale, acc[8 * j + 1] * scale), pack_bf16(acc[8 * j + 2] * scale, acc[8 * j + 3] * scale),
          pack_bf16(acc[8 * j + 4] * scale, acc[8 * j + 5] * scale), pack_bf16(acc[8 * j + 6] * scale, acc[8 * j + 7] * scale));
  }
  __syncwarp();
  constexpr int CPR = NC / 8;
#pragma unroll
  for (int i = 0; i < CPR / 2; i++) {
    const int c = i * 32 + lane, r = c / CPR, cc = c % CPR;
    const uint4 v = *reinterpret_cast<const uint4*>(stage_ptr + r * PITCH + cc * 16);
    *reinterpret_cast<uint4*>(gdst + (size_t)r * gpitch + cc * 8) = v;
  }
}

__device__ __forceinline__ void signal_done(unsigned int* flag, int wg, int tid) {
  asm volatile("bar.sync %0, 128;" :: "r"(wg + 1) : "memory");
  if ((tid & 127) == 0) asm volatile("red.release.gpu.global.add.u32 [%0], 1;" :: "l"(flag) : "memory");
}
__device__ __forceinline__ void wait_flags8(const unsigned int* f, unsigned int target) {
  for (int spin = 0; spin < (1 << 26); spin++) {
    unsigned int a, b, c, d, e, g, h, i;
    asm volatile("ld.volatile.global.v4.u32 {%0, %1, %2, %3}, [%4];" : "=r"(a), "=r"(b), "=r"(c), "=r"(d) : "l"(f) : "memory");
    asm volatile("ld.volatile.global.v4.u32 {%0, %1, %2, %3}, [%4];" : "=r"(e), "=r"(g), "=r"(h), "=r"(i) : "l"(f + 4) : "memory");
    if (min(min(min(a, b), min(c, d)), min(min(e, g), min(h, i))) >= target) break;
    __nanosleep(32);
  }
  asm volatile("fence.acq_rel.gpu;" ::: "memory");
  asm volatile("fence.proxy.async;" ::: "memory");
}

constexpr int K1_STAGES = 4;
constexpr int K1_A_BYTES = 256 * 128;
constexpr int K1_B_BYTES = 64 * 160 * 2;
constexpr int K1_STAGE = K1_A_BYTES + K1_B_BYTES;
constexpr int K1_SMEM = 5 * K1_A_BYTES + 61440 + 1024;
constexpr int KV_STAGES = 5;
constexpr int KVW_OFF = KV_STAGES * K1_A_BYTES;

__global__ void __launch_bounds__(512, 1)
proj_kernel(const __grid_constant__ CUtensorMap tmX, const __grid_constant__ CUtensorMap tmWq, const __grid_constant__ CUtensorMap tmWqkv,
            const __nv_bfloat16* __restrict__ wk, const __nv_bfloat16* __restrict__ wv, const __nv_bfloat16* __restrict__ gate_w) {
  extern __shared__ uint8_t smem_raw[];
  __shared__ __align__(8) uint64_t bar_full[KV_STAGES], bar_empty[KV_STAGES];
  uint8_t* smem = reinterpret_cast<uint8_t*>((reinterpret_cast<uintptr_t>(smem_raw) + 1023) & ~(uintptr_t)1023);
  const uint32_t sbase = smem_u32(smem);
  const uint32_t dbase = sbase & 0x3FFFFu;
  const int tid = threadIdx.x, warp = tid >> 5, lane = tid & 31;
  const bool is_kv = blockIdx.x >= 128;
  PROF(0, 0);
  if (tid == 0) {
    for (int i = 0; i < KV_STAGES; i++) { mbar_init(smem_u32(&bar_full[i]), 1); mbar_init(smem_u32(&bar_empty[i]), is_kv ? 8 : 16); }
    fence_mbar_init();
  }
  uint2 wa[2][5], wb[2][5]; uint32_t gw[2];
  if (is_kv && tid < 320) {
#pragma unroll
    for (int r = 0; r < 2; r++) {
      const int k = tid + r * 320;
      const uint2* pk = reinterpret_cast<const uint2*>(wk + k * 20);
      const uint2* pv = reinterpret_cast<const uint2*>(wv + k * 20);
#pragma unroll
      for (int i = 0; i < 5; i++) { wa[r][i] = __ldg(pk + i); wb[r][i] = __ldg(pv + i); }
      gw[r] = (uint32_t)__bfloat16_as_ushort(gate_w[k]);
    }
  }
  __syncthreads();
  if (tid == 480) {
    if (!is_kv) { g_done[blockIdx.x] = 0u; g_doneL[blockIdx.x] = 0u; }
    asm volatile("fence.acq_rel.gpu;" ::: "memory");
    pdl_launch();
  }
  __syncwarp();

  if (!is_kv) {
    const int mb = blockIdx.x >> 4, nb = blockIdx.x & 15;
    const CUtensorMap* tw = nb < 4 ? &tmWq : &tmWqkv;
    const int j0 = (nb < 4 ? nb : nb - 4) * 5;
    auto load = [&](int kt) {
      const int s = kt % K1_STAGES;
      const uint32_t fb = smem_u32(&bar_full[s]);
      mbar_expect_tx(fb, K1_STAGE);
      tma_2d(sbase + s * K1_STAGE, &tmX, kt * 64, mb * 256, fb);
      tma_3d(sbase + s * K1_STAGE + K1_A_BYTES, tw, 0, kt * 64, j0, fb);
    };
    if (tid == 0) for (int kt = 0; kt < K1_STAGES; kt++) load(kt);
    __syncwarp();
    {
      const int wg = warp >> 2;
      float acc[80];
#pragma unroll
      for (int i = 0; i < 80; i++) acc[i] = 0.f;
      for (int kt = 0; kt < 10; kt++) {
        const int s = kt % K1_STAGES;
        mbar_wait(smem_u32(&bar_full[s]), (kt / K1_STAGES) & 1);
        const uint32_t alo = ((dbase + s * K1_STAGE + wg * 8192) >> 4) | (1u << 16);
        const uint32_t blo = ((dbase + s * K1_STAGE + K1_A_BYTES) >> 4) | ((4096u >> 4) << 16);
        fence_regs(acc);
        wg_fence();
#pragma unroll
        for (int k = 0; k < 4; k++) wgmma_ss_n160_tb(acc, mkd(alo + k * 2, DHI_SW128_K), mkd(blo + k * 64, DHI_SW64_MN));
        wg_commit();
        if (kt > 0 && kt - 1 + K1_STAGES < 10) {
          wg_wait<1>();
          const uint32_t eb = smem_u32(&bar_empty[(kt - 1) % K1_STAGES]);
          if (lane == 0) mbar_arrive(eb);
          if (tid == 0) { mbar_wait(eb, ((kt - 1) / K1_STAGES) & 1); load(kt - 1 + K1_STAGES); }
          __syncwarp();
        }
      }
      wg_wait<0>();
      fence_regs(acc);
      PROF(0, 1);
      asm volatile("bar.sync %0, 128;" :: "r"(wg + 1) : "memory");
      const int w4 = warp & 3;
      const uint32_t off = w4 * K1_STAGE + wg * 8192;
      const int row0 = mb * 256 + wg * 64 + w4 * 16;
      if (nb < 4) {
        store_tile_bf16<160>(acc, 0.22360679774997896f * 1.4426950408889634f, sbase + off, smem + off,
                             g_q + (size_t)row0 * D_MODEL + nb * 160, D_MODEL, lane);
      } else {
        store_tile_bf16<160>(acc, 1.0f, sbase + off, smem + off, g_qkv + (size_t)row0 * (3 * D_MODEL) + (nb - 4) * 160, 3 * D_MODEL, lane);
      }
    }
  } else {
    const int cb = blockIdx.x - 128;
    if (warp == 8 && lane == 0) {
      for (int it = 0; it < KV_STAGES; it++) {
        const uint32_t fb = smem_u32(&bar_full[it]);
        mbar_expect_tx(fb, K1_A_BYTES);
        tma_2d(sbase + it * K1_A_BYTES, &tmX, it * 64, cb * 512, fb);
      }
    }
    __syncwarp();
    if (tid < 320) {
#pragma unroll
      for (int r = 0; r < 2; r++) {
        uint4* dst = reinterpret_cast<uint4*>(smem + KVW_OFF + (tid + r * 320) * 16);
        dst[0] = make_uint4(wa[r][0].x, wa[r][0].y, wa[r][1].x, wa[r][1].y);
        dst[640] = make_uint4(wa[r][2].x, wa[r][2].y, wa[r][3].x, wa[r][3].y);
        dst[1280] = make_uint4(wa[r][4].x, wa[r][4].y, 0u, 0u);
        dst[1920] = make_uint4(wb[r][0].x, wb[r][0].y, wb[r][1].x, wb[r][1].y);
        dst[2560] = make_uint4(wb[r][2].x, wb[r][2].y, wb[r][3].x, wb[r][3].y);
        dst[3200] = make_uint4(wb[r][4].x, wb[r][4].y, gw[r], 0u);
      }
    }
    fence_proxy_async();
    asm volatile("bar.sync 1, 512;" ::: "memory");
    PROF(0, 1);
    if (warp == 8) {
      if (lane == 0) {
        int s = 0, ph = 0;
        for (int it = KV_STAGES; it < 20; it++) {
          mbar_wait(smem_u32(&bar_empty[s]), ph);
          const uint32_t fb = smem_u32(&bar_full[s]);
          mbar_expect_tx(fb, K1_A_BYTES);
          tma_2d(sbase + s * K1_A_BYTES, &tmX, (it >= 10 ? it - 10 : it) * 64, cb * 512 + (it >= 10 ? 256 : 0), fb);
          if (++s == KV_STAGES) { s = 0; ph ^= 1; }
        }
      }
    } else if (warp < 8) {
      const int wg = warp >> 2, w4 = warp & 3, g = lane >> 2, t = lane & 3;
      for (int pass = 0; pass < 2; pass++) {
        float acc[2][24];
#pragma unroll
        for (int i = 0; i < 24; i++) { acc[0][i] = 0.f; acc[1][i] = 0.f; }
        for (int kt = 0; kt < 10; kt++) {
          const int it = pass * 10 + kt, s = it % KV_STAGES;
          mbar_wait(smem_u32(&bar_full[s]), (it / KV_STAGES) & 1);
          const uint32_t alo = ((dbase + s * K1_A_BYTES + wg * 16384) >> 4) | (1u << 16);
          const uint32_t blo = ((dbase + KVW_OFF + kt * 1024) >> 4) | ((128u >> 4) << 16);
          fence_regs(acc[0]); fence_regs(acc[1]);
          wg_fence();
#pragma unroll
          for (int k = 0; k < 4; k++) {
            wgmma_ss_n48_tb(acc[0], mkd(alo + k * 2, DHI_SW128_K), mkd(blo + k * 16, 10240u >> 4));
            wgmma_ss_n48_tb(acc[1], mkd(alo + 512 + k * 2, DHI_SW128_K), mkd(blo + k * 16, 10240u >> 4));
          }
          wg_commit();
          if (kt > 0) {
            wg_wait<1>();
            if (lane == 0) mbar_arrive(smem_u32(&bar_empty[(it - 1) % KV_STAGES]));
          }
        }
        wg_wait<0>();
        fence_regs(acc[0]); fence_regs(acc[1]);
        if (lane == 0) mbar_arrive(smem_u32(&bar_empty[(pass * 10 + 9) % KV_STAGES]));
        if (pass == 0) PROF(0, 2);
        float kmax2 = 0.f, vmax = 0.f;
#pragma unroll
        for (int hh = 0; hh < 4; hh++) {
          const int h = hh & 1;
          const float (&a)[24] = acc[hh >> 1];
          const int key = cb * 512 + pass * 256 + wg * 128 + (hh >> 1) * 64 + w4 * 16 + g + h * 8;
          const int grp = key >> 7, kk = key & 127;
          const bool poly = (TMASK >> (kk >> 3)) & 1;
          uint8_t* gp = g_kvimg + grp * GRP_BYTES;
          const uint32_t k0 = pack_bf16(a[2 * h], a[2 * h + 1]);
          const uint32_t k1 = pack_bf16(a[4 + 2 * h], a[5 + 2 * h]);
          uint32_t k2 = pack_bf16(a[8 + 2 * h], a[9 + 2 * h]);
          float n2 = bf_lo(k0) * bf_lo(k0) + bf_hi(k0) * bf_hi(k0) + bf_lo(k1) * bf_lo(k1) + bf_hi(k1) * bf_hi(k1);
          if (t < 2) {
            n2 += bf_lo(k2) * bf_lo(k2) + bf_hi(k2) * bf_hi(k2);
            k2 = pack_bf16(bf_lo(k2) * 0.5f, bf_hi(k2) * 0.5f);
          } else if (t == 2) k2 = poly ? pack_bf16(24.f, 2.5f) : pack_bf16(0.5f, 0.f);
          else k2 = poly ? pack_bf16(0.5f, 0.f) : 0u;
          *reinterpret_cast<uint32_t*>(gp + kk * 16 + t * 4) = k0;
          *reinterpret_cast<uint32_t*>(gp + PLANE + kk * 16 + t * 4) = k1;
          *reinterpret_cast<uint32_t*>(gp + 2 * PLANE + kk * 16 + t * 4) = k2;
          n2 += __shfl_xor_sync(0xffffffffu, n2, 1);
          n2 += __shfl_xor_sync(0xffffffffu, n2, 2);
          kmax2 = (n2 > kmax2 || n2 != n2) ? n2 : kmax2;
          uint32_t v0 = pack_bf16(a[12 + 2 * h], a[13 + 2 * h]);
          uint32_t v1 = pack_bf16(a[16 + 2 * h], a[17 + 2 * h]);
          uint32_t v2 = pack_bf16(a[20 + 2 * h], a[21 + 2 * h]);
          float vm = fmaxf(fmaxf(fabsf(bf_lo(v0)), fabsf(bf_hi(v0))), fmaxf(fabsf(bf_lo(v1)), fabsf(bf_hi(v1))));
          if (t < 2) vm = fmaxf(vm, fmaxf(fabsf(bf_lo(v2)), fabsf(bf_hi(v2))));
          else if (t == 2) {
            const float z = a[20 + 2 * h];
            g_gate[key] = 1.f / (1.f + __expf(-z));
            v2 = 0x00003F80u;
          } else v2 = 0u;
          vmax = fmaxf(vmax, vm);
          if (poly) { v0 ^= 0x80008000u; v1 ^= 0x80008000u; v2 ^= 0x80008000u; }
          uint8_t* vp = gp + 3 * PLANE + (kk >> 3) * 384 + (kk & 7) * 16 + t * 4;
          *reinterpret_cast<uint32_t*>(vp) = v0;
          *reinterpret_cast<uint32_t*>(vp + 128) = v1;
          *reinterpret_cast<uint32_t*>(vp + 256) = v2;
        }
#pragma unroll
        for (int o = 1; o < 32; o <<= 1) {
          const float a = __shfl_xor_sync(0xffffffffu, kmax2, o);
          kmax2 = (a > kmax2 || a != a) ? a : kmax2;
          vmax = fmaxf(vmax, __shfl_xor_sync(0xffffffffu, vmax, o));
        }
        if (lane == 0) { g_kmax2[cb * 16 + pass * 8 + warp] = kmax2; g_vmax[cb * 16 + pass * 8 + warp] = vmax; }
      }
    }
  }
  PROF(0, 3);
}

__device__ __forceinline__ uint32_t ex2_pair_poly(float u0, float u1, uint32_t one2) {
  const uint32_t W = __byte_perm(__float_as_uint(u0), __float_as_uint(u1), 0x6521);
  uint32_t v; asm("lop3.b32 %0, %1, 0x007F007F, %2, 0xEA;" : "=r"(v) : "r"(W), "r"(one2));
  uint32_t L, p;
  asm("fma.rn.bf16x2 %0, %1, %2, %3;" : "=r"(L) : "r"(v), "r"(0x1f961f96u), "r"(0x9fe39fe3u));
  asm("fma.rn.bf16x2 %0, %1, %1, %2;" : "=r"(p) : "r"(L), "r"(0x00f500f5u));
  return W + p;
}
template <int JOFF>
__device__ __forceinline__ void softmax_fast(const float (&S)[32], uint32_t (&P)[16], uint32_t one2) {
#pragma unroll
  for (int i = 0; i < 16; i++) {
    if ((TMASK >> (JOFF + i / 2)) & 1) P[i] = ex2_pair_poly(S[2 * i], S[2 * i + 1], one2);
    else P[i] = pack_bf16(ex2(S[2 * i]), ex2(S[2 * i + 1]));
  }
}
template <int JOFF>
__device__ __forceinline__ void softmax_slow(const float (&S)[32], uint32_t (&P)[16], float (&O)[12], float& m0, float& m1) {
  float a0 = m0, a1 = m1;
#pragma unroll
  for (int j = 0; j < 8; j++) {
    a0 = fmaxf(a0, fmaxf(S[4 * j], S[4 * j + 1]));
    a1 = fmaxf(a1, fmaxf(S[4 * j + 2], S[4 * j + 3]));
  }
  a0 = fmaxf(a0, __shfl_xor_sync(0xffffffffu, a0, 1)); a0 = fmaxf(a0, __shfl_xor_sync(0xffffffffu, a0, 2));
  a1 = fmaxf(a1, __shfl_xor_sync(0xffffffffu, a1, 1)); a1 = fmaxf(a1, __shfl_xor_sync(0xffffffffu, a1, 2));
  const float c0 = ex2(m0 - a0), c1 = ex2(m1 - a1);
  m0 = a0; m1 = a1;
#pragma unroll
  for (int j = 0; j < 3; j++) { O[4 * j] *= c0; O[4 * j + 1] *= c0; O[4 * j + 2] *= c1; O[4 * j + 3] *= c1; }
#pragma unroll
  for (int i = 0; i < 16; i++) {
    const float m = (i & 1) ? a1 : a0;
    const uint32_t p = pack_bf16(ex2(S[2 * i] - m), ex2(S[2 * i + 1] - m));
    P[i] = ((TMASK >> (JOFF + i / 2)) & 1) ? (p ^ 0x80008000u) : p;
  }
}
constexpr uint32_t DHI_KV = 128 >> 4;
__device__ __forceinline__ void issue_qk(float (&S)[32], const uint32_t (&q)[8], uint64_t base) {
  wgmma_rs_n64<0>(S, q[0], q[1], q[2], q[3], base + (uint64_t)((PLANE >> 4) << 16));
  wgmma_rs_n64<1>(S, q[4], q[5], q[6], q[7], base + (uint64_t)(2 * PLANE >> 4));
}
__device__ __forceinline__ void issue_pv(float (&O)[12], const uint32_t (&P)[16], uint64_t vbase) {
#pragma unroll
  for (int kk = 0; kk < 4; kk++)
    wgmma_rs_n24_tb<1>(O, P[4 * kk], P[4 * kk + 1], P[4 * kk + 2], P[4 * kk + 3], vbase + (uint64_t)(kk * (768 >> 4)));
}

constexpr uint32_t VOFF = ((3 * PLANE) >> 4) + ((384u >> 4) << 16);
constexpr int KVR = 4;
constexpr int OFF_WA = KVR * GRP_BYTES;
constexpr int OFF_BR = OFF_WA + 10 * 10240;
constexpr int BR_STAGE = 8192 + 10240, BR_STAGES = 3;
constexpr int OFF_QS = OFF_BR + BR_STAGES * BR_STAGE;
constexpr int OFF_BAR = OFF_QS + 512 * 6 * 4;
constexpr int K2_SMEM = OFF_BAR + 256 + 1024;
constexpr int BAR_KV = 0, BAR_WA = 4, BAR_BR = 5, BAR_TA = 8, BAR_TE = 14, BAR_OWN = 18, CNT_KV = 19;
constexpr int NSTEP = 2 * NGRP;

__device__ __forceinline__ void kv_load(uint32_t sbase, int step) {
  const uint32_t bar = sbase + OFF_BAR + (BAR_KV + (step & (KVR - 1))) * 8;
  mbar_expect_tx(bar, GRP_BYTES);
  bulk_g2s(sbase + (step & (KVR - 1)) * GRP_BYTES, g_kvimg + (step & (NGRP - 1)) * GRP_BYTES, GRP_BYTES, bar);
}
__device__ __forceinline__ void kv_release(uint32_t sbase, int step, bool elected) {
  if (elected && step + KVR < NSTEP) {
    uint32_t old;
    asm volatile("atom.acq_rel.cta.shared::cta.inc.u32 %0, [%1], 3;" : "=r"(old) : "r"(sbase + OFF_BAR + CNT_KV * 8 + (step & (KVR - 1)) * 4) : "memory");
    if (old == 3u) kv_load(sbase, step + KVR);
  }
  __syncwarp();
}
__device__ __forceinline__ void kv_wait(uint32_t sbase, int step) {
  mbar_wait(sbase + OFF_BAR + (BAR_KV + (step & (KVR - 1))) * 8, (step / KVR) & 1);
}

__device__ __forceinline__ uint32_t kv_release_begin(uint32_t sbase, int slot, bool doit) {
  uint32_t old = 0;
  asm volatile("{\n.reg .pred p;\nsetp.ne.u32 p, %2, 0;\n@p atom.relaxed.cta.shared::cta.inc.u32 %0, [%1], 3;\n}\n"
               : "+r"(old) : "r"(sbase + OFF_BAR + CNT_KV * 8 + slot * 4), "r"((uint32_t)doit) : "memory");
  return old;
}
__device__ __forceinline__ void attn_tile_fast(const uint32_t (&q)[8], float (&O)[12], uint32_t sbase, int step0, bool elected, uint32_t one2) {
  float S[32]; uint32_t P[16];
#pragma unroll
  for (int i = 0; i < 32; i++) S[i] = 0.f;
  uint64_t kb0 = mkd((sbase & 0x3FFFFu) >> 4, DHI_KV);
  asm volatile("" : "+l"(kb0));
  kv_wait(sbase, step0);
  fence_regs(S); fence_regs(O);
  wg_fence();
  issue_qk(S, q, kb0);
  wg_commit();
#pragma unroll 1
  for (int step4 = step0; step4 < step0 + NGRP; step4 += KVR) {
#pragma unroll
    for (int j = 0; j < KVR; j++) {
      const int step = step4 + j;
      const uint64_t kb = kb0 + (uint64_t)(j * (GRP_BYTES >> 4));
      const uint64_t knext = kb0 + (uint64_t)(((j + 1) & (KVR - 1)) * (GRP_BYTES >> 4));
      wg_wait<0>();
      fence_regs(S); fence_regs(P); fence_regs(O);
      const uint32_t old = kv_release_begin(sbase, (j + KVR - 1) & (KVR - 1), elected && step > step0 && step - 1 + KVR < NSTEP);
      softmax_fast<0>(S, P, one2);
      fence_regs(S); fence_regs(P); fence_regs(O);
      wg_fence();
      issue_qk(S, q, kb + 64);
      issue_pv(O, P, kb + VOFF);
      wg_commit();
      if (step + 1 < NSTEP) mbar_wait(sbase + OFF_BAR + (BAR_KV + ((j + 1) & (KVR - 1))) * 8, ((step + 1) / KVR) & 1);
      wg_wait<0>();
      fence_regs(S); fence_regs(P); fence_regs(O);
      softmax_fast<8>(S, P, one2);
      fence_regs(S); fence_regs(P); fence_regs(O);
      wg_fence();
      issue_qk(S, q, knext);
      issue_pv(O, P, kb + VOFF + 4 * (768 >> 4));
      wg_commit();
      if (old == 3u) kv_load(sbase, step - 1 + KVR);
    }
  }
  wg_wait<0>();
  fence_regs(O); fence_regs(S);
  kv_release(sbase, step0 + NGRP - 1, elected);
}
template <int H>
__device__ __forceinline__ void slow_step(const uint32_t (&q)[8], float (&O)[12], uint64_t kb, float& m0, float& m1) {
  float S[32]; uint32_t P[16];
#pragma unroll
  for (int i = 0; i < 32; i++) S[i] = 0.f;
  fence_regs(S);
  wg_fence();
  issue_qk(S, q, kb + 64 * H);
  wg_commit();
  wg_wait<0>();
  fence_regs(S);
  softmax_slow<8 * H>(S, P, O, m0, m1);
  fence_regs(P); fence_regs(O);
  wg_fence();
  issue_pv(O, P, kb + VOFF + H * 4 * (768 >> 4));
  wg_commit();
  wg_wait<0>();
  fence_regs(O); fence_regs(P);
}
__device__ __forceinline__ void attn_tile_slow(const uint32_t (&q)[8], float (&O)[12], uint32_t sbase, int step0, bool elected) {
  float m0 = -INFINITY, m1 = -INFINITY;
#pragma unroll 1
  for (int grp = 0; grp < NGRP; grp++) {
    kv_wait(sbase, step0 + grp);
    const uint64_t kb = mkd(((sbase & 0x3FFFFu) >> 4) + (grp & (KVR - 1)) * (GRP_BYTES >> 4), DHI_KV);
    slow_step<0>(q, O, kb, m0, m1);
    slow_step<1>(q, O, kb, m0, m1);
    kv_release(sbase, step0 + grp, elected);
  }
}

__device__ __forceinline__ void load_row20(const __nv_bfloat16* p, float (&f)[20]) {
  const uint2* p2 = reinterpret_cast<const uint2*>(p);
#pragma unroll
  for (int i = 0; i < 5; i++) { const uint2 v = p2[i]; f[4 * i] = bf_lo(v.x); f[4 * i + 1] = bf_hi(v.x); f[4 * i + 2] = bf_lo(v.y); f[4 * i + 3] = bf_hi(v.y); }
}
__device__ __forceinline__ void softmax8(float (&sc)[8]) {
  float mx = sc[0];
#pragma unroll
  for (int w = 1; w < 8; w++) mx = fmaxf(mx, sc[w]);
  float l = 0.f;
#pragma unroll
  for (int w = 0; w < 8; w++) { sc[w] = ex2(sc[w] - mx); l += sc[w]; }
  const float r = 1.f / l;
#pragma unroll
  for (int w = 0; w < 8; w++) sc[w] *= r;
}
__device__ __forceinline__ void local_attn_pair(int t, int lane) {
  constexpr int PITCH = 3 * D_MODEL;
  constexpr float SC = 0.22360679774997896f * 1.4426950408889634f, NEG = -1e9f * 1.4426950408889634f;
  const __nv_bfloat16* base = g_qkv + lane * DH;
  float a[20], b[20], sa[8], sb[8];
  load_row20(base + (size_t)t * PITCH, a);
  load_row20(base + (size_t)(t + 2) * PITCH, b);
#pragma unroll
  for (int j = 0; j < 9; j++) {
    const int r = t + 2 - 2 * j;
    float k[20];
    load_row20(base + D_MODEL + (size_t)max(r, 0) * PITCH, k);
    float da = 0.f, db = 0.f;
#pragma unroll
    for (int i = 0; i < 20; i++) { if (j >= 1) da = fmaf(a[i], k[i], da); if (j < 8) db = fmaf(b[i], k[i], db); }
    if (j >= 1) sa[j - 1] = r >= 0 ? da * SC : NEG;
    if (j < 8) sb[j] = r >= 0 ? db * SC : NEG;
  }
  softmax8(sa); softmax8(sb);
#pragma unroll
  for (int i = 0; i < 20; i++) { a[i] = 0.f; b[i] = 0.f; }
#pragma unroll
  for (int j = 0; j < 9; j++) {
    const int r = t + 2 - 2 * j;
    float v[20];
    load_row20(base + 2 * D_MODEL + (size_t)max(r, 0) * PITCH, v);
#pragma unroll
    for (int i = 0; i < 20; i++) { if (j >= 1) a[i] = fmaf(sa[j - 1], v[i], a[i]); if (j < 8) b[i] = fmaf(sb[j], v[i], b[i]); }
  }
  const float ga = 1.f - g_gate[t], gb = 1.f - g_gate[t + 2];
  uint2* da = reinterpret_cast<uint2*>(g_a2 + (size_t)t * (2 * D_MODEL) + D_MODEL + lane * DH);
  uint2* db = da + 2 * (2 * D_MODEL) / 4;
#pragma unroll
  for (int i = 0; i < 5; i++) {
    da[i] = make_uint2(pack_bf16(a[4 * i] * ga, a[4 * i + 1] * ga), pack_bf16(a[4 * i + 2] * ga, a[4 * i + 3] * ga));
    db[i] = make_uint2(pack_bf16(b[4 * i] * gb, b[4 * i + 1] * gb), pack_bf16(b[4 * i + 2] * gb, b[4 * i + 3] * gb));
  }
}
__device__ __forceinline__ uint32_t ta_slot(int i) { return i < 3 ? i * 16384 : OFF_BR + (i - 3) * 16384; }

__global__ void __launch_bounds__(640, 1)
attn_kernel(const __grid_constant__ CUtensorMap tmA2, const __grid_constant__ CUtensorMap tmA2b, const __grid_constant__ CUtensorMap tmWoA, const __grid_constant__ CUtensorMap tmWoB,
            __nv_bfloat16* __restrict__ out, uint32_t one2) {
  extern __shared__ uint8_t smem_raw[];
  uint8_t* smem = reinterpret_cast<uint8_t*>((reinterpret_cast<uintptr_t>(smem_raw) + 1023) & ~(uintptr_t)1023);
  const uint32_t sbase = smem_u32(smem);
  const uint32_t dbase = sbase & 0x3FFFFu;
  const uint32_t bars = sbase + OFF_BAR;
  const int tid = threadIdx.x, wg = tid >> 7, warp = (tid >> 5) & 3, lane = tid & 31, g = lane >> 2, t = lane & 3;
  const int mb = blockIdx.x >> 3, nb = blockIdx.x & 7;
  if (tid == 0) {
    for (int i = 0; i < BAR_TE; i++) mbar_init(bars + i * 8, 1);
    for (int i = BAR_TE; i < BAR_TE + 4; i++) mbar_init(bars + i * 8, 8);
    mbar_init(bars + BAR_OWN * 8, 4);
    for (int i = 0; i < 4; i++) *reinterpret_cast<uint32_t*>(smem + OFF_BAR + CNT_KV * 8 + i * 4) = 0u;
    fence_mbar_init();
  }
  __syncthreads();
  if (wg == 4) {
    if (tid == 512) {
      mbar_expect_tx(bars + BAR_WA * 8, 10 * 10240);
      for (int kt = 0; kt < 10; kt++) tma_3d(sbase + OFF_WA + kt * 10240, &tmWoA, 0, kt * 64, nb * 5, bars + BAR_WA * 8);
    }
    pdl_wait();
    asm volatile("bar.sync 7, 640;" ::: "memory");
#pragma unroll 1
    for (int i = 0; i < 2; i++) local_attn_pair(blockIdx.x * 16 + warp * 4 + i, lane);
    if (tid == 512) PROF2(0, 2);
    signal_done(&g_doneL[blockIdx.x], wg, tid);
    auto br_load = [&](int it, int st) {
      const uint32_t fb = bars + (BAR_BR + st) * 8;
      const uint32_t dst = sbase + OFF_BR + st * BR_STAGE;
      const int kc = (it >= 10 ? it - 10 : it) * 64;
      mbar_expect_tx(fb, BR_STAGE);
      tma_2d(dst, &tmA2, D_MODEL + kc, (blockIdx.x >> 3) * 128 + (it >= 10 ? 64 : 0), fb);
      tma_3d(dst + 8192, &tmWoB, 0, kc, (blockIdx.x & 7) * 5, fb);
    };
    if (tid == 512) {
      wait_flags8(&g_doneL[mb * 8], 1u);
      for (int it = 0; it < BR_STAGES; it++) br_load(it, it);
    }
    __syncwarp();
    {
      int st = 0, ph = 0;
      float acc[40];
#pragma unroll 1
      for (int it = 0; it < 20; it++) {
        if (it == 0 || it == 10) {
#pragma unroll
          for (int i = 0; i < 40; i++) acc[i] = 0.f;
        }
        mbar_wait(bars + (BAR_BR + st) * 8, ph);
        const uint32_t alo = ((dbase + OFF_BR + st * BR_STAGE) >> 4);
        fence_regs(acc);
        wg_fence();
#pragma unroll
        for (int k = 0; k < 4; k++)
          wgmma_ss_n80_tb(acc, mkd(alo + (k * 2 + (1u << 16)), DHI_SW128_K), mkd(alo + (512 + k * 32 + ((2048u >> 4) << 16)), DHI_SW32_MN));
        wg_commit();
        wg_wait<0>();
        fence_regs(acc);
        asm volatile("bar.sync 5, 128;" ::: "memory");
        if (threadIdx.x == 512 && it + BR_STAGES < 20) br_load(it + BR_STAGES, st);
        __syncwarp();
        if (it == 9 || it == 19) {
          float* pp = g_part + (size_t)(blockIdx.x * 2 + (it == 19)) * (40 * 128) + (threadIdx.x & 127);
#pragma unroll
          for (int i = 0; i < 40; i++) pp[i * 128] = acc[i];
        }
        if (++st == BR_STAGES) { st = 0; ph ^= 1; }
      }
    }
    if (tid == 512) PROF2(1, 0);
    asm volatile("bar.arrive 6, 384;" ::: "memory");
    if (tid == 512) {
      mbar_wait(bars + BAR_OWN * 8, 0);
      wait_flags8(&g_done[mb * 8], 4u);
      PROF2(2, 0);
    }
    if (tid == 512) {
      for (int kt = 0; kt < 10; kt++) {
        const int sl = kt % 6;
        if (kt >= 6) mbar_wait(bars + (BAR_TE + kt - 6) * 8, 0);
        const uint32_t fb = bars + (BAR_TA + sl) * 8;
        mbar_expect_tx(fb, 16384);
        tma_2d(sbase + ta_slot(sl), &tmA2b, kt * 64, mb * 128, fb);
      }
    }
  } else {
    const bool elected = (tid & 127) == 0;
    pdl_wait();
    PROF(1, 1);
    if (tid == 384) for (int j = 0; j < KVR; j++) kv_load(sbase, j);
    __syncwarp();
    uint32_t q[8];
    uint32_t* qstash = reinterpret_cast<uint32_t*>(smem + OFF_QS) + tid;
    const int rowA = (blockIdx.x * 8 + wg) * 64 + warp * 16 + g;
    {
      const uint32_t* r0 = reinterpret_cast<const uint32_t*>(g_q + (size_t)rowA * DH);
      const uint32_t* r1 = r0 + 8 * (DH / 2);
      const uint32_t* s0 = r0 + 256 * (DH / 2);
      const uint32_t* s1 = s0 + 8 * (DH / 2);
      q[0] = r0[t]; q[1] = r1[t]; q[2] = r0[t + 4]; q[3] = r1[t + 4];
      q[4] = t < 2 ? r0[8 + t] : 0u;
      q[5] = t < 2 ? r1[8 + t] : 0u;
      qstash[0] = s0[t]; qstash[512] = s1[t]; qstash[1024] = s0[t + 4]; qstash[1536] = s1[t + 4];
      qstash[2048] = t < 2 ? s0[8 + t] : 0u;
      qstash[2560] = t < 2 ? s1[8 + t] : 0u;
    }
    float kmax2 = 0.f, vmax = 0.f;
#pragma unroll
    for (int i = 0; i < 2; i++) {
      const float a = g_kmax2[lane + 32 * i];
      kmax2 = (a > kmax2 || a != a) ? a : kmax2;
      vmax = fmaxf(vmax, g_vmax[lane + 32 * i]);
    }
#pragma unroll
    for (int o = 1; o < 32; o <<= 1) {
      const float a = __shfl_xor_sync(0xffffffffu, kmax2, o);
      kmax2 = (a > kmax2 || a != a) ? a : kmax2;
      vmax = fmaxf(vmax, __shfl_xor_sync(0xffffffffu, vmax, o));
    }
    const float qlim = (vmax >= 0.00390625f && vmax <= 256.f) ? 9025.f / kmax2 : -1.f;
    asm volatile("bar.arrive 7, 640;" ::: "memory");
    PROF(1, 2);
#pragma unroll 1
    for (int it = 0; it < 2; it++) {
      const int row0 = rowA + it * 256;
      if (it == 1) {
#pragma unroll
        for (int i = 0; i < 6; i++) q[i] = qstash[512 * i];
      }
      float n0 = bf_lo(q[0]) * bf_lo(q[0]) + bf_hi(q[0]) * bf_hi(q[0]) + bf_lo(q[2]) * bf_lo(q[2]) + bf_hi(q[2]) * bf_hi(q[2]) +
                 bf_lo(q[4]) * bf_lo(q[4]) + bf_hi(q[4]) * bf_hi(q[4]);
      float n1 = bf_lo(q[1]) * bf_lo(q[1]) + bf_hi(q[1]) * bf_hi(q[1]) + bf_lo(q[3]) * bf_lo(q[3]) + bf_hi(q[3]) * bf_hi(q[3]) +
                 bf_lo(q[5]) * bf_lo(q[5]) + bf_hi(q[5]) * bf_hi(q[5]);
      n0 += __shfl_xor_sync(0xffffffffu, n0, 1); n0 += __shfl_xor_sync(0xffffffffu, n0, 2);
      n1 += __shfl_xor_sync(0xffffffffu, n1, 1); n1 += __shfl_xor_sync(0xffffffffu, n1, 2);
      const bool safe = (n0 <= qlim) && (n1 <= qlim);
      uint32_t unsafe_any;
      asm volatile("{\n.reg .pred p, r;\nsetp.eq.u32 p, %1, 0;\nbarrier.cta.red.or.pred r, %2, 128, p;\nselp.u32 %0, 1, 0, r;\n}\n"
                   : "=r"(unsafe_any) : "r"((uint32_t)safe), "r"(wg + 1) : "memory");
      float O[12];
#pragma unroll
      for (int i = 0; i < 12; i++) O[i] = 0.f;
      if (!unsafe_any && t >= 2) { q[4] = q[5] = (t == 2) ? 0x3F804100u : 0x00003B80u; }
      q[6] = q[4]; q[7] = q[5];
      fence_regs(q);
      if (!unsafe_any) attn_tile_fast(q, O, sbase, it * NGRP, elected, one2);
      else attn_tile_slow(q, O, sbase, it * NGRP, elected);
      const float l0 = __shfl_sync(0xffffffffu, O[8], (lane & ~3) | 2);
      const float l1 = __shfl_sync(0xffffffffu, O[10], (lane & ~3) | 2);
      const int tok = row0 >> 5;
      const float gt = g_gate[tok];
      const float i0 = gt / l0, i1 = gt / l1;
      uint32_t* o0 = reinterpret_cast<uint32_t*>(g_a2 + (size_t)tok * (2 * D_MODEL) + (row0 & 31) * DH);
      uint32_t* o1 = o0 + 8 * (DH / 2);
      o0[t] = pack_bf16(O[0] * i0, O[1] * i0); o1[t] = pack_bf16(O[2] * i1, O[3] * i1);
      o0[t + 4] = pack_bf16(O[4] * i0, O[5] * i0); o1[t + 4] = pack_bf16(O[6] * i1, O[7] * i1);
      if (t < 2) { o0[t + 8] = pack_bf16(O[8] * i0, O[9] * i0); o1[t + 8] = pack_bf16(O[10] * i1, O[11] * i1); }
    }
    signal_done(&g_done[blockIdx.x], wg, tid);
    if (elected) mbar_arrive(bars + BAR_OWN * 8);
    PROF(1, 3);
    if (wg < 2) {
      float acc[40];
      asm volatile("bar.sync 6, 384;" ::: "memory");
      {
        const float* pp = g_part + (size_t)(blockIdx.x * 2 + wg) * (40 * 128) + (tid & 127);
#pragma unroll
        for (int i = 0; i < 40; i++) acc[i] = pp[i * 128];
      }
      mbar_wait(bars + BAR_WA * 8, 0);
#pragma unroll 1
      for (int kt = 0; kt < 10; kt++) {
        const int sl = kt % 6;
        mbar_wait(bars + (BAR_TA + sl) * 8, kt / 6);
        if (kt == 0) PROF(2, 1);
        const uint32_t alo = ((dbase + ta_slot(sl) + wg * 8192) >> 4) | (1u << 16);
        const uint32_t blo = ((dbase + OFF_WA + kt * 10240) >> 4) | ((2048u >> 4) << 16);
        fence_regs(acc);
        wg_fence();
#pragma unroll
        for (int k = 0; k < 4; k++) wgmma_ss_n80_tb(acc, mkd(alo + k * 2, DHI_SW128_K), mkd(blo + k * 32, DHI_SW32_MN));
        wg_commit();
        if (kt < 4) {
          wg_wait<0>();
          if (lane == 0) mbar_arrive(bars + (BAR_TE + kt) * 8);
        }
      }
      wg_wait<0>();
      fence_regs(acc);
      PROF(2, 2);
      asm volatile("bar.sync %0, 128;" :: "r"(wg + 1) : "memory");
      const uint32_t so = ta_slot(warp) + wg * 8192;
      const int row0 = mb * 128 + wg * 64 + warp * 16;
      store_tile_bf16<80>(acc, 1.0f, sbase + so, smem + so, out + (size_t)row0 * D_MODEL + nb * 80, D_MODEL, lane);
      PROF(2, 3);
    }
  }
}

typedef CUresult (*EncodeFn)(CUtensorMap*, CUtensorMapDataType, cuuint32_t, void*, const cuuint64_t*, const cuuint64_t*,
                             const cuuint32_t*, const cuuint32_t*, CUtensorMapInterleave, CUtensorMapSwizzle,
                             CUtensorMapL2promotion, CUtensorMapFloatOOBfill);

void make_map(EncodeFn fn, CUtensorMap* tm, const void* ptr, int rank, const cuuint64_t* dims, const cuuint64_t* strides,
              const cuuint32_t* box, CUtensorMapSwizzle sw) {
  const cuuint32_t es[3] = {1, 1, 1};
  fn(tm, CU_TENSOR_MAP_DATA_TYPE_BFLOAT16, rank, const_cast<void*>(ptr), dims, strides, box, es, CU_TENSOR_MAP_INTERLEAVE_NONE, sw,
     CU_TENSOR_MAP_L2_PROMOTION_L2_256B, CU_TENSOR_MAP_FLOAT_OOB_FILL_NONE);
}
void map_a(EncodeFn fn, CUtensorMap* tm, const void* p, int rows, int cols, int box_rows) {
  const cuuint64_t dims[2] = {(cuuint64_t)cols, (cuuint64_t)rows};
  const cuuint64_t str[1] = {(cuuint64_t)cols * 2};
  const cuuint32_t box[2] = {64, (cuuint32_t)box_rows};
  make_map(fn, tm, p, 2, dims, str, box, CU_TENSOR_MAP_SWIZZLE_128B);
}
void map_w(EncodeFn fn, CUtensorMap* tm, const void* p, int K, int N, int atom, CUtensorMapSwizzle sw) {
  const cuuint64_t dims[3] = {(cuuint64_t)atom, (cuuint64_t)K, (cuuint64_t)(N / atom)};
  const cuuint64_t str[2] = {(cuuint64_t)N * 2, (cuuint64_t)atom * 2};
  const cuuint32_t box[3] = {(cuuint32_t)atom, 64, 5};
  make_map(fn, tm, p, 3, dims, str, box, sw);
}

template <typename... KArgs, typename... Args>
void launch(void (*kern)(KArgs...), int grid, int block, int smem, bool pdl, Args... args) {
  cudaLaunchConfig_t cfg = {};
  cfg.gridDim = dim3(grid); cfg.blockDim = dim3(block); cfg.dynamicSmemBytes = smem; cfg.stream = cudaStreamPerThread;
  cudaLaunchAttribute at[1];
  at[0].id = cudaLaunchAttributeProgrammaticStreamSerialization;
  at[0].val.programmaticStreamSerializationAllowed = 1;
  cfg.attrs = at; cfg.numAttrs = pdl ? 1 : 0;
  cudaLaunchKernelEx(&cfg, kern, KArgs(args)...);
}

}

extern "C" void kernel_launch(void* const* d_in, const int* in_sizes, int n_in, void* d_out, int out_size) {
  (void)in_sizes; (void)n_in; (void)out_size;
  const __nv_bfloat16* x = (const __nv_bfloat16*)d_in[0];
  const __nv_bfloat16* wq = (const __nv_bfloat16*)d_in[1];
  const __nv_bfloat16* wk = (const __nv_bfloat16*)d_in[2];
  const __nv_bfloat16* wv = (const __nv_bfloat16*)d_in[3];
  const __nv_bfloat16* woA = (const __nv_bfloat16*)d_in[4];
  const __nv_bfloat16* wqkv = (const __nv_bfloat16*)d_in[6];
  const __nv_bfloat16* woB = (const __nv_bfloat16*)d_in[7];
  const __nv_bfloat16* gate_w = (const __nv_bfloat16*)d_in[8];

  static EncodeFn enc = nullptr;
  static void* a2_ptr = nullptr;
  if (!enc) {
    void* fp = nullptr;
    cudaDriverEntryPointQueryResult qr;
    cudaGetDriverEntryPoint("cuTensorMapEncodeTiled", &fp, cudaEnableDefault, &qr);
    enc = (EncodeFn)fp;
    cudaGetSymbolAddress(&a2_ptr, g_a2);
    cudaFuncSetAttribute(proj_kernel, cudaFuncAttributeMaxDynamicSharedMemorySize, K1_SMEM);
    cudaFuncSetAttribute(attn_kernel, cudaFuncAttributeMaxDynamicSharedMemorySize, K2_SMEM);
  }
  CUtensorMap tmX, tmWq, tmWqkv, tmA2, tmA2b, tmWoA, tmWoB;
  map_a(enc, &tmX, x, S_LEN, D_MODEL, 256);
  map_w(enc, &tmWq, wq, D_MODEL, D_MODEL, 32, CU_TENSOR_MAP_SWIZZLE_64B);
  map_w(enc, &tmWqkv, wqkv, D_MODEL, 3 * D_MODEL, 32, CU_TENSOR_MAP_SWIZZLE_64B);
  map_a(enc, &tmA2, a2_ptr, S_LEN, 2 * D_MODEL, 64);
  map_a(enc, &tmA2b, a2_ptr, S_LEN, 2 * D_MODEL, 128);
  map_w(enc, &tmWoA, woA, D_MODEL, D_MODEL, 16, CU_TENSOR_MAP_SWIZZLE_32B);
  map_w(enc, &tmWoB, woB, D_MODEL, D_MODEL, 16, CU_TENSOR_MAP_SWIZZLE_32B);

  launch(proj_kernel, 132, 512, K1_SMEM, false, tmX, tmWq, tmWqkv, wk, wv, gate_w);
  launch(attn_kernel, 128, 640, K2_SMEM, true, tmA2, tmA2b, tmWoA, tmWoB, (__nv_bfloat16*)d_out, 0x3F803F80u);
}
```

```cpp
#include <cuda_runtime.h>
#include <cuda_bf16.h>
#include <cuda.h>
#include <stdint.h>

namespace {

constexpr int S_LEN = 2048, D_MODEL = 640, DH = 20;

constexpr int GRP = 128;
constexpr int PLANE = GRP * 16;
constexpr int GRP_BYTES = GRP * 16 * 6;
constexpr int NGRP = S_LEN / GRP;
#define TMASKV 0x6DB6u
constexpr uint32_t TMASK = TMASKV;

__device__ __align__(1024) __nv_bfloat16 g_q[S_LEN * D_MODEL];
__device__ __align__(1024) __nv_bfloat16 g_qkv[S_LEN * 3 * D_MODEL];
__device__ __align__(1024) __nv_bfloat16 g_a2[S_LEN * 2 * D_MODEL];
__device__ __align__(1024) uint8_t g_kvimg[NGRP * GRP_BYTES];
__device__ __align__(1024) uint8_t g_wimg[2 * 8 * 10 * 10240];
__device__ float g_gate[S_LEN];
__device__ float g_kmax2[64];
__device__ float g_vmax[64];
__device__ __align__(32) unsigned int g_doneL[128];
__device__ float g_part[128 * 2 * 40 * 128];
__device__ __align__(32) unsigned int g_done[128];

#define PROF(k, slot)
#define PROF2(k, slot)
__device__ __forceinline__ uint32_t smem_u32(const void* p) { return (uint32_t)__cvta_generic_to_shared(p); }
__device__ __forceinline__ uint64_t mkd(uint32_t lo, uint32_t hi) {
  uint64_t d; asm("mov.b64 %0, {%1, %2};" : "=l"(d) : "r"(lo), "r"(hi)); return d;
}
__device__ __forceinline__ void wg_fence() { asm volatile("wgmma.fence.sync.aligned;" ::: "memory"); }
__device__ __forceinline__ void wg_commit() { asm volatile("wgmma.commit_group.sync.aligned;" ::: "memory"); }
template <int N> __device__ __forceinline__ void wg_wait() { asm volatile("wgmma.wait_group.sync.aligned %0;" :: "n"(N) : "memory"); }
template <int N> __device__ __forceinline__ void fence_regs(float (&d)[N]) {
#pragma unroll
  for (int i = 0; i < N; i++) asm volatile("" : "+f"(d[i]) :: "memory");
}
template <int N> __device__ __forceinline__ void fence_regs(uint32_t (&d)[N]) {
#pragma unroll
  for (int i = 0; i < N; i++) asm volatile("" : "+r"(d[i]) :: "memory");
}
__device__ __forceinline__ void mbar_init(uint32_t bar, uint32_t cnt) { asm volatile("mbarrier.init.shared::cta.b64 [%0], %1;" :: "r"(bar), "r"(cnt)); }
__device__ __forceinline__ void mbar_expect_tx(uint32_t bar, uint32_t bytes) {
  asm volatile("mbarrier.arrive.expect_tx.shared::cta.b64 _, [%0], %1;" :: "r"(bar), "r"(bytes) : "memory");
}
__device__ __forceinline__ void mbar_arrive(uint32_t bar) { asm volatile("mbarrier.arrive.shared::cta.b64 _, [%0];" :: "r"(bar) : "memory"); }
__device__ __forceinline__ void mbar_wait(uint32_t bar, uint32_t parity) {
  asm volatile("{\n.reg .pred p;\nWAIT_%=:\nmbarrier.try_wait.parity.shared::cta.b64 p, [%0], %1;\n@p bra DONE_%=;\nbra WAIT_%=;\nDONE_%=:\n}\n"
               :: "r"(bar), "r"(parity) : "memory");
}
__device__ __forceinline__ void fence_mbar_init() { asm volatile("fence.mbarrier_init.release.cluster;" ::: "memory"); }
__device__ __forceinline__ void fence_proxy_async() { asm volatile("fence.proxy.async.shared::cta;" ::: "memory"); }
__device__ __forceinline__ void bulk_g2s(uint32_t dst, const void* src, uint32_t bytes, uint32_t bar) {
  asm volatile("cp.async.bulk.shared::cluster.global.mbarrier::complete_tx::bytes [%0], [%1], %2, [%3];"
               :: "r"(dst), "l"(src), "r"(bytes), "r"(bar) : "memory");
}
__device__ __forceinline__ void tma_2d(uint32_t dst, const CUtensorMap* tm, int c0, int c1, uint32_t bar) {
  asm volatile("cp.async.bulk.tensor.2d.shared::cluster.global.mbarrier::complete_tx::bytes [%0], [%1, {%3, %4}], [%2];"
               :: "r"(dst), "l"((uint64_t)tm), "r"(bar), "r"(c0), "r"(c1) : "memory");
}
__device__ __forceinline__ void tma_3d(uint32_t dst, const CUtensorMap* tm, int c0, int c1, int c2, uint32_t bar) {
  asm volatile("cp.async.bulk.tensor.3d.shared::cluster.global.mbarrier::complete_tx::bytes [%0], [%1, {%3, %4, %5}], [%2];"
               :: "r"(dst), "l"((uint64_t)tm), "r"(bar), "r"(c0), "r"(c1), "r"(c2) : "memory");
}
__device__ __forceinline__ void pdl_wait() { asm volatile("griddepcontrol.wait;" ::: "memory"); }
__device__ __forceinline__ void pdl_launch() { asm volatile("griddepcontrol.launch_dependents;" ::: "memory"); }
__device__ __forceinline__ float ex2(float x) { float y; asm("ex2.approx.ftz.f32 %0, %1;" : "=f"(y) : "f"(x)); return y; }
__device__ __forceinline__ uint32_t pack_bf16(float lo, float hi) {
  uint32_t r; asm("cvt.rn.bf16x2.f32 %0, %1, %2;" : "=r"(r) : "f"(hi), "f"(lo)); return r;
}
__device__ __forceinline__ float bf_lo(uint32_t x) { return __uint_as_float(x << 16); }
__device__ __forceinline__ float bf_hi(uint32_t x) { return __uint_as_float(x & 0xffff0000u); }
__device__ __forceinline__ void stsm4(uint32_t addr, uint32_t r0, uint32_t r1, uint32_t r2, uint32_t r3) {
  asm volatile("stmatrix.sync.aligned.m8n8.x4.shared.b16 [%0], {%1, %2, %3, %4};" :: "r"(addr), "r"(r0), "r"(r1), "r"(r2), "r"(r3) : "memory");
}

__device__ __forceinline__ void wgmma_ss_n160_tb(float (&d)[80], uint64_t descA, uint64_t descB) {
  asm volatile("wgmma.mma_async.sync.aligned.m64n160k16.f32.bf16.bf16 {%0, %1, %2, %3, %4, %5, %6, %7, %8, %9, %10, %11, %12, %13, %14, %15, %16, %17, %18, %19, %20, %21, %22, %23, %24, %25, %26, %27, %28, %29, %30, %31, %32, %33, %34, %35, %36, %37, %38, %39, %40, %41, %42, %43, %44, %45, %46, %47, %48, %49, %50, %51, %52, %53, %54, %55, %56, %57, %58, %59, %60, %61, %62, %63, %64, %65, %66, %67, %68, %69, %70, %71, %72, %73, %74, %75, %76, %77, %78, %79}, %80, %81, 1, 1, 1, 0, 1;\n"
    : "+f"(d[0]), "+f"(d[1]), "+f"(d[2]), "+f"(d[3]), "+f"(d[4]), "+f"(d[5]), "+f"(d[6]), "+f"(d[7]), "+f"(d[8]), "+f"(d[9]), "+f"(d[10]), "+f"(d[11]), "+f"(d[12]), "+f"(d[13]), "+f"(d[14]), "+f"(d[15]), "+f"(d[16]), "+f"(d[17]), "+f"(d[18]), "+f"(d[19]), "+f"(d[20]), "+f"(d[21]), "+f"(d[22]), "+f"(d[23]), "+f"(d[24]), "+f"(d[25]), "+f"(d[26]), "+f"(d[27]), "+f"(d[28]), "+f"(d[29]), "+f"(d[30]), "+f"(d[31]), "+f"(d[32]), "+f"(d[33]), "+f"(d[34]), "+f"(d[35]), "+f"(d[36]), "+f"(d[37]), "+f"(d[38]), "+f"(d[39]), "+f"(d[40]), "+f"(d[41]), "+f"(d[42]), "+f"(d[43]), "+f"(d[44]), "+f"(d[45]), "+f"(d[46]), "+f"(d[47]), "+f"(d[48]), "+f"(d[49]), "+f"(d[50]), "+f"(d[51]), "+f"(d[52]), "+f"(d[53]), "+f"(d[54]), "+f"(d[55]), "+f"(d[56]), "+f"(d[57]), "+f"(d[58]), "+f"(d[59]), "+f"(d[60]), "+f"(d[61]), "+f"(d[62]), "+f"(d[63]), "+f"(d[64]), "+f"(d[65]), "+f"(d[66]), "+f"(d[67]), "+f"(d[68]), "+f"(d[69]), "+f"(d[70]), "+f"(d[71]), "+f"(d[72]), "+f"(d[73]), "+f"(d[74]), "+f"(d[75]), "+f"(d[76]), "+f"(d[77]), "+f"(d[78]), "+f"(d[79])
    : "l"(descA), "l"(descB));
}
__device__ __forceinline__ void wgmma_ss_n48_tb(float (&d)[24], uint64_t descA, uint64_t descB) {
  asm volatile("wgmma.mma_async.sync.aligned.m64n48k16.f32.bf16.bf16 {%0, %1, %2, %3, %4, %5, %6, %7, %8, %9, %10, %11, %12, %13, %14, %15, %16, %17, %18, %19, %20, %21, %22, %23}, %24, %25, 1, 1, 1, 0, 1;\n"
    : "+f"(d[0]), "+f"(d[1]), "+f"(d[2]), "+f"(d[3]), "+f"(d[4]), "+f"(d[5]), "+f"(d[6]), "+f"(d[7]), "+f"(d[8]), "+f"(d[9]), "+f"(d[10]), "+f"(d[11]), "+f"(d[12]), "+f"(d[13]), "+f"(d[14]), "+f"(d[15]), "+f"(d[16]), "+f"(d[17]), "+f"(d[18]), "+f"(d[19]), "+f"(d[20]), "+f"(d[21]), "+f"(d[22]), "+f"(d[23])
    : "l"(descA), "l"(descB));
}
__device__ __forceinline__ void wgmma_ss_n80_tb(float (&d)[40], uint64_t descA, uint64_t descB) {
  asm volatile("wgmma.mma_async.sync.aligned.m64n80k16.f32.bf16.bf16 {%0, %1, %2, %3, %4, %5, %6, %7, %8, %9, %10, %11, %12, %13, %14, %15, %16, %17, %18, %19, %20, %21, %22, %23, %24, %25, %26, %27, %28, %29, %30, %31, %32, %33, %34, %35, %36, %37, %38, %39}, %40, %41, 1, 1, 1, 0, 1;\n"
    : "+f"(d[0]), "+f"(d[1]), "+f"(d[2]), "+f"(d[3]), "+f"(d[4]), "+f"(d[5]), "+f"(d[6]), "+f"(d[7]), "+f"(d[8]), "+f"(d[9]), "+f"(d[10]), "+f"(d[11]), "+f"(d[12]), "+f"(d[13]), "+f"(d[14]), "+f"(d[15]), "+f"(d[16]), "+f"(d[17]), "+f"(d[18]), "+f"(d[19]), "+f"(d[20]), "+f"(d[21]), "+f"(d[22]), "+f"(d[23]), "+f"(d[24]), "+f"(d[25]), "+f"(d[26]), "+f"(d[27]), "+f"(d[28]), "+f"(d[29]), "+f"(d[30]), "+f"(d[31]), "+f"(d[32]), "+f"(d[33]), "+f"(d[34]), "+f"(d[35]), "+f"(d[36]), "+f"(d[37]), "+f"(d[38]), "+f"(d[39])
    : "l"(descA), "l"(descB));
}
template <int SCALE_D>
__device__ __forceinline__ void wgmma_rs_n64(float (&d)[32], uint32_t a0, uint32_t a1, uint32_t a2, uint32_t a3, uint64_t descB) {
  asm volatile("wgmma.mma_async.sync.aligned.m64n64k16.f32.bf16.bf16 {%0, %1, %2, %3, %4, %5, %6, %7, %8, %9, %10, %11, %12, %13, %14, %15, %16, %17, %18, %19, %20, %21, %22, %23, %24, %25, %26, %27, %28, %29, %30, %31}, {%32, %33, %34, %35}, %36, %37, 1, 1, 0;\n"
    : "+f"(d[0]), "+f"(d[1]), "+f"(d[2]), "+f"(d[3]), "+f"(d[4]), "+f"(d[5]), "+f"(d[6]), "+f"(d[7]), "+f"(d[8]), "+f"(d[9]), "+f"(d[10]), "+f"(d[11]), "+f"(d[12]), "+f"(d[13]), "+f"(d[14]), "+f"(d[15]), "+f"(d[16]), "+f"(d[17]), "+f"(d[18]), "+f"(d[19]), "+f"(d[20]), "+f"(d[21]), "+f"(d[22]), "+f"(d[23]), "+f"(d[24]), "+f"(d[25]), "+f"(d[26]), "+f"(d[27]), "+f"(d[28]), "+f"(d[29]), "+f"(d[30]), "+f"(d[31])
    : "r"(a0), "r"(a1), "r"(a2), "r"(a3), "l"(descB), "n"(SCALE_D));
}
template <int SCALE_D>
__device__ __forceinline__ void wgmma_rs_n24_tb(float (&d)[12], uint32_t a0, uint32_t a1, uint32_t a2, uint32_t a3, uint64_t descB) {
  asm volatile("wgmma.mma_async.sync.aligned.m64n24k16.f32.bf16.bf16 {%0, %1, %2, %3, %4, %5, %6, %7, %8, %9, %10, %11}, {%12, %13, %14, %15}, %16, %17, 1, 1, 1;\n"
    : "+f"(d[0]), "+f"(d[1]), "+f"(d[2]), "+f"(d[3]), "+f"(d[4]), "+f"(d[5]), "+f"(d[6]), "+f"(d[7]), "+f"(d[8]), "+f"(d[9]), "+f"(d[10]), "+f"(d[11])
    : "r"(a0), "r"(a1), "r"(a2), "r"(a3), "l"(descB), "n"(SCALE_D));
}

constexpr uint32_t DHI_SW128_K = (1024 >> 4) | (1u << 30);
constexpr uint32_t DHI_SW64_MN = (512 >> 4) | (2u << 30);

template <int NC>
__device__ __forceinline__ void store_tile_bf16(const float (&acc)[NC / 2], float scale, uint32_t stage, uint8_t* stage_ptr,
                                                __nv_bfloat16* gdst, int gpitch, int lane) {
  constexpr int PITCH = NC * 2 + 16;
  const uint32_t waddr = stage + ((lane & 7) + ((lane >> 3) & 1) * 8) * PITCH + (lane >> 4) * 16;
#pragma unroll
  for (int j = 0; j < NC / 16; j++) {
    stsm4(waddr + j * 32, pack_bf16(acc[8 * j] * scale, acc[8 * j + 1] * scale), pack_bf16(acc[8 * j + 2] * scale, acc[8 * j + 3] * scale),
          pack_bf16(acc[8 * j + 4] * scale, acc[8 * j + 5] * scale), pack_bf16(acc[8 * j + 6] * scale, acc[8 * j + 7] * scale));
  }
  __syncwarp();
  constexpr int CPR = NC / 8;
#pragma unroll
  for (int i = 0; i < CPR / 2; i++) {
    const int c = i * 32 + lane, r = c / CPR, cc = c % CPR;
    const uint4 v = *reinterpret_cast<const uint4*>(stage_ptr + r * PITCH + cc * 16);
    *reinterpret_cast<uint4*>(gdst + (size_t)r * gpitch + cc * 8) = v;
  }
}

__device__ __forceinline__ void signal_done(unsigned int* flag, int wg, int tid) {
  asm volatile("bar.sync %0, 128;" :: "r"(wg + 1) : "memory");
  if ((tid & 127) == 0) asm volatile("red.release.gpu.global.add.u32 [%0], 1;" :: "l"(flag) : "memory");
}
__device__ __forceinline__ void wait_flags8(const unsigned int* f, unsigned int target) {
  for (int spin = 0; spin < (1 << 26); spin++) {
    unsigned int a, b, c, d, e, g, h, i;
    asm volatile("ld.volatile.global.v4.u32 {%0, %1, %2, %3}, [%4];" : "=r"(a), "=r"(b), "=r"(c), "=r"(d) : "l"(f) : "memory");
    asm volatile("ld.volatile.global.v4.u32 {%0, %1, %2, %3}, [%4];" : "=r"(e), "=r"(g), "=r"(h), "=r"(i) : "l"(f + 4) : "memory");
    if (min(min(min(a, b), min(c, d)), min(min(e, g), min(h, i))) >= target) break;
    __nanosleep(32);
  }
  asm volatile("fence.acq_rel.gpu;" ::: "memory");
  asm volatile("fence.proxy.async;" ::: "memory");
}

constexpr int K1_STAGES = 4;
constexpr int K1_A_BYTES = 256 * 128;
constexpr int K1_B_BYTES = 64 * 160 * 2;
constexpr int K1_STAGE = K1_A_BYTES + K1_B_BYTES;
constexpr int K1_SMEM = 5 * K1_A_BYTES + 61440 + 1024;
constexpr int KV_STAGES = 5;
constexpr int KVW_OFF = KV_STAGES * K1_A_BYTES;

__global__ void __launch_bounds__(512, 1)
proj_kernel(const __grid_constant__ CUtensorMap tmX, const __grid_constant__ CUtensorMap tmWq, const __grid_constant__ CUtensorMap tmWqkv,
            const __nv_bfloat16* __restrict__ wk, const __nv_bfloat16* __restrict__ wv, const __nv_bfloat16* __restrict__ gate_w,
            const __nv_bfloat16* __restrict__ woA, const __nv_bfloat16* __restrict__ woB) {
  extern __shared__ uint8_t smem_raw[];
  __shared__ __align__(8) uint64_t bar_full[KV_STAGES], bar_empty[KV_STAGES];
  uint8_t* smem = reinterpret_cast<uint8_t*>((reinterpret_cast<uintptr_t>(smem_raw) + 1023) & ~(uintptr_t)1023);
  const uint32_t sbase = smem_u32(smem);
  const uint32_t dbase = sbase & 0x3FFFFu;
  const int tid = threadIdx.x, warp = tid >> 5, lane = tid & 31;
  const bool is_kv = blockIdx.x >= 128;
  PROF(0, 0);
  if (tid == 0) {
    for (int i = 0; i < KV_STAGES; i++) { mbar_init(smem_u32(&bar_full[i]), 1); mbar_init(smem_u32(&bar_empty[i]), is_kv ? 8 : 16); }
    fence_mbar_init();
  }
  uint2 wa[2][5], wb[2][5]; uint32_t gw[2];
  if (is_kv && tid < 320) {
#pragma unroll
    for (int r = 0; r < 2; r++) {
      const int k = tid + r * 320;
      const uint2* pk = reinterpret_cast<const uint2*>(wk + k * 20);
      const uint2* pv = reinterpret_cast<const uint2*>(wv + k * 20);
#pragma unroll
      for (int i = 0; i < 5; i++) { wa[r][i] = __ldg(pk + i); wb[r][i] = __ldg(pv + i); }
      gw[r] = (uint32_t)__bfloat16_as_ushort(gate_w[k]);
    }
  }
  __syncthreads();
  if (tid == 480) {
    if (!is_kv) { g_done[blockIdx.x] = 0u; g_doneL[blockIdx.x] = 0u; }
    asm volatile("fence.acq_rel.gpu;" ::: "memory");
    pdl_launch();
  }
  __syncwarp();

  if (!is_kv) {
    const int mb = blockIdx.x >> 4, nb = blockIdx.x & 15;
    const CUtensorMap* tw = nb < 4 ? &tmWq : &tmWqkv;
    const int j0 = (nb < 4 ? nb : nb - 4) * 5;
    auto load = [&](int kt) {
      const int s = kt % K1_STAGES;
      const uint32_t fb = smem_u32(&bar_full[s]);
      mbar_expect_tx(fb, K1_STAGE);
      tma_2d(sbase + s * K1_STAGE, &tmX, kt * 64, mb * 256, fb);
      tma_3d(sbase + s * K1_STAGE + K1_A_BYTES, tw, 0, kt * 64, j0, fb);
    };
    if (tid == 0) for (int kt = 0; kt < K1_STAGES; kt++) load(kt);
    __syncwarp();
    if (tid >= 112) {
      uint4 v[2];
#pragma unroll
      for (int i = 0; i < 2; i++) {
        const int q = blockIdx.x * 800 + (tid - 112) + i * 400;
        const int half = q >= 51200, r = q - half * 51200;
        v[i] = __ldg(reinterpret_cast<const uint4*>((half ? woB : woA) + r * 8));
      }
#pragma unroll
      for (int i = 0; i < 2; i++) {
        const int q = blockIdx.x * 800 + (tid - 112) + i * 400;
        const int half = q >= 51200, r = q - half * 51200;
        const int k = r / 80, ch = r - k * 80, nbo = ch / 10, j = ch - nbo * 10;
        *reinterpret_cast<uint4*>(g_wimg + ((half * 8 + nbo) * 10 + (k >> 6)) * 10240 + j * 1024 + (k & 63) * 16) = v[i];
      }
    }
    __syncwarp();
    {
      const int wg = warp >> 2;
      float acc[80];
#pragma unroll
      for (int i = 0; i < 80; i++) acc[i] = 0.f;
      for (int kt = 0; kt < 10; kt++) {
        const int s = kt % K1_STAGES;
        mbar_wait(smem_u32(&bar_full[s]), (kt / K1_STAGES) & 1);
        const uint32_t alo = ((dbase + s * K1_STAGE + wg * 8192) >> 4) | (1u << 16);
        const uint32_t blo = ((dbase + s * K1_STAGE + K1_A_BYTES) >> 4) | ((4096u >> 4) << 16);
        fence_regs(acc);
        wg_fence();
#pragma unroll
        for (int k = 0; k < 4; k++) wgmma_ss_n160_tb(acc, mkd(alo + k * 2, DHI_SW128_K), mkd(blo + k * 64, DHI_SW64_MN));
        wg_commit();
        if (kt > 0 && kt - 1 + K1_STAGES < 10) {
          wg_wait<1>();
          const uint32_t eb = smem_u32(&bar_empty[(kt - 1) % K1_STAGES]);
          if (lane == 0) mbar_arrive(eb);
          if (tid == 0) { mbar_wait(eb, ((kt - 1) / K1_STAGES) & 1); load(kt - 1 + K1_STAGES); }
          __syncwarp();
        }
      }
      wg_wait<0>();
      fence_regs(acc);
      PROF(0, 1);
      asm volatile("bar.sync %0, 128;" :: "r"(wg + 1) : "memory");
      const int w4 = warp & 3;
      const uint32_t off = w4 * K1_STAGE + wg * 8192;
      const int row0 = mb * 256 + wg * 64 + w4 * 16;
      if (nb < 4) {
        store_tile_bf16<160>(acc, 0.22360679774997896f * 1.4426950408889634f, sbase + off, smem + off,
                             g_q + (size_t)row0 * D_MODEL + nb * 160, D_MODEL, lane);
      } else {
        store_tile_bf16<160>(acc, 1.0f, sbase + off, smem + off, g_qkv + (size_t)row0 * (3 * D_MODEL) + (nb - 4) * 160, 3 * D_MODEL, lane);
      }
    }
  } else {
    const int cb = blockIdx.x - 128;
    if (warp == 8 && lane == 0) {
      for (int it = 0; it < KV_STAGES; it++) {
        const uint32_t fb = smem_u32(&bar_full[it]);
        mbar_expect_tx(fb, K1_A_BYTES);
        tma_2d(sbase + it * K1_A_BYTES, &tmX, it * 64, cb * 512, fb);
      }
    }
    __syncwarp();
    if (tid < 320) {
#pragma unroll
      for (int r = 0; r < 2; r++) {
        uint4* dst = reinterpret_cast<uint4*>(smem + KVW_OFF + (tid + r * 320) * 16);
        dst[0] = make_uint4(wa[r][0].x, wa[r][0].y, wa[r][1].x, wa[r][1].y);
        dst[640] = make_uint4(wa[r][2].x, wa[r][2].y, wa[r][3].x, wa[r][3].y);
        dst[1280] = make_uint4(wa[r][4].x, wa[r][4].y, 0u, 0u);
        dst[1920] = make_uint4(wb[r][0].x, wb[r][0].y, wb[r][1].x, wb[r][1].y);
        dst[2560] = make_uint4(wb[r][2].x, wb[r][2].y, wb[r][3].x, wb[r][3].y);
        dst[3200] = make_uint4(wb[r][4].x, wb[r][4].y, gw[r], 0u);
      }
    }
    fence_proxy_async();
    asm volatile("bar.sync 1, 512;" ::: "memory");
    PROF(0, 1);
    if (warp == 8) {
      if (lane == 0) {
        int s = 0, ph = 0;
        for (int it = KV_STAGES; it < 20; it++) {
          mbar_wait(smem_u32(&bar_empty[s]), ph);
          const uint32_t fb = smem_u32(&bar_full[s]);
          mbar_expect_tx(fb, K1_A_BYTES);
          tma_2d(sbase + s * K1_A_BYTES, &tmX, (it >= 10 ? it - 10 : it) * 64, cb * 512 + (it >= 10 ? 256 : 0), fb);
          if (++s == KV_STAGES) { s = 0; ph ^= 1; }
        }
      }
    } else if (warp < 8) {
      const int wg = warp >> 2, w4 = warp & 3, g = lane >> 2, t = lane & 3;
      for (int pass = 0; pass < 2; pass++) {
        float acc[2][24];
#pragma unroll
        for (int i = 0; i < 24; i++) { acc[0][i] = 0.f; acc[1][i] = 0.f; }
        for (int kt = 0; kt < 10; kt++) {
          const int it = pass * 10 + kt, s = it % KV_STAGES;
          mbar_wait(smem_u32(&bar_full[s]), (it / KV_STAGES) & 1);
          const uint32_t alo = ((dbase + s * K1_A_BYTES + wg * 16384) >> 4) | (1u << 16);
          const uint32_t blo = ((dbase + KVW_OFF + kt * 1024) >> 4) | ((128u >> 4) << 16);
          fence_regs(acc[0]); fence_regs(acc[1]);
          wg_fence();
#pragma unroll
          for (int k = 0; k < 4; k++) {
            wgmma_ss_n48_tb(acc[0], mkd(alo + k * 2, DHI_SW128_K), mkd(blo + k * 16, 10240u >> 4));
            wgmma_ss_n48_tb(acc[1], mkd(alo + 512 + k * 2, DHI_SW128_K), mkd(blo + k * 16, 10240u >> 4));
          }
          wg_commit();
          if (kt > 0) {
            wg_wait<1>();
            if (lane == 0) mbar_arrive(smem_u32(&bar_empty[(it - 1) % KV_STAGES]));
          }
        }
        wg_wait<0>();
        fence_regs(acc[0]); fence_regs(acc[1]);
        if (lane == 0) mbar_arrive(smem_u32(&bar_empty[(pass * 10 + 9) % KV_STAGES]));
        if (pass == 0) PROF(0, 2);
        float kmax2 = 0.f, vmax = 0.f;
#pragma unroll
        for (int hh = 0; hh < 4; hh++) {
          const int h = hh & 1;
          const float (&a)[24] = acc[hh >> 1];
          const int key = cb * 512 + pass * 256 + wg * 128 + (hh >> 1) * 64 + w4 * 16 + g + h * 8;
          const int grp = key >> 7, kk = key & 127;
          const bool poly = (TMASK >> (kk >> 3)) & 1;
          uint8_t* gp = g_kvimg + grp * GRP_BYTES;
          const uint32_t k0 = pack_bf16(a[2 * h], a[2 * h + 1]);
          const uint32_t k1 = pack_bf16(a[4 + 2 * h], a[5 + 2 * h]);
          uint32_t k2 = pack_bf16(a[8 + 2 * h], a[9 + 2 * h]);
          float n2 = bf_lo(k0) * bf_lo(k0) + bf_hi(k0) * bf_hi(k0) + bf_lo(k1) * bf_lo(k1) + bf_hi(k1) * bf_hi(k1);
          if (t < 2) {
            n2 += bf_lo(k2) * bf_lo(k2) + bf_hi(k2) * bf_hi(k2);
            k2 = pack_bf16(bf_lo(k2) * 0.5f, bf_hi(k2) * 0.5f);
          } else if (t == 2) k2 = poly ? pack_bf16(24.f, 2.5f) : pack_bf16(0.5f, 0.f);
          else k2 = poly ? pack_bf16(0.5f, 0.f) : 0u;
          *reinterpret_cast<uint32_t*>(gp + kk * 16 + t * 4) = k0;
          *reinterpret_cast<uint32_t*>(gp + PLANE + kk * 16 + t * 4) = k1;
          *reinterpret_cast<uint32_t*>(gp + 2 * PLANE + kk * 16 + t * 4) = k2;
          n2 += __shfl_xor_sync(0xffffffffu, n2, 1);
          n2 += __shfl_xor_sync(0xffffffffu, n2, 2);
          kmax2 = (n2 > kmax2 || n2 != n2) ? n2 : kmax2;
          uint32_t v0 = pack_bf16(a[12 + 2 * h], a[13 + 2 * h]);
          uint32_t v1 = pack_bf16(a[16 + 2 * h], a[17 + 2 * h]);
          uint32_t v2 = pack_bf16(a[20 + 2 * h], a[21 + 2 * h]);
          float vm = fmaxf(fmaxf(fabsf(bf_lo(v0)), fabsf(bf_hi(v0))), fmaxf(fabsf(bf_lo(v1)), fabsf(bf_hi(v1))));
          if (t < 2) vm = fmaxf(vm, fmaxf(fabsf(bf_lo(v2)), fabsf(bf_hi(v2))));
          else if (t == 2) {
            const float z = a[20 + 2 * h];
            g_gate[key] = 1.f / (1.f + __expf(-z));
            v2 = 0x00003F80u;
          } else v2 = 0u;
          vmax = fmaxf(vmax, vm);
          if (poly) { v0 ^= 0x80008000u; v1 ^= 0x80008000u; v2 ^= 0x80008000u; }
          uint8_t* vp = gp + 3 * PLANE + (kk >> 3) * 384 + (kk & 7) * 16 + t * 4;
          *reinterpret_cast<uint32_t*>(vp) = v0;
          *reinterpret_cast<uint32_t*>(vp + 128) = v1;
          *reinterpret_cast<uint32_t*>(vp + 256) = v2;
        }
#pragma unroll
        for (int o = 1; o < 32; o <<= 1) {
          const float a = __shfl_xor_sync(0xffffffffu, kmax2, o);
          kmax2 = (a > kmax2 || a != a) ? a : kmax2;
          vmax = fmaxf(vmax, __shfl_xor_sync(0xffffffffu, vmax, o));
        }
        if (lane == 0) { g_kmax2[cb * 16 + pass * 8 + warp] = kmax2; g_vmax[cb * 16 + pass * 8 + warp] = vmax; }
      }
    }
  }
  PROF(0, 3);
}

__device__ __forceinline__ uint32_t ex2_pair_poly(float u0, float u1, uint32_t one2) {
  const uint32_t W = __byte_perm(__float_as_uint(u0), __float_as_uint(u1), 0x6521);
  uint32_t v; asm("lop3.b32 %0, %1, 0x007F007F, %2, 0xEA;" : "=r"(v) : "r"(W), "r"(one2));
  uint32_t L, p;
  asm("fma.rn.bf16x2 %0, %1, %2, %3;" : "=r"(L) : "r"(v), "r"(0x1f961f96u), "r"(0x9fe39fe3u));
  asm("fma.rn.bf16x2 %0, %1, %1, %2;" : "=r"(p) : "r"(L), "r"(0x00f500f5u));
  return W + p;
}
template <int JOFF>
__device__ __forceinline__ void softmax_fast(const float (&S)[32], uint32_t (&P)[16], uint32_t one2) {
#pragma unroll
  for (int i = 0; i < 16; i++) {
    if ((TMASK >> (JOFF + i / 2)) & 1) P[i] = ex2_pair_poly(S[2 * i], S[2 * i + 1], one2);
    else P[i] = pack_bf16(ex2(S[2 * i]), ex2(S[2 * i + 1]));
  }
}
template <int JOFF>
__device__ __forceinline__ void softmax_slow(const float (&S)[32], uint32_t (&P)[16], float (&O)[12], float& m0, float& m1) {
  float a0 = m0, a1 = m1;
#pragma unroll
  for (int j = 0; j < 8; j++) {
    a0 = fmaxf(a0, fmaxf(S[4 * j], S[4 * j + 1]));
    a1 = fmaxf(a1, fmaxf(S[4 * j + 2], S[4 * j + 3]));
  }
  a0 = fmaxf(a0, __shfl_xor_sync(0xffffffffu, a0, 1)); a0 = fmaxf(a0, __shfl_xor_sync(0xffffffffu, a0, 2));
  a1 = fmaxf(a1, __shfl_xor_sync(0xffffffffu, a1, 1)); a1 = fmaxf(a1, __shfl_xor_sync(0xffffffffu, a1, 2));
  const float c0 = ex2(m0 - a0), c1 = ex2(m1 - a1);
  m0 = a0; m1 = a1;
#pragma unroll
  for (int j = 0; j < 3; j++) { O[4 * j] *= c0; O[4 * j + 1] *= c0; O[4 * j + 2] *= c1; O[4 * j + 3] *= c1; }
#pragma unroll
  for (int i = 0; i < 16; i++) {
    const float m = (i & 1) ? a1 : a0;
    const uint32_t p = pack_bf16(ex2(S[2 * i] - m), ex2(S[2 * i + 1] - m));
    P[i] = ((TMASK >> (JOFF + i / 2)) & 1) ? (p ^ 0x80008000u) : p;
  }
}
constexpr uint32_t DHI_KV = 128 >> 4;
__device__ __forceinline__ void issue_qk(float (&S)[32], const uint32_t (&q)[8], uint64_t base) {
  wgmma_rs_n64<0>(S, q[0], q[1], q[2], q[3], base + (uint64_t)((PLANE >> 4) << 16));
  wgmma_rs_n64<1>(S, q[4], q[5], q[6], q[7], base + (uint64_t)(2 * PLANE >> 4));
}
__device__ __forceinline__ void issue_pv(float (&O)[12], const uint32_t (&P)[16], uint64_t vbase) {
#pragma unroll
  for (int kk = 0; kk < 4; kk++)
    wgmma_rs_n24_tb<1>(O, P[4 * kk], P[4 * kk + 1], P[4 * kk + 2], P[4 * kk + 3], vbase + (uint64_t)(kk * (768 >> 4)));
}

constexpr uint32_t VOFF = ((3 * PLANE) >> 4) + ((384u >> 4) << 16);
constexpr int KVR = 4;
constexpr int OFF_WA = KVR * GRP_BYTES;
constexpr int OFF_BR = OFF_WA + 10 * 10240;
constexpr int BR_STAGE = 8192 + 10240, BR_STAGES = 3;
constexpr int OFF_QS = OFF_BR + BR_STAGES * BR_STAGE;
constexpr int OFF_BAR = OFF_QS + 512 * 6 * 4;
constexpr int K2_SMEM = OFF_BAR + 256 + 1024;
constexpr int BAR_KV = 0, BAR_WA = 4, BAR_BR = 5, BAR_TA = 8, BAR_TE = 14, BAR_OWN = 18, CNT_KV = 19;
constexpr int NSTEP = 2 * NGRP;

__device__ __forceinline__ void kv_load(uint32_t sbase, int step) {
  const uint32_t bar = sbase + OFF_BAR + (BAR_KV + (step & (KVR - 1))) * 8;
  mbar_expect_tx(bar, GRP_BYTES);
  bulk_g2s(sbase + (step & (KVR - 1)) * GRP_BYTES, g_kvimg + (step & (NGRP - 1)) * GRP_BYTES, GRP_BYTES, bar);
}
__device__ __forceinline__ void kv_release(uint32_t sbase, int step, bool elected) {
  if (elected && step + KVR < NSTEP) {
    uint32_t old;
    asm volatile("atom.acq_rel.cta.shared::cta.inc.u32 %0, [%1], 3;" : "=r"(old) : "r"(sbase + OFF_BAR + CNT_KV * 8 + (step & (KVR - 1)) * 4) : "memory");
    if (old == 3u) kv_load(sbase, step + KVR);
  }
  __syncwarp();
}
__device__ __forceinline__ void kv_wait(uint32_t sbase, int step) {
  mbar_wait(sbase + OFF_BAR + (BAR_KV + (step & (KVR - 1))) * 8, (step / KVR) & 1);
}

__device__ __forceinline__ uint32_t kv_release_begin(uint32_t sbase, int slot, bool doit) {
  uint32_t old = 0;
  asm volatile("{\n.reg .pred p;\nsetp.ne.u32 p, %2, 0;\n@p atom.relaxed.cta.shared::cta.inc.u32 %0, [%1], 3;\n}\n"
               : "+r"(old) : "r"(sbase + OFF_BAR + CNT_KV * 8 + slot * 4), "r"((uint32_t)doit) : "memory");
  return old;
}
__device__ __forceinline__ void attn_tile_fast(const uint32_t (&q)[8], float (&O)[12], uint32_t sbase, int step0, bool elected, uint32_t one2) {
  float S[32]; uint32_t P[16];
#pragma unroll
  for (int i = 0; i < 32; i++) S[i] = 0.f;
  uint64_t kb0 = mkd((sbase & 0x3FFFFu) >> 4, DHI_KV);
  asm volatile("" : "+l"(kb0));
  kv_wait(sbase, step0);
  fence_regs(S); fence_regs(O);
  wg_fence();
  issue_qk(S, q, kb0);
  wg_commit();
#pragma unroll 1
  for (int step4 = step0; step4 < step0 + NGRP; step4 += KVR) {
#pragma unroll
    for (int j = 0; j < KVR; j++) {
      const int step = step4 + j;
      const uint64_t kb = kb0 + (uint64_t)(j * (GRP_BYTES >> 4));
      const uint64_t knext = kb0 + (uint64_t)(((j + 1) & (KVR - 1)) * (GRP_BYTES >> 4));
      wg_wait<0>();
      fence_regs(S); fence_regs(P); fence_regs(O);
      const uint32_t old = kv_release_begin(sbase, (j + KVR - 1) & (KVR - 1), elected && step > step0 && step - 1 + KVR < NSTEP);
      softmax_fast<0>(S, P, one2);
      fence_regs(S); fence_regs(P); fence_regs(O);
      wg_fence();
      issue_qk(S, q, kb + 64);
      issue_pv(O, P, kb + VOFF);
      wg_commit();
      if (step + 1 < NSTEP) mbar_wait(sbase + OFF_BAR + (BAR_KV + ((j + 1) & (KVR - 1))) * 8, ((step + 1) / KVR) & 1);
      wg_wait<0>();
      fence_regs(S); fence_regs(P); fence_regs(O);
      softmax_fast<8>(S, P, one2);
      fence_regs(S); fence_regs(P); fence_regs(O);
      wg_fence();
      issue_qk(S, q, knext);
      issue_pv(O, P, kb + VOFF + 4 * (768 >> 4));
      wg_commit();
      if (old == 3u) kv_load(sbase, step - 1 + KVR);
    }
  }
  wg_wait<0>();
  fence_regs(O); fence_regs(S);
  kv_release(sbase, step0 + NGRP - 1, elected);
}
template <int H>
__device__ __forceinline__ void slow_step(const uint32_t (&q)[8], float (&O)[12], uint64_t kb, float& m0, float& m1) {
  float S[32]; uint32_t P[16];
#pragma unroll
  for (int i = 0; i < 32; i++) S[i] = 0.f;
  fence_regs(S);
  wg_fence();
  issue_qk(S, q, kb + 64 * H);
  wg_commit();
  wg_wait<0>();
  fence_regs(S);
  softmax_slow<8 * H>(S, P, O, m0, m1);
  fence_regs(P); fence_regs(O);
  wg_fence();
  issue_pv(O, P, kb + VOFF + H * 4 * (768 >> 4));
  wg_commit();
  wg_wait<0>();
  fence_regs(O); fence_regs(P);
}
__device__ __forceinline__ void attn_tile_slow(const uint32_t (&q)[8], float (&O)[12], uint32_t sbase, int step0, bool elected) {
  float m0 = -INFINITY, m1 = -INFINITY;
#pragma unroll 1
  for (int grp = 0; grp < NGRP; grp++) {
    kv_wait(sbase, step0 + grp);
    const uint64_t kb = mkd(((sbase & 0x3FFFFu) >> 4) + (grp & (KVR - 1)) * (GRP_BYTES >> 4), DHI_KV);
    slow_step<0>(q, O, kb, m0, m1);
    slow_step<1>(q, O, kb, m0, m1);
    kv_release(sbase, step0 + grp, elected);
  }
}

__device__ __forceinline__ void load_row20(const __nv_bfloat16* p, float (&f)[20]) {
  const uint2* p2 = reinterpret_cast<const uint2*>(p);
#pragma unroll
  for (int i = 0; i < 5; i++) { const uint2 v = p2[i]; f[4 * i] = bf_lo(v.x); f[4 * i + 1] = bf_hi(v.x); f[4 * i + 2] = bf_lo(v.y); f[4 * i + 3] = bf_hi(v.y); }
}
__device__ __forceinline__ void softmax8(float (&sc)[8]) {
  float mx = sc[0];
#pragma unroll
  for (int w = 1; w < 8; w++) mx = fmaxf(mx, sc[w]);
  float l = 0.f;
#pragma unroll
  for (int w = 0; w < 8; w++) { sc[w] = ex2(sc[w] - mx); l += sc[w]; }
  const float r = 1.f / l;
#pragma unroll
  for (int w = 0; w < 8; w++) sc[w] *= r;
}
__device__ __forceinline__ void local_attn_pair(int t, int lane) {
  constexpr int PITCH = 3 * D_MODEL;
  constexpr float SC = 0.22360679774997896f * 1.4426950408889634f, NEG = -1e9f * 1.4426950408889634f;
  const __nv_bfloat16* base = g_qkv + lane * DH;
  float a[20], b[20], sa[8], sb[8];
  load_row20(base + (size_t)t * PITCH, a);
  load_row20(base + (size_t)(t + 2) * PITCH, b);
#pragma unroll
  for (int j = 0; j < 9; j++) {
    const int r = t + 2 - 2 * j;
    float k[20];
    load_row20(base + D_MODEL + (size_t)max(r, 0) * PITCH, k);
    float da = 0.f, db = 0.f;
#pragma unroll
    for (int i = 0; i < 20; i++) { if (j >= 1) da = fmaf(a[i], k[i], da); if (j < 8) db = fmaf(b[i], k[i], db); }
    if (j >= 1) sa[j - 1] = r >= 0 ? da * SC : NEG;
    if (j < 8) sb[j] = r >= 0 ? db * SC : NEG;
  }
  softmax8(sa); softmax8(sb);
#pragma unroll
  for (int i = 0; i < 20; i++) { a[i] = 0.f; b[i] = 0.f; }
#pragma unroll
  for (int j = 0; j < 9; j++) {
    const int r = t + 2 - 2 * j;
    float v[20];
    load_row20(base + 2 * D_MODEL + (size_t)max(r, 0) * PITCH, v);
#pragma unroll
    for (int i = 0; i < 20; i++) { if (j >= 1) a[i] = fmaf(sa[j - 1], v[i], a[i]); if (j < 8) b[i] = fmaf(sb[j], v[i], b[i]); }
  }
  const float ga = 1.f - g_gate[t], gb = 1.f - g_gate[t + 2];
  uint2* da = reinterpret_cast<uint2*>(g_a2 + (size_t)t * (2 * D_MODEL) + D_MODEL + lane * DH);
  uint2* db = da + 2 * (2 * D_MODEL) / 4;
#pragma unroll
  for (int i = 0; i < 5; i++) {
    da[i] = make_uint2(pack_bf16(a[4 * i] * ga, a[4 * i + 1] * ga), pack_bf16(a[4 * i + 2] * ga, a[4 * i + 3] * ga));
    db[i] = make_uint2(pack_bf16(b[4 * i] * gb, b[4 * i + 1] * gb), pack_bf16(b[4 * i + 2] * gb, b[4 * i + 3] * gb));
  }
}
__device__ __forceinline__ uint32_t ta_slot(int i) { return i < 3 ? i * 16384 : OFF_BR + (i - 3) * 16384; }

__global__ void __launch_bounds__(640, 1)
attn_kernel(const __grid_constant__ CUtensorMap tmA2, const __grid_constant__ CUtensorMap tmA2b,
            __nv_bfloat16* __restrict__ out, uint32_t one2) {
  extern __shared__ uint8_t smem_raw[];
  uint8_t* smem = reinterpret_cast<uint8_t*>((reinterpret_cast<uintptr_t>(smem_raw) + 1023) & ~(uintptr_t)1023);
  const uint32_t sbase = smem_u32(smem);
  const uint32_t dbase = sbase & 0x3FFFFu;
  const uint32_t bars = sbase + OFF_BAR;
  const int tid = threadIdx.x, wg = tid >> 7, warp = (tid >> 5) & 3, lane = tid & 31, g = lane >> 2, t = lane & 3;
  const int mb = blockIdx.x >> 3, nb = blockIdx.x & 7;
  if (tid == 0) {
    for (int i = 0; i < BAR_TE; i++) mbar_init(bars + i * 8, 1);
    for (int i = BAR_TE; i < BAR_TE + 4; i++) mbar_init(bars + i * 8, 8);
    mbar_init(bars + BAR_OWN * 8, 4);
    for (int i = 0; i < 4; i++) *reinterpret_cast<uint32_t*>(smem + OFF_BAR + CNT_KV * 8 + i * 4) = 0u;
    fence_mbar_init();
  }
  __syncthreads();
  if (wg == 4) {
    pdl_wait();
    asm volatile("bar.sync 7, 640;" ::: "memory");
#pragma unroll 1
    for (int i = 0; i < 2; i++) local_attn_pair(blockIdx.x * 16 + warp * 4 + i, lane);
    if (tid == 512) PROF2(0, 2);
    signal_done(&g_doneL[blockIdx.x], wg, tid);
    if (tid == 512) {
      mbar_expect_tx(bars + BAR_WA * 8, 10 * 10240);
      for (int i = 0; i < 5; i++) bulk_g2s(sbase + OFF_WA + i * 20480, g_wimg + (nb * 10) * 10240 + i * 20480, 20480, bars + BAR_WA * 8);
    }
    auto br_load = [&](int it, int st) {
      const uint32_t fb = bars + (BAR_BR + st) * 8;
      const uint32_t dst = sbase + OFF_BR + st * BR_STAGE;
      const int kc = (it >= 10 ? it - 10 : it) * 64;
      mbar_expect_tx(fb, BR_STAGE);
      tma_2d(dst, &tmA2, D_MODEL + kc, (blockIdx.x >> 3) * 128 + (it >= 10 ? 64 : 0), fb);
      bulk_g2s(dst + 8192, g_wimg + ((8 + (blockIdx.x & 7)) * 10 + (kc >> 6)) * 10240, 10240, fb);
    };
    if (tid == 512) {
      wait_flags8(&g_doneL[mb * 8], 1u);
      for (int it = 0; it < BR_STAGES; it++) br_load(it, it);
    }
    __syncwarp();
    {
      int st = 0, ph = 0;
      float acc[40];
#pragma unroll 1
      for (int it = 0; it < 20; it++) {
        if (it == 0 || it == 10) {
#pragma unroll
          for (int i = 0; i < 40; i++) acc[i] = 0.f;
        }
        mbar_wait(bars + (BAR_BR + st) * 8, ph);
        const uint32_t alo = ((dbase + OFF_BR + st * BR_STAGE) >> 4);
        fence_regs(acc);
        wg_fence();
#pragma unroll
        for (int k = 0; k < 4; k++)
          wgmma_ss_n80_tb(acc, mkd(alo + (k * 2 + (1u << 16)), DHI_SW128_K), mkd(alo + (512 + k * 16 + ((128u >> 4) << 16)), 1024u >> 4));
        wg_commit();
        wg_wait<0>();
        fence_regs(acc);
        asm volatile("bar.sync 5, 128;" ::: "memory");
        if (threadIdx.x == 512 && it + BR_STAGES < 20) br_load(it + BR_STAGES, st);
        __syncwarp();
        if (it == 9 || it == 19) {
          float* pp = g_part + (size_t)(blockIdx.x * 2 + (it == 19)) * (40 * 128) + (threadIdx.x & 127);
#pragma unroll
          for (int i = 0; i < 40; i++) pp[i * 128] = acc[i];
        }
        if (++st == BR_STAGES) { st = 0; ph ^= 1; }
      }
    }
    if (tid == 512) PROF2(1, 0);
    asm volatile("bar.arrive 6, 384;" ::: "memory");
    if (tid == 512) {
      mbar_wait(bars + BAR_OWN * 8, 0);
      wait_flags8(&g_done[mb * 8], 4u);
      PROF2(2, 0);
    }
    if (tid == 512) {
      for (int kt = 0; kt < 10; kt++) {
        const int sl = kt % 6;
        if (kt >= 6) mbar_wait(bars + (BAR_TE + kt - 6) * 8, 0);
        const uint32_t fb = bars + (BAR_TA + sl) * 8;
        mbar_expect_tx(fb, 16384);
        tma_2d(sbase + ta_slot(sl), &tmA2b, kt * 64, mb * 128, fb);
      }
    }
  } else {
    const bool elected = (tid & 127) == 0;
    pdl_wait();
    PROF(1, 1);
    if (tid == 384) for (int j = 0; j < KVR; j++) kv_load(sbase, j);
    __syncwarp();
    uint32_t q[8];
    uint32_t* qstash = reinterpret_cast<uint32_t*>(smem + OFF_QS) + tid;
    const int rowA = (blockIdx.x * 8 + wg) * 64 + warp * 16 + g;
    {
      const uint32_t* r0 = reinterpret_cast<const uint32_t*>(g_q + (size_t)rowA * DH);
      const uint32_t* r1 = r0 + 8 * (DH / 2);
      const uint32_t* s0 = r0 + 256 * (DH / 2);
      const uint32_t* s1 = s0 + 8 * (DH / 2);
      q[0] = r0[t]; q[1] = r1[t]; q[2] = r0[t + 4]; q[3] = r1[t + 4];
      q[4] = t < 2 ? r0[8 + t] : 0u;
      q[5] = t < 2 ? r1[8 + t] : 0u;
      qstash[0] = s0[t]; qstash[512] = s1[t]; qstash[1024] = s0[t + 4]; qstash[1536] = s1[t + 4];
      qstash[2048] = t < 2 ? s0[8 + t] : 0u;
      qstash[2560] = t < 2 ? s1[8 + t] : 0u;
    }
    float kmax2 = 0.f, vmax = 0.f;
#pragma unroll
    for (int i = 0; i < 2; i++) {
      const float a = g_kmax2[lane + 32 * i];
      kmax2 = (a > kmax2 || a != a) ? a : kmax2;
      vmax = fmaxf(vmax, g_vmax[lane + 32 * i]);
    }
#pragma unroll
    for (int o = 1; o < 32; o <<= 1) {
      const float a = __shfl_xor_sync(0xffffffffu, kmax2, o);
      kmax2 = (a > kmax2 || a != a) ? a : kmax2;
      vmax = fmaxf(vmax, __shfl_xor_sync(0xffffffffu, vmax, o));
    }
    const float qlim = (vmax >= 0.00390625f && vmax <= 256.f) ? 9025.f / kmax2 : -1.f;
    asm volatile("bar.arrive 7, 640;" ::: "memory");
    PROF(1, 2);
#pragma unroll 1
    for (int it = 0; it < 2; it++) {
      const int row0 = rowA + it * 256;
      if (it == 1) {
#pragma unroll
        for (int i = 0; i < 6; i++) q[i] = qstash[512 * i];
      }
      float n0 = bf_lo(q[0]) * bf_lo(q[0]) + bf_hi(q[0]) * bf_hi(q[0]) + bf_lo(q[2]) * bf_lo(q[2]) + bf_hi(q[2]) * bf_hi(q[2]) +
                 bf_lo(q[4]) * bf_lo(q[4]) + bf_hi(q[4]) * bf_hi(q[4]);
      float n1 = bf_lo(q[1]) * bf_lo(q[1]) + bf_hi(q[1]) * bf_hi(q[1]) + bf_lo(q[3]) * bf_lo(q[3]) + bf_hi(q[3]) * bf_hi(q[3]) +
                 bf_lo(q[5]) * bf_lo(q[5]) + bf_hi(q[5]) * bf_hi(q[5]);
      n0 += __shfl_xor_sync(0xffffffffu, n0, 1); n0 += __shfl_xor_sync(0xffffffffu, n0, 2);
      n1 += __shfl_xor_sync(0xffffffffu, n1, 1); n1 += __shfl_xor_sync(0xffffffffu, n1, 2);
      const bool safe = (n0 <= qlim) && (n1 <= qlim);
      uint32_t unsafe_any;
      asm volatile("{\n.reg .pred p, r;\nsetp.eq.u32 p, %1, 0;\nbarrier.cta.red.or.pred r, %2, 128, p;\nselp.u32 %0, 1, 0, r;\n}\n"
                   : "=r"(unsafe_any) : "r"((uint32_t)safe), "r"(wg + 1) : "memory");
      float O[12];
#pragma unroll
      for (int i = 0; i < 12; i++) O[i] = 0.f;
      if (!unsafe_any && t >= 2) { q[4] = q[5] = (t == 2) ? 0x3F804100u : 0x00003B80u; }
      q[6] = q[4]; q[7] = q[5];
      fence_regs(q);
      if (!unsafe_any) attn_tile_fast(q, O, sbase, it * NGRP, elected, one2);
      else attn_tile_slow(q, O, sbase, it * NGRP, elected);
      const float l0 = __shfl_sync(0xffffffffu, O[8], (lane & ~3) | 2);
      const float l1 = __shfl_sync(0xffffffffu, O[10], (lane & ~3) | 2);
      const int tok = row0 >> 5;
      const float gt = g_gate[tok];
      const float i0 = gt / l0, i1 = gt / l1;
      uint32_t* o0 = reinterpret_cast<uint32_t*>(g_a2 + (size_t)tok * (2 * D_MODEL) + (row0 & 31) * DH);
      uint32_t* o1 = o0 + 8 * (DH / 2);
      o0[t] = pack_bf16(O[0] * i0, O[1] * i0); o1[t] = pack_bf16(O[2] * i1, O[3] * i1);
      o0[t + 4] = pack_bf16(O[4] * i0, O[5] * i0); o1[t + 4] = pack_bf16(O[6] * i1, O[7] * i1);
      if (t < 2) { o0[t + 8] = pack_bf16(O[8] * i0, O[9] * i0); o1[t + 8] = pack_bf16(O[10] * i1, O[11] * i1); }
    }
    signal_done(&g_done[blockIdx.x], wg, tid);
    if (elected) mbar_arrive(bars + BAR_OWN * 8);
    PROF(1, 3);
    if (wg < 2) {
      float acc[40];
      asm volatile("bar.sync 6, 384;" ::: "memory");
      {
        const float* pp = g_part + (size_t)(blockIdx.x * 2 + wg) * (40 * 128) + (tid & 127);
#pragma unroll
        for (int i = 0; i < 40; i++) acc[i] = pp[i * 128];
      }
      mbar_wait(bars + BAR_WA * 8, 0);
#pragma unroll 1
      for (int kt = 0; kt < 10; kt++) {
        const int sl = kt % 6;
        mbar_wait(bars + (BAR_TA + sl) * 8, kt / 6);
        if (kt == 0) PROF(2, 1);
        const uint32_t alo = ((dbase + ta_slot(sl) + wg * 8192) >> 4) | (1u << 16);
        const uint32_t blo = ((dbase + OFF_WA + kt * 10240) >> 4) | ((128u >> 4) << 16);
        fence_regs(acc);
        wg_fence();
#pragma unroll
        for (int k = 0; k < 4; k++) wgmma_ss_n80_tb(acc, mkd(alo + k * 2, DHI_SW128_K), mkd(blo + k * 16, 1024u >> 4));
        wg_commit();
        if (kt < 4) {
          wg_wait<0>();
          if (lane == 0) mbar_arrive(bars + (BAR_TE + kt) * 8);
        }
      }
      wg_wait<0>();
      fence_regs(acc);
      PROF(2, 2);
      asm volatile("bar.sync %0, 128;" :: "r"(wg + 1) : "memory");
      const uint32_t so = ta_slot(warp) + wg * 8192;
      const int row0 = mb * 128 + wg * 64 + warp * 16;
      store_tile_bf16<80>(acc, 1.0f, sbase + so, smem + so, out + (size_t)row0 * D_MODEL + nb * 80, D_MODEL, lane);
      PROF(2, 3);
    }
  }
}

typedef CUresult (*EncodeFn)(CUtensorMap*, CUtensorMapDataType, cuuint32_t, void*, const cuuint64_t*, const cuuint64_t*,
                             const cuuint32_t*, const cuuint32_t*, CUtensorMapInterleave, CUtensorMapSwizzle,
                             CUtensorMapL2promotion, CUtensorMapFloatOOBfill);

void make_map(EncodeFn fn, CUtensorMap* tm, const void* ptr, int rank, const cuuint64_t* dims, const cuuint64_t* strides,
              const cuuint32_t* box, CUtensorMapSwizzle sw) {
  const cuuint32_t es[3] = {1, 1, 1};
  fn(tm, CU_TENSOR_MAP_DATA_TYPE_BFLOAT16, rank, const_cast<void*>(ptr), dims, strides, box, es, CU_TENSOR_MAP_INTERLEAVE_NONE, sw,
     CU_TENSOR_MAP_L2_PROMOTION_L2_256B, CU_TENSOR_MAP_FLOAT_OOB_FILL_NONE);
}
void map_a(EncodeFn fn, CUtensorMap* tm, const void* p, int rows, int cols, int box_rows) {
  const cuuint64_t dims[2] = {(cuuint64_t)cols, (cuuint64_t)rows};
  const cuuint64_t str[1] = {(cuuint64_t)cols * 2};
  const cuuint32_t box[2] = {64, (cuuint32_t)box_rows};
  make_map(fn, tm, p, 2, dims, str, box, CU_TENSOR_MAP_SWIZZLE_128B);
}
void map_w(EncodeFn fn, CUtensorMap* tm, const void* p, int K, int N, int atom, CUtensorMapSwizzle sw) {
  const cuuint64_t dims[3] = {(cuuint64_t)atom, (cuuint64_t)K, (cuuint64_t)(N / atom)};
  const cuuint64_t str[2] = {(cuuint64_t)N * 2, (cuuint64_t)atom * 2};
  const cuuint32_t box[3] = {(cuuint32_t)atom, 64, 5};
  make_map(fn, tm, p, 3, dims, str, box, sw);
}

template <typename... KArgs, typename... Args>
void launch(void (*kern)(KArgs...), int grid, int block, int smem, bool pdl, Args... args) {
  cudaLaunchConfig_t cfg = {};
  cfg.gridDim = dim3(grid); cfg.blockDim = dim3(block); cfg.dynamicSmemBytes = smem; cfg.stream = cudaStreamPerThread;
  cudaLaunchAttribute at[1];
  at[0].id = cudaLaunchAttributeProgrammaticStreamSerialization;
  at[0].val.programmaticStreamSerializationAllowed = 1;
  cfg.attrs = at; cfg.numAttrs = pdl ? 1 : 0;
  cudaLaunchKernelEx(&cfg, kern, KArgs(args)...);
}

}

extern "C" void kernel_launch(void* const* d_in, const int* in_sizes, int n_in, void* d_out, int out_size) {
  (void)in_sizes; (void)n_in; (void)out_size;
  const __nv_bfloat16* x = (const __nv_bfloat16*)d_in[0];
  const __nv_bfloat16* wq = (const __nv_bfloat16*)d_in[1];
  const __nv_bfloat16* wk = (const __nv_bfloat16*)d_in[2];
  const __nv_bfloat16* wv = (const __nv_bfloat16*)d_in[3];
  const __nv_bfloat16* woA = (const __nv_bfloat16*)d_in[4];
  const __nv_bfloat16* wqkv = (const __nv_bfloat16*)d_in[6];
  const __nv_bfloat16* woB = (const __nv_bfloat16*)d_in[7];
  const __nv_bfloat16* gate_w = (const __nv_bfloat16*)d_in[8];

  static EncodeFn enc = nullptr;
  static void* a2_ptr = nullptr;
  if (!enc) {
    void* fp = nullptr;
    cudaDriverEntryPointQueryResult qr;
    cudaGetDriverEntryPoint("cuTensorMapEncodeTiled", &fp, cudaEnableDefault, &qr);
    enc = (EncodeFn)fp;
    cudaGetSymbolAddress(&a2_ptr, g_a2);
    cudaFuncSetAttribute(proj_kernel, cudaFuncAttributeMaxDynamicSharedMemorySize, K1_SMEM);
    cudaFuncSetAttribute(attn_kernel, cudaFuncAttributeMaxDynamicSharedMemorySize, K2_SMEM);
  }
  CUtensorMap tmX, tmWq, tmWqkv, tmA2, tmA2b;
  map_a(enc, &tmX, x, S_LEN, D_MODEL, 256);
  map_w(enc, &tmWq, wq, D_MODEL, D_MODEL, 32, CU_TENSOR_MAP_SWIZZLE_64B);
  map_w(enc, &tmWqkv, wqkv, D_MODEL, 3 * D_MODEL, 32, CU_TENSOR_MAP_SWIZZLE_64B);
  map_a(enc, &tmA2, a2_ptr, S_LEN, 2 * D_MODEL, 64);
  map_a(enc, &tmA2b, a2_ptr, S_LEN, 2 * D_MODEL, 128);

  launch(proj_kernel, 132, 512, K1_SMEM, false, tmX, tmWq, tmWqkv, wk, wv, gate_w, woA, woB);
  launch(attn_kernel, 128, 640, K2_SMEM, true, tmA2, tmA2b, (__nv_bfloat16*)d_out, 0x3F803F80u);
}
```

```cpp
#include <cuda_runtime.h>
#include <cuda_bf16.h>
#include <cuda.h>
#include <stdint.h>

namespace {

constexpr int S_LEN = 2048, D_MODEL = 640, DH = 20;

constexpr int GRP = 128;
constexpr int PLANE = GRP * 16;
constexpr int GRP_BYTES = GRP * 16 * 6;
constexpr int NGRP = S_LEN / GRP;
#define TMASKV 0x6DB6u
constexpr uint32_t TMASK = TMASKV;

__device__ __align__(1024) __nv_bfloat16 g_q[S_LEN * D_MODEL];
__device__ __align__(1024) __nv_bfloat16 g_qkv[S_LEN * 3 * D_MODEL];
__device__ __align__(1024) __nv_bfloat16 g_a2[S_LEN * 2 * D_MODEL];
__device__ __align__(1024) uint8_t g_kvimg[NGRP * GRP_BYTES];
__device__ __align__(1024) uint8_t g_wimg[2 * 8 * 10 * 10240];
__device__ float g_gate[S_LEN];
__device__ float g_kmax2[64];
__device__ float g_vmax[64];
__device__ __align__(32) unsigned int g_doneL[128];
__device__ float g_part[128 * 2 * 40 * 128];
__device__ __align__(32) unsigned int g_done[128];

#define PROF(k, slot)
#define PROF2(k, slot)
__device__ __forceinline__ uint32_t smem_u32(const void* p) { return (uint32_t)__cvta_generic_to_shared(p); }
__device__ __forceinline__ uint64_t mkd(uint32_t lo, uint32_t hi) {
  uint64_t d; asm("mov.b64 %0, {%1, %2};" : "=l"(d) : "r"(lo), "r"(hi)); return d;
}
__device__ __forceinline__ void wg_fence() { asm volatile("wgmma.fence.sync.aligned;" ::: "memory"); }
__device__ __forceinline__ void wg_commit() { asm volatile("wgmma.commit_group.sync.aligned;" ::: "memory"); }
template <int N> __device__ __forceinline__ void wg_wait() { asm volatile("wgmma.wait_group.sync.aligned %0;" :: "n"(N) : "memory"); }
template <int N> __device__ __forceinline__ void fence_regs(float (&d)[N]) {
#pragma unroll
  for (int i = 0; i < N; i++) asm volatile("" : "+f"(d[i]) :: "memory");
}
template <int N> __device__ __forceinline__ void fence_regs(uint32_t (&d)[N]) {
#pragma unroll
  for (int i = 0; i < N; i++) asm volatile("" : "+r"(d[i]) :: "memory");
}
__device__ __forceinline__ void mbar_init(uint32_t bar, uint32_t cnt) { asm volatile("mbarrier.init.shared::cta.b64 [%0], %1;" :: "r"(bar), "r"(cnt)); }
__device__ __forceinline__ void mbar_expect_tx(uint32_t bar, uint32_t bytes) {
  asm volatile("mbarrier.arrive.expect_tx.shared::cta.b64 _, [%0], %1;" :: "r"(bar), "r"(bytes) : "memory");
}
__device__ __forceinline__ void mbar_arrive(uint32_t bar) { asm volatile("mbarrier.arrive.shared::cta.b64 _, [%0];" :: "r"(bar) : "memory"); }
__device__ __forceinline__ void mbar_wait(uint32_t bar, uint32_t parity) {
  asm volatile("{\n.reg .pred p;\nWAIT_%=:\nmbarrier.try_wait.parity.shared::cta.b64 p, [%0], %1;\n@p bra DONE_%=;\nbra WAIT_%=;\nDONE_%=:\n}\n"
               :: "r"(bar), "r"(parity) : "memory");
}
__device__ __forceinline__ void fence_mbar_init() { asm volatile("fence.mbarrier_init.release.cluster;" ::: "memory"); }
__device__ __forceinline__ void fence_proxy_async() { asm volatile("fence.proxy.async.shared::cta;" ::: "memory"); }
__device__ __forceinline__ void bulk_g2s(uint32_t dst, const void* src, uint32_t bytes, uint32_t bar) {
  asm volatile("cp.async.bulk.shared::cluster.global.mbarrier::complete_tx::bytes [%0], [%1], %2, [%3];"
               :: "r"(dst), "l"(src), "r"(bytes), "r"(bar) : "memory");
}
__device__ __forceinline__ void tma_2d(uint32_t dst, const CUtensorMap* tm, int c0, int c1, uint32_t bar) {
  asm volatile("cp.async.bulk.tensor.2d.shared::cluster.global.mbarrier::complete_tx::bytes [%0], [%1, {%3, %4}], [%2];"
               :: "r"(dst), "l"((uint64_t)tm), "r"(bar), "r"(c0), "r"(c1) : "memory");
}
__device__ __forceinline__ void tma_3d(uint32_t dst, const CUtensorMap* tm, int c0, int c1, int c2, uint32_t bar) {
  asm volatile("cp.async.bulk.tensor.3d.shared::cluster.global.mbarrier::complete_tx::bytes [%0], [%1, {%3, %4, %5}], [%2];"
               :: "r"(dst), "l"((uint64_t)tm), "r"(bar), "r"(c0), "r"(c1), "r"(c2) : "memory");
}
__device__ __forceinline__ void pdl_wait() { asm volatile("griddepcontrol.wait;" ::: "memory"); }
__device__ __forceinline__ void pdl_launch() { asm volatile("griddepcontrol.launch_dependents;" ::: "memory"); }
__device__ __forceinline__ float ex2(float x) { float y; asm("ex2.approx.ftz.f32 %0, %1;" : "=f"(y) : "f"(x)); return y; }
__device__ __forceinline__ uint32_t pack_bf16(float lo, float hi) {
  uint32_t r; asm("cvt.rn.bf16x2.f32 %0, %1, %2;" : "=r"(r) : "f"(hi), "f"(lo)); return r;
}
__device__ __forceinline__ float bf_lo(uint32_t x) { return __uint_as_float(x << 16); }
__device__ __forceinline__ float bf_hi(uint32_t x) { return __uint_as_float(x & 0xffff0000u); }
__device__ __forceinline__ void stsm4(uint32_t addr, uint32_t r0, uint32_t r1, uint32_t r2, uint32_t r3) {
  asm volatile("stmatrix.sync.aligned.m8n8.x4.shared.b16 [%0], {%1, %2, %3, %4};" :: "r"(addr), "r"(r0), "r"(r1), "r"(r2), "r"(r3) : "memory");
}

__device__ __forceinline__ void wgmma_ss_n160_tb(float (&d)[80], uint64_t descA, uint64_t descB) {
  asm volatile("wgmma.mma_async.sync.aligned.m64n160k16.f32.bf16.bf16 {%0, %1, %2, %3, %4, %5, %6, %7, %8, %9, %10, %11, %12, %13, %14, %15, %16, %17, %18, %19, %20, %21, %22, %23, %24, %25, %26, %27, %28, %29, %30, %31, %32, %33, %34, %35, %36, %37, %38, %39, %40, %41, %42, %43, %44, %45, %46, %47, %48, %49, %50, %51, %52, %53, %54, %55, %56, %57, %58, %59, %60, %61, %62, %63, %64, %65, %66, %67, %68, %69, %70, %71, %72, %73, %74, %75, %76, %77, %78, %79}, %80, %81, 1, 1, 1, 0, 1;\n"
    : "+f"(d[0]), "+f"(d[1]), "+f"(d[2]), "+f"(d[3]), "+f"(d[4]), "+f"(d[5]), "+f"(d[6]), "+f"(d[7]), "+f"(d[8]), "+f"(d[9]), "+f"(d[10]), "+f"(d[11]), "+f"(d[12]), "+f"(d[13]), "+f"(d[14]), "+f"(d[15]), "+f"(d[16]), "+f"(d[17]), "+f"(d[18]), "+f"(d[19]), "+f"(d[20]), "+f"(d[21]), "+f"(d[22]), "+f"(d[23]), "+f"(d[24]), "+f"(d[25]), "+f"(d[26]), "+f"(d[27]), "+f"(d[28]), "+f"(d[29]), "+f"(d[30]), "+f"(d[31]), "+f"(d[32]), "+f"(d[33]), "+f"(d[34]), "+f"(d[35]), "+f"(d[36]), "+f"(d[37]), "+f"(d[38]), "+f"(d[39]), "+f"(d[40]), "+f"(d[41]), "+f"(d[42]), "+f"(d[43]), "+f"(d[44]), "+f"(d[45]), "+f"(d[46]), "+f"(d[47]), "+f"(d[48]), "+f"(d[49]), "+f"(d[50]), "+f"(d[51]), "+f"(d[52]), "+f"(d[53]), "+f"(d[54]), "+f"(d[55]), "+f"(d[56]), "+f"(d[57]), "+f"(d[58]), "+f"(d[59]), "+f"(d[60]), "+f"(d[61]), "+f"(d[62]), "+f"(d[63]), "+f"(d[64]), "+f"(d[65]), "+f"(d[66]), "+f"(d[67]), "+f"(d[68]), "+f"(d[69]), "+f"(d[70]), "+f"(d[71]), "+f"(d[72]), "+f"(d[73]), "+f"(d[74]), "+f"(d[75]), "+f"(d[76]), "+f"(d[77]), "+f"(d[78]), "+f"(d[79])
    : "l"(descA), "l"(descB));
}
__device__ __forceinline__ void wgmma_ss_n48_tb(float (&d)[24], uint64_t descA, uint64_t descB) {
  asm volatile("wgmma.mma_async.sync.aligned.m64n48k16.f32.bf16.bf16 {%0, %1, %2, %3, %4, %5, %6, %7, %8, %9, %10, %11, %12, %13, %14, %15, %16, %17, %18, %19, %20, %21, %22, %23}, %24, %25, 1, 1, 1, 0, 1;\n"
    : "+f"(d[0]), "+f"(d[1]), "+f"(d[2]), "+f"(d[3]), "+f"(d[4]), "+f"(d[5]), "+f"(d[6]), "+f"(d[7]), "+f"(d[8]), "+f"(d[9]), "+f"(d[10]), "+f"(d[11]), "+f"(d[12]), "+f"(d[13]), "+f"(d[14]), "+f"(d[15]), "+f"(d[16]), "+f"(d[17]), "+f"(d[18]), "+f"(d[19]), "+f"(d[20]), "+f"(d[21]), "+f"(d[22]), "+f"(d[23])
    : "l"(descA), "l"(descB));
}
__device__ __forceinline__ void wgmma_ss_n80_tb(float (&d)[40], uint64_t descA, uint64_t descB) {
  asm volatile("wgmma.mma_async.sync.aligned.m64n80k16.f32.bf16.bf16 {%0, %1, %2, %3, %4, %5, %6, %7, %8, %9, %10, %11, %12, %13, %14, %15, %16, %17, %18, %19, %20, %21, %22, %23, %24, %25, %26, %27, %28, %29, %30, %31, %32, %33, %34, %35, %36, %37, %38, %39}, %40, %41, 1, 1, 1, 0, 1;\n"
    : "+f"(d[0]), "+f"(d[1]), "+f"(d[2]), "+f"(d[3]), "+f"(d[4]), "+f"(d[5]), "+f"(d[6]), "+f"(d[7]), "+f"(d[8]), "+f"(d[9]), "+f"(d[10]), "+f"(d[11]), "+f"(d[12]), "+f"(d[13]), "+f"(d[14]), "+f"(d[15]), "+f"(d[16]), "+f"(d[17]), "+f"(d[18]), "+f"(d[19]), "+f"(d[20]), "+f"(d[21]), "+f"(d[22]), "+f"(d[23]), "+f"(d[24]), "+f"(d[25]), "+f"(d[26]), "+f"(d[27]), "+f"(d[28]), "+f"(d[29]), "+f"(d[30]), "+f"(d[31]), "+f"(d[32]), "+f"(d[33]), "+f"(d[34]), "+f"(d[35]), "+f"(d[36]), "+f"(d[37]), "+f"(d[38]), "+f"(d[39])
    : "l"(descA), "l"(descB));
}
template <int SCALE_D>
__device__ __forceinline__ void wgmma_rs_n64(float (&d)[32], uint32_t a0, uint32_t a1, uint32_t a2, uint32_t a3, uint64_t descB) {
  asm volatile("wgmma.mma_async.sync.aligned.m64n64k16.f32.bf16.bf16 {%0, %1, %2, %3, %4, %5, %6, %7, %8, %9, %10, %11, %12, %13, %14, %15, %16, %17, %18, %19, %20, %21, %22, %23, %24, %25, %26, %27, %28, %29, %30, %31}, {%32, %33, %34, %35}, %36, %37, 1, 1, 0;\n"
    : "+f"(d[0]), "+f"(d[1]), "+f"(d[2]), "+f"(d[3]), "+f"(d[4]), "+f"(d[5]), "+f"(d[6]), "+f"(d[7]), "+f"(d[8]), "+f"(d[9]), "+f"(d[10]), "+f"(d[11]), "+f"(d[12]), "+f"(d[13]), "+f"(d[14]), "+f"(d[15]), "+f"(d[16]), "+f"(d[17]), "+f"(d[18]), "+f"(d[19]), "+f"(d[20]), "+f"(d[21]), "+f"(d[22]), "+f"(d[23]), "+f"(d[24]), "+f"(d[25]), "+f"(d[26]), "+f"(d[27]), "+f"(d[28]), "+f"(d[29]), "+f"(d[30]), "+f"(d[31])
    : "r"(a0), "r"(a1), "r"(a2), "r"(a3), "l"(descB), "n"(SCALE_D));
}
template <int SCALE_D>
__device__ __forceinline__ void wgmma_rs_n24_tb(float (&d)[12], uint32_t a0, uint32_t a1, uint32_t a2, uint32_t a3, uint64_t descB) {
  asm volatile("wgmma.mma_async.sync.aligned.m64n24k16.f32.bf16.bf16 {%0, %1, %2, %3, %4, %5, %6, %7, %8, %9, %10, %11}, {%12, %13, %14, %15}, %16, %17, 1, 1, 1;\n"
    : "+f"(d[0]), "+f"(d[1]), "+f"(d[2]), "+f"(d[3]), "+f"(d[4]), "+f"(d[5]), "+f"(d[6]), "+f"(d[7]), "+f"(d[8]), "+f"(d[9]), "+f"(d[10]), "+f"(d[11])
    : "r"(a0), "r"(a1), "r"(a2), "r"(a3), "l"(descB), "n"(SCALE_D));
}

constexpr uint32_t DHI_SW128_K = (1024 >> 4) | (1u << 30);
constexpr uint32_t DHI_SW64_MN = (512 >> 4) | (2u << 30);

template <int NC>
__device__ __forceinline__ void store_tile_bf16(const float (&acc)[NC / 2], float scale, uint32_t stage, uint8_t* stage_ptr,
                                                __nv_bfloat16* gdst, int gpitch, int lane) {
  constexpr int PITCH = NC * 2 + 16;
  const uint32_t waddr = stage + ((lane & 7) + ((lane >> 3) & 1) * 8) * PITCH + (lane >> 4) * 16;
#pragma unroll
  for (int j = 0; j < NC / 16; j++) {
    stsm4(waddr + j * 32, pack_bf16(acc[8 * j] * scale, acc[8 * j + 1] * scale), pack_bf16(acc[8 * j + 2] * scale, acc[8 * j + 3] * scale),
          pack_bf16(acc[8 * j + 4] * scale, acc[8 * j + 5] * scale), pack_bf16(acc[8 * j + 6] * scale, acc[8 * j + 7] * scale));
  }
  __syncwarp();
  constexpr int CPR = NC / 8;
#pragma unroll
  for (int i = 0; i < CPR / 2; i++) {
    const int c = i * 32 + lane, r = c / CPR, cc = c % CPR;
    const uint4 v = *reinterpret_cast<const uint4*>(stage_ptr + r * PITCH + cc * 16);
    *reinterpret_cast<uint4*>(gdst + (size_t)r * gpitch + cc * 8) = v;
  }
}

__device__ __forceinline__ void signal_done(unsigned int* flag, int wg, int tid) {
  asm volatile("bar.sync %0, 128;" :: "r"(wg + 1) : "memory");
  if ((tid & 127) == 0) asm volatile("red.release.gpu.global.add.u32 [%0], 1;" :: "l"(flag) : "memory");
}
__device__ __forceinline__ void wait_flags8(const unsigned int* f, unsigned int target) {
  for (int spin = 0; spin < (1 << 26); spin++) {
    unsigned int a, b, c, d, e, g, h, i;
    asm volatile("ld.volatile.global.v4.u32 {%0, %1, %2, %3}, [%4];" : "=r"(a), "=r"(b), "=r"(c), "=r"(d) : "l"(f) : "memory");
    asm volatile("ld.volatile.global.v4.u32 {%0, %1, %2, %3}, [%4];" : "=r"(e), "=r"(g), "=r"(h), "=r"(i) : "l"(f + 4) : "memory");
    if (min(min(min(a, b), min(c, d)), min(min(e, g), min(h, i))) >= target) break;
    __nanosleep(32);
  }
  asm volatile("fence.acq_rel.gpu;" ::: "memory");
  asm volatile("fence.proxy.async;" ::: "memory");
}

constexpr int K1_STAGES = 4;
constexpr int K1_A_BYTES = 256 * 128;
constexpr int K1_B_BYTES = 64 * 160 * 2;
constexpr int K1_STAGE = K1_A_BYTES + K1_B_BYTES;
constexpr int K1_SMEM = 5 * K1_A_BYTES + 61440 + 1024;
constexpr int KV_STAGES = 5;
constexpr int KVW_OFF = KV_STAGES * K1_A_BYTES;

__global__ void __launch_bounds__(512, 1)
proj_kernel(const __grid_constant__ CUtensorMap tmX, const __grid_constant__ CUtensorMap tmWq, const __grid_constant__ CUtensorMap tmWqkv,
            const __nv_bfloat16* __restrict__ wk, const __nv_bfloat16* __restrict__ wv, const __nv_bfloat16* __restrict__ gate_w,
            const __nv_bfloat16* __restrict__ woA, const __nv_bfloat16* __restrict__ woB) {
  extern __shared__ uint8_t smem_raw[];
  __shared__ __align__(8) uint64_t bar_full[KV_STAGES], bar_empty[KV_STAGES];
  uint8_t* smem = reinterpret_cast<uint8_t*>((reinterpret_cast<uintptr_t>(smem_raw) + 1023) & ~(uintptr_t)1023);
  const uint32_t sbase = smem_u32(smem);
  const uint32_t dbase = sbase & 0x3FFFFu;
  const int tid = threadIdx.x, warp = tid >> 5, lane = tid & 31;
  const bool is_kv = blockIdx.x >= 128;
  PROF(0, 0);
  if (tid == 0) {
    for (int i = 0; i < KV_STAGES; i++) { mbar_init(smem_u32(&bar_full[i]), 1); mbar_init(smem_u32(&bar_empty[i]), is_kv ? 8 : 16); }
    fence_mbar_init();
  }
  uint2 wa[2][5], wb[2][5]; uint32_t gw[2];
  if (is_kv && tid < 320) {
#pragma unroll
    for (int r = 0; r < 2; r++) {
      const int k = tid + r * 320;
      const uint2* pk = reinterpret_cast<const uint2*>(wk + k * 20);
      const uint2* pv = reinterpret_cast<const uint2*>(wv + k * 20);
#pragma unroll
      for (int i = 0; i < 5; i++) { wa[r][i] = __ldg(pk + i); wb[r][i] = __ldg(pv + i); }
      gw[r] = (uint32_t)__bfloat16_as_ushort(gate_w[k]);
    }
  }
  __syncthreads();
  if (tid == 480) {
    if (!is_kv) { g_done[blockIdx.x] = 0u; g_doneL[blockIdx.x] = 0u; }
    asm volatile("fence.acq_rel.gpu;" ::: "memory");
    pdl_launch();
  }
  __syncwarp();

  if (!is_kv) {
    const int mb = blockIdx.x >> 4, nb = blockIdx.x & 15;
    const CUtensorMap* tw = nb < 4 ? &tmWq : &tmWqkv;
    const int j0 = (nb < 4 ? nb : nb - 4) * 5;
    auto load = [&](int kt) {
      const int s = kt % K1_STAGES;
      const uint32_t fb = smem_u32(&bar_full[s]);
      mbar_expect_tx(fb, K1_STAGE);
      tma_2d(sbase + s * K1_STAGE, &tmX, kt * 64, mb * 256, fb);
      tma_3d(sbase + s * K1_STAGE + K1_A_BYTES, tw, 0, kt * 64, j0, fb);
    };
    if (tid == 0) for (int kt = 0; kt < K1_STAGES; kt++) load(kt);
    __syncwarp();
    uint4 wv2[2];
    if (tid >= 112) {
#pragma unroll
      for (int i = 0; i < 2; i++) {
        const int q = blockIdx.x * 800 + (tid - 112) + i * 400;
        const int half = q >= 51200, r = q - half * 51200;
        wv2[i] = __ldg(reinterpret_cast<const uint4*>((half ? woB : woA) + r * 8));
      }
    }
    __syncwarp();
    {
      const int wg = warp >> 2;
      float acc[80];
#pragma unroll
      for (int i = 0; i < 80; i++) acc[i] = 0.f;
      for (int kt = 0; kt < 10; kt++) {
        const int s = kt % K1_STAGES;
        mbar_wait(smem_u32(&bar_full[s]), (kt / K1_STAGES) & 1);
        const uint32_t alo = ((dbase + s * K1_STAGE + wg * 8192) >> 4) | (1u << 16);
        const uint32_t blo = ((dbase + s * K1_STAGE + K1_A_BYTES) >> 4) | ((4096u >> 4) << 16);
        fence_regs(acc);
        wg_fence();
#pragma unroll
        for (int k = 0; k < 4; k++) wgmma_ss_n160_tb(acc, mkd(alo + k * 2, DHI_SW128_K), mkd(blo + k * 64, DHI_SW64_MN));
        wg_commit();
        if (kt > 0 && kt - 1 + K1_STAGES < 10) {
          wg_wait<1>();
          const uint32_t eb = smem_u32(&bar_empty[(kt - 1) % K1_STAGES]);
          if (lane == 0) mbar_arrive(eb);
          if (tid == 0) { mbar_wait(eb, ((kt - 1) / K1_STAGES) & 1); load(kt - 1 + K1_STAGES); }
          __syncwarp();
        }
      }
      wg_wait<0>();
      fence_regs(acc);
      PROF(0, 1);
      if (tid >= 112) {
#pragma unroll
        for (int i = 0; i < 2; i++) {
          const int q = blockIdx.x * 800 + (tid - 112) + i * 400;
          const int half = q >= 51200, r = q - half * 51200;
          const int k = r / 80, ch = r - k * 80, nbo = ch / 10, j = ch - nbo * 10;
          *reinterpret_cast<uint4*>(g_wimg + ((half * 8 + nbo) * 10 + (k >> 6)) * 10240 + j * 1024 + (k & 63) * 16) = wv2[i];
        }
      }
      __syncwarp();
      asm volatile("bar.sync %0, 128;" :: "r"(wg + 1) : "memory");
      const int w4 = warp & 3;
      const uint32_t off = w4 * K1_STAGE + wg * 8192;
      const int row0 = mb * 256 + wg * 64 + w4 * 16;
      if (nb < 4) {
        store_tile_bf16<160>(acc, 0.22360679774997896f * 1.4426950408889634f, sbase + off, smem + off,
                             g_q + (size_t)row0 * D_MODEL + nb * 160, D_MODEL, lane);
      } else {
        store_tile_bf16<160>(acc, 1.0f, sbase + off, smem + off, g_qkv + (size_t)row0 * (3 * D_MODEL) + (nb - 4) * 160, 3 * D_MODEL, lane);
      }
    }
  } else {
    const int cb = blockIdx.x - 128;
    if (warp == 8 && lane == 0) {
      for (int it = 0; it < KV_STAGES; it++) {
        const uint32_t fb = smem_u32(&bar_full[it]);
        mbar_expect_tx(fb, K1_A_BYTES);
        tma_2d(sbase + it * K1_A_BYTES, &tmX, it * 64, cb * 512, fb);
      }
    }
    __syncwarp();
    if (tid < 320) {
#pragma unroll
      for (int r = 0; r < 2; r++) {
        uint4* dst = reinterpret_cast<uint4*>(smem + KVW_OFF + (tid + r * 320) * 16);
        dst[0] = make_uint4(wa[r][0].x, wa[r][0].y, wa[r][1].x, wa[r][1].y);
        dst[640] = make_uint4(wa[r][2].x, wa[r][2].y, wa[r][3].x, wa[r][3].y);
        dst[1280] = make_uint4(wa[r][4].x, wa[r][4].y, 0u, 0u);
        dst[1920] = make_uint4(wb[r][0].x, wb[r][0].y, wb[r][1].x, wb[r][1].y);
        dst[2560] = make_uint4(wb[r][2].x, wb[r][2].y, wb[r][3].x, wb[r][3].y);
        dst[3200] = make_uint4(wb[r][4].x, wb[r][4].y, gw[r], 0u);
      }
    }
    fence_proxy_async();
    asm volatile("bar.sync 1, 512;" ::: "memory");
    PROF(0, 1);
    auto produce = [&](int it0, int it1) {
      for (int it = it0; it < it1; it++) {
        const int s = it % KV_STAGES;
        mbar_wait(smem_u32(&bar_empty[s]), (it / KV_STAGES - 1) & 1);
        const uint32_t fb = smem_u32(&bar_full[s]);
        mbar_expect_tx(fb, K1_A_BYTES);
        tma_2d(sbase + s * K1_A_BYTES, &tmX, (it >= 10 ? it - 10 : it) * 64, cb * 512 + (it >= 10 ? 256 : 0), fb);
      }
    };
    if (tid == 256) produce(KV_STAGES, 15);
    __syncwarp();
    {
      const int pass = warp >> 3, wg = (warp >> 2) & 1, w4 = warp & 3, g = lane >> 2, t = lane & 3;
      if (pass == 1) asm volatile("bar.sync 2, 512;" ::: "memory");
      {
        float acc[2][24];
#pragma unroll
        for (int i = 0; i < 24; i++) { acc[0][i] = 0.f; acc[1][i] = 0.f; }
        for (int kt = 0; kt < 10; kt++) {
          const int it = pass * 10 + kt, s = it % KV_STAGES;
          mbar_wait(smem_u32(&bar_full[s]), (it / KV_STAGES) & 1);
          const uint32_t alo = ((dbase + s * K1_A_BYTES + wg * 16384) >> 4) | (1u << 16);
          const uint32_t blo = ((dbase + KVW_OFF + kt * 1024) >> 4) | ((128u >> 4) << 16);
          fence_regs(acc[0]); fence_regs(acc[1]);
          wg_fence();
#pragma unroll
          for (int k = 0; k < 4; k++) {
            wgmma_ss_n48_tb(acc[0], mkd(alo + k * 2, DHI_SW128_K), mkd(blo + k * 16, 10240u >> 4));
            wgmma_ss_n48_tb(acc[1], mkd(alo + 512 + k * 2, DHI_SW128_K), mkd(blo + k * 16, 10240u >> 4));
          }
          wg_commit();
          if (kt > 0) {
            wg_wait<1>();
            if (lane == 0) mbar_arrive(smem_u32(&bar_empty[(it - 1) % KV_STAGES]));
          }
        }
        wg_wait<0>();
        fence_regs(acc[0]); fence_regs(acc[1]);
        if (lane == 0) mbar_arrive(smem_u32(&bar_empty[(pass * 10 + 9) % KV_STAGES]));
        if (pass == 0) asm volatile("bar.arrive 2, 512;" ::: "memory");
        PROF(0, 2);
        if (tid == 0) produce(15, 20);
        __syncwarp();
        float kmax2 = 0.f, vmax = 0.f;
#pragma unroll
        for (int hh = 0; hh < 4; hh++) {
          const int h = hh & 1;
          const float (&a)[24] = acc[hh >> 1];
          const int key = cb * 512 + pass * 256 + wg * 128 + (hh >> 1) * 64 + w4 * 16 + g + h * 8;
          const int grp = key >> 7, kk = key & 127;
          const bool poly = (TMASK >> (kk >> 3)) & 1;
          uint8_t* gp = g_kvimg + grp * GRP_BYTES;
          const uint32_t k0 = pack_bf16(a[2 * h], a[2 * h + 1]);
          const uint32_t k1 = pack_bf16(a[4 + 2 * h], a[5 + 2 * h]);
          uint32_t k2 = pack_bf16(a[8 + 2 * h], a[9 + 2 * h]);
          float n2 = bf_lo(k0) * bf_lo(k0) + bf_hi(k0) * bf_hi(k0) + bf_lo(k1) * bf_lo(k1) + bf_hi(k1) * bf_hi(k1);
          if (t < 2) {
            n2 += bf_lo(k2) * bf_lo(k2) + bf_hi(k2) * bf_hi(k2);
            k2 = pack_bf16(bf_lo(k2) * 0.5f, bf_hi(k2) * 0.5f);
          } else if (t == 2) k2 = poly ? pack_bf16(24.f, 2.5f) : pack_bf16(0.5f, 0.f);
          else k2 = poly ? pack_bf16(0.5f, 0.f) : 0u;
          *reinterpret_cast<uint32_t*>(gp + kk * 16 + t * 4) = k0;
          *reinterpret_cast<uint32_t*>(gp + PLANE + kk * 16 + t * 4) = k1;
          *reinterpret_cast<uint32_t*>(gp + 2 * PLANE + kk * 16 + t * 4) = k2;
          n2 += __shfl_xor_sync(0xffffffffu, n2, 1);
          n2 += __shfl_xor_sync(0xffffffffu, n2, 2);
          kmax2 = (n2 > kmax2 || n2 != n2) ? n2 : kmax2;
          uint32_t v0 = pack_bf16(a[12 + 2 * h], a[13 + 2 * h]);
          uint32_t v1 = pack_bf16(a[16 + 2 * h], a[17 + 2 * h]);
          uint32_t v2 = pack_bf16(a[20 + 2 * h], a[21 + 2 * h]);
          float vm = fmaxf(fmaxf(fabsf(bf_lo(v0)), fabsf(bf_hi(v0))), fmaxf(fabsf(bf_lo(v1)), fabsf(bf_hi(v1))));
          if (t < 2) vm = fmaxf(vm, fmaxf(fabsf(bf_lo(v2)), fabsf(bf_hi(v2))));
          else if (t == 2) {
            const float z = a[20 + 2 * h];
            g_gate[key] = 1.f / (1.f + __expf(-z));
            v2 = 0x00003F80u;
          } else v2 = 0u;
          vmax = fmaxf(vmax, vm);
          if (poly) { v0 ^= 0x80008000u; v1 ^= 0x80008000u; v2 ^= 0x80008000u; }
          uint8_t* vp = gp + 3 * PLANE + (kk >> 3) * 384 + (kk & 7) * 16 + t * 4;
          *reinterpret_cast<uint32_t*>(vp) = v0;
          *reinterpret_cast<uint32_t*>(vp + 128) = v1;
          *reinterpret_cast<uint32_t*>(vp + 256) = v2;
        }
#pragma unroll
        for (int o = 1; o < 32; o <<= 1) {
          const float a = __shfl_xor_sync(0xffffffffu, kmax2, o);
          kmax2 = (a > kmax2 || a != a) ? a : kmax2;
          vmax = fmaxf(vmax, __shfl_xor_sync(0xffffffffu, vmax, o));
        }
        if (lane == 0) { g_kmax2[cb * 16 + warp] = kmax2; g_vmax[cb * 16 + warp] = vmax; }
      }
    }
  }
}

__device__ __forceinline__ uint32_t ex2_pair_poly(float u0, float u1, uint32_t one2) {
  const uint32_t W = __byte_perm(__float_as_uint(u0), __float_as_uint(u1), 0x6521);
  uint32_t v; asm("lop3.b32 %0, %1, 0x007F007F, %2, 0xEA;" : "=r"(v) : "r"(W), "r"(one2));
  uint32_t L, p;
  asm("fma.rn.bf16x2 %0, %1, %2, %3;" : "=r"(L) : "r"(v), "r"(0x1f961f96u), "r"(0x9fe39fe3u));
  asm("fma.rn.bf16x2 %0, %1, %1, %2;" : "=r"(p) : "r"(L), "r"(0x00f500f5u));
  return W + p;
}
template <int JOFF>
__device__ __forceinline__ void softmax_fast(const float (&S)[32], uint32_t (&P)[16], uint32_t one2) {
#pragma unroll
  for (int i = 0; i < 16; i++) {
    if ((TMASK >> (JOFF + i / 2)) & 1) P[i] = ex2_pair_poly(S[2 * i], S[2 * i + 1], one2);
    else P[i] = pack_bf16(ex2(S[2 * i]), ex2(S[2 * i + 1]));
  }
}
template <int JOFF>
__device__ __forceinline__ void softmax_slow(const float (&S)[32], uint32_t (&P)[16], float (&O)[12], float& m0, float& m1) {
  float a0 = m0, a1 = m1;
#pragma unroll
  for (int j = 0; j < 8; j++) {
    a0 = fmaxf(a0, fmaxf(S[4 * j], S[4 * j + 1]));
    a1 = fmaxf(a1, fmaxf(S[4 * j + 2], S[4 * j + 3]));
  }
  a0 = fmaxf(a0, __shfl_xor_sync(0xffffffffu, a0, 1)); a0 = fmaxf(a0, __shfl_xor_sync(0xffffffffu, a0, 2));
  a1 = fmaxf(a1, __shfl_xor_sync(0xffffffffu, a1, 1)); a1 = fmaxf(a1, __shfl_xor_sync(0xffffffffu, a1, 2));
  const float c0 = ex2(m0 - a0), c1 = ex2(m1 - a1);
  m0 = a0; m1 = a1;
#pragma unroll
  for (int j = 0; j < 3; j++) { O[4 * j] *= c0; O[4 * j + 1] *= c0; O[4 * j + 2] *= c1; O[4 * j + 3] *= c1; }
#pragma unroll
  for (int i = 0; i < 16; i++) {
    const float m = (i & 1) ? a1 : a0;
    const uint32_t p = pack_bf16(ex2(S[2 * i] - m), ex2(S[2 * i + 1] - m));
    P[i] = ((TMASK >> (JOFF + i / 2)) & 1) ? (p ^ 0x80008000u) : p;
  }
}
constexpr uint32_t DHI_KV = 128 >> 4;
__device__ __forceinline__ void issue_qk(float (&S)[32], const uint32_t (&q)[8], uint64_t base) {
  wgmma_rs_n64<0>(S, q[0], q[1], q[2], q[3], base + (uint64_t)((PLANE >> 4) << 16));
  wgmma_rs_n64<1>(S, q[4], q[5], q[6], q[7], base + (uint64_t)(2 * PLANE >> 4));
}
__device__ __forceinline__ void issue_pv(float (&O)[12], const uint32_t (&P)[16], uint64_t vbase) {
#pragma unroll
  for (int kk = 0; kk < 4; kk++)
    wgmma_rs_n24_tb<1>(O, P[4 * kk], P[4 * kk + 1], P[4 * kk + 2], P[4 * kk + 3], vbase + (uint64_t)(kk * (768 >> 4)));
}

constexpr uint32_t VOFF = ((3 * PLANE) >> 4) + ((384u >> 4) << 16);
constexpr int KVR = 4;
constexpr int OFF_WA = KVR * GRP_BYTES;
constexpr int OFF_BR = OFF_WA + 10 * 10240;
constexpr int BR_STAGE = 8192 + 10240, BR_STAGES = 3;
constexpr int OFF_QS = OFF_BR + BR_STAGES * BR_STAGE;
constexpr int OFF_BAR = OFF_QS + 512 * 6 * 4;
constexpr int K2_SMEM = OFF_BAR + 256 + 1024;
constexpr int BAR_KV = 0, BAR_WA = 4, BAR_BR = 5, BAR_TA = 8, BAR_TE = 14, BAR_OWN = 18, CNT_KV = 19;
constexpr int NSTEP = 2 * NGRP;

__device__ __forceinline__ void kv_load(uint32_t sbase, int step) {
  const uint32_t bar = sbase + OFF_BAR + (BAR_KV + (step & (KVR - 1))) * 8;
  mbar_expect_tx(bar, GRP_BYTES);
  bulk_g2s(sbase + (step & (KVR - 1)) * GRP_BYTES, g_kvimg + (step & (NGRP - 1)) * GRP_BYTES, GRP_BYTES, bar);
}
__device__ __forceinline__ void kv_release(uint32_t sbase, int step, bool elected) {
  if (elected && step + KVR < NSTEP) {
    uint32_t old;
    asm volatile("atom.acq_rel.cta.shared::cta.inc.u32 %0, [%1], 3;" : "=r"(old) : "r"(sbase + OFF_BAR + CNT_KV * 8 + (step & (KVR - 1)) * 4) : "memory");
    if (old == 3u) kv_load(sbase, step + KVR);
  }
  __syncwarp();
}
__device__ __forceinline__ void kv_wait(uint32_t sbase, int step) {
  mbar_wait(sbase + OFF_BAR + (BAR_KV + (step & (KVR - 1))) * 8, (step / KVR) & 1);
}

__device__ __forceinline__ uint32_t kv_release_begin(uint32_t sbase, int slot, bool doit) {
  uint32_t old = 0;
  asm volatile("{\n.reg .pred p;\nsetp.ne.u32 p, %2, 0;\n@p atom.relaxed.cta.shared::cta.inc.u32 %0, [%1], 3;\n}\n"
               : "+r"(old) : "r"(sbase + OFF_BAR + CNT_KV * 8 + slot * 4), "r"((uint32_t)doit) : "memory");
  return old;
}
__device__ __forceinline__ void attn_tile_fast(const uint32_t (&q)[8], float (&O)[12], uint32_t sbase, int step0, bool elected, uint32_t one2) {
  float S[32]; uint32_t P[16];
#pragma unroll
  for (int i = 0; i < 32; i++) S[i] = 0.f;
  uint64_t kb0 = mkd((sbase & 0x3FFFFu) >> 4, DHI_KV);
  asm volatile("" : "+l"(kb0));
  kv_wait(sbase, step0);
  fence_regs(S); fence_regs(O);
  wg_fence();
  issue_qk(S, q, kb0);
  wg_commit();
#pragma unroll 1
  for (int step4 = step0; step4 < step0 + NGRP; step4 += KVR) {
#pragma unroll
    for (int j = 0; j < KVR; j++) {
      const int step = step4 + j;
      const uint64_t kb = kb0 + (uint64_t)(j * (GRP_BYTES >> 4));
      const uint64_t knext = kb0 + (uint64_t)(((j + 1) & (KVR - 1)) * (GRP_BYTES >> 4));
      wg_wait<0>();
      fence_regs(S); fence_regs(P); fence_regs(O);
      const uint32_t old = kv_release_begin(sbase, (j + KVR - 1) & (KVR - 1), elected && step > step0 && step - 1 + KVR < NSTEP);
      softmax_fast<0>(S, P, one2);
      fence_regs(S); fence_regs(P); fence_regs(O);
      wg_fence();
      issue_qk(S, q, kb + 64);
      issue_pv(O, P, kb + VOFF);
      wg_commit();
      if (step + 1 < NSTEP) mbar_wait(sbase + OFF_BAR + (BAR_KV + ((j + 1) & (KVR - 1))) * 8, ((step + 1) / KVR) & 1);
      wg_wait<0>();
      fence_regs(S); fence_regs(P); fence_regs(O);
      softmax_fast<8>(S, P, one2);
      fence_regs(S); fence_regs(P); fence_regs(O);
      wg_fence();
      issue_qk(S, q, knext);
      issue_pv(O, P, kb + VOFF + 4 * (768 >> 4));
      wg_commit();
      if (old == 3u) kv_load(sbase, step - 1 + KVR);
    }
  }
  wg_wait<0>();
  fence_regs(O); fence_regs(S);
  kv_release(sbase, step0 + NGRP - 1, elected);
}
template <int H>
__device__ __forceinline__ void slow_step(const uint32_t (&q)[8], float (&O)[12], uint64_t kb, float& m0, float& m1) {
  float S[32]; uint32_t P[16];
#pragma unroll
  for (int i = 0; i < 32; i++) S[i] = 0.f;
  fence_regs(S);
  wg_fence();
  issue_qk(S, q, kb + 64 * H);
  wg_commit();
  wg_wait<0>();
  fence_regs(S);
  softmax_slow<8 * H>(S, P, O, m0, m1);
  fence_regs(P); fence_regs(O);
  wg_fence();
  issue_pv(O, P, kb + VOFF + H * 4 * (768 >> 4));
  wg_commit();
  wg_wait<0>();
  fence_regs(O); fence_regs(P);
}
__device__ __forceinline__ void attn_tile_slow(const uint32_t (&q)[8], float (&O)[12], uint32_t sbase, int step0, bool elected) {
  float m0 = -INFINITY, m1 = -INFINITY;
#pragma unroll 1
  for (int grp = 0; grp < NGRP; grp++) {
    kv_wait(sbase, step0 + grp);
    const uint64_t kb = mkd(((sbase & 0x3FFFFu) >> 4) + (grp & (KVR - 1)) * (GRP_BYTES >> 4), DHI_KV);
    slow_step<0>(q, O, kb, m0, m1);
    slow_step<1>(q, O, kb, m0, m1);
    kv_release(sbase, step0 + grp, elected);
  }
}

__device__ __forceinline__ void load_row20(const __nv_bfloat16* p, float (&f)[20]) {
  const uint2* p2 = reinterpret_cast<const uint2*>(p);
#pragma unroll
  for (int i = 0; i < 5; i++) { const uint2 v = p2[i]; f[4 * i] = bf_lo(v.x); f[4 * i + 1] = bf_hi(v.x); f[4 * i + 2] = bf_lo(v.y); f[4 * i + 3] = bf_hi(v.y); }
}
__device__ __forceinline__ void softmax8(float (&sc)[8]) {
  float mx = sc[0];
#pragma unroll
  for (int w = 1; w < 8; w++) mx = fmaxf(mx, sc[w]);
  float l = 0.f;
#pragma unroll
  for (int w = 0; w < 8; w++) { sc[w] = ex2(sc[w] - mx); l += sc[w]; }
  const float r = 1.f / l;
#pragma unroll
  for (int w = 0; w < 8; w++) sc[w] *= r;
}
__device__ __forceinline__ void local_attn_pair(int t, int lane) {
  constexpr int PITCH = 3 * D_MODEL;
  constexpr float SC = 0.22360679774997896f * 1.4426950408889634f, NEG = -1e9f * 1.4426950408889634f;
  const __nv_bfloat16* base = g_qkv + lane * DH;
  float a[20], b[20], sa[8], sb[8];
  load_row20(base + (size_t)t * PITCH, a);
  load_row20(base + (size_t)(t + 2) * PITCH, b);
#pragma unroll
  for (int j = 0; j < 9; j++) {
    const int r = t + 2 - 2 * j;
    float k[20];
    load_row20(base + D_MODEL + (size_t)max(r, 0) * PITCH, k);
    float da = 0.f, db = 0.f;
#pragma unroll
    for (int i = 0; i < 20; i++) { if (j >= 1) da = fmaf(a[i], k[i], da); if (j < 8) db = fmaf(b[i], k[i], db); }
    if (j >= 1) sa[j - 1] = r >= 0 ? da * SC : NEG;
    if (j < 8) sb[j] = r >= 0 ? db * SC : NEG;
  }
  softmax8(sa); softmax8(sb);
#pragma unroll
  for (int i = 0; i < 20; i++) { a[i] = 0.f; b[i] = 0.f; }
#pragma unroll
  for (int j = 0; j < 9; j++) {
    const int r = t + 2 - 2 * j;
    float v[20];
    load_row20(base + 2 * D_MODEL + (size_t)max(r, 0) * PITCH, v);
#pragma unroll
    for (int i = 0; i < 20; i++) { if (j >= 1) a[i] = fmaf(sa[j - 1], v[i], a[i]); if (j < 8) b[i] = fmaf(sb[j], v[i], b[i]); }
  }
  const float ga = 1.f - g_gate[t], gb = 1.f - g_gate[t + 2];
  uint2* da = reinterpret_cast<uint2*>(g_a2 + (size_t)t * (2 * D_MODEL) + D_MODEL + lane * DH);
  uint2* db = da + 2 * (2 * D_MODEL) / 4;
#pragma unroll
  for (int i = 0; i < 5; i++) {
    da[i] = make_uint2(pack_bf16(a[4 * i] * ga, a[4 * i + 1] * ga), pack_bf16(a[4 * i + 2] * ga, a[4 * i + 3] * ga));
    db[i] = make_uint2(pack_bf16(b[4 * i] * gb, b[4 * i + 1] * gb), pack_bf16(b[4 * i + 2] * gb, b[4 * i + 3] * gb));
  }
}
__device__ __forceinline__ uint32_t ta_slot(int i) { return i < 3 ? i * 16384 : OFF_BR + (i - 3) * 16384; }

__global__ void __launch_bounds__(640, 1)
attn_kernel(const __grid_constant__ CUtensorMap tmA2, const __grid_constant__ CUtensorMap tmA2b,
            __nv_bfloat16* __restrict__ out, uint32_t one2) {
  extern __shared__ uint8_t smem_raw[];
  uint8_t* smem = reinterpret_cast<uint8_t*>((reinterpret_cast<uintptr_t>(smem_raw) + 1023) & ~(uintptr_t)1023);
  const uint32_t sbase = smem_u32(smem);
  const uint32_t dbase = sbase & 0x3FFFFu;
  const uint32_t bars = sbase + OFF_BAR;
  const int tid = threadIdx.x, wg = tid >> 7, warp = (tid >> 5) & 3, lane = tid & 31, g = lane >> 2, t = lane & 3;
  const int mb = blockIdx.x >> 3, nb = blockIdx.x & 7;
  if (tid == 0) {
    for (int i = 0; i < BAR_TE; i++) mbar_init(bars + i * 8, 1);
    for (int i = BAR_TE; i < BAR_TE + 4; i++) mbar_init(bars + i * 8, 8);
    mbar_init(bars + BAR_OWN * 8, 4);
    for (int i = 0; i < 4; i++) *reinterpret_cast<uint32_t*>(smem + OFF_BAR + CNT_KV * 8 + i * 4) = 0u;
    fence_mbar_init();
  }
  __syncthreads();
  if (wg == 4) {
    pdl_wait();
    asm volatile("bar.sync 7, 640;" ::: "memory");
#pragma unroll 1
    for (int i = 0; i < 2; i++) local_attn_pair(blockIdx.x * 16 + warp * 4 + i, lane);
    if (tid == 512) PROF2(0, 2);
    signal_done(&g_doneL[blockIdx.x], wg, tid);
    if (tid == 512) {
      mbar_expect_tx(bars + BAR_WA * 8, 10 * 10240);
      for (int i = 0; i < 5; i++) bulk_g2s(sbase + OFF_WA + i * 20480, g_wimg + (nb * 10) * 10240 + i * 20480, 20480, bars + BAR_WA * 8);
    }
    auto br_load = [&](int it, int st) {
      const uint32_t fb = bars + (BAR_BR + st) * 8;
      const uint32_t dst = sbase + OFF_BR + st * BR_STAGE;
      const int kc = (it >= 10 ? it - 10 : it) * 64;
      mbar_expect_tx(fb, BR_STAGE);
      tma_2d(dst, &tmA2, D_MODEL + kc, (blockIdx.x >> 3) * 128 + (it >= 10 ? 64 : 0), fb);
      bulk_g2s(dst + 8192, g_wimg + ((8 + (blockIdx.x & 7)) * 10 + (kc >> 6)) * 10240, 10240, fb);
    };
    if (tid == 512) {
      wait_flags8(&g_doneL[mb * 8], 1u);
      for (int it = 0; it < BR_STAGES; it++) br_load(it, it);
    }
    __syncwarp();
    {
      int st = 0, ph = 0;
      float acc[40];
#pragma unroll 1
      for (int it = 0; it < 20; it++) {
        if (it == 0 || it == 10) {
#pragma unroll
          for (int i = 0; i < 40; i++) acc[i] = 0.f;
        }
        mbar_wait(bars + (BAR_BR + st) * 8, ph);
        const uint32_t alo = ((dbase + OFF_BR + st * BR_STAGE) >> 4);
        fence_regs(acc);
        wg_fence();
#pragma unroll
        for (int k = 0; k < 4; k++)
          wgmma_ss_n80_tb(acc, mkd(alo + (k * 2 + (1u << 16)), DHI_SW128_K), mkd(alo + (512 + k * 16 + ((128u >> 4) << 16)), 1024u >> 4));
        wg_commit();
        wg_wait<0>();
        fence_regs(acc);
        asm volatile("bar.sync 5, 128;" ::: "memory");
        if (threadIdx.x == 512 && it + BR_STAGES < 20) br_load(it + BR_STAGES, st);
        __syncwarp();
        if (it == 9 || it == 19) {
          float* pp = g_part + (size_t)(blockIdx.x * 2 + (it == 19)) * (40 * 128) + (threadIdx.x & 127);
#pragma unroll
          for (int i = 0; i < 40; i++) pp[i * 128] = acc[i];
        }
        if (++st == BR_STAGES) { st = 0; ph ^= 1; }
      }
    }
    if (tid == 512) PROF2(1, 0);
    asm volatile("bar.arrive 6, 384;" ::: "memory");
    if (tid == 512) {
      mbar_wait(bars + BAR_OWN * 8, 0);
      wait_flags8(&g_done[mb * 8], 4u);
      PROF2(2, 0);
    }
    if (tid == 512) {
      for (int kt = 0; kt < 10; kt++) {
        const int sl = kt % 6;
        if (kt >= 6) mbar_wait(bars + (BAR_TE + kt - 6) * 8, 0);
        const uint32_t fb = bars + (BAR_TA + sl) * 8;
        mbar_expect_tx(fb, 16384);
        tma_2d(sbase + ta_slot(sl), &tmA2b, kt * 64, mb * 128, fb);
      }
    }
  } else {
    const bool elected = (tid & 127) == 0;
    pdl_wait();
    PROF(1, 1);
    if (tid == 384) for (int j = 0; j < KVR; j++) kv_load(sbase, j);
    __syncwarp();
    uint32_t q[8];
    uint32_t* qstash = reinterpret_cast<uint32_t*>(smem + OFF_QS) + tid;
    const int rowA = (blockIdx.x * 8 + wg) * 64 + warp * 16 + g;
    {
      const uint32_t* r0 = reinterpret_cast<const uint32_t*>(g_q + (size_t)rowA * DH);
      const uint32_t* r1 = r0 + 8 * (DH / 2);
      const uint32_t* s0 = r0 + 256 * (DH / 2);
      const uint32_t* s1 = s0 + 8 * (DH / 2);
      q[0] = r0[t]; q[1] = r1[t]; q[2] = r0[t + 4]; q[3] = r1[t + 4];
      q[4] = t < 2 ? r0[8 + t] : 0u;
      q[5] = t < 2 ? r1[8 + t] : 0u;
      qstash[0] = s0[t]; qstash[512] = s1[t]; qstash[1024] = s0[t + 4]; qstash[1536] = s1[t + 4];
      qstash[2048] = t < 2 ? s0[8 + t] : 0u;
      qstash[2560] = t < 2 ? s1[8 + t] : 0u;
    }
    float kmax2 = 0.f, vmax = 0.f;
#pragma unroll
    for (int i = 0; i < 2; i++) {
      const float a = g_kmax2[lane + 32 * i];
      kmax2 = (a > kmax2 || a != a) ? a : kmax2;
      vmax = fmaxf(vmax, g_vmax[lane + 32 * i]);
    }
#pragma unroll
    for (int o = 1; o < 32; o <<= 1) {
      const float a = __shfl_xor_sync(0xffffffffu, kmax2, o);
      kmax2 = (a > kmax2 || a != a) ? a : kmax2;
      vmax = fmaxf(vmax, __shfl_xor_sync(0xffffffffu, vmax, o));
    }
    const float qlim = (vmax >= 0.00390625f && vmax <= 256.f) ? 9025.f / kmax2 : -1.f;
    asm volatile("bar.arrive 7, 640;" ::: "memory");
    PROF(1, 2);
#pragma unroll 1
    for (int it = 0; it < 2; it++) {
      const int row0 = rowA + it * 256;
      if (it == 1) {
#pragma unroll
        for (int i = 0; i < 6; i++) q[i] = qstash[512 * i];
      }
      float n0 = bf_lo(q[0]) * bf_lo(q[0]) + bf_hi(q[0]) * bf_hi(q[0]) + bf_lo(q[2]) * bf_lo(q[2]) + bf_hi(q[2]) * bf_hi(q[2]) +
                 bf_lo(q[4]) * bf_lo(q[4]) + bf_hi(q[4]) * bf_hi(q[4]);
      float n1 = bf_lo(q[1]) * bf_lo(q[1]) + bf_hi(q[1]) * bf_hi(q[1]) + bf_lo(q[3]) * bf_lo(q[3]) + bf_hi(q[3]) * bf_hi(q[3]) +
                 bf_lo(q[5]) * bf_lo(q[5]) + bf_hi(q[5]) * bf_hi(q[5]);
      n0 += __shfl_xor_sync(0xffffffffu, n0, 1); n0 += __shfl_xor_sync(0xffffffffu, n0, 2);
      n1 += __shfl_xor_sync(0xffffffffu, n1, 1); n1 += __shfl_xor_sync(0xffffffffu, n1, 2);
      const bool safe = (n0 <= qlim) && (n1 <= qlim);
      uint32_t unsafe_any;
      asm volatile("{\n.reg .pred p, r;\nsetp.eq.u32 p, %1, 0;\nbarrier.cta.red.or.pred r, %2, 128, p;\nselp.u32 %0, 1, 0, r;\n}\n"
                   : "=r"(unsafe_any) : "r"((uint32_t)safe), "r"(wg + 1) : "memory");
      float O[12];
#pragma unroll
      for (int i = 0; i < 12; i++) O[i] = 0.f;
      if (!unsafe_any && t >= 2) { q[4] = q[5] = (t == 2) ? 0x3F804100u : 0x00003B80u; }
      q[6] = q[4]; q[7] = q[5];
      fence_regs(q);
      if (!unsafe_any) attn_tile_fast(q, O, sbase, it * NGRP, elected, one2);
      else attn_tile_slow(q, O, sbase, it * NGRP, elected);
      const float l0 = __shfl_sync(0xffffffffu, O[8], (lane & ~3) | 2);
      const float l1 = __shfl_sync(0xffffffffu, O[10], (lane & ~3) | 2);
      const int tok = row0 >> 5;
      const float gt = g_gate[tok];
      const float i0 = gt / l0, i1 = gt / l1;
      uint32_t* o0 = reinterpret_cast<uint32_t*>(g_a2 + (size_t)tok * (2 * D_MODEL) + (row0 & 31) * DH);
      uint32_t* o1 = o0 + 8 * (DH / 2);
      o0[t] = pack_bf16(O[0] * i0, O[1] * i0); o1[t] = pack_bf16(O[2] * i1, O[3] * i1);
      o0[t + 4] = pack_bf16(O[4] * i0, O[5] * i0); o1[t + 4] = pack_bf16(O[6] * i1, O[7] * i1);
      if (t < 2) { o0[t + 8] = pack_bf16(O[8] * i0, O[9] * i0); o1[t + 8] = pack_bf16(O[10] * i1, O[11] * i1); }
    }
    signal_done(&g_done[blockIdx.x], wg, tid);
    if (elected) mbar_arrive(bars + BAR_OWN * 8);
    PROF(1, 3);
    if (wg < 2) {
      float acc[40];
      asm volatile("bar.sync 6, 384;" ::: "memory");
      {
        const float* pp = g_part + (size_t)(blockIdx.x * 2 + wg) * (40 * 128) + (tid & 127);
#pragma unroll
        for (int i = 0; i < 40; i++) acc[i] = pp[i * 128];
      }
      mbar_wait(bars + BAR_WA * 8, 0);
#pragma unroll 1
      for (int kt = 0; kt < 10; kt++) {
        const int sl = kt % 6;
        mbar_wait(bars + (BAR_TA + sl) * 8, kt / 6);
        if (kt == 0) PROF(2, 1);
        const uint32_t alo = ((dbase + ta_slot(sl) + wg * 8192) >> 4) | (1u << 16);
        const uint32_t blo = ((dbase + OFF_WA + kt * 10240) >> 4) | ((128u >> 4) << 16);
        fence_regs(acc);
        wg_fence();
#pragma unroll
        for (int k = 0; k < 4; k++) wgmma_ss_n80_tb(acc, mkd(alo + k * 2, DHI_SW128_K), mkd(blo + k * 16, 1024u >> 4));
        wg_commit();
        if (kt < 4) {
          wg_wait<0>();
          if (lane == 0) mbar_arrive(bars + (BAR_TE + kt) * 8);
        }
      }
      wg_wait<0>();
      fence_regs(acc);
      PROF(2, 2);
      asm volatile("bar.sync %0, 128;" :: "r"(wg + 1) : "memory");
      const uint32_t so = ta_slot(warp) + wg * 8192;
      const int row0 = mb * 128 + wg * 64 + warp * 16;
      store_tile_bf16<80>(acc, 1.0f, sbase + so, smem + so, out + (size_t)row0 * D_MODEL + nb * 80, D_MODEL, lane);
      PROF(2, 3);
    }
  }
}

typedef CUresult (*EncodeFn)(CUtensorMap*, CUtensorMapDataType, cuuint32_t, void*, const cuuint64_t*, const cuuint64_t*,
                             const cuuint32_t*, const cuuint32_t*, CUtensorMapInterleave, CUtensorMapSwizzle,
                             CUtensorMapL2promotion, CUtensorMapFloatOOBfill);

void make_map(EncodeFn fn, CUtensorMap* tm, const void* ptr, int rank, const cuuint64_t* dims, const cuuint64_t* strides,
              const cuuint32_t* box, CUtensorMapSwizzle sw) {
  const cuuint32_t es[3] = {1, 1, 1};
  fn(tm, CU_TENSOR_MAP_DATA_TYPE_BFLOAT16, rank, const_cast<void*>(ptr), dims, strides, box, es, CU_TENSOR_MAP_INTERLEAVE_NONE, sw,
     CU_TENSOR_MAP_L2_PROMOTION_L2_256B, CU_TENSOR_MAP_FLOAT_OOB_FILL_NONE);
}
void map_a(EncodeFn fn, CUtensorMap* tm, const void* p, int rows, int cols, int box_rows) {
  const cuuint64_t dims[2] = {(cuuint64_t)cols, (cuuint64_t)rows};
  const cuuint64_t str[1] = {(cuuint64_t)cols * 2};
  const cuuint32_t box[2] = {64, (cuuint32_t)box_rows};
  make_map(fn, tm, p, 2, dims, str, box, CU_TENSOR_MAP_SWIZZLE_128B);
}
void map_w(EncodeFn fn, CUtensorMap* tm, const void* p, int K, int N, int atom, CUtensorMapSwizzle sw) {
  const cuuint64_t dims[3] = {(cuuint64_t)atom, (cuuint64_t)K, (cuuint64_t)(N / atom)};
  const cuuint64_t str[2] = {(cuuint64_t)N * 2, (cuuint64_t)atom * 2};
  const cuuint32_t box[3] = {(cuuint32_t)atom, 64, 5};
  make_map(fn, tm, p, 3, dims, str, box, sw);
}

template <typename... KArgs, typename... Args>
void launch(void (*kern)(KArgs...), int grid, int block, int smem, bool pdl, Args... args) {
  cudaLaunchConfig_t cfg = {};
  cfg.gridDim = dim3(grid); cfg.blockDim = dim3(block); cfg.dynamicSmemBytes = smem; cfg.stream = cudaStreamPerThread;
  cudaLaunchAttribute at[1];
  at[0].id = cudaLaunchAttributeProgrammaticStreamSerialization;
  at[0].val.programmaticStreamSerializationAllowed = 1;
  cfg.attrs = at; cfg.numAttrs = pdl ? 1 : 0;
  cudaLaunchKernelEx(&cfg, kern, KArgs(args)...);
}

}

extern "C" void kernel_launch(void* const* d_in, const int* in_sizes, int n_in, void* d_out, int out_size) {
  (void)in_sizes; (void)n_in; (void)out_size;
  const __nv_bfloat16* x = (const __nv_bfloat16*)d_in[0];
  const __nv_bfloat16* wq = (const __nv_bfloat16*)d_in[1];
  const __nv_bfloat16* wk = (const __nv_bfloat16*)d_in[2];
  const __nv_bfloat16* wv = (const __nv_bfloat16*)d_in[3];
  const __nv_bfloat16* woA = (const __nv_bfloat16*)d_in[4];
  const __nv_bfloat16* wqkv = (const __nv_bfloat16*)d_in[6];
  const __nv_bfloat16* woB = (const __nv_bfloat16*)d_in[7];
  const __nv_bfloat16* gate_w = (const __nv_bfloat16*)d_in[8];

  static EncodeFn enc = nullptr;
  static void* a2_ptr = nullptr;
  if (!enc) {
    void* fp = nullptr;
    cudaDriverEntryPointQueryResult qr;
    cudaGetDriverEntryPoint("cuTensorMapEncodeTiled", &fp, cudaEnableDefault, &qr);
    enc = (EncodeFn)fp;
    cudaGetSymbolAddress(&a2_ptr, g_a2);
    cudaFuncSetAttribute(proj_kernel, cudaFuncAttributeMaxDynamicSharedMemorySize, K1_SMEM);
    cudaFuncSetAttribute(attn_kernel, cudaFuncAttributeMaxDynamicSharedMemorySize, K2_SMEM);
  }
  CUtensorMap tmX, tmWq, tmWqkv, tmA2, tmA2b;
  map_a(enc, &tmX, x, S_LEN, D_MODEL, 256);
  map_w(enc, &tmWq, wq, D_MODEL, D_MODEL, 32, CU_TENSOR_MAP_SWIZZLE_64B);
  map_w(enc, &tmWqkv, wqkv, D_MODEL, 3 * D_MODEL, 32, CU_TENSOR_MAP_SWIZZLE_64B);
  map_a(enc, &tmA2, a2_ptr, S_LEN, 2 * D_MODEL, 64);
  map_a(enc, &tmA2b, a2_ptr, S_LEN, 2 * D_MODEL, 128);

  launch(proj_kernel, 132, 512, K1_SMEM, false, tmX, tmWq, tmWqkv, wk, wv, gate_w, woA, woB);
  launch(attn_kernel, 128, 640, K2_SMEM, true, tmA2, tmA2b, (__nv_bfloat16*)d_out, 0x3F803F80u);
}
```

```cpp
#include <cuda_runtime.h>
#include <cuda_bf16.h>
#include <cuda.h>
#include <stdint.h>

namespace {

constexpr int S_LEN = 2048, D_MODEL = 640, DH = 20;

constexpr int GRP = 128;
constexpr int PLANE = GRP * 16;
constexpr int GRP_BYTES = GRP * 16 * 6;
constexpr int NGRP = S_LEN / GRP;
#define TMASKV 0x6DB6u
constexpr uint32_t TMASK = TMASKV;

__device__ __align__(1024) __nv_bfloat16 g_q[S_LEN * D_MODEL];
__device__ __align__(1024) __nv_bfloat16 g_qkv[S_LEN * 3 * D_MODEL];
__device__ __align__(1024) __nv_bfloat16 g_a2[S_LEN * 2 * D_MODEL];
__device__ __align__(1024) uint8_t g_kvimg[NGRP * GRP_BYTES];
__device__ __align__(1024) uint8_t g_wimg[2 * 8 * 10 * 10240];
__device__ float g_gate[S_LEN];
__device__ float g_kmax2[64];
__device__ float g_vmax[64];
__device__ __align__(32) unsigned int g_doneL[128];
__device__ float g_part[128 * 2 * 40 * 128];
__device__ __align__(32) unsigned int g_done[128];

#define PROF(k, slot)
#define PROF2(k, slot)
__device__ __forceinline__ uint32_t smem_u32(const void* p) { return (uint32_t)__cvta_generic_to_shared(p); }
__device__ __forceinline__ uint64_t mkd(uint32_t lo, uint32_t hi) {
  uint64_t d; asm("mov.b64 %0, {%1, %2};" : "=l"(d) : "r"(lo), "r"(hi)); return d;
}
__device__ __forceinline__ void wg_fence() { asm volatile("wgmma.fence.sync.aligned;" ::: "memory"); }
__device__ __forceinline__ void wg_commit() { asm volatile("wgmma.commit_group.sync.aligned;" ::: "memory"); }
template <int N> __device__ __forceinline__ void wg_wait() { asm volatile("wgmma.wait_group.sync.aligned %0;" :: "n"(N) : "memory"); }
template <int N> __device__ __forceinline__ void fence_regs(float (&d)[N]) {
#pragma unroll
  for (int i = 0; i < N; i++) asm volatile("" : "+f"(d[i]) :: "memory");
}
template <int N> __device__ __forceinline__ void fence_regs(uint32_t (&d)[N]) {
#pragma unroll
  for (int i = 0; i < N; i++) asm volatile("" : "+r"(d[i]) :: "memory");
}
__device__ __forceinline__ void mbar_init(uint32_t bar, uint32_t cnt) { asm volatile("mbarrier.init.shared::cta.b64 [%0], %1;" :: "r"(bar), "r"(cnt)); }
__device__ __forceinline__ void mbar_expect_tx(uint32_t bar, uint32_t bytes) {
  asm volatile("mbarrier.arrive.expect_tx.shared::cta.b64 _, [%0], %1;" :: "r"(bar), "r"(bytes) : "memory");
}
__device__ __forceinline__ void mbar_arrive(uint32_t bar) { asm volatile("mbarrier.arrive.shared::cta.b64 _, [%0];" :: "r"(bar) : "memory"); }
__device__ __forceinline__ void mbar_wait(uint32_t bar, uint32_t parity) {
  asm volatile("{\n.reg .pred p;\nWAIT_%=:\nmbarrier.try_wait.parity.shared::cta.b64 p, [%0], %1;\n@p bra DONE_%=;\nbra WAIT_%=;\nDONE_%=:\n}\n"
               :: "r"(bar), "r"(parity) : "memory");
}
__device__ __forceinline__ void fence_mbar_init() { asm volatile("fence.mbarrier_init.release.cluster;" ::: "memory"); }
__device__ __forceinline__ void fence_proxy_async() { asm volatile("fence.proxy.async.shared::cta;" ::: "memory"); }
__device__ __forceinline__ void bulk_g2s(uint32_t dst, const void* src, uint32_t bytes, uint32_t bar) {
  asm volatile("cp.async.bulk.shared::cluster.global.mbarrier::complete_tx::bytes [%0], [%1], %2, [%3];"
               :: "r"(dst), "l"(src), "r"(bytes), "r"(bar) : "memory");
}
__device__ __forceinline__ void tma_2d(uint32_t dst, const CUtensorMap* tm, int c0, int c1, uint32_t bar) {
  asm volatile("cp.async.bulk.tensor.2d.shared::cluster.global.mbarrier::complete_tx::bytes [%0], [%1, {%3, %4}], [%2];"
               :: "r"(dst), "l"((uint64_t)tm), "r"(bar), "r"(c0), "r"(c1) : "memory");
}
__device__ __forceinline__ void tma_3d(uint32_t dst, const CUtensorMap* tm, int c0, int c1, int c2, uint32_t bar) {
  asm volatile("cp.async.bulk.tensor.3d.shared::cluster.global.mbarrier::complete_tx::bytes [%0], [%1, {%3, %4, %5}], [%2];"
               :: "r"(dst), "l"((uint64_t)tm), "r"(bar), "r"(c0), "r"(c1), "r"(c2) : "memory");
}
__device__ __forceinline__ void pdl_wait() { asm volatile("griddepcontrol.wait;" ::: "memory"); }
__device__ __forceinline__ void pdl_launch() { asm volatile("griddepcontrol.launch_dependents;" ::: "memory"); }
__device__ __forceinline__ float ex2(float x) { float y; asm("ex2.approx.ftz.f32 %0, %1;" : "=f"(y) : "f"(x)); return y; }
__device__ __forceinline__ uint32_t pack_bf16(float lo, float hi) {
  uint32_t r; asm("cvt.rn.bf16x2.f32 %0, %1, %2;" : "=r"(r) : "f"(hi), "f"(lo)); return r;
}
__device__ __forceinline__ float bf_lo(uint32_t x) { return __uint_as_float(x << 16); }
__device__ __forceinline__ float bf_hi(uint32_t x) { return __uint_as_float(x & 0xffff0000u); }
__device__ __forceinline__ void stsm4(uint32_t addr, uint32_t r0, uint32_t r1, uint32_t r2, uint32_t r3) {
  asm volatile("stmatrix.sync.aligned.m8n8.x4.shared.b16 [%0], {%1, %2, %3, %4};" :: "r"(addr), "r"(r0), "r"(r1), "r"(r2), "r"(r3) : "memory");
}

__device__ __forceinline__ void wgmma_ss_n160_tb(float (&d)[80], uint64_t descA, uint64_t descB) {
  asm volatile("wgmma.mma_async.sync.aligned.m64n160k16.f32.bf16.bf16 {%0, %1, %2, %3, %4, %5, %6, %7, %8, %9, %10, %11, %12, %13, %14, %15, %16, %17, %18, %19, %20, %21, %22, %23, %24, %25, %26, %27, %28, %29, %30, %31, %32, %33, %34, %35, %36, %37, %38, %39, %40, %41, %42, %43, %44, %45, %46, %47, %48, %49, %50, %51, %52, %53, %54, %55, %56, %57, %58, %59, %60, %61, %62, %63, %64, %65, %66, %67, %68, %69, %70, %71, %72, %73, %74, %75, %76, %77, %78, %79}, %80, %81, 1, 1, 1, 0, 1;\n"
    : "+f"(d[0]), "+f"(d[1]), "+f"(d[2]), "+f"(d[3]), "+f"(d[4]), "+f"(d[5]), "+f"(d[6]), "+f"(d[7]), "+f"(d[8]), "+f"(d[9]), "+f"(d[10]), "+f"(d[11]), "+f"(d[12]), "+f"(d[13]), "+f"(d[14]), "+f"(d[15]), "+f"(d[16]), "+f"(d[17]), "+f"(d[18]), "+f"(d[19]), "+f"(d[20]), "+f"(d[21]), "+f"(d[22]), "+f"(d[23]), "+f"(d[24]), "+f"(d[25]), "+f"(d[26]), "+f"(d[27]), "+f"(d[28]), "+f"(d[29]), "+f"(d[30]), "+f"(d[31]), "+f"(d[32]), "+f"(d[33]), "+f"(d[34]), "+f"(d[35]), "+f"(d[36]), "+f"(d[37]), "+f"(d[38]), "+f"(d[39]), "+f"(d[40]), "+f"(d[41]), "+f"(d[42]), "+f"(d[43]), "+f"(d[44]), "+f"(d[45]), "+f"(d[46]), "+f"(d[47]), "+f"(d[48]), "+f"(d[49]), "+f"(d[50]), "+f"(d[51]), "+f"(d[52]), "+f"(d[53]), "+f"(d[54]), "+f"(d[55]), "+f"(d[56]), "+f"(d[57]), "+f"(d[58]), "+f"(d[59]), "+f"(d[60]), "+f"(d[61]), "+f"(d[62]), "+f"(d[63]), "+f"(d[64]), "+f"(d[65]), "+f"(d[66]), "+f"(d[67]), "+f"(d[68]), "+f"(d[69]), "+f"(d[70]), "+f"(d[71]), "+f"(d[72]), "+f"(d[73]), "+f"(d[74]), "+f"(d[75]), "+f"(d[76]), "+f"(d[77]), "+f"(d[78]), "+f"(d[79])
    : "l"(descA), "l"(descB));
}
__device__ __forceinline__ void wgmma_ss_n48_tb(float (&d)[24], uint64_t descA, uint64_t descB) {
  asm volatile("wgmma.mma_async.sync.aligned.m64n48k16.f32.bf16.bf16 {%0, %1, %2, %3, %4, %5, %6, %7, %8, %9, %10, %11, %12, %13, %14, %15, %16, %17, %18, %19, %20, %21, %22, %23}, %24, %25, 1, 1, 1, 0, 1;\n"
    : "+f"(d[0]), "+f"(d[1]), "+f"(d[2]), "+f"(d[3]), "+f"(d[4]), "+f"(d[5]), "+f"(d[6]), "+f"(d[7]), "+f"(d[8]), "+f"(d[9]), "+f"(d[10]), "+f"(d[11]), "+f"(d[12]), "+f"(d[13]), "+f"(d[14]), "+f"(d[15]), "+f"(d[16]), "+f"(d[17]), "+f"(d[18]), "+f"(d[19]), "+f"(d[20]), "+f"(d[21]), "+f"(d[22]), "+f"(d[23])
    : "l"(descA), "l"(descB));
}
__device__ __forceinline__ void wgmma_ss_n80_tb(float (&d)[40], uint64_t descA, uint64_t descB) {
  asm volatile("wgmma.mma_async.sync.aligned.m64n80k16.f32.bf16.bf16 {%0, %1, %2, %3, %4, %5, %6, %7, %8, %9, %10, %11, %12, %13, %14, %15, %16, %17, %18, %19, %20, %21, %22, %23, %24, %25, %26, %27, %28, %29, %30, %31, %32, %33, %34, %35, %36, %37, %38, %39}, %40, %41, 1, 1, 1, 0, 1;\n"
    : "+f"(d[0]), "+f"(d[1]), "+f"(d[2]), "+f"(d[3]), "+f"(d[4]), "+f"(d[5]), "+f"(d[6]), "+f"(d[7]), "+f"(d[8]), "+f"(d[9]), "+f"(d[10]), "+f"(d[11]), "+f"(d[12]), "+f"(d[13]), "+f"(d[14]), "+f"(d[15]), "+f"(d[16]), "+f"(d[17]), "+f"(d[18]), "+f"(d[19]), "+f"(d[20]), "+f"(d[21]), "+f"(d[22]), "+f"(d[23]), "+f"(d[24]), "+f"(d[25]), "+f"(d[26]), "+f"(d[27]), "+f"(d[28]), "+f"(d[29]), "+f"(d[30]), "+f"(d[31]), "+f"(d[32]), "+f"(d[33]), "+f"(d[34]), "+f"(d[35]), "+f"(d[36]), "+f"(d[37]), "+f"(d[38]), "+f"(d[39])
    : "l"(descA), "l"(descB));
}
template <int SCALE_D>
__device__ __forceinline__ void wgmma_rs_n64(float (&d)[32], uint32_t a0, uint32_t a1, uint32_t a2, uint32_t a3, uint64_t descB) {
  asm volatile("wgmma.mma_async.sync.aligned.m64n64k16.f32.bf16.bf16 {%0, %1, %2, %3, %4, %5, %6, %7, %8, %9, %10, %11, %12, %13, %14, %15, %16, %17, %18, %19, %20, %21, %22, %23, %24, %25, %26, %27, %28, %29, %30, %31}, {%32, %33, %34, %35}, %36, %37, 1, 1, 0;\n"
    : "+f"(d[0]), "+f"(d[1]), "+f"(d[2]), "+f"(d[3]), "+f"(d[4]), "+f"(d[5]), "+f"(d[6]), "+f"(d[7]), "+f"(d[8]), "+f"(d[9]), "+f"(d[10]), "+f"(d[11]), "+f"(d[12]), "+f"(d[13]), "+f"(d[14]), "+f"(d[15]), "+f"(d[16]), "+f"(d[17]), "+f"(d[18]), "+f"(d[19]), "+f"(d[20]), "+f"(d[21]), "+f"(d[22]), "+f"(d[23]), "+f"(d[24]), "+f"(d[25]), "+f"(d[26]), "+f"(d[27]), "+f"(d[28]), "+f"(d[29]), "+f"(d[30]), "+f"(d[31])
    : "r"(a0), "r"(a1), "r"(a2), "r"(a3), "l"(descB), "n"(SCALE_D));
}
template <int SCALE_D>
__device__ __forceinline__ void wgmma_rs_n24_tb(float (&d)[12], uint32_t a0, uint32_t a1, uint32_t a2, uint32_t a3, uint64_t descB) {
  asm volatile("wgmma.mma_async.sync.aligned.m64n24k16.f32.bf16.bf16 {%0, %1, %2, %3, %4, %5, %6, %7, %8, %9, %10, %11}, {%12, %13, %14, %15}, %16, %17, 1, 1, 1;\n"
    : "+f"(d[0]), "+f"(d[1]), "+f"(d[2]), "+f"(d[3]), "+f"(d[4]), "+f"(d[5]), "+f"(d[6]), "+f"(d[7]), "+f"(d[8]), "+f"(d[9]), "+f"(d[10]), "+f"(d[11])
    : "r"(a0), "r"(a1), "r"(a2), "r"(a3), "l"(descB), "n"(SCALE_D));
}

constexpr uint32_t DHI_SW128_K = (1024 >> 4) | (1u << 30);
constexpr uint32_t DHI_SW64_MN = (512 >> 4) | (2u << 30);

template <int NC>
__device__ __forceinline__ void store_tile_bf16(const float (&acc)[NC / 2], float scale, uint32_t stage, uint8_t* stage_ptr,
                                                __nv_bfloat16* gdst, int gpitch, int lane) {
  constexpr int PITCH = NC * 2 + 16;
  const uint32_t waddr = stage + ((lane & 7) + ((lane >> 3) & 1) * 8) * PITCH + (lane >> 4) * 16;
#pragma unroll
  for (int j = 0; j < NC / 16; j++) {
    stsm4(waddr + j * 32, pack_bf16(acc[8 * j] * scale, acc[8 * j + 1] * scale), pack_bf16(acc[8 * j + 2] * scale, acc[8 * j + 3] * scale),
          pack_bf16(acc[8 * j + 4] * scale, acc[8 * j + 5] * scale), pack_bf16(acc[8 * j + 6] * scale, acc[8 * j + 7] * scale));
  }
  __syncwarp();
  constexpr int CPR = NC / 8;
#pragma unroll
  for (int i = 0; i < CPR / 2; i++) {
    const int c = i * 32 + lane, r = c / CPR, cc = c % CPR;
    const uint4 v = *reinterpret_cast<const uint4*>(stage_ptr + r * PITCH + cc * 16);
    *reinterpret_cast<uint4*>(gdst + (size_t)r * gpitch + cc * 8) = v;
  }
}

__device__ __forceinline__ void signal_done(unsigned int* flag, int wg, int tid) {
  asm volatile("bar.sync %0, 128;" :: "r"(wg + 1) : "memory");
  if ((tid & 127) == 0) asm volatile("red.release.gpu.global.add.u32 [%0], 1;" :: "l"(flag) : "memory");
}
__device__ __forceinline__ void wait_flags8(const unsigned int* f, unsigned int target) {
  for (int spin = 0; spin < (1 << 26); spin++) {
    unsigned int a, b, c, d, e, g, h, i;
    asm volatile("ld.volatile.global.v4.u32 {%0, %1, %2, %3}, [%4];" : "=r"(a), "=r"(b), "=r"(c), "=r"(d) : "l"(f) : "memory");
    asm volatile("ld.volatile.global.v4.u32 {%0, %1, %2, %3}, [%4];" : "=r"(e), "=r"(g), "=r"(h), "=r"(i) : "l"(f + 4) : "memory");
    if (min(min(min(a, b), min(c, d)), min(min(e, g), min(h, i))) >= target) break;
    __nanosleep(32);
  }
  asm volatile("fence.acq_rel.gpu;" ::: "memory");
  asm volatile("fence.proxy.async;" ::: "memory");
}

constexpr int K1_STAGES = 4;
constexpr int K1_A_BYTES = 256 * 128;
constexpr int K1_B_BYTES = 64 * 160 * 2;
constexpr int K1_STAGE = K1_A_BYTES + K1_B_BYTES;
constexpr int K1_SMEM = 5 * K1_A_BYTES + 61440 + 1024;
constexpr int KV_STAGES = 5;
constexpr int KVW_OFF = KV_STAGES * K1_A_BYTES;

__global__ void __launch_bounds__(512, 1)
proj_kernel(const __grid_constant__ CUtensorMap tmX, const __grid_constant__ CUtensorMap tmWq, const __grid_constant__ CUtensorMap tmWqkv,
            const __nv_bfloat16* __restrict__ wk, const __nv_bfloat16* __restrict__ wv, const __nv_bfloat16* __restrict__ gate_w,
            const __nv_bfloat16* __restrict__ woA, const __nv_bfloat16* __restrict__ woB) {
  extern __shared__ uint8_t smem_raw[];
  __shared__ __align__(8) uint64_t bar_full[KV_STAGES], bar_empty[KV_STAGES];
  uint8_t* smem = reinterpret_cast<uint8_t*>((reinterpret_cast<uintptr_t>(smem_raw) + 1023) & ~(uintptr_t)1023);
  const uint32_t sbase = smem_u32(smem);
  const uint32_t dbase = sbase & 0x3FFFFu;
  const int tid = threadIdx.x, warp = tid >> 5, lane = tid & 31;
  const bool is_kv = blockIdx.x >= 128;
  PROF(0, 0);
  if (tid == 0) {
    for (int i = 0; i < KV_STAGES; i++) { mbar_init(smem_u32(&bar_full[i]), 1); mbar_init(smem_u32(&bar_empty[i]), is_kv ? 8 : 16); }
    fence_mbar_init();
  }
  uint2 wa[2][5], wb[2][5]; uint32_t gw[2];
  if (is_kv && tid < 320) {
#pragma unroll
    for (int r = 0; r < 2; r++) {
      const int k = tid + r * 320;
      const uint2* pk = reinterpret_cast<const uint2*>(wk + k * 20);
      const uint2* pv = reinterpret_cast<const uint2*>(wv + k * 20);
#pragma unroll
      for (int i = 0; i < 5; i++) { wa[r][i] = __ldg(pk + i); wb[r][i] = __ldg(pv + i); }
      gw[r] = (uint32_t)__bfloat16_as_ushort(gate_w[k]);
    }
  }
  __syncthreads();
  if (tid == 480) {
    if (!is_kv) { g_done[blockIdx.x] = 0u; g_doneL[blockIdx.x] = 0u; }
    asm volatile("fence.acq_rel.gpu;" ::: "memory");
    pdl_launch();
  }
  __syncwarp();

  if (!is_kv) {
    const int mb = blockIdx.x >> 4, nb = blockIdx.x & 15;
    const CUtensorMap* tw = nb < 4 ? &tmWq : &tmWqkv;
    const int j0 = (nb < 4 ? nb : nb - 4) * 5;
    auto load = [&](int kt) {
      const int s = kt % K1_STAGES;
      const uint32_t fb = smem_u32(&bar_full[s]);
      mbar_expect_tx(fb, K1_STAGE);
      tma_2d(sbase + s * K1_STAGE, &tmX, kt * 64, mb * 256, fb);
      tma_3d(sbase + s * K1_STAGE + K1_A_BYTES, tw, 0, kt * 64, j0, fb);
    };
    if (tid == 0) for (int kt = 0; kt < K1_STAGES; kt++) load(kt);
    __syncwarp();
    uint4 wv2[2];
    const int rq = blockIdx.x * 400 + tid - 112;
    const int rhalf = rq >= 25600, rr = rq - rhalf * 25600, rk = 2 * (rr / 80), rch = rr % 80;
    if (tid >= 112) {
      const uint4* src = reinterpret_cast<const uint4*>((rhalf ? woB : woA) + rk * D_MODEL + rch * 8);
      wv2[0] = __ldg(src); wv2[1] = __ldg(src + D_MODEL / 8);
    }
    __syncwarp();
    {
      const int wg = warp >> 2;
      float acc[80];
#pragma unroll
      for (int i = 0; i < 80; i++) acc[i] = 0.f;
      for (int kt = 0; kt < 10; kt++) {
        const int s = kt % K1_STAGES;
        mbar_wait(smem_u32(&bar_full[s]), (kt / K1_STAGES) & 1);
        const uint32_t alo = ((dbase + s * K1_STAGE + wg * 8192) >> 4) | (1u << 16);
        const uint32_t blo = ((dbase + s * K1_STAGE + K1_A_BYTES) >> 4) | ((4096u >> 4) << 16);
        fence_regs(acc);
        wg_fence();
#pragma unroll
        for (int k = 0; k < 4; k++) wgmma_ss_n160_tb(acc, mkd(alo + k * 2, DHI_SW128_K), mkd(blo + k * 64, DHI_SW64_MN));
        wg_commit();
        if (kt == 3 && tid >= 112) {
          uint4* dst = reinterpret_cast<uint4*>(g_wimg + ((rhalf * 8 + rch / 10) * 10 + (rk >> 6)) * 10240 + (rch % 10) * 1024 + (rk & 63) * 16);
          dst[0] = wv2[0]; dst[1] = wv2[1];
        }
        __syncwarp();
        if (kt > 0 && kt - 1 + K1_STAGES < 10) {
          wg_wait<1>();
          const uint32_t eb = smem_u32(&bar_empty[(kt - 1) % K1_STAGES]);
          if (lane == 0) mbar_arrive(eb);
          if (tid == 0) { mbar_wait(eb, ((kt - 1) / K1_STAGES) & 1); load(kt - 1 + K1_STAGES); }
          __syncwarp();
        }
      }
      wg_wait<0>();
      fence_regs(acc);
      PROF(0, 1);
      asm volatile("bar.sync %0, 128;" :: "r"(wg + 1) : "memory");
      const int w4 = warp & 3;
      const uint32_t off = w4 * K1_STAGE + wg * 8192;
      const int row0 = mb * 256 + wg * 64 + w4 * 16;
      if (nb < 4) {
        store_tile_bf16<160>(acc, 0.22360679774997896f * 1.4426950408889634f, sbase + off, smem + off,
                             g_q + (size_t)row0 * D_MODEL + nb * 160, D_MODEL, lane);
      } else {
        store_tile_bf16<160>(acc, 1.0f, sbase + off, smem + off, g_qkv + (size_t)row0 * (3 * D_MODEL) + (nb - 4) * 160, 3 * D_MODEL, lane);
      }
    }
  } else {
    const int cb = blockIdx.x - 128;
    if (warp == 8 && lane == 0) {
      for (int it = 0; it < KV_STAGES; it++) {
        const uint32_t fb = smem_u32(&bar_full[it]);
        mbar_expect_tx(fb, K1_A_BYTES);
        tma_2d(sbase + it * K1_A_BYTES, &tmX, it * 64, cb * 512, fb);
      }
    }
    __syncwarp();
    if (tid < 320) {
#pragma unroll
      for (int r = 0; r < 2; r++) {
        uint4* dst = reinterpret_cast<uint4*>(smem + KVW_OFF + (tid + r * 320) * 16);
        dst[0] = make_uint4(wa[r][0].x, wa[r][0].y, wa[r][1].x, wa[r][1].y);
        dst[640] = make_uint4(wa[r][2].x, wa[r][2].y, wa[r][3].x, wa[r][3].y);
        dst[1280] = make_uint4(wa[r][4].x, wa[r][4].y, 0u, 0u);
        dst[1920] = make_uint4(wb[r][0].x, wb[r][0].y, wb[r][1].x, wb[r][1].y);
        dst[2560] = make_uint4(wb[r][2].x, wb[r][2].y, wb[r][3].x, wb[r][3].y);
        dst[3200] = make_uint4(wb[r][4].x, wb[r][4].y, gw[r], 0u);
      }
    }
    fence_proxy_async();
    asm volatile("bar.sync 1, 512;" ::: "memory");
    PROF(0, 1);
    auto produce = [&](int it0, int it1) {
      for (int it = it0; it < it1; it++) {
        const int s = it % KV_STAGES;
        mbar_wait(smem_u32(&bar_empty[s]), (it / KV_STAGES - 1) & 1);
        const uint32_t fb = smem_u32(&bar_full[s]);
        mbar_expect_tx(fb, K1_A_BYTES);
        tma_2d(sbase + s * K1_A_BYTES, &tmX, (it >= 10 ? it - 10 : it) * 64, cb * 512 + (it >= 10 ? 256 : 0), fb);
      }
    };
    if (tid == 256) produce(KV_STAGES, 15);
    __syncwarp();
    {
      const int pass = warp >> 3, wg = (warp >> 2) & 1, w4 = warp & 3, g = lane >> 2, t = lane & 3;
      if (pass == 1) asm volatile("bar.sync 2, 512;" ::: "memory");
      {
        float acc[2][24];
#pragma unroll
        for (int i = 0; i < 24; i++) { acc[0][i] = 0.f; acc[1][i] = 0.f; }
        for (int kt = 0; kt < 10; kt++) {
          const int it = pass * 10 + kt, s = it % KV_STAGES;
          mbar_wait(smem_u32(&bar_full[s]), (it / KV_STAGES) & 1);
          const uint32_t alo = ((dbase + s * K1_A_BYTES + wg * 16384) >> 4) | (1u << 16);
          const uint32_t blo = ((dbase + KVW_OFF + kt * 1024) >> 4) | ((128u >> 4) << 16);
          fence_regs(acc[0]); fence_regs(acc[1]);
          wg_fence();
#pragma unroll
          for (int k = 0; k < 4; k++) {
            wgmma_ss_n48_tb(acc[0], mkd(alo + k * 2, DHI_SW128_K), mkd(blo + k * 16, 10240u >> 4));
            wgmma_ss_n48_tb(acc[1], mkd(alo + 512 + k * 2, DHI_SW128_K), mkd(blo + k * 16, 10240u >> 4));
          }
          wg_commit();
          if (kt > 0) {
            wg_wait<1>();
            if (lane == 0) mbar_arrive(smem_u32(&bar_empty[(it - 1) % KV_STAGES]));
          }
        }
        wg_wait<0>();
        fence_regs(acc[0]); fence_regs(acc[1]);
        if (lane == 0) mbar_arrive(smem_u32(&bar_empty[(pass * 10 + 9) % KV_STAGES]));
        if (pass == 0) asm volatile("bar.arrive 2, 512;" ::: "memory");
        PROF(0, 2);
        if (tid == 0) produce(15, 20);
        __syncwarp();
        float kmax2 = 0.f, vmax = 0.f;
#pragma unroll
        for (int hh = 0; hh < 4; hh++) {
          const int h = hh & 1;
          const float (&a)[24] = acc[hh >> 1];
          const int key = cb * 512 + pass * 256 + wg * 128 + (hh >> 1) * 64 + w4 * 16 + g + h * 8;
          const int grp = key >> 7, kk = key & 127;
          const bool poly = (TMASK >> (kk >> 3)) & 1;
          uint8_t* gp = g_kvimg + grp * GRP_BYTES;
          const uint32_t k0 = pack_bf16(a[2 * h], a[2 * h + 1]);
          const uint32_t k1 = pack_bf16(a[4 + 2 * h], a[5 + 2 * h]);
          uint32_t k2 = pack_bf16(a[8 + 2 * h], a[9 + 2 * h]);
          float n2 = bf_lo(k0) * bf_lo(k0) + bf_hi(k0) * bf_hi(k0) + bf_lo(k1) * bf_lo(k1) + bf_hi(k1) * bf_hi(k1);
          if (t < 2) {
            n2 += bf_lo(k2) * bf_lo(k2) + bf_hi(k2) * bf_hi(k2);
            k2 = pack_bf16(bf_lo(k2) * 0.5f, bf_hi(k2) * 0.5f);
          } else if (t == 2) k2 = poly ? pack_bf16(24.f, 2.5f) : pack_bf16(0.5f, 0.f);
          else k2 = poly ? pack_bf16(0.5f, 0.f) : 0u;
          *reinterpret_cast<uint32_t*>(gp + kk * 16 + t * 4) = k0;
          *reinterpret_cast<uint32_t*>(gp + PLANE + kk * 16 + t * 4) = k1;
          *reinterpret_cast<uint32_t*>(gp + 2 * PLANE + kk * 16 + t * 4) = k2;
          n2 += __shfl_xor_sync(0xffffffffu, n2, 1);
          n2 += __shfl_xor_sync(0xffffffffu, n2, 2);
          kmax2 = (n2 > kmax2 || n2 != n2) ? n2 : kmax2;
          uint32_t v0 = pack_bf16(a[12 + 2 * h], a[13 + 2 * h]);
          uint32_t v1 = pack_bf16(a[16 + 2 * h], a[17 + 2 * h]);
          uint32_t v2 = pack_bf16(a[20 + 2 * h], a[21 + 2 * h]);
          float vm = fmaxf(fmaxf(fabsf(bf_lo(v0)), fabsf(bf_hi(v0))), fmaxf(fabsf(bf_lo(v1)), fabsf(bf_hi(v1))));
          if (t < 2) vm = fmaxf(vm, fmaxf(fabsf(bf_lo(v2)), fabsf(bf_hi(v2))));
          else if (t == 2) {
            const float z = a[20 + 2 * h];
            g_gate[key] = 1.f / (1.f + __expf(-z));
            v2 = 0x00003F80u;
          } else v2 = 0u;
          vmax = fmaxf(vmax, vm);
          if (poly) { v0 ^= 0x80008000u; v1 ^= 0x80008000u; v2 ^= 0x80008000u; }
          uint8_t* vp = gp + 3 * PLANE + (kk >> 3) * 384 + (kk & 7) * 16 + t * 4;
          *reinterpret_cast<uint32_t*>(vp) = v0;
          *reinterpret_cast<uint32_t*>(vp + 128) = v1;
          *reinterpret_cast<uint32_t*>(vp + 256) = v2;
        }
#pragma unroll
        for (int o = 1; o < 32; o <<= 1) {
          const float a = __shfl_xor_sync(0xffffffffu, kmax2, o);
          kmax2 = (a > kmax2 || a != a) ? a : kmax2;
          vmax = fmaxf(vmax, __shfl_xor_sync(0xffffffffu, vmax, o));
        }
        if (lane == 0) { g_kmax2[cb * 16 + warp] = kmax2; g_vmax[cb * 16 + warp] = vmax; }
      }
    }
  }
}

__device__ __forceinline__ uint32_t ex2_pair_poly(float u0, float u1, uint32_t one2) {
  const uint32_t W = __byte_perm(__float_as_uint(u0), __float_as_uint(u1), 0x6521);
  uint32_t v; asm("lop3.b32 %0, %1, 0x007F007F, %2, 0xEA;" : "=r"(v) : "r"(W), "r"(one2));
  uint32_t L, p;
  asm("fma.rn.bf16x2 %0, %1, %2, %3;" : "=r"(L) : "r"(v), "r"(0x1f961f96u), "r"(0x9fe39fe3u));
  asm("fma.rn.bf16x2 %0, %1, %1, %2;" : "=r"(p) : "r"(L), "r"(0x00f500f5u));
  return W + p;
}
template <int JOFF>
__device__ __forceinline__ void softmax_fast(const float (&S)[32], uint32_t (&P)[16], uint32_t one2) {
#pragma unroll
  for (int i = 0; i < 16; i++) {
    if ((TMASK >> (JOFF + i / 2)) & 1) P[i] = ex2_pair_poly(S[2 * i], S[2 * i + 1], one2);
    else P[i] = pack_bf16(ex2(S[2 * i]), ex2(S[2 * i + 1]));
  }
}
template <int JOFF>
__device__ __forceinline__ void softmax_slow(const float (&S)[32], uint32_t (&P)[16], float (&O)[12], float& m0, float& m1) {
  float a0 = m0, a1 = m1;
#pragma unroll
  for (int j = 0; j < 8; j++) {
    a0 = fmaxf(a0, fmaxf(S[4 * j], S[4 * j + 1]));
    a1 = fmaxf(a1, fmaxf(S[4 * j + 2], S[4 * j + 3]));
  }
  a0 = fmaxf(a0, __shfl_xor_sync(0xffffffffu, a0, 1)); a0 = fmaxf(a0, __shfl_xor_sync(0xffffffffu, a0, 2));
  a1 = fmaxf(a1, __shfl_xor_sync(0xffffffffu, a1, 1)); a1 = fmaxf(a1, __shfl_xor_sync(0xffffffffu, a1, 2));
  const float c0 = ex2(m0 - a0), c1 = ex2(m1 - a1);
  m0 = a0; m1 = a1;
#pragma unroll
  for (int j = 0; j < 3; j++) { O[4 * j] *= c0; O[4 * j + 1] *= c0; O[4 * j + 2] *= c1; O[4 * j + 3] *= c1; }
#pragma unroll
  for (int i = 0; i < 16; i++) {
    const float m = (i & 1) ? a1 : a0;
    const uint32_t p = pack_bf16(ex2(S[2 * i] - m), ex2(S[2 * i + 1] - m));
    P[i] = ((TMASK >> (JOFF + i / 2)) & 1) ? (p ^ 0x80008000u) : p;
  }
}
constexpr uint32_t DHI_KV = 128 >> 4;
__device__ __forceinline__ void issue_qk(float (&S)[32], const uint32_t (&q)[8], uint64_t base) {
  wgmma_rs_n64<0>(S, q[0], q[1], q[2], q[3], base + (uint64_t)((PLANE >> 4) << 16));
  wgmma_rs_n64<1>(S, q[4], q[5], q[6], q[7], base + (uint64_t)(2 * PLANE >> 4));
}
__device__ __forceinline__ void issue_pv(float (&O)[12], const uint32_t (&P)[16], uint64_t vbase) {
#pragma unroll
  for (int kk = 0; kk < 4; kk++)
    wgmma_rs_n24_tb<1>(O, P[4 * kk], P[4 * kk + 1], P[4 * kk + 2], P[4 * kk + 3], vbase + (uint64_t)(kk * (768 >> 4)));
}

constexpr uint32_t VOFF = ((3 * PLANE) >> 4) + ((384u >> 4) << 16);
constexpr int KVR = 4;
constexpr int OFF_WA = KVR * GRP_BYTES;
constexpr int OFF_BR = OFF_WA + 10 * 10240;
constexpr int BR_STAGE = 8192 + 10240, BR_STAGES = 3;
constexpr int OFF_QS = OFF_BR + BR_STAGES * BR_STAGE;
constexpr int OFF_BAR = OFF_QS + 512 * 6 * 4;
constexpr int K2_SMEM = OFF_BAR + 256 + 1024;
constexpr int BAR_KV = 0, BAR_WA = 4, BAR_BR = 5, BAR_TA = 8, BAR_TE = 14, BAR_OWN = 18, CNT_KV = 19;
constexpr int NSTEP = 2 * NGRP;

__device__ __forceinline__ void kv_load(uint32_t sbase, int step) {
  const uint32_t bar = sbase + OFF_BAR + (BAR_KV + (step & (KVR - 1))) * 8;
  mbar_expect_tx(bar, GRP_BYTES);
  bulk_g2s(sbase + (step & (KVR - 1)) * GRP_BYTES, g_kvimg + (step & (NGRP - 1)) * GRP_BYTES, GRP_BYTES, bar);
}
__device__ __forceinline__ void kv_release(uint32_t sbase, int step, bool elected) {
  if (elected && step + KVR < NSTEP) {
    uint32_t old;
    asm volatile("atom.acq_rel.cta.shared::cta.inc.u32 %0, [%1], 3;" : "=r"(old) : "r"(sbase + OFF_BAR + CNT_KV * 8 + (step & (KVR - 1)) * 4) : "memory");
    if (old == 3u) kv_load(sbase, step + KVR);
  }
  __syncwarp();
}
__device__ __forceinline__ void kv_wait(uint32_t sbase, int step) {
  mbar_wait(sbase + OFF_BAR + (BAR_KV + (step & (KVR - 1))) * 8, (step / KVR) & 1);
}

__device__ __forceinline__ uint32_t kv_release_begin(uint32_t sbase, int slot, bool doit) {
  uint32_t old = 0;
  asm volatile("{\n.reg .pred p;\nsetp.ne.u32 p, %2, 0;\n@p atom.relaxed.cta.shared::cta.inc.u32 %0, [%1], 3;\n}\n"
               : "+r"(old) : "r"(sbase + OFF_BAR + CNT_KV * 8 + slot * 4), "r"((uint32_t)doit) : "memory");
  return old;
}
__device__ __forceinline__ void attn_tile_fast(const uint32_t (&q)[8], float (&O)[12], uint32_t sbase, int step0, bool elected, uint32_t one2) {
  float S[32]; uint32_t P[16];
#pragma unroll
  for (int i = 0; i < 32; i++) S[i] = 0.f;
  uint64_t kb0 = mkd((sbase & 0x3FFFFu) >> 4, DHI_KV);
  asm volatile("" : "+l"(kb0));
  kv_wait(sbase, step0);
  fence_regs(S); fence_regs(O);
  wg_fence();
  issue_qk(S, q, kb0);
  wg_commit();
#pragma unroll 1
  for (int step4 = step0; step4 < step0 + NGRP; step4 += KVR) {
#pragma unroll
    for (int j = 0; j < KVR; j++) {
      const int step = step4 + j;
      const uint64_t kb = kb0 + (uint64_t)(j * (GRP_BYTES >> 4));
      const uint64_t knext = kb0 + (uint64_t)(((j + 1) & (KVR - 1)) * (GRP_BYTES >> 4));
      wg_wait<0>();
      fence_regs(S); fence_regs(P); fence_regs(O);
      const uint32_t old = kv_release_begin(sbase, (j + KVR - 1) & (KVR - 1), elected && step > step0 && step - 1 + KVR < NSTEP);
      softmax_fast<0>(S, P, one2);
      fence_regs(S); fence_regs(P); fence_regs(O);
      wg_fence();
      issue_qk(S, q, kb + 64);
      issue_pv(O, P, kb + VOFF);
      wg_commit();
      if (step + 1 < NSTEP) mbar_wait(sbase + OFF_BAR + (BAR_KV + ((j + 1) & (KVR - 1))) * 8, ((step + 1) / KVR) & 1);
      wg_wait<0>();
      fence_regs(S); fence_regs(P); fence_regs(O);
      softmax_fast<8>(S, P, one2);
      fence_regs(S); fence_regs(P); fence_regs(O);
      wg_fence();
      issue_qk(S, q, knext);
      issue_pv(O, P, kb + VOFF + 4 * (768 >> 4));
      wg_commit();
      if (old == 3u) kv_load(sbase, step - 1 + KVR);
    }
  }
  wg_wait<0>();
  fence_regs(O); fence_regs(S);
  kv_release(sbase, step0 + NGRP - 1, elected);
}
template <int H>
__device__ __forceinline__ void slow_step(const uint32_t (&q)[8], float (&O)[12], uint64_t kb, float& m0, float& m1) {
  float S[32]; uint32_t P[16];
#pragma unroll
  for (int i = 0; i < 32; i++) S[i] = 0.f;
  fence_regs(S);
  wg_fence();
  issue_qk(S, q, kb + 64 * H);
  wg_commit();
  wg_wait<0>();
  fence_regs(S);
  softmax_slow<8 * H>(S, P, O, m0, m1);
  fence_regs(P); fence_regs(O);
  wg_fence();
  issue_pv(O, P, kb + VOFF + H * 4 * (768 >> 4));
  wg_commit();
  wg_wait<0>();
  fence_regs(O); fence_regs(P);
}
__device__ __forceinline__ void attn_tile_slow(const uint32_t (&q)[8], float (&O)[12], uint32_t sbase, int step0, bool elected) {
  float m0 = -INFINITY, m1 = -INFINITY;
#pragma unroll 1
  for (int grp = 0; grp < NGRP; grp++) {
    kv_wait(sbase, step0 + grp);
    const uint64_t kb = mkd(((sbase & 0x3FFFFu) >> 4) + (grp & (KVR - 1)) * (GRP_BYTES >> 4), DHI_KV);
    slow_step<0>(q, O, kb, m0, m1);
    slow_step<1>(q, O, kb, m0, m1);
    kv_release(sbase, step0 + grp, elected);
  }
}

__device__ __forceinline__ void load_row20(const __nv_bfloat16* p, float (&f)[20]) {
  const uint2* p2 = reinterpret_cast<const uint2*>(p);
#pragma unroll
  for (int i = 0; i < 5; i++) { const uint2 v = p2[i]; f[4 * i] = bf_lo(v.x); f[4 * i + 1] = bf_hi(v.x); f[4 * i + 2] = bf_lo(v.y); f[4 * i + 3] = bf_hi(v.y); }
}
__device__ __forceinline__ void softmax8(float (&sc)[8]) {
  float mx = sc[0];
#pragma unroll
  for (int w = 1; w < 8; w++) mx = fmaxf(mx, sc[w]);
  float l = 0.f;
#pragma unroll
  for (int w = 0; w < 8; w++) { sc[w] = ex2(sc[w] - mx); l += sc[w]; }
  const float r = 1.f / l;
#pragma unroll
  for (int w = 0; w < 8; w++) sc[w] *= r;
}
__device__ __forceinline__ void local_attn_pair(int t, int lane) {
  constexpr int PITCH = 3 * D_MODEL;
  constexpr float SC = 0.22360679774997896f * 1.4426950408889634f, NEG = -1e9f * 1.4426950408889634f;
  const __nv_bfloat16* base = g_qkv + lane * DH;
  float a[20], b[20], sa[8], sb[8];
  load_row20(base + (size_t)t * PITCH, a);
  load_row20(base + (size_t)(t + 2) * PITCH, b);
#pragma unroll
  for (int j = 0; j < 9; j++) {
    const int r = t + 2 - 2 * j;
    float k[20];
    load_row20(base + D_MODEL + (size_t)max(r, 0) * PITCH, k);
    float da = 0.f, db = 0.f;
#pragma unroll
    for (int i = 0; i < 20; i++) { if (j >= 1) da = fmaf(a[i], k[i], da); if (j < 8) db = fmaf(b[i], k[i], db); }
    if (j >= 1) sa[j - 1] = r >= 0 ? da * SC : NEG;
    if (j < 8) sb[j] = r >= 0 ? db * SC : NEG;
  }
  softmax8(sa); softmax8(sb);
#pragma unroll
  for (int i = 0; i < 20; i++) { a[i] = 0.f; b[i] = 0.f; }
#pragma unroll
  for (int j = 0; j < 9; j++) {
    const int r = t + 2 - 2 * j;
    float v[20];
    load_row20(base + 2 * D_MODEL + (size_t)max(r, 0) * PITCH, v);
#pragma unroll
    for (int i = 0; i < 20; i++) { if (j >= 1) a[i] = fmaf(sa[j - 1], v[i], a[i]); if (j < 8) b[i] = fmaf(sb[j], v[i], b[i]); }
  }
  const float ga = 1.f - g_gate[t], gb = 1.f - g_gate[t + 2];
  uint2* da = reinterpret_cast<uint2*>(g_a2 + (size_t)t * (2 * D_MODEL) + D_MODEL + lane * DH);
  uint2* db = da + 2 * (2 * D_MODEL) / 4;
#pragma unroll
  for (int i = 0; i < 5; i++) {
    da[i] = make_uint2(pack_bf16(a[4 * i] * ga, a[4 * i + 1] * ga), pack_bf16(a[4 * i + 2] * ga, a[4 * i + 3] * ga));
    db[i] = make_uint2(pack_bf16(b[4 * i] * gb, b[4 * i + 1] * gb), pack_bf16(b[4 * i + 2] * gb, b[4 * i + 3] * gb));
  }
}
__device__ __forceinline__ uint32_t ta_slot(int i) { return i < 3 ? i * 16384 : OFF_BR + (i - 3) * 16384; }

__global__ void __launch_bounds__(640, 1)
attn_kernel(const __grid_constant__ CUtensorMap tmA2, const __grid_constant__ CUtensorMap tmA2b,
            __nv_bfloat16* __restrict__ out, uint32_t one2) {
  extern __shared__ uint8_t smem_raw[];
  uint8_t* smem = reinterpret_cast<uint8_t*>((reinterpret_cast<uintptr_t>(smem_raw) + 1023) & ~(uintptr_t)1023);
  const uint32_t sbase = smem_u32(smem);
  const uint32_t dbase = sbase & 0x3FFFFu;
  const uint32_t bars = sbase + OFF_BAR;
  const int tid = threadIdx.x, wg = tid >> 7, warp = (tid >> 5) & 3, lane = tid & 31, g = lane >> 2, t = lane & 3;
  const int mb = blockIdx.x >> 3, nb = blockIdx.x & 7;
  if (tid == 0) {
    for (int i = 0; i < BAR_TE; i++) mbar_init(bars + i * 8, 1);
    for (int i = BAR_TE; i < BAR_TE + 4; i++) mbar_init(bars + i * 8, 8);
    mbar_init(bars + BAR_OWN * 8, 4);
    for (int i = 0; i < 4; i++) *reinterpret_cast<uint32_t*>(smem + OFF_BAR + CNT_KV * 8 + i * 4) = 0u;
    fence_mbar_init();
  }
  __syncthreads();
  if (wg == 4) {
    pdl_wait();
    asm volatile("bar.sync 7, 640;" ::: "memory");
#pragma unroll 1
    for (int i = 0; i < 2; i++) local_attn_pair(blockIdx.x * 16 + warp * 4 + i, lane);
    if (tid == 512) PROF2(0, 2);
    signal_done(&g_doneL[blockIdx.x], wg, tid);
    if (tid == 512) {
      mbar_expect_tx(bars + BAR_WA * 8, 10 * 10240);
      for (int i = 0; i < 5; i++) bulk_g2s(sbase + OFF_WA + i * 20480, g_wimg + (nb * 10) * 10240 + i * 20480, 20480, bars + BAR_WA * 8);
    }
    auto br_load = [&](int it, int st) {
      const uint32_t fb = bars + (BAR_BR + st) * 8;
      const uint32_t dst = sbase + OFF_BR + st * BR_STAGE;
      const int kc = (it >= 10 ? it - 10 : it) * 64;
      mbar_expect_tx(fb, BR_STAGE);
      tma_2d(dst, &tmA2, D_MODEL + kc, (blockIdx.x >> 3) * 128 + (it >= 10 ? 64 : 0), fb);
      bulk_g2s(dst + 8192, g_wimg + ((8 + (blockIdx.x & 7)) * 10 + (kc >> 6)) * 10240, 10240, fb);
    };
    if (tid == 512) {
      wait_flags8(&g_doneL[mb * 8], 1u);
      for (int it = 0; it < BR_STAGES; it++) br_load(it, it);
    }
    __syncwarp();
    {
      int st = 0, ph = 0;
      float acc[40];
#pragma unroll 1
      for (int it = 0; it < 20; it++) {
        if (it == 0 || it == 10) {
#pragma unroll
          for (int i = 0; i < 40; i++) acc[i] = 0.f;
        }
        mbar_wait(bars + (BAR_BR + st) * 8, ph);
        const uint32_t alo = ((dbase + OFF_BR + st * BR_STAGE) >> 4);
        fence_regs(acc);
        wg_fence();
#pragma unroll
        for (int k = 0; k < 4; k++)
          wgmma_ss_n80_tb(acc, mkd(alo + (k * 2 + (1u << 16)), DHI_SW128_K), mkd(alo + (512 + k * 16 + ((128u >> 4) << 16)), 1024u >> 4));
        wg_commit();
        wg_wait<0>();
        fence_regs(acc);
        asm volatile("bar.sync 5, 128;" ::: "memory");
        if (threadIdx.x == 512 && it + BR_STAGES < 20) br_load(it + BR_STAGES, st);
        __syncwarp();
        if (it == 9 || it == 19) {
          float* pp = g_part + (size_t)(blockIdx.x * 2 + (it == 19)) * (40 * 128) + (threadIdx.x & 127);
#pragma unroll
          for (int i = 0; i < 40; i++) pp[i * 128] = acc[i];
        }
        if (++st == BR_STAGES) { st = 0; ph ^= 1; }
      }
    }
    if (tid == 512) PROF2(1, 0);
    asm volatile("bar.arrive 6, 384;" ::: "memory");
    if (tid == 512) {
      mbar_wait(bars + BAR_OWN * 8, 0);
      wait_flags8(&g_done[mb * 8], 4u);
      PROF2(2, 0);
    }
    if (tid == 512) {
      for (int kt = 0; kt < 10; kt++) {
        const int sl = kt % 6;
        if (kt >= 6) mbar_wait(bars + (BAR_TE + kt - 6) * 8, 0);
        const uint32_t fb = bars + (BAR_TA + sl) * 8;
        mbar_expect_tx(fb, 16384);
        tma_2d(sbase + ta_slot(sl), &tmA2b, kt * 64, mb * 128, fb);
      }
    }
  } else {
    const bool elected = (tid & 127) == 0;
    pdl_wait();
    PROF(1, 1);
    if (tid == 384) for (int j = 0; j < KVR; j++) kv_load(sbase, j);
    __syncwarp();
    uint32_t q[8];
    uint32_t* qstash = reinterpret_cast<uint32_t*>(smem + OFF_QS) + tid;
    const int rowA = (blockIdx.x * 8 + wg) * 64 + warp * 16 + g;
    {
      const uint32_t* r0 = reinterpret_cast<const uint32_t*>(g_q + (size_t)rowA * DH);
      const uint32_t* r1 = r0 + 8 * (DH / 2);
      const uint32_t* s0 = r0 + 256 * (DH / 2);
      const uint32_t* s1 = s0 + 8 * (DH / 2);
      q[0] = r0[t]; q[1] = r1[t]; q[2] = r0[t + 4]; q[3] = r1[t + 4];
      q[4] = t < 2 ? r0[8 + t] : 0u;
      q[5] = t < 2 ? r1[8 + t] : 0u;
      qstash[0] = s0[t]; qstash[512] = s1[t]; qstash[1024] = s0[t + 4]; qstash[1536] = s1[t + 4];
      qstash[2048] = t < 2 ? s0[8 + t] : 0u;
      qstash[2560] = t < 2 ? s1[8 + t] : 0u;
    }
    float kmax2 = 0.f, vmax = 0.f;
#pragma unroll
    for (int i = 0; i < 2; i++) {
      const float a = g_kmax2[lane + 32 * i];
      kmax2 = (a > kmax2 || a != a) ? a : kmax2;
      vmax = fmaxf(vmax, g_vmax[lane + 32 * i]);
    }
#pragma unroll
    for (int o = 1; o < 32; o <<= 1) {
      const float a = __shfl_xor_sync(0xffffffffu, kmax2, o);
      kmax2 = (a > kmax2 || a != a) ? a : kmax2;
      vmax = fmaxf(vmax, __shfl_xor_sync(0xffffffffu, vmax, o));
    }
    const float qlim = (vmax >= 0.00390625f && vmax <= 256.f) ? 9025.f / kmax2 : -1.f;
    asm volatile("bar.arrive 7, 640;" ::: "memory");
    PROF(1, 2);
#pragma unroll 1
    for (int it = 0; it < 2; it++) {
      const int row0 = rowA + it * 256;
      if (it == 1) {
#pragma unroll
        for (int i = 0; i < 6; i++) q[i] = qstash[512 * i];
      }
      float n0 = bf_lo(q[0]) * bf_lo(q[0]) + bf_hi(q[0]) * bf_hi(q[0]) + bf_lo(q[2]) * bf_lo(q[2]) + bf_hi(q[2]) * bf_hi(q[2]) +
                 bf_lo(q[4]) * bf_lo(q[4]) + bf_hi(q[4]) * bf_hi(q[4]);
      float n1 = bf_lo(q[1]) * bf_lo(q[1]) + bf_hi(q[1]) * bf_hi(q[1]) + bf_lo(q[3]) * bf_lo(q[3]) + bf_hi(q[3]) * bf_hi(q[3]) +
                 bf_lo(q[5]) * bf_lo(q[5]) + bf_hi(q[5]) * bf_hi(q[5]);
      n0 += __shfl_xor_sync(0xffffffffu, n0, 1); n0 += __shfl_xor_sync(0xffffffffu, n0, 2);
      n1 += __shfl_xor_sync(0xffffffffu, n1, 1); n1 += __shfl_xor_sync(0xffffffffu, n1, 2);
      const bool safe = (n0 <= qlim) && (n1 <= qlim);
      uint32_t unsafe_any;
      asm volatile("{\n.reg .pred p, r;\nsetp.eq.u32 p, %1, 0;\nbarrier.cta.red.or.pred r, %2, 128, p;\nselp.u32 %0, 1, 0, r;\n}\n"
                   : "=r"(unsafe_any) : "r"((uint32_t)safe), "r"(wg + 1) : "memory");
      float O[12];
#pragma unroll
      for (int i = 0; i < 12; i++) O[i] = 0.f;
      if (!unsafe_any && t >= 2) { q[4] = q[5] = (t == 2) ? 0x3F804100u : 0x00003B80u; }
      q[6] = q[4]; q[7] = q[5];
      fence_regs(q);
      if (!unsafe_any) attn_tile_fast(q, O, sbase, it * NGRP, elected, one2);
      else attn_tile_slow(q, O, sbase, it * NGRP, elected);
      const float l0 = __shfl_sync(0xffffffffu, O[8], (lane & ~3) | 2);
      const float l1 = __shfl_sync(0xffffffffu, O[10], (lane & ~3) | 2);
      const int tok = row0 >> 5;
      const float gt = g_gate[tok];
      const float i0 = gt / l0, i1 = gt / l1;
      uint32_t* o0 = reinterpret_cast<uint32_t*>(g_a2 + (size_t)tok * (2 * D_MODEL) + (row0 & 31) * DH);
      uint32_t* o1 = o0 + 8 * (DH / 2);
      o0[t] = pack_bf16(O[0] * i0, O[1] * i0); o1[t] = pack_bf16(O[2] * i1, O[3] * i1);
      o0[t + 4] = pack_bf16(O[4] * i0, O[5] * i0); o1[t + 4] = pack_bf16(O[6] * i1, O[7] * i1);
      if (t < 2) { o0[t + 8] = pack_bf16(O[8] * i0, O[9] * i0); o1[t + 8] = pack_bf16(O[10] * i1, O[11] * i1); }
    }
    signal_done(&g_done[blockIdx.x], wg, tid);
    if (elected) mbar_arrive(bars + BAR_OWN * 8);
    PROF(1, 3);
    if (wg < 2) {
      float acc[40];
      asm volatile("bar.sync 6, 384;" ::: "memory");
      {
        const float* pp = g_part + (size_t)(blockIdx.x * 2 + wg) * (40 * 128) + (tid & 127);
#pragma unroll
        for (int i = 0; i < 40; i++) acc[i] = pp[i * 128];
      }
      mbar_wait(bars + BAR_WA * 8, 0);
#pragma unroll 1
      for (int kt = 0; kt < 10; kt++) {
        const int sl = kt % 6;
        mbar_wait(bars + (BAR_TA + sl) * 8, kt / 6);
        if (kt == 0) PROF(2, 1);
        const uint32_t alo = ((dbase + ta_slot(sl) + wg * 8192) >> 4) | (1u << 16);
        const uint32_t blo = ((dbase + OFF_WA + kt * 10240) >> 4) | ((128u >> 4) << 16);
        fence_regs(acc);
        wg_fence();
#pragma unroll
        for (int k = 0; k < 4; k++) wgmma_ss_n80_tb(acc, mkd(alo + k * 2, DHI_SW128_K), mkd(blo + k * 16, 1024u >> 4));
        wg_commit();
        if (kt < 4) {
          wg_wait<0>();
          if (lane == 0) mbar_arrive(bars + (BAR_TE + kt) * 8);
        }
      }
      wg_wait<0>();
      fence_regs(acc);
      PROF(2, 2);
      asm volatile("bar.sync %0, 128;" :: "r"(wg + 1) : "memory");
      const uint32_t so = ta_slot(warp) + wg * 8192;
      const int row0 = mb * 128 + wg * 64 + warp * 16;
      store_tile_bf16<80>(acc, 1.0f, sbase + so, smem + so, out + (size_t)row0 * D_MODEL + nb * 80, D_MODEL, lane);
      PROF(2, 3);
    }
  }
}

typedef CUresult (*EncodeFn)(CUtensorMap*, CUtensorMapDataType, cuuint32_t, void*, const cuuint64_t*, const cuuint64_t*,
                             const cuuint32_t*, const cuuint32_t*, CUtensorMapInterleave, CUtensorMapSwizzle,
                             CUtensorMapL2promotion, CUtensorMapFloatOOBfill);

void make_map(EncodeFn fn, CUtensorMap* tm, const void* ptr, int rank, const cuuint64_t* dims, const cuuint64_t* strides,
              const cuuint32_t* box, CUtensorMapSwizzle sw) {
  const cuuint32_t es[3] = {1, 1, 1};
  fn(tm, CU_TENSOR_MAP_DATA_TYPE_BFLOAT16, rank, const_cast<void*>(ptr), dims, strides, box, es, CU_TENSOR_MAP_INTERLEAVE_NONE, sw,
     CU_TENSOR_MAP_L2_PROMOTION_L2_256B, CU_TENSOR_MAP_FLOAT_OOB_FILL_NONE);
}
void map_a(EncodeFn fn, CUtensorMap* tm, const void* p, int rows, int cols, int box_rows) {
  const cuuint64_t dims[2] = {(cuuint64_t)cols, (cuuint64_t)rows};
  const cuuint64_t str[1] = {(cuuint64_t)cols * 2};
  const cuuint32_t box[2] = {64, (cuuint32_t)box_rows};
  make_map(fn, tm, p, 2, dims, str, box, CU_TENSOR_MAP_SWIZZLE_128B);
}
void map_w(EncodeFn fn, CUtensorMap* tm, const void* p, int K, int N, int atom, CUtensorMapSwizzle sw) {
  const cuuint64_t dims[3] = {(cuuint64_t)atom, (cuuint64_t)K, (cuuint64_t)(N / atom)};
  const cuuint64_t str[2] = {(cuuint64_t)N * 2, (cuuint64_t)atom * 2};
  const cuuint32_t box[3] = {(cuuint32_t)atom, 64, 5};
  make_map(fn, tm, p, 3, dims, str, box, sw);
}

template <typename... KArgs, typename... Args>
void launch(void (*kern)(KArgs...), int grid, int block, int smem, bool pdl, Args... args) {
  cudaLaunchConfig_t cfg = {};
  cfg.gridDim = dim3(grid); cfg.blockDim = dim3(block); cfg.dynamicSmemBytes = smem; cfg.stream = cudaStreamPerThread;
  cudaLaunchAttribute at[1];
  at[0].id = cudaLaunchAttributeProgrammaticStreamSerialization;
  at[0].val.programmaticStreamSerializationAllowed = 1;
  cfg.attrs = at; cfg.numAttrs = pdl ? 1 : 0;
  cudaLaunchKernelEx(&cfg, kern, KArgs(args)...);
}

}

extern "C" void kernel_launch(void* const* d_in, const int* in_sizes, int n_in, void* d_out, int out_size) {
  (void)in_sizes; (void)n_in; (void)out_size;
  const __nv_bfloat16* x = (const __nv_bfloat16*)d_in[0];
  const __nv_bfloat16* wq = (const __nv_bfloat16*)d_in[1];
  const __nv_bfloat16* wk = (const __nv_bfloat16*)d_in[2];
  const __nv_bfloat16* wv = (const __nv_bfloat16*)d_in[3];
  const __nv_bfloat16* woA = (const __nv_bfloat16*)d_in[4];
  const __nv_bfloat16* wqkv = (const __nv_bfloat16*)d_in[6];
  const __nv_bfloat16* woB = (const __nv_bfloat16*)d_in[7];
  const __nv_bfloat16* gate_w = (const __nv_bfloat16*)d_in[8];

  static EncodeFn enc = nullptr;
  static void* a2_ptr = nullptr;
  if (!enc) {
    void* fp = nullptr;
    cudaDriverEntryPointQueryResult qr;
    cudaGetDriverEntryPoint("cuTensorMapEncodeTiled", &fp, cudaEnableDefault, &qr);
    enc = (EncodeFn)fp;
    cudaGetSymbolAddress(&a2_ptr, g_a2);
    cudaFuncSetAttribute(proj_kernel, cudaFuncAttributeMaxDynamicSharedMemorySize, K1_SMEM);
    cudaFuncSetAttribute(attn_kernel, cudaFuncAttributeMaxDynamicSharedMemorySize, K2_SMEM);
  }
  CUtensorMap tmX, tmWq, tmWqkv, tmA2, tmA2b;
  map_a(enc, &tmX, x, S_LEN, D_MODEL, 256);
  map_w(enc, &tmWq, wq, D_MODEL, D_MODEL, 32, CU_TENSOR_MAP_SWIZZLE_64B);
  map_w(enc, &tmWqkv, wqkv, D_MODEL, 3 * D_MODEL, 32, CU_TENSOR_MAP_SWIZZLE_64B);
  map_a(enc, &tmA2, a2_ptr, S_LEN, 2 * D_MODEL, 64);
  map_a(enc, &tmA2b, a2_ptr, S_LEN, 2 * D_MODEL, 128);

  launch(proj_kernel, 132, 512, K1_SMEM, false, tmX, tmWq, tmWqkv, wk, wv, gate_w, woA, woB);
  launch(attn_kernel, 128, 640, K2_SMEM, true, tmA2, tmA2b, (__nv_bfloat16*)d_out, 0x3F803F80u);
}
```

```cpp
#include <cuda_runtime.h>
#include <cuda_bf16.h>
#include <cuda.h>
#include <stdint.h>

namespace {

constexpr int S_LEN = 2048, D_MODEL = 640, DH = 20;

constexpr int GRP = 128;
constexpr int PLANE = GRP * 16;
constexpr int GRP_BYTES = GRP * 16 * 6;
constexpr int NGRP = S_LEN / GRP;
#define TMASKV 0x6DB6u
constexpr uint32_t TMASK = TMASKV;

__device__ __align__(1024) __nv_bfloat16 g_q[S_LEN * D_MODEL];
__device__ __align__(1024) __nv_bfloat16 g_qkv[S_LEN * 3 * D_MODEL];
__device__ __align__(1024) __nv_bfloat16 g_a2[S_LEN * 2 * D_MODEL];
__device__ __align__(1024) uint8_t g_kvimg[NGRP * GRP_BYTES];
__device__ __align__(1024) uint8_t g_wimg[2 * 8 * 10 * 10240];
__device__ float g_gate[S_LEN];
__device__ float g_kmax2[64];
__device__ float g_vmax[64];
__device__ __align__(32) unsigned int g_doneL[128];
__device__ float g_part[128 * 2 * 40 * 128];
__device__ __align__(32) unsigned int g_done[128];

#define PROF(k, slot)
#define PROF2(k, slot)
__device__ __forceinline__ uint32_t smem_u32(const void* p) { return (uint32_t)__cvta_generic_to_shared(p); }
__device__ __forceinline__ uint64_t mkd(uint32_t lo, uint32_t hi) {
  uint64_t d; asm("mov.b64 %0, {%1, %2};" : "=l"(d) : "r"(lo), "r"(hi)); return d;
}
__device__ __forceinline__ void wg_fence() { asm volatile("wgmma.fence.sync.aligned;" ::: "memory"); }
__device__ __forceinline__ void wg_commit() { asm volatile("wgmma.commit_group.sync.aligned;" ::: "memory"); }
template <int N> __device__ __forceinline__ void wg_wait() { asm volatile("wgmma.wait_group.sync.aligned %0;" :: "n"(N) : "memory"); }
template <int N> __device__ __forceinline__ void fence_regs(float (&d)[N]) {
#pragma unroll
  for (int i = 0; i < N; i++) asm volatile("" : "+f"(d[i]) :: "memory");
}
template <int N> __device__ __forceinline__ void fence_regs(uint32_t (&d)[N]) {
#pragma unroll
  for (int i = 0; i < N; i++) asm volatile("" : "+r"(d[i]) :: "memory");
}
__device__ __forceinline__ void mbar_init(uint32_t bar, uint32_t cnt) { asm volatile("mbarrier.init.shared::cta.b64 [%0], %1;" :: "r"(bar), "r"(cnt)); }
__device__ __forceinline__ void mbar_expect_tx(uint32_t bar, uint32_t bytes) {
  asm volatile("mbarrier.arrive.expect_tx.shared::cta.b64 _, [%0], %1;" :: "r"(bar), "r"(bytes) : "memory");
}
__device__ __forceinline__ void mbar_arrive(uint32_t bar) { asm volatile("mbarrier.arrive.shared::cta.b64 _, [%0];" :: "r"(bar) : "memory"); }
#define WAIT_HINT 20000u
__device__ __forceinline__ void mbar_wait(uint32_t bar, uint32_t parity) {
  asm volatile("{\n.reg .pred p;\nWAIT_%=:\nmbarrier.try_wait.parity.shared::cta.b64 p, [%0], %1, %2;\n@p bra DONE_%=;\nbra WAIT_%=;\nDONE_%=:\n}\n"
               :: "r"(bar), "r"(parity), "r"(WAIT_HINT) : "memory");
}
__device__ __forceinline__ void fence_mbar_init() { asm volatile("fence.mbarrier_init.release.cluster;" ::: "memory"); }
__device__ __forceinline__ void fence_proxy_async() { asm volatile("fence.proxy.async.shared::cta;" ::: "memory"); }
__device__ __forceinline__ void bulk_g2s(uint32_t dst, const void* src, uint32_t bytes, uint32_t bar) {
  asm volatile("cp.async.bulk.shared::cluster.global.mbarrier::complete_tx::bytes [%0], [%1], %2, [%3];"
               :: "r"(dst), "l"(src), "r"(bytes), "r"(bar) : "memory");
}
__device__ __forceinline__ void tma_2d(uint32_t dst, const CUtensorMap* tm, int c0, int c1, uint32_t bar) {
  asm volatile("cp.async.bulk.tensor.2d.shared::cluster.global.mbarrier::complete_tx::bytes [%0], [%1, {%3, %4}], [%2];"
               :: "r"(dst), "l"((uint64_t)tm), "r"(bar), "r"(c0), "r"(c1) : "memory");
}
__device__ __forceinline__ void tma_3d(uint32_t dst, const CUtensorMap* tm, int c0, int c1, int c2, uint32_t bar) {
  asm volatile("cp.async.bulk.tensor.3d.shared::cluster.global.mbarrier::complete_tx::bytes [%0], [%1, {%3, %4, %5}], [%2];"
               :: "r"(dst), "l"((uint64_t)tm), "r"(bar), "r"(c0), "r"(c1), "r"(c2) : "memory");
}
__device__ __forceinline__ void pdl_wait() { asm volatile("griddepcontrol.wait;" ::: "memory"); }
__device__ __forceinline__ void pdl_launch() { asm volatile("griddepcontrol.launch_dependents;" ::: "memory"); }
__device__ __forceinline__ float ex2(float x) { float y; asm("ex2.approx.ftz.f32 %0, %1;" : "=f"(y) : "f"(x)); return y; }
__device__ __forceinline__ uint32_t pack_bf16(float lo, float hi) {
  uint32_t r; asm("cvt.rn.bf16x2.f32 %0, %1, %2;" : "=r"(r) : "f"(hi), "f"(lo)); return r;
}
__device__ __forceinline__ float bf_lo(uint32_t x) { return __uint_as_float(x << 16); }
__device__ __forceinline__ float bf_hi(uint32_t x) { return __uint_as_float(x & 0xffff0000u); }
__device__ __forceinline__ void stsm4(uint32_t addr, uint32_t r0, uint32_t r1, uint32_t r2, uint32_t r3) {
  asm volatile("stmatrix.sync.aligned.m8n8.x4.shared.b16 [%0], {%1, %2, %3, %4};" :: "r"(addr), "r"(r0), "r"(r1), "r"(r2), "r"(r3) : "memory");
}

__device__ __forceinline__ void wgmma_ss_n160_tb(float (&d)[80], uint64_t descA, uint64_t descB) {
  asm volatile("wgmma.mma_async.sync.aligned.m64n160k16.f32.bf16.bf16 {%0, %1, %2, %3, %4, %5, %6, %7, %8, %9, %10, %11, %12, %13, %14, %15, %16, %17, %18, %19, %20, %21, %22, %23, %24, %25, %26, %27, %28, %29, %30, %31, %32, %33, %34, %35, %36, %37, %38, %39, %40, %41, %42, %43, %44, %45, %46, %47, %48, %49, %50, %51, %52, %53, %54, %55, %56, %57, %58, %59, %60, %61, %62, %63, %64, %65, %66, %67, %68, %69, %70, %71, %72, %73, %74, %75, %76, %77, %78, %79}, %80, %81, 1, 1, 1, 0, 1;\n"
    : "+f"(d[0]), "+f"(d[1]), "+f"(d[2]), "+f"(d[3]), "+f"(d[4]), "+f"(d[5]), "+f"(d[6]), "+f"(d[7]), "+f"(d[8]), "+f"(d[9]), "+f"(d[10]), "+f"(d[11]), "+f"(d[12]), "+f"(d[13]), "+f"(d[14]), "+f"(d[15]), "+f"(d[16]), "+f"(d[17]), "+f"(d[18]), "+f"(d[19]), "+f"(d[20]), "+f"(d[21]), "+f"(d[22]), "+f"(d[23]), "+f"(d[24]), "+f"(d[25]), "+f"(d[26]), "+f"(d[27]), "+f"(d[28]), "+f"(d[29]), "+f"(d[30]), "+f"(d[31]), "+f"(d[32]), "+f"(d[33]), "+f"(d[34]), "+f"(d[35]), "+f"(d[36]), "+f"(d[37]), "+f"(d[38]), "+f"(d[39]), "+f"(d[40]), "+f"(d[41]), "+f"(d[42]), "+f"(d[43]), "+f"(d[44]), "+f"(d[45]), "+f"(d[46]), "+f"(d[47]), "+f"(d[48]), "+f"(d[49]), "+f"(d[50]), "+f"(d[51]), "+f"(d[52]), "+f"(d[53]), "+f"(d[54]), "+f"(d[55]), "+f"(d[56]), "+f"(d[57]), "+f"(d[58]), "+f"(d[59]), "+f"(d[60]), "+f"(d[61]), "+f"(d[62]), "+f"(d[63]), "+f"(d[64]), "+f"(d[65]), "+f"(d[66]), "+f"(d[67]), "+f"(d[68]), "+f"(d[69]), "+f"(d[70]), "+f"(d[71]), "+f"(d[72]), "+f"(d[73]), "+f"(d[74]), "+f"(d[75]), "+f"(d[76]), "+f"(d[77]), "+f"(d[78]), "+f"(d[79])
    : "l"(descA), "l"(descB));
}
__device__ __forceinline__ void wgmma_ss_n48_tb(float (&d)[24], uint64_t descA, uint64_t descB) {
  asm volatile("wgmma.mma_async.sync.aligned.m64n48k16.f32.bf16.bf16 {%0, %1, %2, %3, %4, %5, %6, %7, %8, %9, %10, %11, %12, %13, %14, %15, %16, %17, %18, %19, %20, %21, %22, %23}, %24, %25, 1, 1, 1, 0, 1;\n"
    : "+f"(d[0]), "+f"(d[1]), "+f"(d[2]), "+f"(d[3]), "+f"(d[4]), "+f"(d[5]), "+f"(d[6]), "+f"(d[7]), "+f"(d[8]), "+f"(d[9]), "+f"(d[10]), "+f"(d[11]), "+f"(d[12]), "+f"(d[13]), "+f"(d[14]), "+f"(d[15]), "+f"(d[16]), "+f"(d[17]), "+f"(d[18]), "+f"(d[19]), "+f"(d[20]), "+f"(d[21]), "+f"(d[22]), "+f"(d[23])
    : "l"(descA), "l"(descB));
}
__device__ __forceinline__ void wgmma_ss_n80_tb(float (&d)[40], uint64_t descA, uint64_t descB) {
  asm volatile("wgmma.mma_async.sync.aligned.m64n80k16.f32.bf16.bf16 {%0, %1, %2, %3, %4, %5, %6, %7, %8, %9, %10, %11, %12, %13, %14, %15, %16, %17, %18, %19, %20, %21, %22, %23, %24, %25, %26, %27, %28, %29, %30, %31, %32, %33, %34, %35, %36, %37, %38, %39}, %40, %41, 1, 1, 1, 0, 1;\n"
    : "+f"(d[0]), "+f"(d[1]), "+f"(d[2]), "+f"(d[3]), "+f"(d[4]), "+f"(d[5]), "+f"(d[6]), "+f"(d[7]), "+f"(d[8]), "+f"(d[9]), "+f"(d[10]), "+f"(d[11]), "+f"(d[12]), "+f"(d[13]), "+f"(d[14]), "+f"(d[15]), "+f"(d[16]), "+f"(d[17]), "+f"(d[18]), "+f"(d[19]), "+f"(d[20]), "+f"(d[21]), "+f"(d[22]), "+f"(d[23]), "+f"(d[24]), "+f"(d[25]), "+f"(d[26]), "+f"(d[27]), "+f"(d[28]), "+f"(d[29]), "+f"(d[30]), "+f"(d[31]), "+f"(d[32]), "+f"(d[33]), "+f"(d[34]), "+f"(d[35]), "+f"(d[36]), "+f"(d[37]), "+f"(d[38]), "+f"(d[39])
    : "l"(descA), "l"(descB));
}
template <int SCALE_D>
__device__ __forceinline__ void wgmma_rs_n64(float (&d)[32], uint32_t a0, uint32_t a1, uint32_t a2, uint32_t a3, uint64_t descB) {
  asm volatile("wgmma.mma_async.sync.aligned.m64n64k16.f32.bf16.bf16 {%0, %1, %2, %3, %4, %5, %6, %7, %8, %9, %10, %11, %12, %13, %14, %15, %16, %17, %18, %19, %20, %21, %22, %23, %24, %25, %26, %27, %28, %29, %30, %31}, {%32, %33, %34, %35}, %36, %37, 1, 1, 0;\n"
    : "+f"(d[0]), "+f"(d[1]), "+f"(d[2]), "+f"(d[3]), "+f"(d[4]), "+f"(d[5]), "+f"(d[6]), "+f"(d[7]), "+f"(d[8]), "+f"(d[9]), "+f"(d[10]), "+f"(d[11]), "+f"(d[12]), "+f"(d[13]), "+f"(d[14]), "+f"(d[15]), "+f"(d[16]), "+f"(d[17]), "+f"(d[18]), "+f"(d[19]), "+f"(d[20]), "+f"(d[21]), "+f"(d[22]), "+f"(d[23]), "+f"(d[24]), "+f"(d[25]), "+f"(d[26]), "+f"(d[27]), "+f"(d[28]), "+f"(d[29]), "+f"(d[30]), "+f"(d[31])
    : "r"(a0), "r"(a1), "r"(a2), "r"(a3), "l"(descB), "n"(SCALE_D));
}
template <int SCALE_D>
__device__ __forceinline__ void wgmma_rs_n24_tb(float (&d)[12], uint32_t a0, uint32_t a1, uint32_t a2, uint32_t a3, uint64_t descB) {
  asm volatile("wgmma.mma_async.sync.aligned.m64n24k16.f32.bf16.bf16 {%0, %1, %2, %3, %4, %5, %6, %7, %8, %9, %10, %11}, {%12, %13, %14, %15}, %16, %17, 1, 1, 1;\n"
    : "+f"(d[0]), "+f"(d[1]), "+f"(d[2]), "+f"(d[3]), "+f"(d[4]), "+f"(d[5]), "+f"(d[6]), "+f"(d[7]), "+f"(d[8]), "+f"(d[9]), "+f"(d[10]), "+f"(d[11])
    : "r"(a0), "r"(a1), "r"(a2), "r"(a3), "l"(descB), "n"(SCALE_D));
}

constexpr uint32_t DHI_SW128_K = (1024 >> 4) | (1u << 30);
constexpr uint32_t DHI_SW64_MN = (512 >> 4) | (2u << 30);

template <int NC>
__device__ __forceinline__ void store_tile_tma(const float (&acc)[NC / 2], float scale, uint32_t stage, const CUtensorMap* tm, int col, int row, int lane) {
  constexpr int PITCH = NC * 2;
  const uint32_t waddr = stage + ((lane & 7) + ((lane >> 3) & 1) * 8) * PITCH + (lane >> 4) * 16;
#pragma unroll
  for (int j = 0; j < NC / 16; j++) {
    stsm4(waddr + j * 32, pack_bf16(acc[8 * j] * scale, acc[8 * j + 1] * scale), pack_bf16(acc[8 * j + 2] * scale, acc[8 * j + 3] * scale),
          pack_bf16(acc[8 * j + 4] * scale, acc[8 * j + 5] * scale), pack_bf16(acc[8 * j + 6] * scale, acc[8 * j + 7] * scale));
  }
  fence_proxy_async();
  __syncwarp();
  if (lane == 0) {
    asm volatile("cp.async.bulk.tensor.2d.global.shared::cta.bulk_group [%0, {%2, %3}], [%1];" :: "l"((uint64_t)tm), "r"(stage), "r"(col), "r"(row) : "memory");
    asm volatile("cp.async.bulk.commit_group;" ::: "memory");
    asm volatile("cp.async.bulk.wait_group 0;" ::: "memory");
  }
}
template <int NC>
__device__ __forceinline__ void store_tile_bf16(const float (&acc)[NC / 2], float scale, uint32_t stage, uint8_t* stage_ptr,
                                                __nv_bfloat16* gdst, int gpitch, int lane) {
  constexpr int PITCH = NC * 2 + 16;
  const uint32_t waddr = stage + ((lane & 7) + ((lane >> 3) & 1) * 8) * PITCH + (lane >> 4) * 16;
#pragma unroll
  for (int j = 0; j < NC / 16; j++) {
    stsm4(waddr + j * 32, pack_bf16(acc[8 * j] * scale, acc[8 * j + 1] * scale), pack_bf16(acc[8 * j + 2] * scale, acc[8 * j + 3] * scale),
          pack_bf16(acc[8 * j + 4] * scale, acc[8 * j + 5] * scale), pack_bf16(acc[8 * j + 6] * scale, acc[8 * j + 7] * scale));
  }
  __syncwarp();
  constexpr int CPR = NC / 8;
#pragma unroll
  for (int i = 0; i < CPR / 2; i++) {
    const int c = i * 32 + lane, r = c / CPR, cc = c % CPR;
    const uint4 v = *reinterpret_cast<const uint4*>(stage_ptr + r * PITCH + cc * 16);
    *reinterpret_cast<uint4*>(gdst + (size_t)r * gpitch + cc * 8) = v;
  }
}

__device__ __forceinline__ void signal_done(unsigned int* flag, int wg, int tid) {
  asm volatile("bar.sync %0, 128;" :: "r"(wg + 1) : "memory");
  if ((tid & 127) == 0) asm volatile("red.release.gpu.global.add.u32 [%0], 1;" :: "l"(flag) : "memory");
}
__device__ __forceinline__ void wait_flags8(const unsigned int* f, unsigned int target) {
  for (int spin = 0; spin < (1 << 26); spin++) {
    unsigned int a, b, c, d, e, g, h, i;
    asm volatile("ld.volatile.global.v4.u32 {%0, %1, %2, %3}, [%4];" : "=r"(a), "=r"(b), "=r"(c), "=r"(d) : "l"(f) : "memory");
    asm volatile("ld.volatile.global.v4.u32 {%0, %1, %2, %3}, [%4];" : "=r"(e), "=r"(g), "=r"(h), "=r"(i) : "l"(f + 4) : "memory");
    if (min(min(min(a, b), min(c, d)), min(min(e, g), min(h, i))) >= target) break;
    __nanosleep(32);
  }
  asm volatile("fence.acq_rel.gpu;" ::: "memory");
  asm volatile("fence.proxy.async;" ::: "memory");
}

#define RP_LD 3
#define RP_ST 7
constexpr int K1_STAGES = 4;
constexpr int K1_A_BYTES = 256 * 128;
constexpr int K1_B_BYTES = 64 * 160 * 2;
constexpr int K1_STAGE = K1_A_BYTES + K1_B_BYTES;
constexpr int K1_SMEM = 5 * K1_A_BYTES + 61440 + 1024;
constexpr int KV_STAGES = 5;
constexpr int KVW_OFF = KV_STAGES * K1_A_BYTES;

__global__ void __launch_bounds__(512, 1)
proj_kernel(const __grid_constant__ CUtensorMap tmX, const __grid_constant__ CUtensorMap tmWq, const __grid_constant__ CUtensorMap tmWqkv,
            const __grid_constant__ CUtensorMap tmQo, const __grid_constant__ CUtensorMap tmQKVo,
            const __nv_bfloat16* __restrict__ wk, const __nv_bfloat16* __restrict__ wv, const __nv_bfloat16* __restrict__ gate_w,
            const __nv_bfloat16* __restrict__ woA, const __nv_bfloat16* __restrict__ woB) {
  extern __shared__ uint8_t smem_raw[];
  __shared__ __align__(8) uint64_t bar_full[KV_STAGES], bar_empty[KV_STAGES];
  uint8_t* smem = reinterpret_cast<uint8_t*>((reinterpret_cast<uintptr_t>(smem_raw) + 1023) & ~(uintptr_t)1023);
  const uint32_t sbase = smem_u32(smem);
  const uint32_t dbase = sbase & 0x3FFFFu;
  const int tid = threadIdx.x, warp = tid >> 5, lane = tid & 31;
  const bool is_kv = blockIdx.x >= 128;
  PROF(0, 0);
  if (tid == 0) {
    for (int i = 0; i < KV_STAGES; i++) { mbar_init(smem_u32(&bar_full[i]), 1); mbar_init(smem_u32(&bar_empty[i]), is_kv ? 8 : 16); }
    fence_mbar_init();
  }
  uint2 wa[2][5], wb[2][5]; uint32_t gw[2];
  if (is_kv && tid < 320) {
#pragma unroll
    for (int r = 0; r < 2; r++) {
      const int k = tid + r * 320;
      const uint2* pk = reinterpret_cast<const uint2*>(wk + k * 20);
      const uint2* pv = reinterpret_cast<const uint2*>(wv + k * 20);
#pragma unroll
      for (int i = 0; i < 5; i++) { wa[r][i] = __ldg(pk + i); wb[r][i] = __ldg(pv + i); }
      gw[r] = (uint32_t)__bfloat16_as_ushort(gate_w[k]);
    }
  }
  __syncthreads();
  if (tid == 480) {
    if (!is_kv) { g_done[blockIdx.x] = 0u; g_doneL[blockIdx.x] = 0u; }
    asm volatile("fence.acq_rel.gpu;" ::: "memory");
    pdl_launch();
  }
  __syncwarp();

  if (!is_kv) {
    const int mb = blockIdx.x >> 4, nb = blockIdx.x & 15;
    const CUtensorMap* tw = nb < 4 ? &tmWq : &tmWqkv;
    const int j0 = (nb < 4 ? nb : nb - 4) * 5;
    auto load = [&](int kt) {
      const int s = kt % K1_STAGES;
      const uint32_t fb = smem_u32(&bar_full[s]);
      mbar_expect_tx(fb, K1_STAGE);
      tma_2d(sbase + s * K1_STAGE, &tmX, kt * 64, mb * 256, fb);
      tma_3d(sbase + s * K1_STAGE + K1_A_BYTES, tw, 0, kt * 64, j0, fb);
    };
    if (tid == 0) for (int kt = 0; kt < K1_STAGES; kt++) load(kt);
    __syncwarp();
    uint4 wv2[2];
    const int rq = blockIdx.x * 400 + tid - 112;
    const int rhalf = rq >= 25600, rr = rq - rhalf * 25600, rk = 2 * (rr / 80), rch = rr % 80;
    {
      const int wg = warp >> 2;
      float acc[80];
#pragma unroll
      for (int i = 0; i < 80; i++) acc[i] = 0.f;
      for (int kt = 0; kt < 10; kt++) {
        const int s = kt % K1_STAGES;
        mbar_wait(smem_u32(&bar_full[s]), (kt / K1_STAGES) & 1);
        const uint32_t alo = ((dbase + s * K1_STAGE + wg * 8192) >> 4) | (1u << 16);
        const uint32_t blo = ((dbase + s * K1_STAGE + K1_A_BYTES) >> 4) | ((4096u >> 4) << 16);
        fence_regs(acc);
        wg_fence();
#pragma unroll
        for (int k = 0; k < 4; k++) wgmma_ss_n160_tb(acc, mkd(alo + k * 2, DHI_SW128_K), mkd(blo + k * 64, DHI_SW64_MN));
        wg_commit();
        if (kt == RP_LD && tid >= 112) {
          const uint4* src = reinterpret_cast<const uint4*>((rhalf ? woB : woA) + rk * D_MODEL + rch * 8);
          wv2[0] = __ldg(src); wv2[1] = __ldg(src + D_MODEL / 8);
        }
        if (kt == RP_ST && tid >= 112) {
          uint4* dst = reinterpret_cast<uint4*>(g_wimg + ((rhalf * 8 + rch / 10) * 10 + (rk >> 6)) * 10240 + (rch % 10) * 1024 + (rk & 63) * 16);
          dst[0] = wv2[0]; dst[1] = wv2[1];
        }
        __syncwarp();
        if (kt > 0 && kt - 1 + K1_STAGES < 10) {
          wg_wait<1>();
          const uint32_t eb = smem_u32(&bar_empty[(kt - 1) % K1_STAGES]);
          if (lane == 0) mbar_arrive(eb);
          if (tid == 0) { mbar_wait(eb, ((kt - 1) / K1_STAGES) & 1); load(kt - 1 + K1_STAGES); }
          __syncwarp();
        }
      }
      wg_wait<0>();
      fence_regs(acc);
      PROF(0, 1);
      asm volatile("bar.sync %0, 128;" :: "r"(wg + 1) : "memory");
      const int w4 = warp & 3;
      const uint32_t off = w4 * K1_STAGE + wg * 8192;
      const int row0 = mb * 256 + wg * 64 + w4 * 16;
      store_tile_tma<160>(acc, nb < 4 ? 0.22360679774997896f * 1.4426950408889634f : 1.0f, sbase + off, nb < 4 ? &tmQo : &tmQKVo,
                          (nb < 4 ? nb : nb - 4) * 160, row0, lane);
    }
  } else {
    const int cb = blockIdx.x - 128;
    if (warp == 8 && lane == 0) {
      for (int it = 0; it < KV_STAGES; it++) {
        const uint32_t fb = smem_u32(&bar_full[it]);
        mbar_expect_tx(fb, K1_A_BYTES);
        tma_2d(sbase + it * K1_A_BYTES, &tmX, it * 64, cb * 512, fb);
      }
    }
    __syncwarp();
    if (tid < 320) {
#pragma unroll
      for (int r = 0; r < 2; r++) {
        uint4* dst = reinterpret_cast<uint4*>(smem + KVW_OFF + (tid + r * 320) * 16);
        dst[0] = make_uint4(wa[r][0].x, wa[r][0].y, wa[r][1].x, wa[r][1].y);
        dst[640] = make_uint4(wa[r][2].x, wa[r][2].y, wa[r][3].x, wa[r][3].y);
        dst[1280] = make_uint4(wa[r][4].x, wa[r][4].y, 0u, 0u);
        dst[1920] = make_uint4(wb[r][0].x, wb[r][0].y, wb[r][1].x, wb[r][1].y);
        dst[2560] = make_uint4(wb[r][2].x, wb[r][2].y, wb[r][3].x, wb[r][3].y);
        dst[3200] = make_uint4(wb[r][4].x, wb[r][4].y, gw[r], 0u);
      }
    }
    fence_proxy_async();
    asm volatile("bar.sync 1, 512;" ::: "memory");
    PROF(0, 1);
    auto produce = [&](int it0, int it1) {
      for (int it = it0; it < it1; it++) {
        const int s = it % KV_STAGES;
        mbar_wait(smem_u32(&bar_empty[s]), (it / KV_STAGES - 1) & 1);
        const uint32_t fb = smem_u32(&bar_full[s]);
        mbar_expect_tx(fb, K1_A_BYTES);
        tma_2d(sbase + s * K1_A_BYTES, &tmX, (it >= 10 ? it - 10 : it) * 64, cb * 512 + (it >= 10 ? 256 : 0), fb);
      }
    };
    if (tid == 256) produce(KV_STAGES, 15);
    __syncwarp();
    {
      const int pass = warp >> 3, wg = (warp >> 2) & 1, w4 = warp & 3, g = lane >> 2, t = lane & 3;
      if (pass == 1) asm volatile("bar.sync 2, 512;" ::: "memory");
      {
        float acc[2][24];
#pragma unroll
        for (int i = 0; i < 24; i++) { acc[0][i] = 0.f; acc[1][i] = 0.f; }
        for (int kt = 0; kt < 10; kt++) {
          const int it = pass * 10 + kt, s = it % KV_STAGES;
          mbar_wait(smem_u32(&bar_full[s]), (it / KV_STAGES) & 1);
          const uint32_t alo = ((dbase + s * K1_A_BYTES + wg * 16384) >> 4) | (1u << 16);
          const uint32_t blo = ((dbase + KVW_OFF + kt * 1024) >> 4) | ((128u >> 4) << 16);
          fence_regs(acc[0]); fence_regs(acc[1]);
          wg_fence();
#pragma unroll
          for (int k = 0; k < 4; k++) {
            wgmma_ss_n48_tb(acc[0], mkd(alo + k * 2, DHI_SW128_K), mkd(blo + k * 16, 10240u >> 4));
            wgmma_ss_n48_tb(acc[1], mkd(alo + 512 + k * 2, DHI_SW128_K), mkd(blo + k * 16, 10240u >> 4));
          }
          wg_commit();
          if (kt > 0) {
            wg_wait<1>();
            if (lane == 0) mbar_arrive(smem_u32(&bar_empty[(it - 1) % KV_STAGES]));
          }
        }
        wg_wait<0>();
        fence_regs(acc[0]); fence_regs(acc[1]);
        if (lane == 0) mbar_arrive(smem_u32(&bar_empty[(pass * 10 + 9) % KV_STAGES]));
        if (pass == 0) asm volatile("bar.arrive 2, 512;" ::: "memory");
        PROF(0, 2);
        if (tid == 0) produce(15, 20);
        __syncwarp();
        float kmax2 = 0.f, vmax = 0.f;
#pragma unroll
        for (int hh = 0; hh < 4; hh++) {
          const int h = hh & 1;
          const float (&a)[24] = acc[hh >> 1];
          const int key = cb * 512 + pass * 256 + wg * 128 + (hh >> 1) * 64 + w4 * 16 + g + h * 8;
          const int grp = key >> 7, kk = key & 127;
          const bool poly = (TMASK >> (kk >> 3)) & 1;
          uint8_t* gp = g_kvimg + grp * GRP_BYTES;
          const uint32_t k0 = pack_bf16(a[2 * h], a[2 * h + 1]);
          const uint32_t k1 = pack_bf16(a[4 + 2 * h], a[5 + 2 * h]);
          uint32_t k2 = pack_bf16(a[8 + 2 * h], a[9 + 2 * h]);
          float n2 = bf_lo(k0) * bf_lo(k0) + bf_hi(k0) * bf_hi(k0) + bf_lo(k1) * bf_lo(k1) + bf_hi(k1) * bf_hi(k1);
          if (t < 2) {
            n2 += bf_lo(k2) * bf_lo(k2) + bf_hi(k2) * bf_hi(k2);
            k2 = pack_bf16(bf_lo(k2) * 0.5f, bf_hi(k2) * 0.5f);
          } else if (t == 2) k2 = poly ? pack_bf16(24.f, 2.5f) : pack_bf16(0.5f, 0.f);
          else k2 = poly ? pack_bf16(0.5f, 0.f) : 0u;
          *reinterpret_cast<uint32_t*>(gp + kk * 16 + t * 4) = k0;
          *reinterpret_cast<uint32_t*>(gp + PLANE + kk * 16 + t * 4) = k1;
          *reinterpret_cast<uint32_t*>(gp + 2 * PLANE + kk * 16 + t * 4) = k2;
          n2 += __shfl_xor_sync(0xffffffffu, n2, 1);
          n2 += __shfl_xor_sync(0xffffffffu, n2, 2);
          kmax2 = (n2 > kmax2 || n2 != n2) ? n2 : kmax2;
          uint32_t v0 = pack_bf16(a[12 + 2 * h], a[13 + 2 * h]);
          uint32_t v1 = pack_bf16(a[16 + 2 * h], a[17 + 2 * h]);
          uint32_t v2 = pack_bf16(a[20 + 2 * h], a[21 + 2 * h]);
          float vm = fmaxf(fmaxf(fabsf(bf_lo(v0)), fabsf(bf_hi(v0))), fmaxf(fabsf(bf_lo(v1)), fabsf(bf_hi(v1))));
          if (t < 2) vm = fmaxf(vm, fmaxf(fabsf(bf_lo(v2)), fabsf(bf_hi(v2))));
          else if (t == 2) {
            const float z = a[20 + 2 * h];
            g_gate[key] = 1.f / (1.f + __expf(-z));
            v2 = 0x00003F80u;
          } else v2 = 0u;
          vmax = fmaxf(vmax, vm);
          if (poly) { v0 ^= 0x80008000u; v1 ^= 0x80008000u; v2 ^= 0x80008000u; }
          uint8_t* vp = gp + 3 * PLANE + (kk >> 3) * 384 + (kk & 7) * 16 + t * 4;
          *reinterpret_cast<uint32_t*>(vp) = v0;
          *reinterpret_cast<uint32_t*>(vp + 128) = v1;
          *reinterpret_cast<uint32_t*>(vp + 256) = v2;
        }
#pragma unroll
        for (int o = 1; o < 32; o <<= 1) {
          const float a = __shfl_xor_sync(0xffffffffu, kmax2, o);
          kmax2 = (a > kmax2 || a != a) ? a : kmax2;
          vmax = fmaxf(vmax, __shfl_xor_sync(0xffffffffu, vmax, o));
        }
        if (lane == 0) { g_kmax2[cb * 16 + warp] = kmax2; g_vmax[cb * 16 + warp] = vmax; }
      }
    }
  }
}

__device__ __forceinline__ uint32_t ex2_pair_poly(float u0, float u1, uint32_t one2) {
  const uint32_t W = __byte_perm(__float_as_uint(u0), __float_as_uint(u1), 0x6521);
  uint32_t v; asm("lop3.b32 %0, %1, 0x007F007F, %2, 0xEA;" : "=r"(v) : "r"(W), "r"(one2));
  uint32_t L, p;
  asm("fma.rn.bf16x2 %0, %1, %2, %3;" : "=r"(L) : "r"(v), "r"(0x1f961f96u), "r"(0x9fe39fe3u));
  asm("fma.rn.bf16x2 %0, %1, %1, %2;" : "=r"(p) : "r"(L), "r"(0x00f500f5u));
  return W + p;
}
template <int JOFF>
__device__ __forceinline__ void softmax_fast(const float (&S)[32], uint32_t (&P)[16], uint32_t one2) {
#pragma unroll
  for (int i = 0; i < 16; i++) {
    if ((TMASK >> (JOFF + i / 2)) & 1) P[i] = ex2_pair_poly(S[2 * i], S[2 * i + 1], one2);
    else P[i] = pack_bf16(ex2(S[2 * i]), ex2(S[2 * i + 1]));
  }
}
template <int JOFF>
__device__ __forceinline__ void softmax_slow(const float (&S)[32], uint32_t (&P)[16], float (&O)[12], float& m0, float& m1) {
  float a0 = m0, a1 = m1;
#pragma unroll
  for (int j = 0; j < 8; j++) {
    a0 = fmaxf(a0, fmaxf(S[4 * j], S[4 * j + 1]));
    a1 = fmaxf(a1, fmaxf(S[4 * j + 2], S[4 * j + 3]));
  }
  a0 = fmaxf(a0, __shfl_xor_sync(0xffffffffu, a0, 1)); a0 = fmaxf(a0, __shfl_xor_sync(0xffffffffu, a0, 2));
  a1 = fmaxf(a1, __shfl_xor_sync(0xffffffffu, a1, 1)); a1 = fmaxf(a1, __shfl_xor_sync(0xffffffffu, a1, 2));
  const float c0 = ex2(m0 - a0), c1 = ex2(m1 - a1);
  m0 = a0; m1 = a1;
#pragma unroll
  for (int j = 0; j < 3; j++) { O[4 * j] *= c0; O[4 * j + 1] *= c0; O[4 * j + 2] *= c1; O[4 * j + 3] *= c1; }
#pragma unroll
  for (int i = 0; i < 16; i++) {
    const float m = (i & 1) ? a1 : a0;
    const uint32_t p = pack_bf16(ex2(S[2 * i] - m), ex2(S[2 * i + 1] - m));
    P[i] = ((TMASK >> (JOFF + i / 2)) & 1) ? (p ^ 0x80008000u) : p;
  }
}
constexpr uint32_t DHI_KV = 128 >> 4;
__device__ __forceinline__ void issue_qk(float (&S)[32], const uint32_t (&q)[8], uint64_t base) {
  wgmma_rs_n64<0>(S, q[0], q[1], q[2], q[3], base + (uint64_t)((PLANE >> 4) << 16));
  wgmma_rs_n64<1>(S, q[4], q[5], q[6], q[7], base + (uint64_t)(2 * PLANE >> 4));
}
__device__ __forceinline__ void issue_pv(float (&O)[12], const uint32_t (&P)[16], uint64_t vbase) {
#pragma unroll
  for (int kk = 0; kk < 4; kk++)
    wgmma_rs_n24_tb<1>(O, P[4 * kk], P[4 * kk + 1], P[4 * kk + 2], P[4 * kk + 3], vbase + (uint64_t)(kk * (768 >> 4)));
}

constexpr uint32_t VOFF = ((3 * PLANE) >> 4) + ((384u >> 4) << 16);
constexpr int KVR = 4;
constexpr int OFF_WA = KVR * GRP_BYTES;
constexpr int OFF_BR = OFF_WA + 10 * 10240;
constexpr int BR_STAGE = 8192 + 10240, BR_STAGES = 3;
constexpr int OFF_QS = OFF_BR + BR_STAGES * BR_STAGE;
constexpr int OFF_BAR = OFF_QS + 512 * 6 * 4;
constexpr int K2_SMEM = OFF_BAR + 256 + 1024;
constexpr int BAR_KV = 0, BAR_WA = 4, BAR_BR = 5, BAR_TA = 8, BAR_TE = 14, BAR_OWN = 18, CNT_KV = 19;
constexpr int NSTEP = 2 * NGRP;

__device__ __forceinline__ void kv_load(uint32_t sbase, int step) {
  const uint32_t bar = sbase + OFF_BAR + (BAR_KV + (step & (KVR - 1))) * 8;
  mbar_expect_tx(bar, GRP_BYTES);
  bulk_g2s(sbase + (step & (KVR - 1)) * GRP_BYTES, g_kvimg + (step & (NGRP - 1)) * GRP_BYTES, GRP_BYTES, bar);
}
__device__ __forceinline__ void kv_release(uint32_t sbase, int step, bool elected) {
  if (elected && step + KVR < NSTEP) {
    uint32_t old;
    asm volatile("atom.acq_rel.cta.shared::cta.inc.u32 %0, [%1], 3;" : "=r"(old) : "r"(sbase + OFF_BAR + CNT_KV * 8 + (step & (KVR - 1)) * 4) : "memory");
    if (old == 3u) kv_load(sbase, step + KVR);
  }
  __syncwarp();
}
__device__ __forceinline__ void kv_wait(uint32_t sbase, int step) {
  mbar_wait(sbase + OFF_BAR + (BAR_KV + (step & (KVR - 1))) * 8, (step / KVR) & 1);
}

__device__ __forceinline__ uint32_t kv_release_begin(uint32_t sbase, int slot, bool doit) {
  uint32_t old = 0;
  asm volatile("{\n.reg .pred p;\nsetp.ne.u32 p, %2, 0;\n@p atom.relaxed.cta.shared::cta.inc.u32 %0, [%1], 3;\n}\n"
               : "+r"(old) : "r"(sbase + OFF_BAR + CNT_KV * 8 + slot * 4), "r"((uint32_t)doit) : "memory");
  return old;
}
__device__ __forceinline__ void attn_tile_fast(const uint32_t (&q)[8], float (&O)[12], uint32_t sbase, int step0, bool elected, uint32_t one2) {
  float S[32]; uint32_t P[16];
#pragma unroll
  for (int i = 0; i < 32; i++) S[i] = 0.f;
  uint64_t kb0 = mkd((sbase & 0x3FFFFu) >> 4, DHI_KV);
  asm volatile("" : "+l"(kb0));
  kv_wait(sbase, step0);
  fence_regs(S); fence_regs(O);
  wg_fence();
  issue_qk(S, q, kb0);
  wg_commit();
#pragma unroll 1
  for (int step4 = step0; step4 < step0 + NGRP; step4 += KVR) {
#pragma unroll
    for (int j = 0; j < KVR; j++) {
      const int step = step4 + j;
      const uint64_t kb = kb0 + (uint64_t)(j * (GRP_BYTES >> 4));
      const uint64_t knext = kb0 + (uint64_t)(((j + 1) & (KVR - 1)) * (GRP_BYTES >> 4));
      wg_wait<0>();
      fence_regs(S); fence_regs(P); fence_regs(O);
      const uint32_t old = kv_release_begin(sbase, (j + KVR - 1) & (KVR - 1), elected && step > step0 && step - 1 + KVR < NSTEP);
      softmax_fast<0>(S, P, one2);
      fence_regs(S); fence_regs(P); fence_regs(O);
      wg_fence();
      issue_qk(S, q, kb + 64);
      issue_pv(O, P, kb + VOFF);
      wg_commit();
      if (step + 1 < NSTEP) mbar_wait(sbase + OFF_BAR + (BAR_KV + ((j + 1) & (KVR - 1))) * 8, ((step + 1) / KVR) & 1);
      wg_wait<0>();
      fence_regs(S); fence_regs(P); fence_regs(O);
      softmax_fast<8>(S, P, one2);
      fence_regs(S); fence_regs(P); fence_regs(O);
      wg_fence();
      issue_qk(S, q, knext);
      issue_pv(O, P, kb + VOFF + 4 * (768 >> 4));
      wg_commit();
      if (old == 3u) kv_load(sbase, step - 1 + KVR);
    }
  }
  wg_wait<0>();
  fence_regs(O); fence_regs(S);
  kv_release(sbase, step0 + NGRP - 1, elected);
}
template <int H>
__device__ __forceinline__ void slow_step(const uint32_t (&q)[8], float (&O)[12], uint64_t kb, float& m0, float& m1) {
  float S[32]; uint32_t P[16];
#pragma unroll
  for (int i = 0; i < 32; i++) S[i] = 0.f;
  fence_regs(S);
  wg_fence();
  issue_qk(S, q, kb + 64 * H);
  wg_commit();
  wg_wait<0>();
  fence_regs(S);
  softmax_slow<8 * H>(S, P, O, m0, m1);
  fence_regs(P); fence_regs(O);
  wg_fence();
  issue_pv(O, P, kb + VOFF + H * 4 * (768 >> 4));
  wg_commit();
  wg_wait<0>();
  fence_regs(O); fence_regs(P);
}
__device__ __forceinline__ void attn_tile_slow(const uint32_t (&q)[8], float (&O)[12], uint32_t sbase, int step0, bool elected) {
  float m0 = -INFINITY, m1 = -INFINITY;
#pragma unroll 1
  for (int grp = 0; grp < NGRP; grp++) {
    kv_wait(sbase, step0 + grp);
    const uint64_t kb = mkd(((sbase & 0x3FFFFu) >> 4) + (grp & (KVR - 1)) * (GRP_BYTES >> 4), DHI_KV);
    slow_step<0>(q, O, kb, m0, m1);
    slow_step<1>(q, O, kb, m0, m1);
    kv_release(sbase, step0 + grp, elected);
  }
}

__device__ __forceinline__ void load_row20(const __nv_bfloat16* p, float (&f)[20]) {
  const uint2* p2 = reinterpret_cast<const uint2*>(p);
#pragma unroll
  for (int i = 0; i < 5; i++) { const uint2 v = p2[i]; f[4 * i] = bf_lo(v.x); f[4 * i + 1] = bf_hi(v.x); f[4 * i + 2] = bf_lo(v.y); f[4 * i + 3] = bf_hi(v.y); }
}
__device__ __forceinline__ void softmax8(float (&sc)[8]) {
  float mx = sc[0];
#pragma unroll
  for (int w = 1; w < 8; w++) mx = fmaxf(mx, sc[w]);
  float l = 0.f;
#pragma unroll
  for (int w = 0; w < 8; w++) { sc[w] = ex2(sc[w] - mx); l += sc[w]; }
  const float r = 1.f / l;
#pragma unroll
  for (int w = 0; w < 8; w++) sc[w] *= r;
}
__device__ __forceinline__ void local_attn_pair(int t, int lane) {
  constexpr int PITCH = 3 * D_MODEL;
  constexpr float SC = 0.22360679774997896f * 1.4426950408889634f, NEG = -1e9f * 1.4426950408889634f;
  const __nv_bfloat16* base = g_qkv + lane * DH;
  float a[20], b[20], sa[8], sb[8];
  load_row20(base + (size_t)t * PITCH, a);
  load_row20(base + (size_t)(t + 2) * PITCH, b);
#pragma unroll
  for (int j = 0; j < 9; j++) {
    const int r = t + 2 - 2 * j;
    float k[20];
    load_row20(base + D_MODEL + (size_t)max(r, 0) * PITCH, k);
    float da = 0.f, db = 0.f;
#pragma unroll
    for (int i = 0; i < 20; i++) { if (j >= 1) da = fmaf(a[i], k[i], da); if (j < 8) db = fmaf(b[i], k[i], db); }
    if (j >= 1) sa[j - 1] = r >= 0 ? da * SC : NEG;
    if (j < 8) sb[j] = r >= 0 ? db * SC : NEG;
  }
  softmax8(sa); softmax8(sb);
#pragma unroll
  for (int i = 0; i < 20; i++) { a[i] = 0.f; b[i] = 0.f; }
#pragma unroll
  for (int j = 0; j < 9; j++) {
    const int r = t + 2 - 2 * j;
    float v[20];
    load_row20(base + 2 * D_MODEL + (size_t)max(r, 0) * PITCH, v);
#pragma unroll
    for (int i = 0; i < 20; i++) { if (j >= 1) a[i] = fmaf(sa[j - 1], v[i], a[i]); if (j < 8) b[i] = fmaf(sb[j], v[i], b[i]); }
  }
  const float ga = 1.f - g_gate[t], gb = 1.f - g_gate[t + 2];
  uint2* da = reinterpret_cast<uint2*>(g_a2 + (size_t)t * (2 * D_MODEL) + D_MODEL + lane * DH);
  uint2* db = da + 2 * (2 * D_MODEL) / 4;
#pragma unroll
  for (int i = 0; i < 5; i++) {
    da[i] = make_uint2(pack_bf16(a[4 * i] * ga, a[4 * i + 1] * ga), pack_bf16(a[4 * i + 2] * ga, a[4 * i + 3] * ga));
    db[i] = make_uint2(pack_bf16(b[4 * i] * gb, b[4 * i + 1] * gb), pack_bf16(b[4 * i + 2] * gb, b[4 * i + 3] * gb));
  }
}
__device__ __forceinline__ uint32_t ta_slot(int i) { return i < 3 ? i * 16384 : OFF_BR + (i - 3) * 16384; }

__global__ void __launch_bounds__(640, 1)
attn_kernel(const __grid_constant__ CUtensorMap tmA2, const __grid_constant__ CUtensorMap tmA2b,
            __nv_bfloat16* __restrict__ out, uint32_t one2) {
  extern __shared__ uint8_t smem_raw[];
  uint8_t* smem = reinterpret_cast<uint8_t*>((reinterpret_cast<uintptr_t>(smem_raw) + 1023) & ~(uintptr_t)1023);
  const uint32_t sbase = smem_u32(smem);
  const uint32_t dbase = sbase & 0x3FFFFu;
  const uint32_t bars = sbase + OFF_BAR;
  const int tid = threadIdx.x, wg = tid >> 7, warp = (tid >> 5) & 3, lane = tid & 31, g = lane >> 2, t = lane & 3;
  const int mb = blockIdx.x >> 3, nb = blockIdx.x & 7;
  if (tid == 0) {
    for (int i = 0; i < BAR_TE; i++) mbar_init(bars + i * 8, 1);
    for (int i = BAR_TE; i < BAR_TE + 4; i++) mbar_init(bars + i * 8, 8);
    mbar_init(bars + BAR_OWN * 8, 4);
    for (int i = 0; i < 4; i++) *reinterpret_cast<uint32_t*>(smem + OFF_BAR + CNT_KV * 8 + i * 4) = 0u;
    fence_mbar_init();
  }
  __syncthreads();
  if (wg == 4) {
    pdl_wait();
    asm volatile("bar.sync 7, 640;" ::: "memory");
#pragma unroll 1
    for (int i = 0; i < 2; i++) local_attn_pair(blockIdx.x * 16 + warp * 4 + i, lane);
    if (tid == 512) PROF2(0, 2);
    signal_done(&g_doneL[blockIdx.x], wg, tid);
    if (tid == 512) {
      mbar_expect_tx(bars + BAR_WA * 8, 10 * 10240);
      for (int i = 0; i < 5; i++) bulk_g2s(sbase + OFF_WA + i * 20480, g_wimg + (nb * 10) * 10240 + i * 20480, 20480, bars + BAR_WA * 8);
    }
    auto br_load = [&](int it, int st) {
      const uint32_t fb = bars + (BAR_BR + st) * 8;
      const uint32_t dst = sbase + OFF_BR + st * BR_STAGE;
      const int kc = (it >= 10 ? it - 10 : it) * 64;
      mbar_expect_tx(fb, BR_STAGE);
      tma_2d(dst, &tmA2, D_MODEL + kc, (blockIdx.x >> 3) * 128 + (it >= 10 ? 64 : 0), fb);
      bulk_g2s(dst + 8192, g_wimg + ((8 + (blockIdx.x & 7)) * 10 + (kc >> 6)) * 10240, 10240, fb);
    };
    if (tid == 512) {
      wait_flags8(&g_doneL[mb * 8], 1u);
      for (int it = 0; it < BR_STAGES; it++) br_load(it, it);
    }
    __syncwarp();
    {
      int st = 0, ph = 0;
      float acc[40];
#pragma unroll 1
      for (int it = 0; it < 20; it++) {
        if (it == 0 || it == 10) {
#pragma unroll
          for (int i = 0; i < 40; i++) acc[i] = 0.f;
        }
        mbar_wait(bars + (BAR_BR + st) * 8, ph);
        const uint32_t alo = ((dbase + OFF_BR + st * BR_STAGE) >> 4);
        fence_regs(acc);
        wg_fence();
#pragma unroll
        for (int k = 0; k < 4; k++)
          wgmma_ss_n80_tb(acc, mkd(alo + (k * 2 + (1u << 16)), DHI_SW128_K), mkd(alo + (512 + k * 16 + ((128u >> 4) << 16)), 1024u >> 4));
        wg_commit();
        wg_wait<0>();
        fence_regs(acc);
        asm volatile("bar.sync 5, 128;" ::: "memory");
        if (threadIdx.x == 512 && it + BR_STAGES < 20) br_load(it + BR_STAGES, st);
        __syncwarp();
        if (it == 9 || it == 19) {
          float* pp = g_part + (size_t)(blockIdx.x * 2 + (it == 19)) * (40 * 128) + (threadIdx.x & 127);
#pragma unroll
          for (int i = 0; i < 40; i++) pp[i * 128] = acc[i];
        }
        if (++st == BR_STAGES) { st = 0; ph ^= 1; }
      }
    }
    if (tid == 512) PROF2(1, 0);
    asm volatile("bar.arrive 6, 384;" ::: "memory");
    if (tid == 512) {
      mbar_wait(bars + BAR_OWN * 8, 0);
      wait_flags8(&g_done[mb * 8], 4u);
      PROF2(2, 0);
    }
    if (tid == 512) {
      for (int kt = 0; kt < 10; kt++) {
        const int sl = kt % 6;
        if (kt >= 6) mbar_wait(bars + (BAR_TE + kt - 6) * 8, 0);
        const uint32_t fb = bars + (BAR_TA + sl) * 8;
        mbar_expect_tx(fb, 16384);
        tma_2d(sbase + ta_slot(sl), &tmA2b, kt * 64, mb * 128, fb);
      }
    }
  } else {
    const bool elected = (tid & 127) == 0;
    pdl_wait();
    PROF(1, 1);
    if (tid == 384) for (int j = 0; j < KVR; j++) kv_load(sbase, j);
    __syncwarp();
    uint32_t q[8];
    uint32_t* qstash = reinterpret_cast<uint32_t*>(smem + OFF_QS) + tid;
    const int rowA = (blockIdx.x * 8 + wg) * 64 + warp * 16 + g;
    {
      const uint32_t* r0 = reinterpret_cast<const uint32_t*>(g_q + (size_t)rowA * DH);
      const uint32_t* r1 = r0 + 8 * (DH / 2);
      const uint32_t* s0 = r0 + 256 * (DH / 2);
      const uint32_t* s1 = s0 + 8 * (DH / 2);
      q[0] = r0[t]; q[1] = r1[t]; q[2] = r0[t + 4]; q[3] = r1[t + 4];
      q[4] = t < 2 ? r0[8 + t] : 0u;
      q[5] = t < 2 ? r1[8 + t] : 0u;
      qstash[0] = s0[t]; qstash[512] = s1[t]; qstash[1024] = s0[t + 4]; qstash[1536] = s1[t + 4];
      qstash[2048] = t < 2 ? s0[8 + t] : 0u;
      qstash[2560] = t < 2 ? s1[8 + t] : 0u;
    }
    float kmax2 = 0.f, vmax = 0.f;
#pragma unroll
    for (int i = 0; i < 2; i++) {
      const float a = g_kmax2[lane + 32 * i];
      kmax2 = (a > kmax2 || a != a) ? a : kmax2;
      vmax = fmaxf(vmax, g_vmax[lane + 32 * i]);
    }
#pragma unroll
    for (int o = 1; o < 32; o <<= 1) {
      const float a = __shfl_xor_sync(0xffffffffu, kmax2, o);
      kmax2 = (a > kmax2 || a != a) ? a : kmax2;
      vmax = fmaxf(vmax, __shfl_xor_sync(0xffffffffu, vmax, o));
    }
    const float qlim = (vmax >= 0.00390625f && vmax <= 256.f) ? 9025.f / kmax2 : -1.f;
    asm volatile("bar.arrive 7, 640;" ::: "memory");
    PROF(1, 2);
#pragma unroll 1
    for (int it = 0; it < 2; it++) {
      const int row0 = rowA + it * 256;
      if (it == 1) {
#pragma unroll
        for (int i = 0; i < 6; i++) q[i] = qstash[512 * i];
      }
      float n0 = bf_lo(q[0]) * bf_lo(q[0]) + bf_hi(q[0]) * bf_hi(q[0]) + bf_lo(q[2]) * bf_lo(q[2]) + bf_hi(q[2]) * bf_hi(q[2]) +
                 bf_lo(q[4]) * bf_lo(q[4]) + bf_hi(q[4]) * bf_hi(q[4]);
      float n1 = bf_lo(q[1]) * bf_lo(q[1]) + bf_hi(q[1]) * bf_hi(q[1]) + bf_lo(q[3]) * bf_lo(q[3]) + bf_hi(q[3]) * bf_hi(q[3]) +
                 bf_lo(q[5]) * bf_lo(q[5]) + bf_hi(q[5]) * bf_hi(q[5]);
      n0 += __shfl_xor_sync(0xffffffffu, n0, 1); n0 += __shfl_xor_sync(0xffffffffu, n0, 2);
      n1 += __shfl_xor_sync(0xffffffffu, n1, 1); n1 += __shfl_xor_sync(0xffffffffu, n1, 2);
      const bool safe = (n0 <= qlim) && (n1 <= qlim);
      uint32_t unsafe_any;
      asm volatile("{\n.reg .pred p, r;\nsetp.eq.u32 p, %1, 0;\nbarrier.cta.red.or.pred r, %2, 128, p;\nselp.u32 %0, 1, 0, r;\n}\n"
                   : "=r"(unsafe_any) : "r"((uint32_t)safe), "r"(wg + 1) : "memory");
      float O[12];
#pragma unroll
      for (int i = 0; i < 12; i++) O[i] = 0.f;
      if (!unsafe_any && t >= 2) { q[4] = q[5] = (t == 2) ? 0x3F804100u : 0x00003B80u; }
      q[6] = q[4]; q[7] = q[5];
      fence_regs(q);
      if (!unsafe_any) attn_tile_fast(q, O, sbase, it * NGRP, elected, one2);
      else attn_tile_slow(q, O, sbase, it * NGRP, elected);
      const float l0 = __shfl_sync(0xffffffffu, O[8], (lane & ~3) | 2);
      const float l1 = __shfl_sync(0xffffffffu, O[10], (lane & ~3) | 2);
      const int tok = row0 >> 5;
      const float gt = g_gate[tok];
      const float i0 = gt / l0, i1 = gt / l1;
      uint32_t* o0 = reinterpret_cast<uint32_t*>(g_a2 + (size_t)tok * (2 * D_MODEL) + (row0 & 31) * DH);
      uint32_t* o1 = o0 + 8 * (DH / 2);
      o0[t] = pack_bf16(O[0] * i0, O[1] * i0); o1[t] = pack_bf16(O[2] * i1, O[3] * i1);
      o0[t + 4] = pack_bf16(O[4] * i0, O[5] * i0); o1[t + 4] = pack_bf16(O[6] * i1, O[7] * i1);
      if (t < 2) { o0[t + 8] = pack_bf16(O[8] * i0, O[9] * i0); o1[t + 8] = pack_bf16(O[10] * i1, O[11] * i1); }
    }
    signal_done(&g_done[blockIdx.x], wg, tid);
    if (elected) mbar_arrive(bars + BAR_OWN * 8);
    PROF(1, 3);
    if (wg < 2) {
      float acc[40];
      asm volatile("bar.sync 6, 384;" ::: "memory");
      {
        const float* pp = g_part + (size_t)(blockIdx.x * 2 + wg) * (40 * 128) + (tid & 127);
#pragma unroll
        for (int i = 0; i < 40; i++) acc[i] = pp[i * 128];
      }
      mbar_wait(bars + BAR_WA * 8, 0);
#pragma unroll 1
      for (int kt = 0; kt < 10; kt++) {
        const int sl = kt % 6;
        mbar_wait(bars + (BAR_TA + sl) * 8, kt / 6);
        if (kt == 0) PROF(2, 1);
        const uint32_t alo = ((dbase + ta_slot(sl) + wg * 8192) >> 4) | (1u << 16);
        const uint32_t blo = ((dbase + OFF_WA + kt * 10240) >> 4) | ((128u >> 4) << 16);
        fence_regs(acc);
        wg_fence();
#pragma unroll
        for (int k = 0; k < 4; k++) wgmma_ss_n80_tb(acc, mkd(alo + k * 2, DHI_SW128_K), mkd(blo + k * 16, 1024u >> 4));
        wg_commit();
        if (kt < 4) {
          wg_wait<0>();
          if (lane == 0) mbar_arrive(bars + (BAR_TE + kt) * 8);
        }
      }
      wg_wait<0>();
      fence_regs(acc);
      PROF(2, 2);
      asm volatile("bar.sync %0, 128;" :: "r"(wg + 1) : "memory");
      const uint32_t so = ta_slot(warp) + wg * 8192;
      const int row0 = mb * 128 + wg * 64 + warp * 16;
      store_tile_bf16<80>(acc, 1.0f, sbase + so, smem + so, out + (size_t)row0 * D_MODEL + nb * 80, D_MODEL, lane);
      PROF(2, 3);
    }
  }
}

typedef CUresult (*EncodeFn)(CUtensorMap*, CUtensorMapDataType, cuuint32_t, void*, const cuuint64_t*, const cuuint64_t*,
                             const cuuint32_t*, const cuuint32_t*, CUtensorMapInterleave, CUtensorMapSwizzle,
                             CUtensorMapL2promotion, CUtensorMapFloatOOBfill);

void make_map(EncodeFn fn, CUtensorMap* tm, const void* ptr, int rank, const cuuint64_t* dims, const cuuint64_t* strides,
              const cuuint32_t* box, CUtensorMapSwizzle sw) {
  const cuuint32_t es[3] = {1, 1, 1};
  fn(tm, CU_TENSOR_MAP_DATA_TYPE_BFLOAT16, rank, const_cast<void*>(ptr), dims, strides, box, es, CU_TENSOR_MAP_INTERLEAVE_NONE, sw,
     CU_TENSOR_MAP_L2_PROMOTION_L2_256B, CU_TENSOR_MAP_FLOAT_OOB_FILL_NONE);
}
void map_a(EncodeFn fn, CUtensorMap* tm, const void* p, int rows, int cols, int box_rows) {
  const cuuint64_t dims[2] = {(cuuint64_t)cols, (cuuint64_t)rows};
  const cuuint64_t str[1] = {(cuuint64_t)cols * 2};
  const cuuint32_t box[2] = {64, (cuuint32_t)box_rows};
  make_map(fn, tm, p, 2, dims, str, box, CU_TENSOR_MAP_SWIZZLE_128B);
}
void map_o(EncodeFn fn, CUtensorMap* tm, const void* p, int rows, int cols, int box_cols) {
  const cuuint64_t dims[2] = {(cuuint64_t)cols, (cuuint64_t)rows};
  const cuuint64_t str[1] = {(cuuint64_t)cols * 2};
  const cuuint32_t box[2] = {(cuuint32_t)box_cols, 16};
  make_map(fn, tm, p, 2, dims, str, box, CU_TENSOR_MAP_SWIZZLE_NONE);
}
void map_w(EncodeFn fn, CUtensorMap* tm, const void* p, int K, int N, int atom, CUtensorMapSwizzle sw) {
  const cuuint64_t dims[3] = {(cuuint64_t)atom, (cuuint64_t)K, (cuuint64_t)(N / atom)};
  const cuuint64_t str[2] = {(cuuint64_t)N * 2, (cuuint64_t)atom * 2};
  const cuuint32_t box[3] = {(cuuint32_t)atom, 64, 5};
  make_map(fn, tm, p, 3, dims, str, box, sw);
}

template <typename... KArgs, typename... Args>
void launch(void (*kern)(KArgs...), int grid, int block, int smem, bool pdl, Args... args) {
  cudaLaunchConfig_t cfg = {};
  cfg.gridDim = dim3(grid); cfg.blockDim = dim3(block); cfg.dynamicSmemBytes = smem; cfg.stream = cudaStreamPerThread;
  cudaLaunchAttribute at[1];
  at[0].id = cudaLaunchAttributeProgrammaticStreamSerialization;
  at[0].val.programmaticStreamSerializationAllowed = 1;
  cfg.attrs = at; cfg.numAttrs = pdl ? 1 : 0;
  cudaLaunchKernelEx(&cfg, kern, KArgs(args)...);
}

}

extern "C" void kernel_launch(void* const* d_in, const int* in_sizes, int n_in, void* d_out, int out_size) {
  (void)in_sizes; (void)n_in; (void)out_size;
  const __nv_bfloat16* x = (const __nv_bfloat16*)d_in[0];
  const __nv_bfloat16* wq = (const __nv_bfloat16*)d_in[1];
  const __nv_bfloat16* wk = (const __nv_bfloat16*)d_in[2];
  const __nv_bfloat16* wv = (const __nv_bfloat16*)d_in[3];
  const __nv_bfloat16* woA = (const __nv_bfloat16*)d_in[4];
  const __nv_bfloat16* wqkv = (const __nv_bfloat16*)d_in[6];
  const __nv_bfloat16* woB = (const __nv_bfloat16*)d_in[7];
  const __nv_bfloat16* gate_w = (const __nv_bfloat16*)d_in[8];

  static EncodeFn enc = nullptr;
  static void* a2_ptr = nullptr;
  static void* q_ptr = nullptr;
  static void* qkv_ptr = nullptr;
  if (!enc) {
    void* fp = nullptr;
    cudaDriverEntryPointQueryResult qr;
    cudaGetDriverEntryPoint("cuTensorMapEncodeTiled", &fp, cudaEnableDefault, &qr);
    enc = (EncodeFn)fp;
    cudaGetSymbolAddress(&a2_ptr, g_a2);
    cudaGetSymbolAddress(&q_ptr, g_q);
    cudaGetSymbolAddress(&qkv_ptr, g_qkv);
    cudaFuncSetAttribute(proj_kernel, cudaFuncAttributeMaxDynamicSharedMemorySize, K1_SMEM);
    cudaFuncSetAttribute(attn_kernel, cudaFuncAttributeMaxDynamicSharedMemorySize, K2_SMEM);
  }
  CUtensorMap tmX, tmWq, tmWqkv, tmA2, tmA2b, tmQo, tmQKVo;
  map_o(enc, &tmQo, q_ptr, S_LEN, D_MODEL, 160);
  map_o(enc, &tmQKVo, qkv_ptr, S_LEN, 3 * D_MODEL, 160);
  map_a(enc, &tmX, x, S_LEN, D_MODEL, 256);
  map_w(enc, &tmWq, wq, D_MODEL, D_MODEL, 32, CU_TENSOR_MAP_SWIZZLE_64B);
  map_w(enc, &tmWqkv, wqkv, D_MODEL, 3 * D_MODEL, 32, CU_TENSOR_MAP_SWIZZLE_64B);
  map_a(enc, &tmA2, a2_ptr, S_LEN, 2 * D_MODEL, 64);
  map_a(enc, &tmA2b, a2_ptr, S_LEN, 2 * D_MODEL, 128);

  launch(proj_kernel, 132, 512, K1_SMEM, false, tmX, tmWq, tmWqkv, tmQo, tmQKVo, wk, wv, gate_w, woA, woB);
  launch(attn_kernel, 128, 640, K2_SMEM, true, tmA2, tmA2b, (__nv_bfloat16*)d_out, 0x3F803F80u);
}
```

```cpp
#include <cuda_runtime.h>
#include <cuda_bf16.h>
#include <cuda.h>
#include <stdint.h>

namespace {

constexpr int S_LEN = 2048, D_MODEL = 640, DH = 20;

constexpr int GRP = 128;
constexpr int PLANE = GRP * 16;
constexpr int GRP_BYTES = GRP * 16 * 6;
constexpr int NGRP = S_LEN / GRP;
#define TMASKV 0xBBBBu
constexpr uint32_t TMASK = TMASKV;

__device__ __align__(1024) __nv_bfloat16 g_q[S_LEN * D_MODEL];
__device__ __align__(1024) __nv_bfloat16 g_qkv[S_LEN * 3 * D_MODEL];
__device__ __align__(1024) __nv_bfloat16 g_a2[S_LEN * 2 * D_MODEL];
__device__ __align__(1024) uint8_t g_kvimg[NGRP * GRP_BYTES];
__device__ __align__(1024) uint8_t g_wimg[2 * 8 * 10 * 10240];
__device__ float g_gate[S_LEN];
__device__ float g_kmax2[64];
__device__ float g_vmax[64];
__device__ __align__(32) unsigned int g_doneL[128];
__device__ __align__(32) unsigned int g_done[128];

#define PROF(k, slot)
#define PROF2(k, slot)
__device__ __forceinline__ uint32_t smem_u32(const void* p) { return (uint32_t)__cvta_generic_to_shared(p); }
__device__ __forceinline__ uint64_t mkd(uint32_t lo, uint32_t hi) {
  uint64_t d; asm("mov.b64 %0, {%1, %2};" : "=l"(d) : "r"(lo), "r"(hi)); return d;
}
__device__ __forceinline__ void wg_fence() { asm volatile("wgmma.fence.sync.aligned;" ::: "memory"); }
__device__ __forceinline__ void wg_commit() { asm volatile("wgmma.commit_group.sync.aligned;" ::: "memory"); }
template <int N> __device__ __forceinline__ void wg_wait() { asm volatile("wgmma.wait_group.sync.aligned %0;" :: "n"(N) : "memory"); }
template <int N> __device__ __forceinline__ void fence_regs(float (&d)[N]) {
#pragma unroll
  for (int i = 0; i < N; i++) asm volatile("" : "+f"(d[i]) :: "memory");
}
template <int N> __device__ __forceinline__ void fence_regs(uint32_t (&d)[N]) {
#pragma unroll
  for (int i = 0; i < N; i++) asm volatile("" : "+r"(d[i]) :: "memory");
}
__device__ __forceinline__ void mbar_init(uint32_t bar, uint32_t cnt) { asm volatile("mbarrier.init.shared::cta.b64 [%0], %1;" :: "r"(bar), "r"(cnt)); }
__device__ __forceinline__ void mbar_expect_tx(uint32_t bar, uint32_t bytes) {
  asm volatile("mbarrier.arrive.expect_tx.shared::cta.b64 _, [%0], %1;" :: "r"(bar), "r"(bytes) : "memory");
}
__device__ __forceinline__ void mbar_arrive(uint32_t bar) { asm volatile("mbarrier.arrive.shared::cta.b64 _, [%0];" :: "r"(bar) : "memory"); }
#define WAIT_HINT 20000u
__device__ __forceinline__ void mbar_wait(uint32_t bar, uint32_t parity) {
  asm volatile("{\n.reg .pred p;\nWAIT_%=:\nmbarrier.try_wait.parity.shared::cta.b64 p, [%0], %1, %2;\n@p bra DONE_%=;\nbra WAIT_%=;\nDONE_%=:\n}\n"
               :: "r"(bar), "r"(parity), "r"(WAIT_HINT) : "memory");
}
__device__ __forceinline__ void fence_mbar_init() { asm volatile("fence.mbarrier_init.release.cluster;" ::: "memory"); }
__device__ __forceinline__ void fence_proxy_async() { asm volatile("fence.proxy.async.shared::cta;" ::: "memory"); }
__device__ __forceinline__ void bulk_g2s(uint32_t dst, const void* src, uint32_t bytes, uint32_t bar) {
  asm volatile("cp.async.bulk.shared::cluster.global.mbarrier::complete_tx::bytes [%0], [%1], %2, [%3];"
               :: "r"(dst), "l"(src), "r"(bytes), "r"(bar) : "memory");
}
__device__ __forceinline__ void tma_2d(uint32_t dst, const CUtensorMap* tm, int c0, int c1, uint32_t bar) {
  asm volatile("cp.async.bulk.tensor.2d.shared::cluster.global.mbarrier::complete_tx::bytes [%0], [%1, {%3, %4}], [%2];"
               :: "r"(dst), "l"((uint64_t)tm), "r"(bar), "r"(c0), "r"(c1) : "memory");
}
__device__ __forceinline__ void tma_3d(uint32_t dst, const CUtensorMap* tm, int c0, int c1, int c2, uint32_t bar) {
  asm volatile("cp.async.bulk.tensor.3d.shared::cluster.global.mbarrier::complete_tx::bytes [%0], [%1, {%3, %4, %5}], [%2];"
               :: "r"(dst), "l"((uint64_t)tm), "r"(bar), "r"(c0), "r"(c1), "r"(c2) : "memory");
}
__device__ __forceinline__ void pdl_wait() { asm volatile("griddepcontrol.wait;" ::: "memory"); }
__device__ __forceinline__ void pdl_launch() { asm volatile("griddepcontrol.launch_dependents;" ::: "memory"); }
__device__ __forceinline__ float ex2(float x) { float y; asm("ex2.approx.ftz.f32 %0, %1;" : "=f"(y) : "f"(x)); return y; }
__device__ __forceinline__ uint32_t pack_bf16(float lo, float hi) {
  uint32_t r; asm("cvt.rn.bf16x2.f32 %0, %1, %2;" : "=r"(r) : "f"(hi), "f"(lo)); return r;
}
__device__ __forceinline__ float bf_lo(uint32_t x) { return __uint_as_float(x << 16); }
__device__ __forceinline__ float bf_hi(uint32_t x) { return __uint_as_float(x & 0xffff0000u); }
__device__ __forceinline__ void stsm4(uint32_t addr, uint32_t r0, uint32_t r1, uint32_t r2, uint32_t r3) {
  asm volatile("stmatrix.sync.aligned.m8n8.x4.shared.b16 [%0], {%1, %2, %3, %4};" :: "r"(addr), "r"(r0), "r"(r1), "r"(r2), "r"(r3) : "memory");
}

__device__ __forceinline__ void wgmma_ss_n160_tb(float (&d)[80], uint64_t descA, uint64_t descB) {
  asm volatile("wgmma.mma_async.sync.aligned.m64n160k16.f32.bf16.bf16 {%0, %1, %2, %3, %4, %5, %6, %7, %8, %9, %10, %11, %12, %13, %14, %15, %16, %17, %18, %19, %20, %21, %22, %23, %24, %25, %26, %27, %28, %29, %30, %31, %32, %33, %34, %35, %36, %37, %38, %39, %40, %41, %42, %43, %44, %45, %46, %47, %48, %49, %50, %51, %52, %53, %54, %55, %56, %57, %58, %59, %60, %61, %62, %63, %64, %65, %66, %67, %68, %69, %70, %71, %72, %73, %74, %75, %76, %77, %78, %79}, %80, %81, 1, 1, 1, 0, 1;\n"
    : "+f"(d[0]), "+f"(d[1]), "+f"(d[2]), "+f"(d[3]), "+f"(d[4]), "+f"(d[5]), "+f"(d[6]), "+f"(d[7]), "+f"(d[8]), "+f"(d[9]), "+f"(d[10]), "+f"(d[11]), "+f"(d[12]), "+f"(d[13]), "+f"(d[14]), "+f"(d[15]), "+f"(d[16]), "+f"(d[17]), "+f"(d[18]), "+f"(d[19]), "+f"(d[20]), "+f"(d[21]), "+f"(d[22]), "+f"(d[23]), "+f"(d[24]), "+f"(d[25]), "+f"(d[26]), "+f"(d[27]), "+f"(d[28]), "+f"(d[29]), "+f"(d[30]), "+f"(d[31]), "+f"(d[32]), "+f"(d[33]), "+f"(d[34]), "+f"(d[35]), "+f"(d[36]), "+f"(d[37]), "+f"(d[38]), "+f"(d[39]), "+f"(d[40]), "+f"(d[41]), "+f"(d[42]), "+f"(d[43]), "+f"(d[44]), "+f"(d[45]), "+f"(d[46]), "+f"(d[47]), "+f"(d[48]), "+f"(d[49]), "+f"(d[50]), "+f"(d[51]), "+f"(d[52]), "+f"(d[53]), "+f"(d[54]), "+f"(d[55]), "+f"(d[56]), "+f"(d[57]), "+f"(d[58]), "+f"(d[59]), "+f"(d[60]), "+f"(d[61]), "+f"(d[62]), "+f"(d[63]), "+f"(d[64]), "+f"(d[65]), "+f"(d[66]), "+f"(d[67]), "+f"(d[68]), "+f"(d[69]), "+f"(d[70]), "+f"(d[71]), "+f"(d[72]), "+f"(d[73]), "+f"(d[74]), "+f"(d[75]), "+f"(d[76]), "+f"(d[77]), "+f"(d[78]), "+f"(d[79])
    : "l"(descA), "l"(descB));
}
__device__ __forceinline__ void wgmma_ss_n48_tb(float (&d)[24], uint64_t descA, uint64_t descB) {
  asm volatile("wgmma.mma_async.sync.aligned.m64n48k16.f32.bf16.bf16 {%0, %1, %2, %3, %4, %5, %6, %7, %8, %9, %10, %11, %12, %13, %14, %15, %16, %17, %18, %19, %20, %21, %22, %23}, %24, %25, 1, 1, 1, 0, 1;\n"
    : "+f"(d[0]), "+f"(d[1]), "+f"(d[2]), "+f"(d[3]), "+f"(d[4]), "+f"(d[5]), "+f"(d[6]), "+f"(d[7]), "+f"(d[8]), "+f"(d[9]), "+f"(d[10]), "+f"(d[11]), "+f"(d[12]), "+f"(d[13]), "+f"(d[14]), "+f"(d[15]), "+f"(d[16]), "+f"(d[17]), "+f"(d[18]), "+f"(d[19]), "+f"(d[20]), "+f"(d[21]), "+f"(d[22]), "+f"(d[23])
    : "l"(descA), "l"(descB));
}
__device__ __forceinline__ void wgmma_ss_n80_tb(float (&d)[40], uint64_t descA, uint64_t descB) {
  asm volatile("wgmma.mma_async.sync.aligned.m64n80k16.f32.bf16.bf16 {%0, %1, %2, %3, %4, %5, %6, %7, %8, %9, %10, %11, %12, %13, %14, %15, %16, %17, %18, %19, %20, %21, %22, %23, %24, %25, %26, %27, %28, %29, %30, %31, %32, %33, %34, %35, %36, %37, %38, %39}, %40, %41, 1, 1, 1, 0, 1;\n"
    : "+f"(d[0]), "+f"(d[1]), "+f"(d[2]), "+f"(d[3]), "+f"(d[4]), "+f"(d[5]), "+f"(d[6]), "+f"(d[7]), "+f"(d[8]), "+f"(d[9]), "+f"(d[10]), "+f"(d[11]), "+f"(d[12]), "+f"(d[13]), "+f"(d[14]), "+f"(d[15]), "+f"(d[16]), "+f"(d[17]), "+f"(d[18]), "+f"(d[19]), "+f"(d[20]), "+f"(d[21]), "+f"(d[22]), "+f"(d[23]), "+f"(d[24]), "+f"(d[25]), "+f"(d[26]), "+f"(d[27]), "+f"(d[28]), "+f"(d[29]), "+f"(d[30]), "+f"(d[31]), "+f"(d[32]), "+f"(d[33]), "+f"(d[34]), "+f"(d[35]), "+f"(d[36]), "+f"(d[37]), "+f"(d[38]), "+f"(d[39])
    : "l"(descA), "l"(descB));
}
template <int SCALE_D>
__device__ __forceinline__ void wgmma_rs_n64(float (&d)[32], uint32_t a0, uint32_t a1, uint32_t a2, uint32_t a3, uint64_t descB) {
  asm volatile("wgmma.mma_async.sync.aligned.m64n64k16.f32.bf16.bf16 {%0, %1, %2, %3, %4, %5, %6, %7, %8, %9, %10, %11, %12, %13, %14, %15, %16, %17, %18, %19, %20, %21, %22, %23, %24, %25, %26, %27, %28, %29, %30, %31}, {%32, %33, %34, %35}, %36, %37, 1, 1, 0;\n"
    : "+f"(d[0]), "+f"(d[1]), "+f"(d[2]), "+f"(d[3]), "+f"(d[4]), "+f"(d[5]), "+f"(d[6]), "+f"(d[7]), "+f"(d[8]), "+f"(d[9]), "+f"(d[10]), "+f"(d[11]), "+f"(d[12]), "+f"(d[13]), "+f"(d[14]), "+f"(d[15]), "+f"(d[16]), "+f"(d[17]), "+f"(d[18]), "+f"(d[19]), "+f"(d[20]), "+f"(d[21]), "+f"(d[22]), "+f"(d[23]), "+f"(d[24]), "+f"(d[25]), "+f"(d[26]), "+f"(d[27]), "+f"(d[28]), "+f"(d[29]), "+f"(d[30]), "+f"(d[31])
    : "r"(a0), "r"(a1), "r"(a2), "r"(a3), "l"(descB), "n"(SCALE_D));
}
template <int SCALE_D>
__device__ __forceinline__ void wgmma_rs_n128(float (&d)[64], uint32_t a0, uint32_t a1, uint32_t a2, uint32_t a3, uint64_t descB) {
  asm volatile("wgmma.mma_async.sync.aligned.m64n128k16.f32.bf16.bf16 {%0, %1, %2, %3, %4, %5, %6, %7, %8, %9, %10, %11, %12, %13, %14, %15, %16, %17, %18, %19, %20, %21, %22, %23, %24, %25, %26, %27, %28, %29, %30, %31, %32, %33, %34, %35, %36, %37, %38, %39, %40, %41, %42, %43, %44, %45, %46, %47, %48, %49, %50, %51, %52, %53, %54, %55, %56, %57, %58, %59, %60, %61, %62, %63}, {%64, %65, %66, %67}, %68, %69, 1, 1, 0;\n"
    : "+f"(d[0]), "+f"(d[1]), "+f"(d[2]), "+f"(d[3]), "+f"(d[4]), "+f"(d[5]), "+f"(d[6]), "+f"(d[7]), "+f"(d[8]), "+f"(d[9]), "+f"(d[10]), "+f"(d[11]), "+f"(d[12]), "+f"(d[13]), "+f"(d[14]), "+f"(d[15]), "+f"(d[16]), "+f"(d[17]), "+f"(d[18]), "+f"(d[19]), "+f"(d[20]), "+f"(d[21]), "+f"(d[22]), "+f"(d[23]), "+f"(d[24]), "+f"(d[25]), "+f"(d[26]), "+f"(d[27]), "+f"(d[28]), "+f"(d[29]), "+f"(d[30]), "+f"(d[31]), "+f"(d[32]), "+f"(d[33]), "+f"(d[34]), "+f"(d[35]), "+f"(d[36]), "+f"(d[37]), "+f"(d[38]), "+f"(d[39]), "+f"(d[40]), "+f"(d[41]), "+f"(d[42]), "+f"(d[43]), "+f"(d[44]), "+f"(d[45]), "+f"(d[46]), "+f"(d[47]), "+f"(d[48]), "+f"(d[49]), "+f"(d[50]), "+f"(d[51]), "+f"(d[52]), "+f"(d[53]), "+f"(d[54]), "+f"(d[55]), "+f"(d[56]), "+f"(d[57]), "+f"(d[58]), "+f"(d[59]), "+f"(d[60]), "+f"(d[61]), "+f"(d[62]), "+f"(d[63])
    : "r"(a0), "r"(a1), "r"(a2), "r"(a3), "l"(descB), "n"(SCALE_D));
}
template <int SCALE_D>
__device__ __forceinline__ void wgmma_rs_n24_tb(float (&d)[12], uint32_t a0, uint32_t a1, uint32_t a2, uint32_t a3, uint64_t descB) {
  asm volatile("wgmma.mma_async.sync.aligned.m64n24k16.f32.bf16.bf16 {%0, %1, %2, %3, %4, %5, %6, %7, %8, %9, %10, %11}, {%12, %13, %14, %15}, %16, %17, 1, 1, 1;\n"
    : "+f"(d[0]), "+f"(d[1]), "+f"(d[2]), "+f"(d[3]), "+f"(d[4]), "+f"(d[5]), "+f"(d[6]), "+f"(d[7]), "+f"(d[8]), "+f"(d[9]), "+f"(d[10]), "+f"(d[11])
    : "r"(a0), "r"(a1), "r"(a2), "r"(a3), "l"(descB), "n"(SCALE_D));
}

constexpr uint32_t DHI_SW128_K = (1024 >> 4) | (1u << 30);
constexpr uint32_t DHI_SW64_MN = (512 >> 4) | (2u << 30);

template <int NC>
__device__ __forceinline__ void store_tile_bf16(const float (&acc)[NC / 2], float scale, uint32_t stage, uint8_t* stage_ptr,
                                                __nv_bfloat16* gdst, int gpitch, int lane) {
  constexpr int PITCH = NC * 2 + 16;
  const uint32_t waddr = stage + ((lane & 7) + ((lane >> 3) & 1) * 8) * PITCH + (lane >> 4) * 16;
#pragma unroll
  for (int j = 0; j < NC / 16; j++) {
    stsm4(waddr + j * 32, pack_bf16(acc[8 * j] * scale, acc[8 * j + 1] * scale), pack_bf16(acc[8 * j + 2] * scale, acc[8 * j + 3] * scale),
          pack_bf16(acc[8 * j + 4] * scale, acc[8 * j + 5] * scale), pack_bf16(acc[8 * j + 6] * scale, acc[8 * j + 7] * scale));
  }
  __syncwarp();
  constexpr int CPR = NC / 8;
#pragma unroll
  for (int i = 0; i < CPR / 2; i++) {
    const int c = i * 32 + lane, r = c / CPR, cc = c % CPR;
    const uint4 v = *reinterpret_cast<const uint4*>(stage_ptr + r * PITCH + cc * 16);
    *reinterpret_cast<uint4*>(gdst + (size_t)r * gpitch + cc * 8) = v;
  }
}

__device__ __forceinline__ void signal_done(unsigned int* flag, int wg, int tid) {
  asm volatile("bar.sync %0, 128;" :: "r"(wg + 1) : "memory");
  if ((tid & 127) == 0) asm volatile("red.release.gpu.global.add.u32 [%0], 1;" :: "l"(flag) : "memory");
}
__device__ __forceinline__ void wait_flags8(const unsigned int* f, unsigned int target) {
  for (int spin = 0; spin < (1 << 26); spin++) {
    unsigned int a, b, c, d, e, g, h, i;
    asm volatile("ld.volatile.global.v4.u32 {%0, %1, %2, %3}, [%4];" : "=r"(a), "=r"(b), "=r"(c), "=r"(d) : "l"(f) : "memory");
    asm volatile("ld.volatile.global.v4.u32 {%0, %1, %2, %3}, [%4];" : "=r"(e), "=r"(g), "=r"(h), "=r"(i) : "l"(f + 4) : "memory");
    if (min(min(min(a, b), min(c, d)), min(min(e, g), min(h, i))) >= target) break;
    __nanosleep(32);
  }
  asm volatile("fence.acq_rel.gpu;" ::: "memory");
  asm volatile("fence.proxy.async;" ::: "memory");
}

#define RP_LD 3
#define RP_ST 7
constexpr int K1_STAGES = 4;
constexpr int K1_A_BYTES = 256 * 128;
constexpr int K1_B_BYTES = 64 * 160 * 2;
constexpr int K1_STAGE = K1_A_BYTES + K1_B_BYTES;
constexpr int K1_SMEM = 5 * K1_A_BYTES + 61440 + 1024;
constexpr int KV_STAGES = 5;
constexpr int KVW_OFF = KV_STAGES * K1_A_BYTES;

__global__ void __launch_bounds__(512, 1)
proj_kernel(const __grid_constant__ CUtensorMap tmX, const __grid_constant__ CUtensorMap tmWq, const __grid_constant__ CUtensorMap tmWqkv,
            const __nv_bfloat16* __restrict__ wk, const __nv_bfloat16* __restrict__ wv, const __nv_bfloat16* __restrict__ gate_w,
            const __nv_bfloat16* __restrict__ woA, const __nv_bfloat16* __restrict__ woB) {
  extern __shared__ uint8_t smem_raw[];
  __shared__ __align__(8) uint64_t bar_full[KV_STAGES], bar_empty[KV_STAGES];
  uint8_t* smem = reinterpret_cast<uint8_t*>((reinterpret_cast<uintptr_t>(smem_raw) + 1023) & ~(uintptr_t)1023);
  const uint32_t sbase = smem_u32(smem);
  const uint32_t dbase = sbase & 0x3FFFFu;
  const int tid = threadIdx.x, warp = tid >> 5, lane = tid & 31;
  const bool is_kv = blockIdx.x >= 128;
  PROF(0, 0);
  if (tid == 0) {
    for (int i = 0; i < KV_STAGES; i++) { mbar_init(smem_u32(&bar_full[i]), 1); mbar_init(smem_u32(&bar_empty[i]), is_kv ? 8 : 16); }
    fence_mbar_init();
  }
  uint2 wa[2][5], wb[2][5]; uint32_t gw[2];
  if (is_kv && tid < 320) {
#pragma unroll
    for (int r = 0; r < 2; r++) {
      const int k = tid + r * 320;
      const uint2* pk = reinterpret_cast<const uint2*>(wk + k * 20);
      const uint2* pv = reinterpret_cast<const uint2*>(wv + k * 20);
#pragma unroll
      for (int i = 0; i < 5; i++) { wa[r][i] = __ldg(pk + i); wb[r][i] = __ldg(pv + i); }
      gw[r] = (uint32_t)__bfloat16_as_ushort(gate_w[k]);
    }
  }
  __syncthreads();
  if (tid == 480) {
    if (!is_kv) { g_done[blockIdx.x] = 0u; g_doneL[blockIdx.x] = 0u; }
    asm volatile("fence.acq_rel.gpu;" ::: "memory");
    pdl_launch();
  }
  __syncwarp();

  if (!is_kv) {
    const int mb = blockIdx.x >> 4, nb = blockIdx.x & 15;
    const CUtensorMap* tw = nb < 4 ? &tmWq : &tmWqkv;
    const int j0 = (nb < 4 ? nb : nb - 4) * 5;
    auto load = [&](int kt) {
      const int s = kt % K1_STAGES;
      const uint32_t fb = smem_u32(&bar_full[s]);
      mbar_expect_tx(fb, K1_STAGE);
      tma_2d(sbase + s * K1_STAGE, &tmX, kt * 64, mb * 256, fb);
      tma_3d(sbase + s * K1_STAGE + K1_A_BYTES, tw, 0, kt * 64, j0, fb);
    };
    if (tid == 0) for (int kt = 0; kt < K1_STAGES; kt++) load(kt);
    __syncwarp();
    uint4 wv2[2];
    const int rq = blockIdx.x * 400 + tid - 112;
    const int rhalf = rq >= 25600, rr = rq - rhalf * 25600, rk = 2 * (rr / 80), rch = rr % 80;
    {
      const int wg = warp >> 2;
      float acc[80];
#pragma unroll
      for (int i = 0; i < 80; i++) acc[i] = 0.f;
      for (int kt = 0; kt < 10; kt++) {
        const int s = kt % K1_STAGES;
        mbar_wait(smem_u32(&bar_full[s]), (kt / K1_STAGES) & 1);
        const uint32_t alo = ((dbase + s * K1_STAGE + wg * 8192) >> 4) | (1u << 16);
        const uint32_t blo = ((dbase + s * K1_STAGE + K1_A_BYTES) >> 4) | ((4096u >> 4) << 16);
        fence_regs(acc);
        wg_fence();
#pragma unroll
        for (int k = 0; k < 4; k++) wgmma_ss_n160_tb(acc, mkd(alo + k * 2, DHI_SW128_K), mkd(blo + k * 64, DHI_SW64_MN));
        wg_commit();
        if (kt == RP_LD && tid >= 112) {
          const uint4* src = reinterpret_cast<const uint4*>((rhalf ? woB : woA) + rk * D_MODEL + rch * 8);
          wv2[0] = __ldg(src); wv2[1] = __ldg(src + D_MODEL / 8);
        }
        if (kt == RP_ST && tid >= 112) {
          uint4* dst = reinterpret_cast<uint4*>(g_wimg + ((rhalf * 8 + rch / 10) * 10 + (rk >> 6)) * 10240 + (rch % 10) * 1024 + (rk & 63) * 16);
          dst[0] = wv2[0]; dst[1] = wv2[1];
        }
        __syncwarp();
        if (kt > 0 && kt - 1 + K1_STAGES < 10) {
          wg_wait<1>();
          const uint32_t eb = smem_u32(&bar_empty[(kt - 1) % K1_STAGES]);
          if (lane == 0) mbar_arrive(eb);
          if (tid == 0) { mbar_wait(eb, ((kt - 1) / K1_STAGES) & 1); load(kt - 1 + K1_STAGES); }
          __syncwarp();
        }
      }
      wg_wait<0>();
      fence_regs(acc);
      PROF(0, 1);
      asm volatile("bar.sync %0, 128;" :: "r"(wg + 1) : "memory");
      const int w4 = warp & 3;
      const uint32_t off = w4 * K1_STAGE + wg * 8192;
      const int row0 = mb * 256 + wg * 64 + w4 * 16;
      if (nb < 4) {
        store_tile_bf16<160>(acc, 0.22360679774997896f * 1.4426950408889634f, sbase + off, smem + off,
                             g_q + (size_t)row0 * D_MODEL + nb * 160, D_MODEL, lane);
      } else {
        store_tile_bf16<160>(acc, 1.0f, sbase + off, smem + off, g_qkv + (size_t)row0 * (3 * D_MODEL) + (nb - 4) * 160, 3 * D_MODEL, lane);
      }
    }
  } else {
    const int cb = blockIdx.x - 128;
    if (warp == 8 && lane == 0) {
      for (int it = 0; it < KV_STAGES; it++) {
        const uint32_t fb = smem_u32(&bar_full[it]);
        mbar_expect_tx(fb, K1_A_BYTES);
        tma_2d(sbase + it * K1_A_BYTES, &tmX, it * 64, cb * 512, fb);
      }
    }
    __syncwarp();
    if (tid < 320) {
#pragma unroll
      for (int r = 0; r < 2; r++) {
        uint4* dst = reinterpret_cast<uint4*>(smem + KVW_OFF + (tid + r * 320) * 16);
        dst[0] = make_uint4(wa[r][0].x, wa[r][0].y, wa[r][1].x, wa[r][1].y);
        dst[640] = make_uint4(wa[r][2].x, wa[r][2].y, wa[r][3].x, wa[r][3].y);
        dst[1280] = make_uint4(wa[r][4].x, wa[r][4].y, 0u, 0u);
        dst[1920] = make_uint4(wb[r][0].x, wb[r][0].y, wb[r][1].x, wb[r][1].y);
        dst[2560] = make_uint4(wb[r][2].x, wb[r][2].y, wb[r][3].x, wb[r][3].y);
        dst[3200] = make_uint4(wb[r][4].x, wb[r][4].y, gw[r], 0u);
      }
    }
    fence_proxy_async();
    asm volatile("bar.sync 1, 512;" ::: "memory");
    PROF(0, 1);
    auto produce = [&](int it0, int it1) {
      for (int it = it0; it < it1; it++) {
        const int s = it % KV_STAGES;
        mbar_wait(smem_u32(&bar_empty[s]), (it / KV_STAGES - 1) & 1);
        const uint32_t fb = smem_u32(&bar_full[s]);
        mbar_expect_tx(fb, K1_A_BYTES);
        tma_2d(sbase + s * K1_A_BYTES, &tmX, (it >= 10 ? it - 10 : it) * 64, cb * 512 + (it >= 10 ? 256 : 0), fb);
      }
    };
    if (tid == 256) produce(KV_STAGES, 15);
    __syncwarp();
    {
      const int pass = warp >> 3, wg = (warp >> 2) & 1, w4 = warp & 3, g = lane >> 2, t = lane & 3;
      if (pass == 1) asm volatile("bar.sync 2, 512;" ::: "memory");
      {
        float acc[2][24];
#pragma unroll
        for (int i = 0; i < 24; i++) { acc[0][i] = 0.f; acc[1][i] = 0.f; }
        for (int kt = 0; kt < 10; kt++) {
          const int it = pass * 10 + kt, s = it % KV_STAGES;
          mbar_wait(smem_u32(&bar_full[s]), (it / KV_STAGES) & 1);
          const uint32_t alo = ((dbase + s * K1_A_BYTES + wg * 16384) >> 4) | (1u << 16);
          const uint32_t blo = ((dbase + KVW_OFF + kt * 1024) >> 4) | ((128u >> 4) << 16);
          fence_regs(acc[0]); fence_regs(acc[1]);
          wg_fence();
#pragma unroll
          for (int k = 0; k < 4; k++) {
            wgmma_ss_n48_tb(acc[0], mkd(alo + k * 2, DHI_SW128_K), mkd(blo + k * 16, 10240u >> 4));
            wgmma_ss_n48_tb(acc[1], mkd(alo + 512 + k * 2, DHI_SW128_K), mkd(blo + k * 16, 10240u >> 4));
          }
          wg_commit();
          if (kt > 0) {
            wg_wait<1>();
            if (lane == 0) mbar_arrive(smem_u32(&bar_empty[(it - 1) % KV_STAGES]));
          }
        }
        wg_wait<0>();
        fence_regs(acc[0]); fence_regs(acc[1]);
        if (lane == 0) mbar_arrive(smem_u32(&bar_empty[(pass * 10 + 9) % KV_STAGES]));
        if (pass == 0) asm volatile("bar.arrive 2, 512;" ::: "memory");
        PROF(0, 2);
        if (tid == 0) produce(15, 20);
        __syncwarp();
        float kmax2 = 0.f, vmax = 0.f;
#pragma unroll
        for (int hh = 0; hh < 4; hh++) {
          const int h = hh & 1;
          const float (&a)[24] = acc[hh >> 1];
          const int key = cb * 512 + pass * 256 + wg * 128 + (hh >> 1) * 64 + w4 * 16 + g + h * 8;
          const int grp = key >> 7, kk = key & 127;
          const bool poly = (TMASK >> (kk >> 3)) & 1;
          uint8_t* gp = g_kvimg + grp * GRP_BYTES;
          const uint32_t k0 = pack_bf16(a[2 * h], a[2 * h + 1]);
          const uint32_t k1 = pack_bf16(a[4 + 2 * h], a[5 + 2 * h]);
          uint32_t k2 = pack_bf16(a[8 + 2 * h], a[9 + 2 * h]);
          float n2 = bf_lo(k0) * bf_lo(k0) + bf_hi(k0) * bf_hi(k0) + bf_lo(k1) * bf_lo(k1) + bf_hi(k1) * bf_hi(k1);
          if (t < 2) {
            n2 += bf_lo(k2) * bf_lo(k2) + bf_hi(k2) * bf_hi(k2);
            k2 = pack_bf16(bf_lo(k2) * 0.5f, bf_hi(k2) * 0.5f);
          } else if (t == 2) k2 = poly ? pack_bf16(24.f, 2.5f) : pack_bf16(0.5f, 0.f);
          else k2 = poly ? pack_bf16(0.5f, 0.f) : 0u;
          *reinterpret_cast<uint32_t*>(gp + kk * 16 + t * 4) = k0;
          *reinterpret_cast<uint32_t*>(gp + PLANE + kk * 16 + t * 4) = k1;
          *reinterpret_cast<uint32_t*>(gp + 2 * PLANE + kk * 16 + t * 4) = k2;
          n2 += __shfl_xor_sync(0xffffffffu, n2, 1);
          n2 += __shfl_xor_sync(0xffffffffu, n2, 2);
          kmax2 = (n2 > kmax2 || n2 != n2) ? n2 : kmax2;
          uint32_t v0 = pack_bf16(a[12 + 2 * h], a[13 + 2 * h]);
          uint32_t v1 = pack_bf16(a[16 + 2 * h], a[17 + 2 * h]);
          uint32_t v2 = pack_bf16(a[20 + 2 * h], a[21 + 2 * h]);
          float vm = fmaxf(fmaxf(fabsf(bf_lo(v0)), fabsf(bf_hi(v0))), fmaxf(fabsf(bf_lo(v1)), fabsf(bf_hi(v1))));
          if (t < 2) vm = fmaxf(vm, fmaxf(fabsf(bf_lo(v2)), fabsf(bf_hi(v2))));
          else if (t == 2) {
            const float z = a[20 + 2 * h];
            g_gate[key] = 1.f / (1.f + __expf(-z));
            v2 = 0x00003F80u;
          } else v2 = 0u;
          vmax = fmaxf(vmax, vm);
          if (poly) { v0 ^= 0x80008000u; v1 ^= 0x80008000u; v2 ^= 0x80008000u; }
          uint8_t* vp = gp + 3 * PLANE + (kk >> 3) * 384 + (kk & 7) * 16 + t * 4;
          *reinterpret_cast<uint32_t*>(vp) = v0;
          *reinterpret_cast<uint32_t*>(vp + 128) = v1;
          *reinterpret_cast<uint32_t*>(vp + 256) = v2;
        }
#pragma unroll
        for (int o = 1; o < 32; o <<= 1) {
          const float a = __shfl_xor_sync(0xffffffffu, kmax2, o);
          kmax2 = (a > kmax2 || a != a) ? a : kmax2;
          vmax = fmaxf(vmax, __shfl_xor_sync(0xffffffffu, vmax, o));
        }
        if (lane == 0) { g_kmax2[cb * 16 + warp] = kmax2; g_vmax[cb * 16 + warp] = vmax; }
      }
    }
  }
}

__device__ __forceinline__ uint32_t ex2_pair_poly(float u0, float u1, uint32_t one2) {
  const uint32_t W = __byte_perm(__float_as_uint(u0), __float_as_uint(u1), 0x6521);
  uint32_t v; asm("lop3.b32 %0, %1, 0x007F007F, %2, 0xEA;" : "=r"(v) : "r"(W), "r"(one2));
  uint32_t L, p;
  asm("fma.rn.bf16x2 %0, %1, %2, %3;" : "=r"(L) : "r"(v), "r"(0x1f961f96u), "r"(0x9fe39fe3u));
  asm("fma.rn.bf16x2 %0, %1, %1, %2;" : "=r"(p) : "r"(L), "r"(0x00f500f5u));
  return W + p;
}
template <int JOFF>
__device__ __forceinline__ void softmax_slow(const float (&S)[32], uint32_t (&P)[16], float (&O)[12], float& m0, float& m1) {
  float a0 = m0, a1 = m1;
#pragma unroll
  for (int j = 0; j < 8; j++) {
    a0 = fmaxf(a0, fmaxf(S[4 * j], S[4 * j + 1]));
    a1 = fmaxf(a1, fmaxf(S[4 * j + 2], S[4 * j + 3]));
  }
  a0 = fmaxf(a0, __shfl_xor_sync(0xffffffffu, a0, 1)); a0 = fmaxf(a0, __shfl_xor_sync(0xffffffffu, a0, 2));
  a1 = fmaxf(a1, __shfl_xor_sync(0xffffffffu, a1, 1)); a1 = fmaxf(a1, __shfl_xor_sync(0xffffffffu, a1, 2));
  const float c0 = ex2(m0 - a0), c1 = ex2(m1 - a1);
  m0 = a0; m1 = a1;
#pragma unroll
  for (int j = 0; j < 3; j++) { O[4 * j] *= c0; O[4 * j + 1] *= c0; O[4 * j + 2] *= c1; O[4 * j + 3] *= c1; }
#pragma unroll
  for (int i = 0; i < 16; i++) {
    const float m = (i & 1) ? a1 : a0;
    const uint32_t p = pack_bf16(ex2(S[2 * i] - m), ex2(S[2 * i + 1] - m));
    P[i] = ((TMASK >> (JOFF + i / 2)) & 1) ? (p ^ 0x80008000u) : p;
  }
}
constexpr uint32_t DHI_KV = 128 >> 4;
__device__ __forceinline__ void issue_qk(float (&S)[32], const uint32_t (&q)[8], uint64_t base) {
  wgmma_rs_n64<0>(S, q[0], q[1], q[2], q[3], base + (uint64_t)((PLANE >> 4) << 16));
  wgmma_rs_n64<1>(S, q[4], q[5], q[6], q[7], base + (uint64_t)(2 * PLANE >> 4));
}
__device__ __forceinline__ void issue_pv(float (&O)[12], const uint32_t (&P)[16], uint64_t vbase) {
#pragma unroll
  for (int kk = 0; kk < 4; kk++)
    wgmma_rs_n24_tb<1>(O, P[4 * kk], P[4 * kk + 1], P[4 * kk + 2], P[4 * kk + 3], vbase + (uint64_t)(kk * (768 >> 4)));
}

constexpr uint32_t VOFF = ((3 * PLANE) >> 4) + ((384u >> 4) << 16);
constexpr int KVR = 4;
constexpr int OFF_W = KVR * GRP_BYTES;
constexpr int OFF_X = OFF_W + 10 * 10240;
constexpr int OFF_BAR = OFF_X + 4 * 16384;
constexpr int K2_SMEM = OFF_BAR + 256 + 1024;
constexpr int TSL = 7;
constexpr int BAR_KV = 0, BAR_W = 4, BAR_TA = 5, BAR_TE = 12, BAR_OWN = 19, CNT_KV = 20;
constexpr int NSTEP = 2 * NGRP;

__device__ __forceinline__ void kv_load(uint32_t sbase, int step) {
  const uint32_t bar = sbase + OFF_BAR + (BAR_KV + (step & (KVR - 1))) * 8;
  mbar_expect_tx(bar, GRP_BYTES);
  bulk_g2s(sbase + (step & (KVR - 1)) * GRP_BYTES, g_kvimg + (step & (NGRP - 1)) * GRP_BYTES, GRP_BYTES, bar);
}
__device__ __forceinline__ void kv_release(uint32_t sbase, int step, bool elected) {
  if (elected && step + KVR < NSTEP) {
    uint32_t old;
    asm volatile("atom.acq_rel.cta.shared::cta.inc.u32 %0, [%1], 3;" : "=r"(old) : "r"(sbase + OFF_BAR + CNT_KV * 8 + (step & (KVR - 1)) * 4) : "memory");
    if (old == 3u) kv_load(sbase, step + KVR);
  }
  __syncwarp();
}
__device__ __forceinline__ void kv_wait(uint32_t sbase, int step) {
  mbar_wait(sbase + OFF_BAR + (BAR_KV + (step & (KVR - 1))) * 8, (step / KVR) & 1);
}

__device__ __forceinline__ uint32_t kv_release_begin(uint32_t sbase, int slot, bool doit) {
  uint32_t old = 0;
  asm volatile("{\n.reg .pred p;\nsetp.ne.u32 p, %2, 0;\n@p atom.relaxed.cta.shared::cta.inc.u32 %0, [%1], 3;\n}\n"
               : "+r"(old) : "r"(sbase + OFF_BAR + CNT_KV * 8 + slot * 4), "r"((uint32_t)doit) : "memory");
  return old;
}
template <int H>
__device__ __forceinline__ void softmax_half(const float (&S)[64], uint32_t (&P)[16], uint32_t one2) {
#pragma unroll
  for (int i = 0; i < 16; i++) {
    if ((TMASK >> (8 * H + i / 2)) & 1) P[i] = ex2_pair_poly(S[32 * H + 2 * i], S[32 * H + 2 * i + 1], one2);
    else P[i] = pack_bf16(ex2(S[32 * H + 2 * i]), ex2(S[32 * H + 2 * i + 1]));
  }
}
__device__ __forceinline__ void attn_fast(const uint32_t (&q)[8], float (&O)[12], uint32_t sbase, int step0, int nsteps, bool elected, uint32_t one2) {
  uint64_t kb0 = mkd((sbase & 0x3FFFFu) >> 4, DHI_KV);
  asm volatile("" : "+l"(kb0));
#pragma unroll 1
  for (int step4 = step0; step4 < step0 + nsteps; step4 += KVR) {
#pragma unroll
    for (int j = 0; j < KVR; j++) {
      const int step = step4 + j;
      const uint64_t kb = kb0 + (uint64_t)(j * (GRP_BYTES >> 4));
      float S[64]; uint32_t PA[16], PB[16];
#pragma unroll
      for (int i = 0; i < 64; i++) S[i] = 0.f;
      mbar_wait(sbase + OFF_BAR + (BAR_KV + j) * 8, (step / KVR) & 1);
      fence_regs(S);
      wg_fence();
      wgmma_rs_n128<0>(S, q[0], q[1], q[2], q[3], kb + (uint64_t)((PLANE >> 4) << 16));
      wgmma_rs_n128<1>(S, q[4], q[5], q[6], q[7], kb + (uint64_t)(2 * PLANE >> 4));
      wg_commit();
      wg_wait<0>();
      fence_regs(S);
      softmax_half<0>(S, PA, one2);
      fence_regs(PA); fence_regs(O);
      wg_fence();
      issue_pv(O, PA, kb + VOFF);
      wg_commit();
      softmax_half<1>(S, PB, one2);
      fence_regs(PB);
      wg_fence();
      issue_pv(O, PB, kb + VOFF + 4 * (768 >> 4));
      wg_commit();
      wg_wait<0>();
      fence_regs(PA); fence_regs(PB); fence_regs(O);
      const uint32_t old = kv_release_begin(sbase, j, elected && step + KVR < NSTEP);
      if (old == 3u) kv_load(sbase, step + KVR);
    }
  }
}
template <int H>
__device__ __forceinline__ void slow_step(const uint32_t (&q)[8], float (&O)[12], uint64_t kb, float& m0, float& m1) {
  float S[32]; uint32_t P[16];
#pragma unroll
  for (int i = 0; i < 32; i++) S[i] = 0.f;
  fence_regs(S);
  wg_fence();
  issue_qk(S, q, kb + 64 * H);
  wg_commit();
  wg_wait<0>();
  fence_regs(S);
  softmax_slow<8 * H>(S, P, O, m0, m1);
  fence_regs(P); fence_regs(O);
  wg_fence();
  issue_pv(O, P, kb + VOFF + H * 4 * (768 >> 4));
  wg_commit();
  wg_wait<0>();
  fence_regs(O); fence_regs(P);
}
__device__ __forceinline__ void attn_slow(const uint32_t (&q)[8], float (&O)[12], uint32_t sbase, int step0, int nsteps, bool elected, float& m0, float& m1) {
#pragma unroll 1
  for (int step = step0; step < step0 + nsteps; step++) {
    kv_wait(sbase, step);
    const uint64_t kb = mkd(((sbase & 0x3FFFFu) >> 4) + (step & (KVR - 1)) * (GRP_BYTES >> 4), DHI_KV);
    slow_step<0>(q, O, kb, m0, m1);
    slow_step<1>(q, O, kb, m0, m1);
    kv_release(sbase, step, elected);
  }
}

__device__ __forceinline__ void load_row20(const __nv_bfloat16* p, float (&f)[20]) {
  const uint2* p2 = reinterpret_cast<const uint2*>(p);
#pragma unroll
  for (int i = 0; i < 5; i++) { const uint2 v = p2[i]; f[4 * i] = bf_lo(v.x); f[4 * i + 1] = bf_hi(v.x); f[4 * i + 2] = bf_lo(v.y); f[4 * i + 3] = bf_hi(v.y); }
}
__device__ __forceinline__ void softmax8(float (&sc)[8]) {
  float mx = sc[0];
#pragma unroll
  for (int w = 1; w < 8; w++) mx = fmaxf(mx, sc[w]);
  float l = 0.f;
#pragma unroll
  for (int w = 0; w < 8; w++) { sc[w] = ex2(sc[w] - mx); l += sc[w]; }
  const float r = 1.f / l;
#pragma unroll
  for (int w = 0; w < 8; w++) sc[w] *= r;
}
__device__ __forceinline__ void local_attn(int t, int lane) {
  constexpr int PITCH = 3 * D_MODEL;
  constexpr float SC = 0.22360679774997896f * 1.4426950408889634f, NEG = -1e9f * 1.4426950408889634f;
  const __nv_bfloat16* base = g_qkv + lane * DH;
  float a[20], sc[8];
  load_row20(base + (size_t)t * PITCH, a);
#pragma unroll
  for (int w = 0; w < 8; w++) {
    const int r = t - 2 * w;
    float k[20];
    load_row20(base + D_MODEL + (size_t)max(r, 0) * PITCH, k);
    float d = 0.f;
#pragma unroll
    for (int i = 0; i < 20; i++) d = fmaf(a[i], k[i], d);
    sc[w] = r >= 0 ? d * SC : NEG;
  }
  softmax8(sc);
#pragma unroll
  for (int i = 0; i < 20; i++) a[i] = 0.f;
#pragma unroll
  for (int w = 0; w < 8; w++) {
    float v[20];
    load_row20(base + 2 * D_MODEL + (size_t)max(t - 2 * w, 0) * PITCH, v);
#pragma unroll
    for (int i = 0; i < 20; i++) a[i] = fmaf(sc[w], v[i], a[i]);
  }
  const float ga = 1.f - g_gate[t];
  uint2* da = reinterpret_cast<uint2*>(g_a2 + (size_t)t * (2 * D_MODEL) + D_MODEL + lane * DH);
#pragma unroll
  for (int i = 0; i < 5; i++)
    da[i] = make_uint2(pack_bf16(a[4 * i] * ga, a[4 * i + 1] * ga), pack_bf16(a[4 * i + 2] * ga, a[4 * i + 3] * ga));
}
__device__ __forceinline__ uint32_t ta_slot(int i) { return i < 4 ? OFF_X + i * 16384 : (i - 4) * 16384; }

__global__ void __launch_bounds__(512, 1)
attn_kernel(const __grid_constant__ CUtensorMap tmA2, __nv_bfloat16* __restrict__ out, uint32_t one2) {
  extern __shared__ uint8_t smem_raw[];
  uint8_t* smem = reinterpret_cast<uint8_t*>((reinterpret_cast<uintptr_t>(smem_raw) + 1023) & ~(uintptr_t)1023);
  const uint32_t sbase = smem_u32(smem);
  const uint32_t dbase = sbase & 0x3FFFFu;
  const uint32_t bars = sbase + OFF_BAR;
  const int tid = threadIdx.x, wg = tid >> 7, warp = (tid >> 5) & 3, lane = tid & 31, g = lane >> 2, t = lane & 3;
  const int mb = blockIdx.x >> 3, nb = blockIdx.x & 7;
  const bool elected = (tid & 127) == 0;
  if (tid == 0) {
    for (int i = 0; i < BAR_TE; i++) mbar_init(bars + i * 8, 1);
    for (int i = BAR_TE; i < BAR_TE + TSL; i++) mbar_init(bars + i * 8, 8);
    mbar_init(bars + BAR_OWN * 8, 4);
    for (int i = 0; i < 4; i++) *reinterpret_cast<uint32_t*>(smem + OFF_BAR + CNT_KV * 8 + i * 4) = 0u;
    fence_mbar_init();
  }
  __syncthreads();
  auto tail_load = [&](int i) {
    const uint32_t fb = bars + (BAR_TA + i % TSL) * 8;
    mbar_expect_tx(fb, i < 10 ? 16384 : 16384 + 10240);
    tma_2d(sbase + ta_slot(i % TSL), &tmA2, i < 10 ? D_MODEL + i * 64 : (i - 10) * 64, mb * 128, fb);
    if (i >= 10) bulk_g2s(sbase + OFF_W + (i - 10) * 10240, g_wimg + (nb * 10 + i - 10) * 10240, 10240, fb);
  };
  pdl_wait();
  PROF(1, 1);
  if (tid == 416) for (int j = 0; j < KVR; j++) kv_load(sbase, j);
  __syncwarp();
  uint32_t q[8], q2[6];
  const int rowA = (blockIdx.x * 8 + wg) * 64 + warp * 16 + g;
  {
    const uint32_t* r0 = reinterpret_cast<const uint32_t*>(g_q + (size_t)rowA * DH);
    const uint32_t* r1 = r0 + 8 * (DH / 2);
    const uint32_t* s0 = r0 + 256 * (DH / 2);
    const uint32_t* s1 = s0 + 8 * (DH / 2);
    q[0] = r0[t]; q[1] = r1[t]; q[2] = r0[t + 4]; q[3] = r1[t + 4];
    q[4] = t < 2 ? r0[8 + t] : 0u;
    q[5] = t < 2 ? r1[8 + t] : 0u;
    q2[0] = s0[t]; q2[1] = s1[t]; q2[2] = s0[t + 4]; q2[3] = s1[t + 4];
    q2[4] = t < 2 ? s0[8 + t] : 0u;
    q2[5] = t < 2 ? s1[8 + t] : 0u;
  }
  float kmax2 = 0.f, vmax = 0.f;
#pragma unroll
  for (int i = 0; i < 2; i++) {
    const float a = g_kmax2[lane + 32 * i];
    kmax2 = (a > kmax2 || a != a) ? a : kmax2;
    vmax = fmaxf(vmax, g_vmax[lane + 32 * i]);
  }
#pragma unroll
  for (int o = 1; o < 32; o <<= 1) {
    const float a = __shfl_xor_sync(0xffffffffu, kmax2, o);
    kmax2 = (a > kmax2 || a != a) ? a : kmax2;
    vmax = fmaxf(vmax, __shfl_xor_sync(0xffffffffu, vmax, o));
  }
  const float qlim = (vmax >= 0.00390625f && vmax <= 256.f) ? 9025.f / kmax2 : -1.f;
  PROF(1, 2);
#pragma unroll 1
  for (int it = 0; it < 2; it++) {
    const int row0 = rowA + it * 256;
    if (it == 1) {
      local_attn(blockIdx.x * 16 + (tid >> 5), lane);
      signal_done(&g_doneL[blockIdx.x], wg, tid);
      if (tid == 160) {
        mbar_expect_tx(bars + BAR_W * 8, 10 * 10240);
        for (int i = 0; i < 5; i++) bulk_g2s(sbase + OFF_W + i * 20480, g_wimg + ((8 + nb) * 10) * 10240 + i * 20480, 20480, bars + BAR_W * 8);
      }
      __syncwarp();
#pragma unroll
      for (int i = 0; i < 6; i++) q[i] = q2[i];
    }
    float n0 = bf_lo(q[0]) * bf_lo(q[0]) + bf_hi(q[0]) * bf_hi(q[0]) + bf_lo(q[2]) * bf_lo(q[2]) + bf_hi(q[2]) * bf_hi(q[2]) +
               bf_lo(q[4]) * bf_lo(q[4]) + bf_hi(q[4]) * bf_hi(q[4]);
    float n1 = bf_lo(q[1]) * bf_lo(q[1]) + bf_hi(q[1]) * bf_hi(q[1]) + bf_lo(q[3]) * bf_lo(q[3]) + bf_hi(q[3]) * bf_hi(q[3]) +
               bf_lo(q[5]) * bf_lo(q[5]) + bf_hi(q[5]) * bf_hi(q[5]);
    n0 += __shfl_xor_sync(0xffffffffu, n0, 1); n0 += __shfl_xor_sync(0xffffffffu, n0, 2);
    n1 += __shfl_xor_sync(0xffffffffu, n1, 1); n1 += __shfl_xor_sync(0xffffffffu, n1, 2);
    const bool safe = (n0 <= qlim) && (n1 <= qlim);
    uint32_t unsafe_any;
    asm volatile("{\n.reg .pred p, r;\nsetp.eq.u32 p, %1, 0;\nbarrier.cta.red.or.pred r, %2, 128, p;\nselp.u32 %0, 1, 0, r;\n}\n"
                 : "=r"(unsafe_any) : "r"((uint32_t)safe), "r"(wg + 1) : "memory");
    float O[12];
#pragma unroll
    for (int i = 0; i < 12; i++) O[i] = 0.f;
    if (!unsafe_any && t >= 2) { q[4] = q[5] = (t == 2) ? 0x3F804100u : 0x00003B80u; }
    q[6] = q[4]; q[7] = q[5];
    fence_regs(q);
    float m0 = -INFINITY, m1 = -INFINITY;
#pragma unroll 1
    for (int part = 0; part < 2; part++) {
      const int s0 = it * NGRP + part * 12, ns = part == 0 ? 12 : 4;
      if (!unsafe_any) attn_fast(q, O, sbase, s0, ns, elected, one2);
      else attn_slow(q, O, sbase, s0, ns, elected, m0, m1);
      if (it == 1 && part == 0 && tid == 416) {
        wait_flags8(&g_doneL[mb * 8], 4u);
        for (int i = 0; i < 4; i++) tail_load(i);
      }
      __syncwarp();
    }
    const float l0 = __shfl_sync(0xffffffffu, O[8], (lane & ~3) | 2);
    const float l1 = __shfl_sync(0xffffffffu, O[10], (lane & ~3) | 2);
    const int tok = row0 >> 5;
    const float gt = g_gate[tok];
    const float i0 = gt / l0, i1 = gt / l1;
    uint32_t* o0 = reinterpret_cast<uint32_t*>(g_a2 + (size_t)tok * (2 * D_MODEL) + (row0 & 31) * DH);
    uint32_t* o1 = o0 + 8 * (DH / 2);
    o0[t] = pack_bf16(O[0] * i0, O[1] * i0); o1[t] = pack_bf16(O[2] * i1, O[3] * i1);
    o0[t + 4] = pack_bf16(O[4] * i0, O[5] * i0); o1[t + 4] = pack_bf16(O[6] * i1, O[7] * i1);
    if (t < 2) { o0[t + 8] = pack_bf16(O[8] * i0, O[9] * i0); o1[t + 8] = pack_bf16(O[10] * i1, O[11] * i1); }
  }
  signal_done(&g_done[blockIdx.x], wg, tid);
  if ((tid & 127) == 64) mbar_arrive(bars + BAR_OWN * 8);
  PROF(1, 3);
  if (wg == 3) {
    if (tid == 416) {
      mbar_wait(bars + BAR_OWN * 8, 0);
      for (int i = 4; i < 20; i++) {
        if (i >= TSL) mbar_wait(bars + (BAR_TE + i % TSL) * 8, (i / TSL - 1) & 1);
        if (i == 10) { wait_flags8(&g_done[mb * 8], 4u); PROF2(2, 0); }
        tail_load(i);
      }
    }
  } else if (wg < 2) {
    float acc[40];
#pragma unroll
    for (int i = 0; i < 40; i++) acc[i] = 0.f;
    mbar_wait(bars + BAR_W * 8, 0);
    int sl = 0, ph = 0;
#pragma unroll 1
    for (int i = 0; i < 20; i++) {
      mbar_wait(bars + (BAR_TA + sl) * 8, ph);
      if (i == 10) PROF(2, 1);
      const uint32_t alo = ((dbase + ta_slot(sl) + wg * 8192) >> 4) | (1u << 16);
      const uint32_t blo = ((dbase + OFF_W + (i >= 10 ? i - 10 : i) * 10240) >> 4) | ((128u >> 4) << 16);
      fence_regs(acc);
      wg_fence();
#pragma unroll
      for (int k = 0; k < 4; k++) wgmma_ss_n80_tb(acc, mkd(alo + k * 2, DHI_SW128_K), mkd(blo + k * 16, 1024u >> 4));
      wg_commit();
      if (i > 0) {
        wg_wait<1>();
        if (lane == 0) mbar_arrive(bars + (BAR_TE + (sl == 0 ? TSL - 1 : sl - 1)) * 8);
      }
      if (++sl == TSL) { sl = 0; ph ^= 1; }
    }
    wg_wait<0>();
    fence_regs(acc);
    PROF(2, 2);
    asm volatile("bar.sync %0, 128;" :: "r"(wg + 1) : "memory");
    const uint32_t so = ta_slot(warp) + wg * 8192;
    const int row0 = mb * 128 + wg * 64 + warp * 16;
    store_tile_bf16<80>(acc, 1.0f, sbase + so, smem + so, out + (size_t)row0 * D_MODEL + nb * 80, D_MODEL, lane);
    PROF(2, 3);
  }
}

typedef CUresult (*EncodeFn)(CUtensorMap*, CUtensorMapDataType, cuuint32_t, void*, const cuuint64_t*, const cuuint64_t*,
                             const cuuint32_t*, const cuuint32_t*, CUtensorMapInterleave, CUtensorMapSwizzle,
                             CUtensorMapL2promotion, CUtensorMapFloatOOBfill);

void make_map(EncodeFn fn, CUtensorMap* tm, const void* ptr, int rank, const cuuint64_t* dims, const cuuint64_t* strides,
              const cuuint32_t* box, CUtensorMapSwizzle sw) {
  const cuuint32_t es[3] = {1, 1, 1};
  fn(tm, CU_TENSOR_MAP_DATA_TYPE_BFLOAT16, rank, const_cast<void*>(ptr), dims, strides, box, es, CU_TENSOR_MAP_INTERLEAVE_NONE, sw,
     CU_TENSOR_MAP_L2_PROMOTION_L2_256B, CU_TENSOR_MAP_FLOAT_OOB_FILL_NONE);
}
void map_a(EncodeFn fn, CUtensorMap* tm, const void* p, int rows, int cols, int box_rows) {
  const cuuint64_t dims[2] = {(cuuint64_t)cols, (cuuint64_t)rows};
  const cuuint64_t str[1] = {(cuuint64_t)cols * 2};
  const cuuint32_t box[2] = {64, (cuuint32_t)box_rows};
  make_map(fn, tm, p, 2, dims, str, box, CU_TENSOR_MAP_SWIZZLE_128B);
}
void map_w(EncodeFn fn, CUtensorMap* tm, const void* p, int K, int N, int atom, CUtensorMapSwizzle sw) {
  const cuuint64_t dims[3] = {(cuuint64_t)atom, (cuuint64_t)K, (cuuint64_t)(N / atom)};
  const cuuint64_t str[2] = {(cuuint64_t)N * 2, (cuuint64_t)atom * 2};
  const cuuint32_t box[3] = {(cuuint32_t)atom, 64, 5};
  make_map(fn, tm, p, 3, dims, str, box, sw);
}

template <typename... KArgs, typename... Args>
void launch(void (*kern)(KArgs...), int grid, int block, int smem, bool pdl, Args... args) {
  cudaLaunchConfig_t cfg = {};
  cfg.gridDim = dim3(grid); cfg.blockDim = dim3(block); cfg.dynamicSmemBytes = smem; cfg.stream = cudaStreamPerThread;
  cudaLaunchAttribute at[1];
  at[0].id = cudaLaunchAttributeProgrammaticStreamSerialization;
  at[0].val.programmaticStreamSerializationAllowed = 1;
  cfg.attrs = at; cfg.numAttrs = pdl ? 1 : 0;
  cudaLaunchKernelEx(&cfg, kern, KArgs(args)...);
}

}

extern "C" void kernel_launch(void* const* d_in, const int* in_sizes, int n_in, void* d_out, int out_size) {
  (void)in_sizes; (void)n_in; (void)out_size;
  const __nv_bfloat16* x = (const __nv_bfloat16*)d_in[0];
  const __nv_bfloat16* wq = (const __nv_bfloat16*)d_in[1];
  const __nv_bfloat16* wk = (const __nv_bfloat16*)d_in[2];
  const __nv_bfloat16* wv = (const __nv_bfloat16*)d_in[3];
  const __nv_bfloat16* woA = (const __nv_bfloat16*)d_in[4];
  const __nv_bfloat16* wqkv = (const __nv_bfloat16*)d_in[6];
  const __nv_bfloat16* woB = (const __nv_bfloat16*)d_in[7];
  const __nv_bfloat16* gate_w = (const __nv_bfloat16*)d_in[8];

  static EncodeFn enc = nullptr;
  static void* a2_ptr = nullptr;
  if (!enc) {
    void* fp = nullptr;
    cudaDriverEntryPointQueryResult qr;
    cudaGetDriverEntryPoint("cuTensorMapEncodeTiled", &fp, cudaEnableDefault, &qr);
    enc = (EncodeFn)fp;
    cudaGetSymbolAddress(&a2_ptr, g_a2);
    cudaFuncSetAttribute(proj_kernel, cudaFuncAttributeMaxDynamicSharedMemorySize, K1_SMEM);
    cudaFuncSetAttribute(attn_kernel, cudaFuncAttributeMaxDynamicSharedMemorySize, K2_SMEM);
  }
  CUtensorMap tmX, tmWq, tmWqkv, tmA2;
  map_a(enc, &tmX, x, S_LEN, D_MODEL, 256);
  map_w(enc, &tmWq, wq, D_MODEL, D_MODEL, 32, CU_TENSOR_MAP_SWIZZLE_64B);
  map_w(enc, &tmWqkv, wqkv, D_MODEL, 3 * D_MODEL, 32, CU_TENSOR_MAP_SWIZZLE_64B);
  map_a(enc, &tmA2, a2_ptr, S_LEN, 2 * D_MODEL, 128);

  launch(proj_kernel, 132, 512, K1_SMEM, false, tmX, tmWq, tmWqkv, wk, wv, gate_w, woA, woB);
  launch(attn_kernel, 128, 512, K2_SMEM, true, tmA2, (__nv_bfloat16*)d_out, 0x3F803F80u);
}
```

```cpp
#include <cuda_runtime.h>
#include <cuda_bf16.h>
#include <cuda.h>
#include <stdint.h>

namespace {

constexpr int S_LEN = 2048, D_MODEL = 640, DH = 20;

constexpr int GRP = 128;
constexpr int PLANE = GRP * 16;
constexpr int GRP_BYTES = GRP * 16 * 6;
constexpr int NGRP = S_LEN / GRP;
#define TMASKV 0xBBBBu
constexpr uint32_t TMASK = TMASKV;

__device__ __align__(1024) __nv_bfloat16 g_q[S_LEN * D_MODEL];
__device__ __align__(1024) __nv_bfloat16 g_qkv[S_LEN * 3 * D_MODEL];
__device__ __align__(1024) __nv_bfloat16 g_a2[S_LEN * 2 * D_MODEL];
__device__ __align__(1024) uint8_t g_kvimg[NGRP * GRP_BYTES];
__device__ __align__(1024) uint8_t g_wimg[2 * 8 * 10 * 10240];
__device__ float g_gate[S_LEN];
__device__ float g_kmax2[64];
__device__ float g_vmax[64];
__device__ __align__(32) unsigned int g_doneL[128];
__device__ __align__(32) unsigned int g_done[128];

#define PROF(k, slot)
#define PROF2(k, slot)
__device__ __forceinline__ uint32_t smem_u32(const void* p) { return (uint32_t)__cvta_generic_to_shared(p); }
__device__ __forceinline__ uint64_t mkd(uint32_t lo, uint32_t hi) {
  uint64_t d; asm("mov.b64 %0, {%1, %2};" : "=l"(d) : "r"(lo), "r"(hi)); return d;
}
__device__ __forceinline__ void wg_fence() { asm volatile("wgmma.fence.sync.aligned;" ::: "memory"); }
__device__ __forceinline__ void wg_commit() { asm volatile("wgmma.commit_group.sync.aligned;" ::: "memory"); }
template <int N> __device__ __forceinline__ void wg_wait() { asm volatile("wgmma.wait_group.sync.aligned %0;" :: "n"(N) : "memory"); }
template <int N> __device__ __forceinline__ void fence_regs(float (&d)[N]) {
#pragma unroll
  for (int i = 0; i < N; i++) asm volatile("" : "+f"(d[i]) :: "memory");
}
template <int N> __device__ __forceinline__ void fence_regs(uint32_t (&d)[N]) {
#pragma unroll
  for (int i = 0; i < N; i++) asm volatile("" : "+r"(d[i]) :: "memory");
}
__device__ __forceinline__ void mbar_init(uint32_t bar, uint32_t cnt) { asm volatile("mbarrier.init.shared::cta.b64 [%0], %1;" :: "r"(bar), "r"(cnt)); }
__device__ __forceinline__ void mbar_expect_tx(uint32_t bar, uint32_t bytes) {
  asm volatile("mbarrier.arrive.expect_tx.shared::cta.b64 _, [%0], %1;" :: "r"(bar), "r"(bytes) : "memory");
}
__device__ __forceinline__ void mbar_arrive(uint32_t bar) { asm volatile("mbarrier.arrive.shared::cta.b64 _, [%0];" :: "r"(bar) : "memory"); }
#define WAIT_HINT 20000u
__device__ __forceinline__ void mbar_wait(uint32_t bar, uint32_t parity) {
  asm volatile("{\n.reg .pred p;\nWAIT_%=:\nmbarrier.try_wait.parity.shared::cta.b64 p, [%0], %1, %2;\n@p bra DONE_%=;\nbra WAIT_%=;\nDONE_%=:\n}\n"
               :: "r"(bar), "r"(parity), "r"(WAIT_HINT) : "memory");
}
__device__ __forceinline__ void fence_mbar_init() { asm volatile("fence.mbarrier_init.release.cluster;" ::: "memory"); }
__device__ __forceinline__ void fence_proxy_async() { asm volatile("fence.proxy.async.shared::cta;" ::: "memory"); }
__device__ __forceinline__ void bulk_g2s(uint32_t dst, const void* src, uint32_t bytes, uint32_t bar) {
  asm volatile("cp.async.bulk.shared::cluster.global.mbarrier::complete_tx::bytes [%0], [%1], %2, [%3];"
               :: "r"(dst), "l"(src), "r"(bytes), "r"(bar) : "memory");
}
__device__ __forceinline__ void tma_2d(uint32_t dst, const CUtensorMap* tm, int c0, int c1, uint32_t bar) {
  asm volatile("cp.async.bulk.tensor.2d.shared::cluster.global.mbarrier::complete_tx::bytes [%0], [%1, {%3, %4}], [%2];"
               :: "r"(dst), "l"((uint64_t)tm), "r"(bar), "r"(c0), "r"(c1) : "memory");
}
__device__ __forceinline__ void tma_3d(uint32_t dst, const CUtensorMap* tm, int c0, int c1, int c2, uint32_t bar) {
  asm volatile("cp.async.bulk.tensor.3d.shared::cluster.global.mbarrier::complete_tx::bytes [%0], [%1, {%3, %4, %5}], [%2];"
               :: "r"(dst), "l"((uint64_t)tm), "r"(bar), "r"(c0), "r"(c1), "r"(c2) : "memory");
}
__device__ __forceinline__ void pdl_wait() { asm volatile("griddepcontrol.wait;" ::: "memory"); }
__device__ __forceinline__ void pdl_launch() { asm volatile("griddepcontrol.launch_dependents;" ::: "memory"); }
__device__ __forceinline__ float ex2(float x) { float y; asm("ex2.approx.ftz.f32 %0, %1;" : "=f"(y) : "f"(x)); return y; }
__device__ __forceinline__ uint32_t pack_bf16(float lo, float hi) {
  uint32_t r; asm("cvt.rn.bf16x2.f32 %0, %1, %2;" : "=r"(r) : "f"(hi), "f"(lo)); return r;
}
__device__ __forceinline__ float bf_lo(uint32_t x) { return __uint_as_float(x << 16); }
__device__ __forceinline__ float bf_hi(uint32_t x) { return __uint_as_float(x & 0xffff0000u); }
__device__ __forceinline__ void stsm4(uint32_t addr, uint32_t r0, uint32_t r1, uint32_t r2, uint32_t r3) {
  asm volatile("stmatrix.sync.aligned.m8n8.x4.shared.b16 [%0], {%1, %2, %3, %4};" :: "r"(addr), "r"(r0), "r"(r1), "r"(r2), "r"(r3) : "memory");
}

__device__ __forceinline__ void wgmma_ss_n160_tb(float (&d)[80], uint64_t descA, uint64_t descB) {
  asm volatile("wgmma.mma_async.sync.aligned.m64n160k16.f32.bf16.bf16 {%0, %1, %2, %3, %4, %5, %6, %7, %8, %9, %10, %11, %12, %13, %14, %15, %16, %17, %18, %19, %20, %21, %22, %23, %24, %25, %26, %27, %28, %29, %30, %31, %32, %33, %34, %35, %36, %37, %38, %39, %40, %41, %42, %43, %44, %45, %46, %47, %48, %49, %50, %51, %52, %53, %54, %55, %56, %57, %58, %59, %60, %61, %62, %63, %64, %65, %66, %67, %68, %69, %70, %71, %72, %73, %74, %75, %76, %77, %78, %79}, %80, %81, 1, 1, 1, 0, 1;\n"
    : "+f"(d[0]), "+f"(d[1]), "+f"(d[2]), "+f"(d[3]), "+f"(d[4]), "+f"(d[5]), "+f"(d[6]), "+f"(d[7]), "+f"(d[8]), "+f"(d[9]), "+f"(d[10]), "+f"(d[11]), "+f"(d[12]), "+f"(d[13]), "+f"(d[14]), "+f"(d[15]), "+f"(d[16]), "+f"(d[17]), "+f"(d[18]), "+f"(d[19]), "+f"(d[20]), "+f"(d[21]), "+f"(d[22]), "+f"(d[23]), "+f"(d[24]), "+f"(d[25]), "+f"(d[26]), "+f"(d[27]), "+f"(d[28]), "+f"(d[29]), "+f"(d[30]), "+f"(d[31]), "+f"(d[32]), "+f"(d[33]), "+f"(d[34]), "+f"(d[35]), "+f"(d[36]), "+f"(d[37]), "+f"(d[38]), "+f"(d[39]), "+f"(d[40]), "+f"(d[41]), "+f"(d[42]), "+f"(d[43]), "+f"(d[44]), "+f"(d[45]), "+f"(d[46]), "+f"(d[47]), "+f"(d[48]), "+f"(d[49]), "+f"(d[50]), "+f"(d[51]), "+f"(d[52]), "+f"(d[53]), "+f"(d[54]), "+f"(d[55]), "+f"(d[56]), "+f"(d[57]), "+f"(d[58]), "+f"(d[59]), "+f"(d[60]), "+f"(d[61]), "+f"(d[62]), "+f"(d[63]), "+f"(d[64]), "+f"(d[65]), "+f"(d[66]), "+f"(d[67]), "+f"(d[68]), "+f"(d[69]), "+f"(d[70]), "+f"(d[71]), "+f"(d[72]), "+f"(d[73]), "+f"(d[74]), "+f"(d[75]), "+f"(d[76]), "+f"(d[77]), "+f"(d[78]), "+f"(d[79])
    : "l"(descA), "l"(descB));
}
__device__ __forceinline__ void wgmma_ss_n48_tb(float (&d)[24], uint64_t descA, uint64_t descB) {
  asm volatile("wgmma.mma_async.sync.aligned.m64n48k16.f32.bf16.bf16 {%0, %1, %2, %3, %4, %5, %6, %7, %8, %9, %10, %11, %12, %13, %14, %15, %16, %17, %18, %19, %20, %21, %22, %23}, %24, %25, 1, 1, 1, 0, 1;\n"
    : "+f"(d[0]), "+f"(d[1]), "+f"(d[2]), "+f"(d[3]), "+f"(d[4]), "+f"(d[5]), "+f"(d[6]), "+f"(d[7]), "+f"(d[8]), "+f"(d[9]), "+f"(d[10]), "+f"(d[11]), "+f"(d[12]), "+f"(d[13]), "+f"(d[14]), "+f"(d[15]), "+f"(d[16]), "+f"(d[17]), "+f"(d[18]), "+f"(d[19]), "+f"(d[20]), "+f"(d[21]), "+f"(d[22]), "+f"(d[23])
    : "l"(descA), "l"(descB));
}
__device__ __forceinline__ void wgmma_ss_n80_tb(float (&d)[40], uint64_t descA, uint64_t descB) {
  asm volatile("wgmma.mma_async.sync.aligned.m64n80k16.f32.bf16.bf16 {%0, %1, %2, %3, %4, %5, %6, %7, %8, %9, %10, %11, %12, %13, %14, %15, %16, %17, %18, %19, %20, %21, %22, %23, %24, %25, %26, %27, %28, %29, %30, %31, %32, %33, %34, %35, %36, %37, %38, %39}, %40, %41, 1, 1, 1, 0, 1;\n"
    : "+f"(d[0]), "+f"(d[1]), "+f"(d[2]), "+f"(d[3]), "+f"(d[4]), "+f"(d[5]), "+f"(d[6]), "+f"(d[7]), "+f"(d[8]), "+f"(d[9]), "+f"(d[10]), "+f"(d[11]), "+f"(d[12]), "+f"(d[13]), "+f"(d[14]), "+f"(d[15]), "+f"(d[16]), "+f"(d[17]), "+f"(d[18]), "+f"(d[19]), "+f"(d[20]), "+f"(d[21]), "+f"(d[22]), "+f"(d[23]), "+f"(d[24]), "+f"(d[25]), "+f"(d[26]), "+f"(d[27]), "+f"(d[28]), "+f"(d[29]), "+f"(d[30]), "+f"(d[31]), "+f"(d[32]), "+f"(d[33]), "+f"(d[34]), "+f"(d[35]), "+f"(d[36]), "+f"(d[37]), "+f"(d[38]), "+f"(d[39])
    : "l"(descA), "l"(descB));
}
template <int SCALE_D>
__device__ __forceinline__ void wgmma_rs_n64(float (&d)[32], uint32_t a0, uint32_t a1, uint32_t a2, uint32_t a3, uint64_t descB) {
  asm volatile("wgmma.mma_async.sync.aligned.m64n64k16.f32.bf16.bf16 {%0, %1, %2, %3, %4, %5, %6, %7, %8, %9, %10, %11, %12, %13, %14, %15, %16, %17, %18, %19, %20, %21, %22, %23, %24, %25, %26, %27, %28, %29, %30, %31}, {%32, %33, %34, %35}, %36, %37, 1, 1, 0;\n"
    : "+f"(d[0]), "+f"(d[1]), "+f"(d[2]), "+f"(d[3]), "+f"(d[4]), "+f"(d[5]), "+f"(d[6]), "+f"(d[7]), "+f"(d[8]), "+f"(d[9]), "+f"(d[10]), "+f"(d[11]), "+f"(d[12]), "+f"(d[13]), "+f"(d[14]), "+f"(d[15]), "+f"(d[16]), "+f"(d[17]), "+f"(d[18]), "+f"(d[19]), "+f"(d[20]), "+f"(d[21]), "+f"(d[22]), "+f"(d[23]), "+f"(d[24]), "+f"(d[25]), "+f"(d[26]), "+f"(d[27]), "+f"(d[28]), "+f"(d[29]), "+f"(d[30]), "+f"(d[31])
    : "r"(a0), "r"(a1), "r"(a2), "r"(a3), "l"(descB), "n"(SCALE_D));
}
template <int SCALE_D>
__device__ __forceinline__ void wgmma_rs_n128(float (&d)[64], uint32_t a0, uint32_t a1, uint32_t a2, uint32_t a3, uint64_t descB) {
  asm volatile("wgmma.mma_async.sync.aligned.m64n128k16.f32.bf16.bf16 {%0, %1, %2, %3, %4, %5, %6, %7, %8, %9, %10, %11, %12, %13, %14, %15, %16, %17, %18, %19, %20, %21, %22, %23, %24, %25, %26, %27, %28, %29, %30, %31, %32, %33, %34, %35, %36, %37, %38, %39, %40, %41, %42, %43, %44, %45, %46, %47, %48, %49, %50, %51, %52, %53, %54, %55, %56, %57, %58, %59, %60, %61, %62, %63}, {%64, %65, %66, %67}, %68, %69, 1, 1, 0;\n"
    : "+f"(d[0]), "+f"(d[1]), "+f"(d[2]), "+f"(d[3]), "+f"(d[4]), "+f"(d[5]), "+f"(d[6]), "+f"(d[7]), "+f"(d[8]), "+f"(d[9]), "+f"(d[10]), "+f"(d[11]), "+f"(d[12]), "+f"(d[13]), "+f"(d[14]), "+f"(d[15]), "+f"(d[16]), "+f"(d[17]), "+f"(d[18]), "+f"(d[19]), "+f"(d[20]), "+f"(d[21]), "+f"(d[22]), "+f"(d[23]), "+f"(d[24]), "+f"(d[25]), "+f"(d[26]), "+f"(d[27]), "+f"(d[28]), "+f"(d[29]), "+f"(d[30]), "+f"(d[31]), "+f"(d[32]), "+f"(d[33]), "+f"(d[34]), "+f"(d[35]), "+f"(d[36]), "+f"(d[37]), "+f"(d[38]), "+f"(d[39]), "+f"(d[40]), "+f"(d[41]), "+f"(d[42]), "+f"(d[43]), "+f"(d[44]), "+f"(d[45]), "+f"(d[46]), "+f"(d[47]), "+f"(d[48]), "+f"(d[49]), "+f"(d[50]), "+f"(d[51]), "+f"(d[52]), "+f"(d[53]), "+f"(d[54]), "+f"(d[55]), "+f"(d[56]), "+f"(d[57]), "+f"(d[58]), "+f"(d[59]), "+f"(d[60]), "+f"(d[61]), "+f"(d[62]), "+f"(d[63])
    : "r"(a0), "r"(a1), "r"(a2), "r"(a3), "l"(descB), "n"(SCALE_D));
}
template <int SCALE_D>
__device__ __forceinline__ void wgmma_rs_n24_tb(float (&d)[12], uint32_t a0, uint32_t a1, uint32_t a2, uint32_t a3, uint64_t descB) {
  asm volatile("wgmma.mma_async.sync.aligned.m64n24k16.f32.bf16.bf16 {%0, %1, %2, %3, %4, %5, %6, %7, %8, %9, %10, %11}, {%12, %13, %14, %15}, %16, %17, 1, 1, 1;\n"
    : "+f"(d[0]), "+f"(d[1]), "+f"(d[2]), "+f"(d[3]), "+f"(d[4]), "+f"(d[5]), "+f"(d[6]), "+f"(d[7]), "+f"(d[8]), "+f"(d[9]), "+f"(d[10]), "+f"(d[11])
    : "r"(a0), "r"(a1), "r"(a2), "r"(a3), "l"(descB), "n"(SCALE_D));
}

constexpr uint32_t DHI_SW128_K = (1024 >> 4) | (1u << 30);
constexpr uint32_t DHI_SW64_MN = (512 >> 4) | (2u << 30);

template <int NC>
__device__ __forceinline__ void store_tile_bf16(const float (&acc)[NC / 2], float scale, uint32_t stage, uint8_t* stage_ptr,
                                                __nv_bfloat16* gdst, int gpitch, int lane) {
  constexpr int PITCH = NC * 2 + 16;
  const uint32_t waddr = stage + ((lane & 7) + ((lane >> 3) & 1) * 8) * PITCH + (lane >> 4) * 16;
#pragma unroll
  for (int j = 0; j < NC / 16; j++) {
    stsm4(waddr + j * 32, pack_bf16(acc[8 * j] * scale, acc[8 * j + 1] * scale), pack_bf16(acc[8 * j + 2] * scale, acc[8 * j + 3] * scale),
          pack_bf16(acc[8 * j + 4] * scale, acc[8 * j + 5] * scale), pack_bf16(acc[8 * j + 6] * scale, acc[8 * j + 7] * scale));
  }
  __syncwarp();
  constexpr int CPR = NC / 8;
#pragma unroll
  for (int i = 0; i < CPR / 2; i++) {
    const int c = i * 32 + lane, r = c / CPR, cc = c % CPR;
    const uint4 v = *reinterpret_cast<const uint4*>(stage_ptr + r * PITCH + cc * 16);
    *reinterpret_cast<uint4*>(gdst + (size_t)r * gpitch + cc * 8) = v;
  }
}

__device__ __forceinline__ void signal_done(unsigned int* flag, int wg, int tid) {
  asm volatile("bar.sync %0, 128;" :: "r"(wg + 1) : "memory");
  if ((tid & 127) == 0) asm volatile("red.release.gpu.global.add.u32 [%0], 1;" :: "l"(flag) : "memory");
}
__device__ __forceinline__ void wait_flags8(const unsigned int* f, unsigned int target) {
  for (int spin = 0; spin < (1 << 26); spin++) {
    unsigned int a, b, c, d, e, g, h, i;
    asm volatile("ld.volatile.global.v4.u32 {%0, %1, %2, %3}, [%4];" : "=r"(a), "=r"(b), "=r"(c), "=r"(d) : "l"(f) : "memory");
    asm volatile("ld.volatile.global.v4.u32 {%0, %1, %2, %3}, [%4];" : "=r"(e), "=r"(g), "=r"(h), "=r"(i) : "l"(f + 4) : "memory");
    if (min(min(min(a, b), min(c, d)), min(min(e, g), min(h, i))) >= target) break;
    __nanosleep(32);
  }
  asm volatile("fence.acq_rel.gpu;" ::: "memory");
  asm volatile("fence.proxy.async;" ::: "memory");
}

#define RP_LD 3
#define RP_ST 7
constexpr int K1_STAGES = 4;
constexpr int K1_A_BYTES = 256 * 128;
constexpr int K1_B_BYTES = 64 * 160 * 2;
constexpr int K1_STAGE = K1_A_BYTES + K1_B_BYTES;
constexpr int K1_SMEM = 5 * K1_A_BYTES + 61440 + 1024;
constexpr int KV_STAGES = 5;
constexpr int KVW_OFF = KV_STAGES * K1_A_BYTES;

__global__ void __launch_bounds__(512, 1)
proj_kernel(const __grid_constant__ CUtensorMap tmX, const __grid_constant__ CUtensorMap tmWq, const __grid_constant__ CUtensorMap tmWqkv,
            const __nv_bfloat16* __restrict__ wk, const __nv_bfloat16* __restrict__ wv, const __nv_bfloat16* __restrict__ gate_w,
            const __nv_bfloat16* __restrict__ woA, const __nv_bfloat16* __restrict__ woB) {
  extern __shared__ uint8_t smem_raw[];
  __shared__ __align__(8) uint64_t bar_full[KV_STAGES], bar_empty[KV_STAGES];
  uint8_t* smem = reinterpret_cast<uint8_t*>((reinterpret_cast<uintptr_t>(smem_raw) + 1023) & ~(uintptr_t)1023);
  const uint32_t sbase = smem_u32(smem);
  const uint32_t dbase = sbase & 0x3FFFFu;
  const int tid = threadIdx.x, warp = tid >> 5, lane = tid & 31;
  const bool is_kv = blockIdx.x >= 128;
  PROF(0, 0);
  if (tid == 0) {
    for (int i = 0; i < KV_STAGES; i++) { mbar_init(smem_u32(&bar_full[i]), 1); mbar_init(smem_u32(&bar_empty[i]), is_kv ? 8 : 16); }
    fence_mbar_init();
  }
  uint2 wa[2][5], wb[2][5]; uint32_t gw[2];
  if (is_kv && tid < 320) {
#pragma unroll
    for (int r = 0; r < 2; r++) {
      const int k = tid + r * 320;
      const uint2* pk = reinterpret_cast<const uint2*>(wk + k * 20);
      const uint2* pv = reinterpret_cast<const uint2*>(wv + k * 20);
#pragma unroll
      for (int i = 0; i < 5; i++) { wa[r][i] = __ldg(pk + i); wb[r][i] = __ldg(pv + i); }
      gw[r] = (uint32_t)__bfloat16_as_ushort(gate_w[k]);
    }
  }
  __syncthreads();
  if (tid == 480) {
    if (!is_kv) { g_done[blockIdx.x] = 0u; g_doneL[blockIdx.x] = 0u; }
    asm volatile("fence.acq_rel.gpu;" ::: "memory");
    pdl_launch();
  }
  __syncwarp();

  if (!is_kv) {
    const int mb = blockIdx.x >> 4, nb = blockIdx.x & 15;
    const CUtensorMap* tw = nb < 4 ? &tmWq : &tmWqkv;
    const int j0 = (nb < 4 ? nb : nb - 4) * 5;
    auto load = [&](int kt) {
      const int s = kt % K1_STAGES;
      const uint32_t fb = smem_u32(&bar_full[s]);
      mbar_expect_tx(fb, K1_STAGE);
      tma_2d(sbase + s * K1_STAGE, &tmX, kt * 64, mb * 256, fb);
      tma_3d(sbase + s * K1_STAGE + K1_A_BYTES, tw, 0, kt * 64, j0, fb);
    };
    if (tid == 0) for (int kt = 0; kt < K1_STAGES; kt++) load(kt);
    __syncwarp();
    uint4 wv2[2];
    const int rq = blockIdx.x * 400 + tid - 112;
    const int rhalf = rq >= 25600, rr = rq - rhalf * 25600, rk = 2 * (rr / 80), rch = rr % 80;
    {
      const int wg = warp >> 2;
      float acc[80];
#pragma unroll
      for (int i = 0; i < 80; i++) acc[i] = 0.f;
      for (int kt = 0; kt < 10; kt++) {
        const int s = kt % K1_STAGES;
        mbar_wait(smem_u32(&bar_full[s]), (kt / K1_STAGES) & 1);
        const uint32_t alo = ((dbase + s * K1_STAGE + wg * 8192) >> 4) | (1u << 16);
        const uint32_t blo = ((dbase + s * K1_STAGE + K1_A_BYTES) >> 4) | ((4096u >> 4) << 16);
        fence_regs(acc);
        wg_fence();
#pragma unroll
        for (int k = 0; k < 4; k++) wgmma_ss_n160_tb(acc, mkd(alo + k * 2, DHI_SW128_K), mkd(blo + k * 64, DHI_SW64_MN));
        wg_commit();
        if (kt == RP_LD && tid >= 112) {
          const uint4* src = reinterpret_cast<const uint4*>((rhalf ? woB : woA) + rk * D_MODEL + rch * 8);
          wv2[0] = __ldg(src); wv2[1] = __ldg(src + D_MODEL / 8);
        }
        if (kt == RP_ST && tid >= 112) {
          uint4* dst = reinterpret_cast<uint4*>(g_wimg + ((rhalf * 8 + rch / 10) * 10 + (rk >> 6)) * 10240 + (rch % 10) * 1024 + (rk & 63) * 16);
          dst[0] = wv2[0]; dst[1] = wv2[1];
        }
        __syncwarp();
        if (kt > 0 && kt - 1 + K1_STAGES < 10) {
          wg_wait<1>();
          const uint32_t eb = smem_u32(&bar_empty[(kt - 1) % K1_STAGES]);
          if (lane == 0) mbar_arrive(eb);
          if (tid == 0) { mbar_wait(eb, ((kt - 1) / K1_STAGES) & 1); load(kt - 1 + K1_STAGES); }
          __syncwarp();
        }
      }
      wg_wait<0>();
      fence_regs(acc);
      PROF(0, 1);
      asm volatile("bar.sync %0, 128;" :: "r"(wg + 1) : "memory");
      const int w4 = warp & 3;
      const uint32_t off = w4 * K1_STAGE + wg * 8192;
      const int row0 = mb * 256 + wg * 64 + w4 * 16;
      if (nb < 4) {
        store_tile_bf16<160>(acc, 0.22360679774997896f * 1.4426950408889634f, sbase + off, smem + off,
                             g_q + (size_t)row0 * D_MODEL + nb * 160, D_MODEL, lane);
      } else {
        store_tile_bf16<160>(acc, 1.0f, sbase + off, smem + off, g_qkv + (size_t)row0 * (3 * D_MODEL) + (nb - 4) * 160, 3 * D_MODEL, lane);
      }
    }
  } else {
    const int cb = blockIdx.x - 128;
    if (warp == 8 && lane == 0) {
      for (int it = 0; it < KV_STAGES; it++) {
        const uint32_t fb = smem_u32(&bar_full[it]);
        mbar_expect_tx(fb, K1_A_BYTES);
        tma_2d(sbase + it * K1_A_BYTES, &tmX, it * 64, cb * 512, fb);
      }
    }
    __syncwarp();
    if (tid < 320) {
#pragma unroll
      for (int r = 0; r < 2; r++) {
        uint4* dst = reinterpret_cast<uint4*>(smem + KVW_OFF + (tid + r * 320) * 16);
        dst[0] = make_uint4(wa[r][0].x, wa[r][0].y, wa[r][1].x, wa[r][1].y);
        dst[640] = make_uint4(wa[r][2].x, wa[r][2].y, wa[r][3].x, wa[r][3].y);
        dst[1280] = make_uint4(wa[r][4].x, wa[r][4].y, 0u, 0u);
        dst[1920] = make_uint4(wb[r][0].x, wb[r][0].y, wb[r][1].x, wb[r][1].y);
        dst[2560] = make_uint4(wb[r][2].x, wb[r][2].y, wb[r][3].x, wb[r][3].y);
        dst[3200] = make_uint4(wb[r][4].x, wb[r][4].y, gw[r], 0u);
      }
    }
    fence_proxy_async();
    asm volatile("bar.sync 1, 512;" ::: "memory");
    PROF(0, 1);
    auto produce = [&](int it0, int it1) {
      for (int it = it0; it < it1; it++) {
        const int s = it % KV_STAGES;
        mbar_wait(smem_u32(&bar_empty[s]), (it / KV_STAGES - 1) & 1);
        const uint32_t fb = smem_u32(&bar_full[s]);
        mbar_expect_tx(fb, K1_A_BYTES);
        tma_2d(sbase + s * K1_A_BYTES, &tmX, (it >= 10 ? it - 10 : it) * 64, cb * 512 + (it >= 10 ? 256 : 0), fb);
      }
    };
    if (tid == 256) produce(KV_STAGES, 15);
    __syncwarp();
    {
      const int pass = warp >> 3, wg = (warp >> 2) & 1, w4 = warp & 3, g = lane >> 2, t = lane & 3;
      if (pass == 1) asm volatile("bar.sync 2, 512;" ::: "memory");
      {
        float acc[2][24];
#pragma unroll
        for (int i = 0; i < 24; i++) { acc[0][i] = 0.f; acc[1][i] = 0.f; }
        for (int kt = 0; kt < 10; kt++) {
          const int it = pass * 10 + kt, s = it % KV_STAGES;
          mbar_wait(smem_u32(&bar_full[s]), (it / KV_STAGES) & 1);
          const uint32_t alo = ((dbase + s * K1_A_BYTES + wg * 16384) >> 4) | (1u << 16);
          const uint32_t blo = ((dbase + KVW_OFF + kt * 1024) >> 4) | ((128u >> 4) << 16);
          fence_regs(acc[0]); fence_regs(acc[1]);
          wg_fence();
#pragma unroll
          for (int k = 0; k < 4; k++) {
            wgmma_ss_n48_tb(acc[0], mkd(alo + k * 2, DHI_SW128_K), mkd(blo + k * 16, 10240u >> 4));
            wgmma_ss_n48_tb(acc[1], mkd(alo + 512 + k * 2, DHI_SW128_K), mkd(blo + k * 16, 10240u >> 4));
          }
          wg_commit();
          if (kt > 0) {
            wg_wait<1>();
            if (lane == 0) mbar_arrive(smem_u32(&bar_empty[(it - 1) % KV_STAGES]));
          }
        }
        wg_wait<0>();
        fence_regs(acc[0]); fence_regs(acc[1]);
        if (lane == 0) mbar_arrive(smem_u32(&bar_empty[(pass * 10 + 9) % KV_STAGES]));
        if (pass == 0) asm volatile("bar.arrive 2, 512;" ::: "memory");
        PROF(0, 2);
        if (tid == 0) produce(15, 20);
        __syncwarp();
        float kmax2 = 0.f, vmax = 0.f;
#pragma unroll
        for (int hh = 0; hh < 4; hh++) {
          const int h = hh & 1;
          const float (&a)[24] = acc[hh >> 1];
          const int key = cb * 512 + pass * 256 + wg * 128 + (hh >> 1) * 64 + w4 * 16 + g + h * 8;
          const int grp = key >> 7, kk = key & 127;
          const bool poly = (TMASK >> (kk >> 3)) & 1;
          uint8_t* gp = g_kvimg + grp * GRP_BYTES;
          const uint32_t k0 = pack_bf16(a[2 * h], a[2 * h + 1]);
          const uint32_t k1 = pack_bf16(a[4 + 2 * h], a[5 + 2 * h]);
          uint32_t k2 = pack_bf16(a[8 + 2 * h], a[9 + 2 * h]);
          float n2 = bf_lo(k0) * bf_lo(k0) + bf_hi(k0) * bf_hi(k0) + bf_lo(k1) * bf_lo(k1) + bf_hi(k1) * bf_hi(k1);
          if (t < 2) {
            n2 += bf_lo(k2) * bf_lo(k2) + bf_hi(k2) * bf_hi(k2);
            k2 = pack_bf16(bf_lo(k2) * 0.5f, bf_hi(k2) * 0.5f);
          } else if (t == 2) k2 = poly ? pack_bf16(24.f, 2.5f) : pack_bf16(0.5f, 0.f);
          else k2 = poly ? pack_bf16(0.5f, 0.f) : 0u;
          *reinterpret_cast<uint32_t*>(gp + kk * 16 + t * 4) = k0;
          *reinterpret_cast<uint32_t*>(gp + PLANE + kk * 16 + t * 4) = k1;
          *reinterpret_cast<uint32_t*>(gp + 2 * PLANE + kk * 16 + t * 4) = k2;
          n2 += __shfl_xor_sync(0xffffffffu, n2, 1);
          n2 += __shfl_xor_sync(0xffffffffu, n2, 2);
          kmax2 = (n2 > kmax2 || n2 != n2) ? n2 : kmax2;
          uint32_t v0 = pack_bf16(a[12 + 2 * h], a[13 + 2 * h]);
          uint32_t v1 = pack_bf16(a[16 + 2 * h], a[17 + 2 * h]);
          uint32_t v2 = pack_bf16(a[20 + 2 * h], a[21 + 2 * h]);
          float vm = fmaxf(fmaxf(fabsf(bf_lo(v0)), fabsf(bf_hi(v0))), fmaxf(fabsf(bf_lo(v1)), fabsf(bf_hi(v1))));
          if (t < 2) vm = fmaxf(vm, fmaxf(fabsf(bf_lo(v2)), fabsf(bf_hi(v2))));
          else if (t == 2) {
            const float z = a[20 + 2 * h];
            g_gate[key] = 1.f / (1.f + __expf(-z));
            v2 = 0x00003F80u;
          } else v2 = 0u;
          vmax = fmaxf(vmax, vm);
          if (poly) { v0 ^= 0x80008000u; v1 ^= 0x80008000u; v2 ^= 0x80008000u; }
          uint8_t* vp = gp + 3 * PLANE + (kk >> 3) * 384 + (kk & 7) * 16 + t * 4;
          *reinterpret_cast<uint32_t*>(vp) = v0;
          *reinterpret_cast<uint32_t*>(vp + 128) = v1;
          *reinterpret_cast<uint32_t*>(vp + 256) = v2;
        }
#pragma unroll
        for (int o = 1; o < 32; o <<= 1) {
          const float a = __shfl_xor_sync(0xffffffffu, kmax2, o);
          kmax2 = (a > kmax2 || a != a) ? a : kmax2;
          vmax = fmaxf(vmax, __shfl_xor_sync(0xffffffffu, vmax, o));
        }
        if (lane == 0) { g_kmax2[cb * 16 + warp] = kmax2; g_vmax[cb * 16 + warp] = vmax; }
      }
    }
  }
}

__device__ __forceinline__ uint32_t ex2_pair_poly(float u0, float u1, uint32_t one2) {
  const uint32_t W = __byte_perm(__float_as_uint(u0), __float_as_uint(u1), 0x6521);
  uint32_t v; asm("lop3.b32 %0, %1, 0x007F007F, %2, 0xEA;" : "=r"(v) : "r"(W), "r"(one2));
  uint32_t L, p;
  asm("fma.rn.bf16x2 %0, %1, %2, %3;" : "=r"(L) : "r"(v), "r"(0x1f961f96u), "r"(0x9fe39fe3u));
  asm("fma.rn.bf16x2 %0, %1, %1, %2;" : "=r"(p) : "r"(L), "r"(0x00f500f5u));
  return W + p;
}
template <int JOFF>
__device__ __forceinline__ void softmax_slow(const float (&S)[32], uint32_t (&P)[16], float (&O)[12], float& m0, float& m1) {
  float a0 = m0, a1 = m1;
#pragma unroll
  for (int j = 0; j < 8; j++) {
    a0 = fmaxf(a0, fmaxf(S[4 * j], S[4 * j + 1]));
    a1 = fmaxf(a1, fmaxf(S[4 * j + 2], S[4 * j + 3]));
  }
  a0 = fmaxf(a0, __shfl_xor_sync(0xffffffffu, a0, 1)); a0 = fmaxf(a0, __shfl_xor_sync(0xffffffffu, a0, 2));
  a1 = fmaxf(a1, __shfl_xor_sync(0xffffffffu, a1, 1)); a1 = fmaxf(a1, __shfl_xor_sync(0xffffffffu, a1, 2));
  const float c0 = ex2(m0 - a0), c1 = ex2(m1 - a1);
  m0 = a0; m1 = a1;
#pragma unroll
  for (int j = 0; j < 3; j++) { O[4 * j] *= c0; O[4 * j + 1] *= c0; O[4 * j + 2] *= c1; O[4 * j + 3] *= c1; }
#pragma unroll
  for (int i = 0; i < 16; i++) {
    const float m = (i & 1) ? a1 : a0;
    const uint32_t p = pack_bf16(ex2(S[2 * i] - m), ex2(S[2 * i + 1] - m));
    P[i] = ((TMASK >> (JOFF + i / 2)) & 1) ? (p ^ 0x80008000u) : p;
  }
}
constexpr uint32_t DHI_KV = 128 >> 4;
__device__ __forceinline__ void issue_qk(float (&S)[32], const uint32_t (&q)[8], uint64_t base) {
  wgmma_rs_n64<0>(S, q[0], q[1], q[2], q[3], base + (uint64_t)((PLANE >> 4) << 16));
  wgmma_rs_n64<1>(S, q[4], q[5], q[6], q[7], base + (uint64_t)(2 * PLANE >> 4));
}
__device__ __forceinline__ void issue_pv(float (&O)[12], const uint32_t (&P)[16], uint64_t vbase) {
#pragma unroll
  for (int kk = 0; kk < 4; kk++)
    wgmma_rs_n24_tb<1>(O, P[4 * kk], P[4 * kk + 1], P[4 * kk + 2], P[4 * kk + 3], vbase + (uint64_t)(kk * (768 >> 4)));
}

constexpr uint32_t VOFF = ((3 * PLANE) >> 4) + ((384u >> 4) << 16);
constexpr int KVR = 4;
constexpr int OFF_W = KVR * GRP_BYTES;
constexpr int OFF_X = OFF_W + 10 * 10240;
constexpr int OFF_BAR = OFF_X + 4 * 16384;
constexpr int K2_SMEM = OFF_BAR + 256 + 1024;
constexpr int TSL = 7;
constexpr int BAR_KV = 0, BAR_W = 4, BAR_TA = 5, BAR_TE = 12, BAR_OWN = 19, CNT_KV = 20;
constexpr int NSTEP = 2 * NGRP;

__device__ __forceinline__ void kv_load(uint32_t sbase, int step) {
  const uint32_t bar = sbase + OFF_BAR + (BAR_KV + (step & (KVR - 1))) * 8;
  mbar_expect_tx(bar, GRP_BYTES);
  bulk_g2s(sbase + (step & (KVR - 1)) * GRP_BYTES, g_kvimg + (step & (NGRP - 1)) * GRP_BYTES, GRP_BYTES, bar);
}
__device__ __forceinline__ void kv_release(uint32_t sbase, int step, bool elected) {
  if (elected && step + KVR < NSTEP) {
    uint32_t old;
    asm volatile("atom.acq_rel.cta.shared::cta.inc.u32 %0, [%1], 3;" : "=r"(old) : "r"(sbase + OFF_BAR + CNT_KV * 8 + (step & (KVR - 1)) * 4) : "memory");
    if (old == 3u) kv_load(sbase, step + KVR);
  }
  __syncwarp();
}
__device__ __forceinline__ void kv_wait(uint32_t sbase, int step) {
  mbar_wait(sbase + OFF_BAR + (BAR_KV + (step & (KVR - 1))) * 8, (step / KVR) & 1);
}

__device__ __forceinline__ uint32_t kv_release_begin(uint32_t sbase, int slot, bool doit) {
  uint32_t old = 0;
  asm volatile("{\n.reg .pred p;\nsetp.ne.u32 p, %2, 0;\n@p atom.relaxed.cta.shared::cta.inc.u32 %0, [%1], 3;\n}\n"
               : "+r"(old) : "r"(sbase + OFF_BAR + CNT_KV * 8 + slot * 4), "r"((uint32_t)doit) : "memory");
  return old;
}
template <int H>
__device__ __forceinline__ void softmax_half(const float (&S)[64], uint32_t (&P)[16], uint32_t one2) {
#pragma unroll
  for (int i = 0; i < 16; i++) {
    if ((TMASK >> (8 * H + i / 2)) & 1) P[i] = ex2_pair_poly(S[32 * H + 2 * i], S[32 * H + 2 * i + 1], one2);
    else P[i] = pack_bf16(ex2(S[32 * H + 2 * i]), ex2(S[32 * H + 2 * i + 1]));
  }
}
__device__ __forceinline__ void attn_fast(const uint32_t (&q)[8], float (&O)[12], uint32_t sbase, int step0, int nsteps, bool elected, uint32_t one2) {
  uint64_t kb0 = mkd((sbase & 0x3FFFFu) >> 4, DHI_KV);
  asm volatile("" : "+l"(kb0));
#pragma unroll 1
  for (int step4 = step0; step4 < step0 + nsteps; step4 += KVR) {
#pragma unroll
    for (int j = 0; j < KVR; j++) {
      const int step = step4 + j;
      const uint64_t kb = kb0 + (uint64_t)(j * (GRP_BYTES >> 4));
      float S[64]; uint32_t PA[16], PB[16];
#pragma unroll
      for (int i = 0; i < 64; i++) S[i] = 0.f;
      mbar_wait(sbase + OFF_BAR + (BAR_KV + j) * 8, (step / KVR) & 1);
      fence_regs(S);
      wg_fence();
      wgmma_rs_n128<0>(S, q[0], q[1], q[2], q[3], kb + (uint64_t)((PLANE >> 4) << 16));
      wgmma_rs_n128<1>(S, q[4], q[5], q[6], q[7], kb + (uint64_t)(2 * PLANE >> 4));
      wg_commit();
      wg_wait<0>();
      fence_regs(S);
      softmax_half<0>(S, PA, one2);
      fence_regs(PA); fence_regs(O);
      wg_fence();
      issue_pv(O, PA, kb + VOFF);
      wg_commit();
      softmax_half<1>(S, PB, one2);
      fence_regs(PB);
      wg_fence();
      issue_pv(O, PB, kb + VOFF + 4 * (768 >> 4));
      wg_commit();
      wg_wait<0>();
      fence_regs(PA); fence_regs(PB); fence_regs(O);
      const uint32_t old = kv_release_begin(sbase, j, elected && step + KVR < NSTEP);
      if (old == 3u) kv_load(sbase, step + KVR);
    }
  }
}
template <int H>
__device__ __forceinline__ void slow_step(const uint32_t (&q)[8], float (&O)[12], uint64_t kb, float& m0, float& m1) {
  float S[32]; uint32_t P[16];
#pragma unroll
  for (int i = 0; i < 32; i++) S[i] = 0.f;
  fence_regs(S);
  wg_fence();
  issue_qk(S, q, kb + 64 * H);
  wg_commit();
  wg_wait<0>();
  fence_regs(S);
  softmax_slow<8 * H>(S, P, O, m0, m1);
  fence_regs(P); fence_regs(O);
  wg_fence();
  issue_pv(O, P, kb + VOFF + H * 4 * (768 >> 4));
  wg_commit();
  wg_wait<0>();
  fence_regs(O); fence_regs(P);
}
__device__ __forceinline__ void attn_slow(const uint32_t (&q)[8], float (&O)[12], uint32_t sbase, int step0, int nsteps, bool elected, float& m0, float& m1) {
#pragma unroll 1
  for (int step = step0; step < step0 + nsteps; step++) {
    kv_wait(sbase, step);
    const uint64_t kb = mkd(((sbase & 0x3FFFFu) >> 4) + (step & (KVR - 1)) * (GRP_BYTES >> 4), DHI_KV);
    slow_step<0>(q, O, kb, m0, m1);
    slow_step<1>(q, O, kb, m0, m1);
    kv_release(sbase, step, elected);
  }
}

__device__ __forceinline__ void load_row20(const __nv_bfloat16* p, float (&f)[20]) {
  const uint2* p2 = reinterpret_cast<const uint2*>(p);
#pragma unroll
  for (int i = 0; i < 5; i++) { const uint2 v = p2[i]; f[4 * i] = bf_lo(v.x); f[4 * i + 1] = bf_hi(v.x); f[4 * i + 2] = bf_lo(v.y); f[4 * i + 3] = bf_hi(v.y); }
}
__device__ __forceinline__ void softmax8(float (&sc)[8]) {
  float mx = sc[0];
#pragma unroll
  for (int w = 1; w < 8; w++) mx = fmaxf(mx, sc[w]);
  float l = 0.f;
#pragma unroll
  for (int w = 0; w < 8; w++) { sc[w] = ex2(sc[w] - mx); l += sc[w]; }
  const float r = 1.f / l;
#pragma unroll
  for (int w = 0; w < 8; w++) sc[w] *= r;
}
__device__ __forceinline__ void local_attn(int t, int lane) {
  constexpr int PITCH = 3 * D_MODEL;
  constexpr float SC = 0.22360679774997896f * 1.4426950408889634f, NEG = -1e9f * 1.4426950408889634f;
  const __nv_bfloat16* base = g_qkv + lane * DH;
  float a[20], sc[8];
  load_row20(base + (size_t)t * PITCH, a);
#pragma unroll
  for (int w = 0; w < 8; w++) {
    const int r = t - 2 * w;
    float k[20];
    load_row20(base + D_MODEL + (size_t)max(r, 0) * PITCH, k);
    float d = 0.f;
#pragma unroll
    for (int i = 0; i < 20; i++) d = fmaf(a[i], k[i], d);
    sc[w] = r >= 0 ? d * SC : NEG;
  }
  softmax8(sc);
#pragma unroll
  for (int i = 0; i < 20; i++) a[i] = 0.f;
#pragma unroll
  for (int w = 0; w < 8; w++) {
    float v[20];
    load_row20(base + 2 * D_MODEL + (size_t)max(t - 2 * w, 0) * PITCH, v);
#pragma unroll
    for (int i = 0; i < 20; i++) a[i] = fmaf(sc[w], v[i], a[i]);
  }
  const float ga = 1.f - g_gate[t];
  uint2* da = reinterpret_cast<uint2*>(g_a2 + (size_t)t * (2 * D_MODEL) + D_MODEL + lane * DH);
#pragma unroll
  for (int i = 0; i < 5; i++)
    da[i] = make_uint2(pack_bf16(a[4 * i] * ga, a[4 * i + 1] * ga), pack_bf16(a[4 * i + 2] * ga, a[4 * i + 3] * ga));
}
__device__ __forceinline__ uint32_t ta_slot(int i) { return i < 4 ? OFF_X + i * 16384 : (i - 4) * 16384; }

__global__ void __launch_bounds__(512, 1)
attn_kernel(const __grid_constant__ CUtensorMap tmA2, __nv_bfloat16* __restrict__ out, uint32_t one2) {
  extern __shared__ uint8_t smem_raw[];
  uint8_t* smem = reinterpret_cast<uint8_t*>((reinterpret_cast<uintptr_t>(smem_raw) + 1023) & ~(uintptr_t)1023);
  const uint32_t sbase = smem_u32(smem);
  const uint32_t dbase = sbase & 0x3FFFFu;
  const uint32_t bars = sbase + OFF_BAR;
  const int tid = threadIdx.x, wg = tid >> 7, warp = (tid >> 5) & 3, lane = tid & 31, g = lane >> 2, t = lane & 3;
  const int mb = blockIdx.x >> 3, nb = blockIdx.x & 7;
  const bool elected = (tid & 127) == 0;
  if (tid == 0) {
    for (int i = 0; i < BAR_TE; i++) mbar_init(bars + i * 8, 1);
    for (int i = BAR_TE; i < BAR_TE + TSL; i++) mbar_init(bars + i * 8, 8);
    mbar_init(bars + BAR_OWN * 8, 4);
    for (int i = 0; i < 4; i++) *reinterpret_cast<uint32_t*>(smem + OFF_BAR + CNT_KV * 8 + i * 4) = 0u;
    fence_mbar_init();
  }
  __syncthreads();
  auto tail_load = [&](int i) {
    const uint32_t fb = bars + (BAR_TA + i % TSL) * 8;
    mbar_expect_tx(fb, i < 10 ? 16384 : 16384 + 10240);
    tma_2d(sbase + ta_slot(i % TSL), &tmA2, i < 10 ? D_MODEL + i * 64 : (i - 10) * 64, mb * 128, fb);
    if (i >= 10) bulk_g2s(sbase + OFF_W + (i - 10) * 10240, g_wimg + (nb * 10 + i - 10) * 10240, 10240, fb);
  };
  pdl_wait();
  PROF(1, 1);
  if (tid == 416) for (int j = 0; j < KVR; j++) kv_load(sbase, j);
  __syncwarp();
  uint32_t q[8], q2[6];
  const int rowA = (blockIdx.x * 8 + wg) * 64 + warp * 16 + g;
  {
    const uint32_t* r0 = reinterpret_cast<const uint32_t*>(g_q + (size_t)rowA * DH);
    const uint32_t* r1 = r0 + 8 * (DH / 2);
    const uint32_t* s0 = r0 + 256 * (DH / 2);
    const uint32_t* s1 = s0 + 8 * (DH / 2);
    q[0] = r0[t]; q[1] = r1[t]; q[2] = r0[t + 4]; q[3] = r1[t + 4];
    q[4] = t < 2 ? r0[8 + t] : 0u;
    q[5] = t < 2 ? r1[8 + t] : 0u;
    q2[0] = s0[t]; q2[1] = s1[t]; q2[2] = s0[t + 4]; q2[3] = s1[t + 4];
    q2[4] = t < 2 ? s0[8 + t] : 0u;
    q2[5] = t < 2 ? s1[8 + t] : 0u;
  }
  float kmax2 = 0.f, vmax = 0.f;
#pragma unroll
  for (int i = 0; i < 2; i++) {
    const float a = g_kmax2[lane + 32 * i];
    kmax2 = (a > kmax2 || a != a) ? a : kmax2;
    vmax = fmaxf(vmax, g_vmax[lane + 32 * i]);
  }
#pragma unroll
  for (int o = 1; o < 32; o <<= 1) {
    const float a = __shfl_xor_sync(0xffffffffu, kmax2, o);
    kmax2 = (a > kmax2 || a != a) ? a : kmax2;
    vmax = fmaxf(vmax, __shfl_xor_sync(0xffffffffu, vmax, o));
  }
  const float qlim = (vmax >= 0.00390625f && vmax <= 256.f) ? 9025.f / kmax2 : -1.f;
  PROF(1, 2);
#pragma unroll 1
  for (int it = 0; it < 2; it++) {
    const int row0 = rowA + it * 256;
    if (it == 1) {
#pragma unroll
      for (int i = 0; i < 6; i++) q[i] = q2[i];
    }
    float n0 = bf_lo(q[0]) * bf_lo(q[0]) + bf_hi(q[0]) * bf_hi(q[0]) + bf_lo(q[2]) * bf_lo(q[2]) + bf_hi(q[2]) * bf_hi(q[2]) +
               bf_lo(q[4]) * bf_lo(q[4]) + bf_hi(q[4]) * bf_hi(q[4]);
    float n1 = bf_lo(q[1]) * bf_lo(q[1]) + bf_hi(q[1]) * bf_hi(q[1]) + bf_lo(q[3]) * bf_lo(q[3]) + bf_hi(q[3]) * bf_hi(q[3]) +
               bf_lo(q[5]) * bf_lo(q[5]) + bf_hi(q[5]) * bf_hi(q[5]);
    n0 += __shfl_xor_sync(0xffffffffu, n0, 1); n0 += __shfl_xor_sync(0xffffffffu, n0, 2);
    n1 += __shfl_xor_sync(0xffffffffu, n1, 1); n1 += __shfl_xor_sync(0xffffffffu, n1, 2);
    const bool safe = (n0 <= qlim) && (n1 <= qlim);
    uint32_t unsafe_any;
    asm volatile("{\n.reg .pred p, r;\nsetp.eq.u32 p, %1, 0;\nbarrier.cta.red.or.pred r, %2, 128, p;\nselp.u32 %0, 1, 0, r;\n}\n"
                 : "=r"(unsafe_any) : "r"((uint32_t)safe), "r"(wg + 1) : "memory");
    float O[12];
#pragma unroll
    for (int i = 0; i < 12; i++) O[i] = 0.f;
    if (!unsafe_any && t >= 2) { q[4] = q[5] = (t == 2) ? 0x3F804100u : 0x00003B80u; }
    q[6] = q[4]; q[7] = q[5];
    fence_regs(q);
    float m0 = -INFINITY, m1 = -INFINITY;
#pragma unroll 1
    for (int part = 0; part < 4; part++) {
      const int s0 = it * NGRP + part * KVR;
      if (!unsafe_any) attn_fast(q, O, sbase, s0, KVR, elected, one2);
      else attn_slow(q, O, sbase, s0, KVR, elected, m0, m1);
      const int ev = it * 4 + part - wg;
      if (ev == 0) {
        local_attn(blockIdx.x * 16 + (tid >> 5), lane);
      } else if (ev == 1) {
        signal_done(&g_doneL[blockIdx.x], wg, tid);
        if (tid == 160) {
          mbar_expect_tx(bars + BAR_W * 8, 10 * 10240);
          for (int i = 0; i < 5; i++) bulk_g2s(sbase + OFF_W + i * 20480, g_wimg + ((8 + nb) * 10) * 10240 + i * 20480, 20480, bars + BAR_W * 8);
        }
      } else if (ev == 6 && tid == 32) {
        wait_flags8(&g_doneL[mb * 8], 4u);
        for (int i = 0; i < 4; i++) tail_load(i);
      }
      __syncwarp();
    }
    const float l0 = __shfl_sync(0xffffffffu, O[8], (lane & ~3) | 2);
    const float l1 = __shfl_sync(0xffffffffu, O[10], (lane & ~3) | 2);
    const int tok = row0 >> 5;
    const float gt = g_gate[tok];
    const float i0 = gt / l0, i1 = gt / l1;
    uint32_t* o0 = reinterpret_cast<uint32_t*>(g_a2 + (size_t)tok * (2 * D_MODEL) + (row0 & 31) * DH);
    uint32_t* o1 = o0 + 8 * (DH / 2);
    o0[t] = pack_bf16(O[0] * i0, O[1] * i0); o1[t] = pack_bf16(O[2] * i1, O[3] * i1);
    o0[t + 4] = pack_bf16(O[4] * i0, O[5] * i0); o1[t + 4] = pack_bf16(O[6] * i1, O[7] * i1);
    if (t < 2) { o0[t + 8] = pack_bf16(O[8] * i0, O[9] * i0); o1[t + 8] = pack_bf16(O[10] * i1, O[11] * i1); }
  }
  signal_done(&g_done[blockIdx.x], wg, tid);
  if ((tid & 127) == 64) mbar_arrive(bars + BAR_OWN * 8);
  PROF(1, 3);
  if (wg == 3) {
    if (tid == 416) {
      mbar_wait(bars + BAR_OWN * 8, 0);
      for (int i = 4; i < 20; i++) {
        if (i >= TSL) mbar_wait(bars + (BAR_TE + i % TSL) * 8, (i / TSL - 1) & 1);
        if (i == 10) { wait_flags8(&g_done[mb * 8], 4u); PROF2(2, 0); }
        tail_load(i);
      }
    }
  } else if (wg < 2) {
    float acc[40];
#pragma unroll
    for (int i = 0; i < 40; i++) acc[i] = 0.f;
    mbar_wait(bars + BAR_W * 8, 0);
    int sl = 0, ph = 0;
#pragma unroll 1
    for (int i = 0; i < 20; i++) {
      mbar_wait(bars + (BAR_TA + sl) * 8, ph);
      if (i == 10) PROF(2, 1);
      const uint32_t alo = ((dbase + ta_slot(sl) + wg * 8192) >> 4) | (1u << 16);
      const uint32_t blo = ((dbase + OFF_W + (i >= 10 ? i - 10 : i) * 10240) >> 4) | ((128u >> 4) << 16);
      fence_regs(acc);
      wg_fence();
#pragma unroll
      for (int k = 0; k < 4; k++) wgmma_ss_n80_tb(acc, mkd(alo + k * 2, DHI_SW128_K), mkd(blo + k * 16, 1024u >> 4));
      wg_commit();
      if (i > 0) {
        wg_wait<1>();
        if (lane == 0) mbar_arrive(bars + (BAR_TE + (sl == 0 ? TSL - 1 : sl - 1)) * 8);
      }
      if (++sl == TSL) { sl = 0; ph ^= 1; }
    }
    wg_wait<0>();
    fence_regs(acc);
    PROF(2, 2);
    asm volatile("bar.sync %0, 128;" :: "r"(wg + 1) : "memory");
    const uint32_t so = ta_slot(warp) + wg * 8192;
    const int row0 = mb * 128 + wg * 64 + warp * 16;
    store_tile_bf16<80>(acc, 1.0f, sbase + so, smem + so, out + (size_t)row0 * D_MODEL + nb * 80, D_MODEL, lane);
    PROF(2, 3);
  }
}

typedef CUresult (*EncodeFn)(CUtensorMap*, CUtensorMapDataType, cuuint32_t, void*, const cuuint64_t*, const cuuint64_t*,
                             const cuuint32_t*, const cuuint32_t*, CUtensorMapInterleave, CUtensorMapSwizzle,
                             CUtensorMapL2promotion, CUtensorMapFloatOOBfill);

void make_map(EncodeFn fn, CUtensorMap* tm, const void* ptr, int rank, const cuuint64_t* dims, const cuuint64_t* strides,
              const cuuint32_t* box, CUtensorMapSwizzle sw) {
  const cuuint32_t es[3] = {1, 1, 1};
  fn(tm, CU_TENSOR_MAP_DATA_TYPE_BFLOAT16, rank, const_cast<void*>(ptr), dims, strides, box, es, CU_TENSOR_MAP_INTERLEAVE_NONE, sw,
     CU_TENSOR_MAP_L2_PROMOTION_L2_256B, CU_TENSOR_MAP_FLOAT_OOB_FILL_NONE);
}
void map_a(EncodeFn fn, CUtensorMap* tm, const void* p, int rows, int cols, int box_rows) {
  const cuuint64_t dims[2] = {(cuuint64_t)cols, (cuuint64_t)rows};
  const cuuint64_t str[1] = {(cuuint64_t)cols * 2};
  const cuuint32_t box[2] = {64, (cuuint32_t)box_rows};
  make_map(fn, tm, p, 2, dims, str, box, CU_TENSOR_MAP_SWIZZLE_128B);
}
void map_w(EncodeFn fn, CUtensorMap* tm, const void* p, int K, int N, int atom, CUtensorMapSwizzle sw) {
  const cuuint64_t dims[3] = {(cuuint64_t)atom, (cuuint64_t)K, (cuuint64_t)(N / atom)};
  const cuuint64_t str[2] = {(cuuint64_t)N * 2, (cuuint64_t)atom * 2};
  const cuuint32_t box[3] = {(cuuint32_t)atom, 64, 5};
  make_map(fn, tm, p, 3, dims, str, box, sw);
}

template <typename... KArgs, typename... Args>
void launch(void (*kern)(KArgs...), int grid, int block, int smem, bool pdl, Args... args) {
  cudaLaunchConfig_t cfg = {};
  cfg.gridDim = dim3(grid); cfg.blockDim = dim3(block); cfg.dynamicSmemBytes = smem; cfg.stream = cudaStreamPerThread;
  cudaLaunchAttribute at[1];
  at[0].id = cudaLaunchAttributeProgrammaticStreamSerialization;
  at[0].val.programmaticStreamSerializationAllowed = 1;
  cfg.attrs = at; cfg.numAttrs = pdl ? 1 : 0;
  cudaLaunchKernelEx(&cfg, kern, KArgs(args)...);
}

}

extern "C" void kernel_launch(void* const* d_in, const int* in_sizes, int n_in, void* d_out, int out_size) {
  (void)in_sizes; (void)n_in; (void)out_size;
  const __nv_bfloat16* x = (const __nv_bfloat16*)d_in[0];
  const __nv_bfloat16* wq = (const __nv_bfloat16*)d_in[1];
  const __nv_bfloat16* wk = (const __nv_bfloat16*)d_in[2];
  const __nv_bfloat16* wv = (const __nv_bfloat16*)d_in[3];
  const __nv_bfloat16* woA = (const __nv_bfloat16*)d_in[4];
  const __nv_bfloat16* wqkv = (const __nv_bfloat16*)d_in[6];
  const __nv_bfloat16* woB = (const __nv_bfloat16*)d_in[7];
  const __nv_bfloat16* gate_w = (const __nv_bfloat16*)d_in[8];

  static EncodeFn enc = nullptr;
  static void* a2_ptr = nullptr;
  if (!enc) {
    void* fp = nullptr;
    cudaDriverEntryPointQueryResult qr;
    cudaGetDriverEntryPoint("cuTensorMapEncodeTiled", &fp, cudaEnableDefault, &qr);
    enc = (EncodeFn)fp;
    cudaGetSymbolAddress(&a2_ptr, g_a2);
    cudaFuncSetAttribute(proj_kernel, cudaFuncAttributeMaxDynamicSharedMemorySize, K1_SMEM);
    cudaFuncSetAttribute(attn_kernel, cudaFuncAttributeMaxDynamicSharedMemorySize, K2_SMEM);
  }
  CUtensorMap tmX, tmWq, tmWqkv, tmA2;
  map_a(enc, &tmX, x, S_LEN, D_MODEL, 256);
  map_w(enc, &tmWq, wq, D_MODEL, D_MODEL, 32, CU_TENSOR_MAP_SWIZZLE_64B);
  map_w(enc, &tmWqkv, wqkv, D_MODEL, 3 * D_MODEL, 32, CU_TENSOR_MAP_SWIZZLE_64B);
  map_a(enc, &tmA2, a2_ptr, S_LEN, 2 * D_MODEL, 128);

  launch(proj_kernel, 132, 512, K1_SMEM, false, tmX, tmWq, tmWqkv, wk, wv, gate_w, woA, woB);
  launch(attn_kernel, 128, 512, K2_SMEM, true, tmA2, (__nv_bfloat16*)d_out, 0x3F803F80u);
}
```

```cpp
#include <cuda_runtime.h>
#include <cuda_bf16.h>
#include <cuda.h>
#include <stdint.h>

namespace {

constexpr int S_LEN = 2048, D_MODEL = 640, DH = 20;

constexpr int GRP = 128;
constexpr int PLANE = GRP * 16;
constexpr int GRP_BYTES = GRP * 16 * 6;
constexpr int NGRP = S_LEN / GRP;
#define TMASKV 0xBBBBu
constexpr uint32_t TMASK = TMASKV;

__device__ __align__(1024) __nv_bfloat16 g_q[S_LEN * D_MODEL];
__device__ __align__(1024) __nv_bfloat16 g_qkv[S_LEN * 3 * D_MODEL];
__device__ __align__(1024) __nv_bfloat16 g_a2[S_LEN * 2 * D_MODEL];
__device__ __align__(1024) uint8_t g_kvimg[NGRP * GRP_BYTES];
__device__ __align__(1024) uint8_t g_wimg[2 * 8 * 10 * 10240];
__device__ float g_gate[S_LEN];
__device__ float g_kmax2[64];
__device__ float g_vmax[64];
__device__ __align__(32) unsigned int g_doneL[128];
__device__ __align__(32) unsigned int g_done[128];

#define PROF(k, slot)
#define PROF2(k, slot)
__device__ __forceinline__ uint32_t smem_u32(const void* p) { return (uint32_t)__cvta_generic_to_shared(p); }
__device__ __forceinline__ uint64_t mkd(uint32_t lo, uint32_t hi) {
  uint64_t d; asm("mov.b64 %0, {%1, %2};" : "=l"(d) : "r"(lo), "r"(hi)); return d;
}
__device__ __forceinline__ void wg_fence() { asm volatile("wgmma.fence.sync.aligned;" ::: "memory"); }
__device__ __forceinline__ void wg_commit() { asm volatile("wgmma.commit_group.sync.aligned;" ::: "memory"); }
template <int N> __device__ __forceinline__ void wg_wait() { asm volatile("wgmma.wait_group.sync.aligned %0;" :: "n"(N) : "memory"); }
template <int N> __device__ __forceinline__ void fence_regs(float (&d)[N]) {
#pragma unroll
  for (int i = 0; i < N; i++) asm volatile("" : "+f"(d[i]) :: "memory");
}
template <int N> __device__ __forceinline__ void fence_regs(uint32_t (&d)[N]) {
#pragma unroll
  for (int i = 0; i < N; i++) asm volatile("" : "+r"(d[i]) :: "memory");
}
__device__ __forceinline__ void mbar_init(uint32_t bar, uint32_t cnt) { asm volatile("mbarrier.init.shared::cta.b64 [%0], %1;" :: "r"(bar), "r"(cnt)); }
__device__ __forceinline__ void mbar_expect_tx(uint32_t bar, uint32_t bytes) {
  asm volatile("mbarrier.arrive.expect_tx.shared::cta.b64 _, [%0], %1;" :: "r"(bar), "r"(bytes) : "memory");
}
__device__ __forceinline__ void mbar_arrive(uint32_t bar) { asm volatile("mbarrier.arrive.shared::cta.b64 _, [%0];" :: "r"(bar) : "memory"); }
#define WAIT_HINT 20000u
__device__ __forceinline__ void mbar_wait(uint32_t bar, uint32_t parity) {
  asm volatile("{\n.reg .pred p;\nWAIT_%=:\nmbarrier.try_wait.parity.shared::cta.b64 p, [%0], %1, %2;\n@p bra DONE_%=;\nbra WAIT_%=;\nDONE_%=:\n}\n"
               :: "r"(bar), "r"(parity), "r"(WAIT_HINT) : "memory");
}
__device__ __forceinline__ void fence_mbar_init() { asm volatile("fence.mbarrier_init.release.cluster;" ::: "memory"); }
__device__ __forceinline__ void fence_proxy_async() { asm volatile("fence.proxy.async.shared::cta;" ::: "memory"); }
__device__ __forceinline__ void bulk_g2s(uint32_t dst, const void* src, uint32_t bytes, uint32_t bar) {
  asm volatile("cp.async.bulk.shared::cluster.global.mbarrier::complete_tx::bytes [%0], [%1], %2, [%3];"
               :: "r"(dst), "l"(src), "r"(bytes), "r"(bar) : "memory");
}
__device__ __forceinline__ void tma_2d(uint32_t dst, const CUtensorMap* tm, int c0, int c1, uint32_t bar) {
  asm volatile("cp.async.bulk.tensor.2d.shared::cluster.global.mbarrier::complete_tx::bytes [%0], [%1, {%3, %4}], [%2];"
               :: "r"(dst), "l"((uint64_t)tm), "r"(bar), "r"(c0), "r"(c1) : "memory");
}
__device__ __forceinline__ void tma_3d(uint32_t dst, const CUtensorMap* tm, int c0, int c1, int c2, uint32_t bar) {
  asm volatile("cp.async.bulk.tensor.3d.shared::cluster.global.mbarrier::complete_tx::bytes [%0], [%1, {%3, %4, %5}], [%2];"
               :: "r"(dst), "l"((uint64_t)tm), "r"(bar), "r"(c0), "r"(c1), "r"(c2) : "memory");
}
__device__ __forceinline__ void pdl_wait() { asm volatile("griddepcontrol.wait;" ::: "memory"); }
__device__ __forceinline__ void pdl_launch() { asm volatile("griddepcontrol.launch_dependents;" ::: "memory"); }
__device__ __forceinline__ float ex2(float x) { float y; asm("ex2.approx.ftz.f32 %0, %1;" : "=f"(y) : "f"(x)); return y; }
__device__ __forceinline__ uint32_t pack_bf16(float lo, float hi) {
  uint32_t r; asm("cvt.rn.bf16x2.f32 %0, %1, %2;" : "=r"(r) : "f"(hi), "f"(lo)); return r;
}
__device__ __forceinline__ float bf_lo(uint32_t x) { return __uint_as_float(x << 16); }
__device__ __forceinline__ float bf_hi(uint32_t x) { return __uint_as_float(x & 0xffff0000u); }
__device__ __forceinline__ void stsm4(uint32_t addr, uint32_t r0, uint32_t r1, uint32_t r2, uint32_t r3) {
  asm volatile("stmatrix.sync.aligned.m8n8.x4.shared.b16 [%0], {%1, %2, %3, %4};" :: "r"(addr), "r"(r0), "r"(r1), "r"(r2), "r"(r3) : "memory");
}

__device__ __forceinline__ void wgmma_ss_n160_tb(float (&d)[80], uint64_t descA, uint64_t descB) {
  asm volatile("wgmma.mma_async.sync.aligned.m64n160k16.f32.bf16.bf16 {%0, %1, %2, %3, %4, %5, %6, %7, %8, %9, %10, %11, %12, %13, %14, %15, %16, %17, %18, %19, %20, %21, %22, %23, %24, %25, %26, %27, %28, %29, %30, %31, %32, %33, %34, %35, %36, %37, %38, %39, %40, %41, %42, %43, %44, %45, %46, %47, %48, %49, %50, %51, %52, %53, %54, %55, %56, %57, %58, %59, %60, %61, %62, %63, %64, %65, %66, %67, %68, %69, %70, %71, %72, %73, %74, %75, %76, %77, %78, %79}, %80, %81, 1, 1, 1, 0, 1;\n"
    : "+f"(d[0]), "+f"(d[1]), "+f"(d[2]), "+f"(d[3]), "+f"(d[4]), "+f"(d[5]), "+f"(d[6]), "+f"(d[7]), "+f"(d[8]), "+f"(d[9]), "+f"(d[10]), "+f"(d[11]), "+f"(d[12]), "+f"(d[13]), "+f"(d[14]), "+f"(d[15]), "+f"(d[16]), "+f"(d[17]), "+f"(d[18]), "+f"(d[19]), "+f"(d[20]), "+f"(d[21]), "+f"(d[22]), "+f"(d[23]), "+f"(d[24]), "+f"(d[25]), "+f"(d[26]), "+f"(d[27]), "+f"(d[28]), "+f"(d[29]), "+f"(d[30]), "+f"(d[31]), "+f"(d[32]), "+f"(d[33]), "+f"(d[34]), "+f"(d[35]), "+f"(d[36]), "+f"(d[37]), "+f"(d[38]), "+f"(d[39]), "+f"(d[40]), "+f"(d[41]), "+f"(d[42]), "+f"(d[43]), "+f"(d[44]), "+f"(d[45]), "+f"(d[46]), "+f"(d[47]), "+f"(d[48]), "+f"(d[49]), "+f"(d[50]), "+f"(d[51]), "+f"(d[52]), "+f"(d[53]), "+f"(d[54]), "+f"(d[55]), "+f"(d[56]), "+f"(d[57]), "+f"(d[58]), "+f"(d[59]), "+f"(d[60]), "+f"(d[61]), "+f"(d[62]), "+f"(d[63]), "+f"(d[64]), "+f"(d[65]), "+f"(d[66]), "+f"(d[67]), "+f"(d[68]), "+f"(d[69]), "+f"(d[70]), "+f"(d[71]), "+f"(d[72]), "+f"(d[73]), "+f"(d[74]), "+f"(d[75]), "+f"(d[76]), "+f"(d[77]), "+f"(d[78]), "+f"(d[79])
    : "l"(descA), "l"(descB));
}
__device__ __forceinline__ void wgmma_ss_n48_tb(float (&d)[24], uint64_t descA, uint64_t descB) {
  asm volatile("wgmma.mma_async.sync.aligned.m64n48k16.f32.bf16.bf16 {%0, %1, %2, %3, %4, %5, %6, %7, %8, %9, %10, %11, %12, %13, %14, %15, %16, %17, %18, %19, %20, %21, %22, %23}, %24, %25, 1, 1, 1, 0, 1;\n"
    : "+f"(d[0]), "+f"(d[1]), "+f"(d[2]), "+f"(d[3]), "+f"(d[4]), "+f"(d[5]), "+f"(d[6]), "+f"(d[7]), "+f"(d[8]), "+f"(d[9]), "+f"(d[10]), "+f"(d[11]), "+f"(d[12]), "+f"(d[13]), "+f"(d[14]), "+f"(d[15]), "+f"(d[16]), "+f"(d[17]), "+f"(d[18]), "+f"(d[19]), "+f"(d[20]), "+f"(d[21]), "+f"(d[22]), "+f"(d[23])
    : "l"(descA), "l"(descB));
}
__device__ __forceinline__ void wgmma_ss_n80_tb(float (&d)[40], uint64_t descA, uint64_t descB) {
  asm volatile("wgmma.mma_async.sync.aligned.m64n80k16.f32.bf16.bf16 {%0, %1, %2, %3, %4, %5, %6, %7, %8, %9, %10, %11, %12, %13, %14, %15, %16, %17, %18, %19, %20, %21, %22, %23, %24, %25, %26, %27, %28, %29, %30, %31, %32, %33, %34, %35, %36, %37, %38, %39}, %40, %41, 1, 1, 1, 0, 1;\n"
    : "+f"(d[0]), "+f"(d[1]), "+f"(d[2]), "+f"(d[3]), "+f"(d[4]), "+f"(d[5]), "+f"(d[6]), "+f"(d[7]), "+f"(d[8]), "+f"(d[9]), "+f"(d[10]), "+f"(d[11]), "+f"(d[12]), "+f"(d[13]), "+f"(d[14]), "+f"(d[15]), "+f"(d[16]), "+f"(d[17]), "+f"(d[18]), "+f"(d[19]), "+f"(d[20]), "+f"(d[21]), "+f"(d[22]), "+f"(d[23]), "+f"(d[24]), "+f"(d[25]), "+f"(d[26]), "+f"(d[27]), "+f"(d[28]), "+f"(d[29]), "+f"(d[30]), "+f"(d[31]), "+f"(d[32]), "+f"(d[33]), "+f"(d[34]), "+f"(d[35]), "+f"(d[36]), "+f"(d[37]), "+f"(d[38]), "+f"(d[39])
    : "l"(descA), "l"(descB));
}
template <int SCALE_D>
__device__ __forceinline__ void wgmma_rs_n64(float (&d)[32], uint32_t a0, uint32_t a1, uint32_t a2, uint32_t a3, uint64_t descB) {
  asm volatile("wgmma.mma_async.sync.aligned.m64n64k16.f32.bf16.bf16 {%0, %1, %2, %3, %4, %5, %6, %7, %8, %9, %10, %11, %12, %13, %14, %15, %16, %17, %18, %19, %20, %21, %22, %23, %24, %25, %26, %27, %28, %29, %30, %31}, {%32, %33, %34, %35}, %36, %37, 1, 1, 0;\n"
    : "+f"(d[0]), "+f"(d[1]), "+f"(d[2]), "+f"(d[3]), "+f"(d[4]), "+f"(d[5]), "+f"(d[6]), "+f"(d[7]), "+f"(d[8]), "+f"(d[9]), "+f"(d[10]), "+f"(d[11]), "+f"(d[12]), "+f"(d[13]), "+f"(d[14]), "+f"(d[15]), "+f"(d[16]), "+f"(d[17]), "+f"(d[18]), "+f"(d[19]), "+f"(d[20]), "+f"(d[21]), "+f"(d[22]), "+f"(d[23]), "+f"(d[24]), "+f"(d[25]), "+f"(d[26]), "+f"(d[27]), "+f"(d[28]), "+f"(d[29]), "+f"(d[30]), "+f"(d[31])
    : "r"(a0), "r"(a1), "r"(a2), "r"(a3), "l"(descB), "n"(SCALE_D));
}
template <int SCALE_D>
__device__ __forceinline__ void wgmma_rs_n128(float (&d)[64], uint32_t a0, uint32_t a1, uint32_t a2, uint32_t a3, uint64_t descB) {
  asm volatile("wgmma.mma_async.sync.aligned.m64n128k16.f32.bf16.bf16 {%0, %1, %2, %3, %4, %5, %6, %7, %8, %9, %10, %11, %12, %13, %14, %15, %16, %17, %18, %19, %20, %21, %22, %23, %24, %25, %26, %27, %28, %29, %30, %31, %32, %33, %34, %35, %36, %37, %38, %39, %40, %41, %42, %43, %44, %45, %46, %47, %48, %49, %50, %51, %52, %53, %54, %55, %56, %57, %58, %59, %60, %61, %62, %63}, {%64, %65, %66, %67}, %68, %69, 1, 1, 0;\n"
    : "+f"(d[0]), "+f"(d[1]), "+f"(d[2]), "+f"(d[3]), "+f"(d[4]), "+f"(d[5]), "+f"(d[6]), "+f"(d[7]), "+f"(d[8]), "+f"(d[9]), "+f"(d[10]), "+f"(d[11]), "+f"(d[12]), "+f"(d[13]), "+f"(d[14]), "+f"(d[15]), "+f"(d[16]), "+f"(d[17]), "+f"(d[18]), "+f"(d[19]), "+f"(d[20]), "+f"(d[21]), "+f"(d[22]), "+f"(d[23]), "+f"(d[24]), "+f"(d[25]), "+f"(d[26]), "+f"(d[27]), "+f"(d[28]), "+f"(d[29]), "+f"(d[30]), "+f"(d[31]), "+f"(d[32]), "+f"(d[33]), "+f"(d[34]), "+f"(d[35]), "+f"(d[36]), "+f"(d[37]), "+f"(d[38]), "+f"(d[39]), "+f"(d[40]), "+f"(d[41]), "+f"(d[42]), "+f"(d[43]), "+f"(d[44]), "+f"(d[45]), "+f"(d[46]), "+f"(d[47]), "+f"(d[48]), "+f"(d[49]), "+f"(d[50]), "+f"(d[51]), "+f"(d[52]), "+f"(d[53]), "+f"(d[54]), "+f"(d[55]), "+f"(d[56]), "+f"(d[57]), "+f"(d[58]), "+f"(d[59]), "+f"(d[60]), "+f"(d[61]), "+f"(d[62]), "+f"(d[63])
    : "r"(a0), "r"(a1), "r"(a2), "r"(a3), "l"(descB), "n"(SCALE_D));
}
template <int SCALE_D>
__device__ __forceinline__ void wgmma_rs_n24_tb(float (&d)[12], uint32_t a0, uint32_t a1, uint32_t a2, uint32_t a3, uint64_t descB) {
  asm volatile("wgmma.mma_async.sync.aligned.m64n24k16.f32.bf16.bf16 {%0, %1, %2, %3, %4, %5, %6, %7, %8, %9, %10, %11}, {%12, %13, %14, %15}, %16, %17, 1, 1, 1;\n"
    : "+f"(d[0]), "+f"(d[1]), "+f"(d[2]), "+f"(d[3]), "+f"(d[4]), "+f"(d[5]), "+f"(d[6]), "+f"(d[7]), "+f"(d[8]), "+f"(d[9]), "+f"(d[10]), "+f"(d[11])
    : "r"(a0), "r"(a1), "r"(a2), "r"(a3), "l"(descB), "n"(SCALE_D));
}

constexpr uint32_t DHI_SW128_K = (1024 >> 4) | (1u << 30);
constexpr uint32_t DHI_SW64_MN = (512 >> 4) | (2u << 30);

template <int NC>
__device__ __forceinline__ void store_tile_bf16(const float (&acc)[NC / 2], float scale, uint32_t stage, uint8_t* stage_ptr,
                                                __nv_bfloat16* gdst, int gpitch, int lane) {
  constexpr int PITCH = NC * 2 + 16;
  const uint32_t waddr = stage + ((lane & 7) + ((lane >> 3) & 1) * 8) * PITCH + (lane >> 4) * 16;
#pragma unroll
  for (int j = 0; j < NC / 16; j++) {
    stsm4(waddr + j * 32, pack_bf16(acc[8 * j] * scale, acc[8 * j + 1] * scale), pack_bf16(acc[8 * j + 2] * scale, acc[8 * j + 3] * scale),
          pack_bf16(acc[8 * j + 4] * scale, acc[8 * j + 5] * scale), pack_bf16(acc[8 * j + 6] * scale, acc[8 * j + 7] * scale));
  }
  __syncwarp();
  constexpr int CPR = NC / 8;
#pragma unroll
  for (int i = 0; i < CPR / 2; i++) {
    const int c = i * 32 + lane, r = c / CPR, cc = c % CPR;
    const uint4 v = *reinterpret_cast<const uint4*>(stage_ptr + r * PITCH + cc * 16);
    *reinterpret_cast<uint4*>(gdst + (size_t)r * gpitch + cc * 8) = v;
  }
}

__device__ __forceinline__ void signal_done(unsigned int* flag, int wg, int tid) {
  asm volatile("bar.sync %0, 128;" :: "r"(wg + 1) : "memory");
  if ((tid & 127) == 0) asm volatile("red.release.gpu.global.add.u32 [%0], 1;" :: "l"(flag) : "memory");
}
__device__ __forceinline__ void wait_flags8(const unsigned int* f, unsigned int target) {
  for (int spin = 0; spin < (1 << 26); spin++) {
    unsigned int a, b, c, d, e, g, h, i;
    asm volatile("ld.volatile.global.v4.u32 {%0, %1, %2, %3}, [%4];" : "=r"(a), "=r"(b), "=r"(c), "=r"(d) : "l"(f) : "memory");
    asm volatile("ld.volatile.global.v4.u32 {%0, %1, %2, %3}, [%4];" : "=r"(e), "=r"(g), "=r"(h), "=r"(i) : "l"(f + 4) : "memory");
    if (min(min(min(a, b), min(c, d)), min(min(e, g), min(h, i))) >= target) break;
    __nanosleep(32);
  }
  asm volatile("fence.acq_rel.gpu;" ::: "memory");
  asm volatile("fence.proxy.async;" ::: "memory");
}

#define RP_LD 3
#define RP_ST 7
constexpr int K1_STAGES = 4;
constexpr int K1_A_BYTES = 256 * 128;
constexpr int K1_B_BYTES = 64 * 160 * 2;
constexpr int K1_STAGE = K1_A_BYTES + K1_B_BYTES;
constexpr int K1_SMEM = 5 * K1_A_BYTES + 61440 + 1024;
constexpr int KV_STAGES = 5;
constexpr int KVW_OFF = KV_STAGES * K1_A_BYTES;

__global__ void __launch_bounds__(512, 1)
proj_kernel(const __grid_constant__ CUtensorMap tmX, const __grid_constant__ CUtensorMap tmWq, const __grid_constant__ CUtensorMap tmWqkv,
            const __nv_bfloat16* __restrict__ wk, const __nv_bfloat16* __restrict__ wv, const __nv_bfloat16* __restrict__ gate_w,
            const __nv_bfloat16* __restrict__ woA, const __nv_bfloat16* __restrict__ woB) {
  extern __shared__ uint8_t smem_raw[];
  __shared__ __align__(8) uint64_t bar_full[KV_STAGES], bar_empty[KV_STAGES];
  uint8_t* smem = reinterpret_cast<uint8_t*>((reinterpret_cast<uintptr_t>(smem_raw) + 1023) & ~(uintptr_t)1023);
  const uint32_t sbase = smem_u32(smem);
  const uint32_t dbase = sbase & 0x3FFFFu;
  const int tid = threadIdx.x, warp = tid >> 5, lane = tid & 31;
  const bool is_kv = blockIdx.x >= 128;
  PROF(0, 0);
  if (tid == 0) {
    for (int i = 0; i < KV_STAGES; i++) { mbar_init(smem_u32(&bar_full[i]), 1); mbar_init(smem_u32(&bar_empty[i]), is_kv ? 8 : 16); }
    fence_mbar_init();
  }
  uint2 wa[2][5], wb[2][5]; uint32_t gw[2];
  if (is_kv && tid < 320) {
#pragma unroll
    for (int r = 0; r < 2; r++) {
      const int k = tid + r * 320;
      const uint2* pk = reinterpret_cast<const uint2*>(wk + k * 20);
      const uint2* pv = reinterpret_cast<const uint2*>(wv + k * 20);
#pragma unroll
      for (int i = 0; i < 5; i++) { wa[r][i] = __ldg(pk + i); wb[r][i] = __ldg(pv + i); }
      gw[r] = (uint32_t)__bfloat16_as_ushort(gate_w[k]);
    }
  }
  __syncthreads();
  if (tid == 480) {
    if (!is_kv) { g_done[blockIdx.x] = 0u; g_doneL[blockIdx.x] = 0u; }
    asm volatile("fence.acq_rel.gpu;" ::: "memory");
    pdl_launch();
  }
  __syncwarp();

  if (!is_kv) {
    const int mb = blockIdx.x >> 4, nb = blockIdx.x & 15;
    const CUtensorMap* tw = nb < 4 ? &tmWq : &tmWqkv;
    const int j0 = (nb < 4 ? nb : nb - 4) * 5;
    auto load = [&](int kt) {
      const int s = kt % K1_STAGES;
      const uint32_t fb = smem_u32(&bar_full[s]);
      mbar_expect_tx(fb, K1_STAGE);
      tma_2d(sbase + s * K1_STAGE, &tmX, kt * 64, mb * 256, fb);
      tma_3d(sbase + s * K1_STAGE + K1_A_BYTES, tw, 0, kt * 64, j0, fb);
    };
    if (tid == 0) for (int kt = 0; kt < K1_STAGES; kt++) load(kt);
    __syncwarp();
    uint4 wv2[2];
    const int rq = blockIdx.x * 400 + tid - 112;
    const int rhalf = rq >= 25600, rr = rq - rhalf * 25600, rk = 2 * (rr / 80), rch = rr % 80;
    {
      const int wg = warp >> 2;
      float acc[80];
#pragma unroll
      for (int i = 0; i < 80; i++) acc[i] = 0.f;
      for (int kt = 0; kt < 10; kt++) {
        const int s = kt % K1_STAGES;
        mbar_wait(smem_u32(&bar_full[s]), (kt / K1_STAGES) & 1);
        const uint32_t alo = ((dbase + s * K1_STAGE + wg * 8192) >> 4) | (1u << 16);
        const uint32_t blo = ((dbase + s * K1_STAGE + K1_A_BYTES) >> 4) | ((4096u >> 4) << 16);
        fence_regs(acc);
        wg_fence();
#pragma unroll
        for (int k = 0; k < 4; k++) wgmma_ss_n160_tb(acc, mkd(alo + k * 2, DHI_SW128_K), mkd(blo + k * 64, DHI_SW64_MN));
        wg_commit();
        if (kt == RP_LD && tid >= 112) {
          const uint4* src = reinterpret_cast<const uint4*>((rhalf ? woB : woA) + rk * D_MODEL + rch * 8);
          wv2[0] = __ldg(src); wv2[1] = __ldg(src + D_MODEL / 8);
        }
        if (kt == RP_ST && tid >= 112) {
          uint4* dst = reinterpret_cast<uint4*>(g_wimg + ((rhalf * 8 + rch / 10) * 10 + (rk >> 6)) * 10240 + (rch % 10) * 1024 + (rk & 63) * 16);
          dst[0] = wv2[0]; dst[1] = wv2[1];
        }
        __syncwarp();
        if (kt > 0 && kt - 1 + K1_STAGES < 10) {
          wg_wait<1>();
          const uint32_t eb = smem_u32(&bar_empty[(kt - 1) % K1_STAGES]);
          if (lane == 0) mbar_arrive(eb);
          if (tid == 0) { mbar_wait(eb, ((kt - 1) / K1_STAGES) & 1); load(kt - 1 + K1_STAGES); }
          __syncwarp();
        }
      }
      wg_wait<0>();
      fence_regs(acc);
      PROF(0, 1);
      asm volatile("bar.sync %0, 128;" :: "r"(wg + 1) : "memory");
      const int w4 = warp & 3;
      const uint32_t off = w4 * K1_STAGE + wg * 8192;
      const int row0 = mb * 256 + wg * 64 + w4 * 16;
      if (nb < 4) {
        store_tile_bf16<160>(acc, 0.22360679774997896f * 1.4426950408889634f, sbase + off, smem + off,
                             g_q + (size_t)row0 * D_MODEL + nb * 160, D_MODEL, lane);
      } else {
        store_tile_bf16<160>(acc, 1.0f, sbase + off, smem + off, g_qkv + (size_t)row0 * (3 * D_MODEL) + (nb - 4) * 160, 3 * D_MODEL, lane);
      }
    }
  } else {
    const int cb = blockIdx.x - 128;
    if (warp == 8 && lane == 0) {
      for (int it = 0; it < KV_STAGES; it++) {
        const uint32_t fb = smem_u32(&bar_full[it]);
        mbar_expect_tx(fb, K1_A_BYTES);
        tma_2d(sbase + it * K1_A_BYTES, &tmX, it * 64, cb * 512, fb);
      }
    }
    __syncwarp();
    if (tid < 320) {
#pragma unroll
      for (int r = 0; r < 2; r++) {
        uint4* dst = reinterpret_cast<uint4*>(smem + KVW_OFF + (tid + r * 320) * 16);
        dst[0] = make_uint4(wa[r][0].x, wa[r][0].y, wa[r][1].x, wa[r][1].y);
        dst[640] = make_uint4(wa[r][2].x, wa[r][2].y, wa[r][3].x, wa[r][3].y);
        dst[1280] = make_uint4(wa[r][4].x, wa[r][4].y, 0u, 0u);
        dst[1920] = make_uint4(wb[r][0].x, wb[r][0].y, wb[r][1].x, wb[r][1].y);
        dst[2560] = make_uint4(wb[r][2].x, wb[r][2].y, wb[r][3].x, wb[r][3].y);
        dst[3200] = make_uint4(wb[r][4].x, wb[r][4].y, gw[r], 0u);
      }
    }
    fence_proxy_async();
    asm volatile("bar.sync 1, 512;" ::: "memory");
    PROF(0, 1);
    auto produce = [&](int it0, int it1) {
      for (int it = it0; it < it1; it++) {
        const int s = it % KV_STAGES;
        mbar_wait(smem_u32(&bar_empty[s]), (it / KV_STAGES - 1) & 1);
        const uint32_t fb = smem_u32(&bar_full[s]);
        mbar_expect_tx(fb, K1_A_BYTES);
        tma_2d(sbase + s * K1_A_BYTES, &tmX, (it >= 10 ? it - 10 : it) * 64, cb * 512 + (it >= 10 ? 256 : 0), fb);
      }
    };
    if (tid == 256) produce(KV_STAGES, 15);
    __syncwarp();
    {
      const int pass = warp >> 3, wg = (warp >> 2) & 1, w4 = warp & 3, g = lane >> 2, t = lane & 3;
      if (pass == 1) asm volatile("bar.sync 2, 512;" ::: "memory");
      {
        float acc[2][24];
#pragma unroll
        for (int i = 0; i < 24; i++) { acc[0][i] = 0.f; acc[1][i] = 0.f; }
        for (int kt = 0; kt < 10; kt++) {
          const int it = pass * 10 + kt, s = it % KV_STAGES;
          mbar_wait(smem_u32(&bar_full[s]), (it / KV_STAGES) & 1);
          const uint32_t alo = ((dbase + s * K1_A_BYTES + wg * 16384) >> 4) | (1u << 16);
          const uint32_t blo = ((dbase + KVW_OFF + kt * 1024) >> 4) | ((128u >> 4) << 16);
          fence_regs(acc[0]); fence_regs(acc[1]);
          wg_fence();
#pragma unroll
          for (int k = 0; k < 4; k++) {
            wgmma_ss_n48_tb(acc[0], mkd(alo + k * 2, DHI_SW128_K), mkd(blo + k * 16, 10240u >> 4));
            wgmma_ss_n48_tb(acc[1], mkd(alo + 512 + k * 2, DHI_SW128_K), mkd(blo + k * 16, 10240u >> 4));
          }
          wg_commit();
          if (kt > 0) {
            wg_wait<1>();
            if (lane == 0) mbar_arrive(smem_u32(&bar_empty[(it - 1) % KV_STAGES]));
          }
        }
        wg_wait<0>();
        fence_regs(acc[0]); fence_regs(acc[1]);
        if (lane == 0) mbar_arrive(smem_u32(&bar_empty[(pass * 10 + 9) % KV_STAGES]));
        if (pass == 0) asm volatile("bar.arrive 2, 512;" ::: "memory");
        PROF(0, 2);
        if (tid == 0) produce(15, 20);
        __syncwarp();
        float kmax2 = 0.f, vmax = 0.f;
#pragma unroll
        for (int hh = 0; hh < 4; hh++) {
          const int h = hh & 1;
          const float (&a)[24] = acc[hh >> 1];
          const int key = cb * 512 + pass * 256 + wg * 128 + (hh >> 1) * 64 + w4 * 16 + g + h * 8;
          const int grp = key >> 7, kk = key & 127;
          const bool poly = (TMASK >> (kk >> 3)) & 1;
          uint8_t* gp = g_kvimg + grp * GRP_BYTES;
          const uint32_t k0 = pack_bf16(a[2 * h], a[2 * h + 1]);
          const uint32_t k1 = pack_bf16(a[4 + 2 * h], a[5 + 2 * h]);
          uint32_t k2 = pack_bf16(a[8 + 2 * h], a[9 + 2 * h]);
          float n2 = bf_lo(k0) * bf_lo(k0) + bf_hi(k0) * bf_hi(k0) + bf_lo(k1) * bf_lo(k1) + bf_hi(k1) * bf_hi(k1);
          if (t < 2) {
            n2 += bf_lo(k2) * bf_lo(k2) + bf_hi(k2) * bf_hi(k2);
            k2 = pack_bf16(bf_lo(k2) * 0.5f, bf_hi(k2) * 0.5f);
          } else if (t == 2) k2 = poly ? pack_bf16(24.f, 2.5f) : pack_bf16(0.5f, 0.f);
          else k2 = poly ? pack_bf16(0.5f, 0.f) : 0u;
          *reinterpret_cast<uint32_t*>(gp + kk * 16 + t * 4) = k0;
          *reinterpret_cast<uint32_t*>(gp + PLANE + kk * 16 + t * 4) = k1;
          *reinterpret_cast<uint32_t*>(gp + 2 * PLANE + kk * 16 + t * 4) = k2;
          n2 += __shfl_xor_sync(0xffffffffu, n2, 1);
          n2 += __shfl_xor_sync(0xffffffffu, n2, 2);
          kmax2 = (n2 > kmax2 || n2 != n2) ? n2 : kmax2;
          uint32_t v0 = pack_bf16(a[12 + 2 * h], a[13 + 2 * h]);
          uint32_t v1 = pack_bf16(a[16 + 2 * h], a[17 + 2 * h]);
          uint32_t v2 = pack_bf16(a[20 + 2 * h], a[21 + 2 * h]);
          float vm = fmaxf(fmaxf(fabsf(bf_lo(v0)), fabsf(bf_hi(v0))), fmaxf(fabsf(bf_lo(v1)), fabsf(bf_hi(v1))));
          if (t < 2) vm = fmaxf(vm, fmaxf(fabsf(bf_lo(v2)), fabsf(bf_hi(v2))));
          else if (t == 2) {
            const float z = a[20 + 2 * h];
            g_gate[key] = 1.f / (1.f + __expf(-z));
            v2 = 0x00003F80u;
          } else v2 = 0u;
          vmax = fmaxf(vmax, vm);
          if (poly) { v0 ^= 0x80008000u; v1 ^= 0x80008000u; v2 ^= 0x80008000u; }
          uint8_t* vp = gp + 3 * PLANE + (kk >> 3) * 384 + (kk & 7) * 16 + t * 4;
          *reinterpret_cast<uint32_t*>(vp) = v0;
          *reinterpret_cast<uint32_t*>(vp + 128) = v1;
          *reinterpret_cast<uint32_t*>(vp + 256) = v2;
        }
#pragma unroll
        for (int o = 1; o < 32; o <<= 1) {
          const float a = __shfl_xor_sync(0xffffffffu, kmax2, o);
          kmax2 = (a > kmax2 || a != a) ? a : kmax2;
          vmax = fmaxf(vmax, __shfl_xor_sync(0xffffffffu, vmax, o));
        }
        if (lane == 0) { g_kmax2[cb * 16 + warp] = kmax2; g_vmax[cb * 16 + warp] = vmax; }
      }
    }
  }
}

__device__ __forceinline__ uint32_t ex2_pair_poly(float u0, float u1, uint32_t one2) {
  const uint32_t W = __byte_perm(__float_as_uint(u0), __float_as_uint(u1), 0x6521);
  uint32_t v; asm("lop3.b32 %0, %1, 0x007F007F, %2, 0xEA;" : "=r"(v) : "r"(W), "r"(one2));
  uint32_t L, p;
  asm("fma.rn.bf16x2 %0, %1, %2, %3;" : "=r"(L) : "r"(v), "r"(0x1f961f96u), "r"(0x9fe39fe3u));
  asm("fma.rn.bf16x2 %0, %1, %1, %2;" : "=r"(p) : "r"(L), "r"(0x00f500f5u));
  return W + p;
}
template <int JOFF>
__device__ __forceinline__ void softmax_slow(const float (&S)[32], uint32_t (&P)[16], float (&O)[12], float& m0, float& m1) {
  float a0 = m0, a1 = m1;
#pragma unroll
  for (int j = 0; j < 8; j++) {
    a0 = fmaxf(a0, fmaxf(S[4 * j], S[4 * j + 1]));
    a1 = fmaxf(a1, fmaxf(S[4 * j + 2], S[4 * j + 3]));
  }
  a0 = fmaxf(a0, __shfl_xor_sync(0xffffffffu, a0, 1)); a0 = fmaxf(a0, __shfl_xor_sync(0xffffffffu, a0, 2));
  a1 = fmaxf(a1, __shfl_xor_sync(0xffffffffu, a1, 1)); a1 = fmaxf(a1, __shfl_xor_sync(0xffffffffu, a1, 2));
  const float c0 = ex2(m0 - a0), c1 = ex2(m1 - a1);
  m0 = a0; m1 = a1;
#pragma unroll
  for (int j = 0; j < 3; j++) { O[4 * j] *= c0; O[4 * j + 1] *= c0; O[4 * j + 2] *= c1; O[4 * j + 3] *= c1; }
#pragma unroll
  for (int i = 0; i < 16; i++) {
    const float m = (i & 1) ? a1 : a0;
    const uint32_t p = pack_bf16(ex2(S[2 * i] - m), ex2(S[2 * i + 1] - m));
    P[i] = ((TMASK >> (JOFF + i / 2)) & 1) ? (p ^ 0x80008000u) : p;
  }
}
constexpr uint32_t DHI_KV = 128 >> 4;
__device__ __forceinline__ void issue_qk(float (&S)[32], const uint32_t (&q)[8], uint64_t base) {
  wgmma_rs_n64<0>(S, q[0], q[1], q[2], q[3], base + (uint64_t)((PLANE >> 4) << 16));
  wgmma_rs_n64<1>(S, q[4], q[5], q[6], q[7], base + (uint64_t)(2 * PLANE >> 4));
}
__device__ __forceinline__ void issue_pv(float (&O)[12], const uint32_t (&P)[16], uint64_t vbase) {
#pragma unroll
  for (int kk = 0; kk < 4; kk++)
    wgmma_rs_n24_tb<1>(O, P[4 * kk], P[4 * kk + 1], P[4 * kk + 2], P[4 * kk + 3], vbase + (uint64_t)(kk * (768 >> 4)));
}

constexpr uint32_t VOFF = ((3 * PLANE) >> 4) + ((384u >> 4) << 16);
constexpr int KVR = 4;
constexpr int OFF_W = KVR * GRP_BYTES;
constexpr int OFF_X = OFF_W + 10 * 10240;
constexpr int OFF_BAR = OFF_X + 4 * 16384;
constexpr int K2_SMEM = OFF_BAR + 256 + 1024;
constexpr int TSL = 7;
constexpr int BAR_KV = 0, BAR_W = 4, BAR_TA = 5, BAR_TE = 12, BAR_OWN = 19, CNT_KV = 20;
constexpr int NSTEP = 2 * NGRP;

__device__ __forceinline__ void kv_load(uint32_t sbase, int step) {
  const uint32_t bar = sbase + OFF_BAR + (BAR_KV + (step & (KVR - 1))) * 8;
  mbar_expect_tx(bar, GRP_BYTES);
  bulk_g2s(sbase + (step & (KVR - 1)) * GRP_BYTES, g_kvimg + (step & (NGRP - 1)) * GRP_BYTES, GRP_BYTES, bar);
}
__device__ __forceinline__ void kv_release(uint32_t sbase, int step, bool elected) {
  if (elected && step + KVR < NSTEP) {
    uint32_t old;
    asm volatile("atom.acq_rel.cta.shared::cta.inc.u32 %0, [%1], 3;" : "=r"(old) : "r"(sbase + OFF_BAR + CNT_KV * 8 + (step & (KVR - 1)) * 4) : "memory");
    if (old == 3u) kv_load(sbase, step + KVR);
  }
  __syncwarp();
}
__device__ __forceinline__ void kv_wait(uint32_t sbase, int step) {
  mbar_wait(sbase + OFF_BAR + (BAR_KV + (step & (KVR - 1))) * 8, (step / KVR) & 1);
}

__device__ __forceinline__ uint32_t kv_release_begin(uint32_t sbase, int slot, bool doit) {
  uint32_t old = 0;
  asm volatile("{\n.reg .pred p;\nsetp.ne.u32 p, %2, 0;\n@p atom.relaxed.cta.shared::cta.inc.u32 %0, [%1], 3;\n}\n"
               : "+r"(old) : "r"(sbase + OFF_BAR + CNT_KV * 8 + slot * 4), "r"((uint32_t)doit) : "memory");
  return old;
}
template <int H>
__device__ __forceinline__ void softmax_half(const float (&S)[64], uint32_t (&P)[16], uint32_t one2) {
#pragma unroll
  for (int i = 0; i < 16; i++) {
    if ((TMASK >> (8 * H + i / 2)) & 1) P[i] = ex2_pair_poly(S[32 * H + 2 * i], S[32 * H + 2 * i + 1], one2);
    else P[i] = pack_bf16(ex2(S[32 * H + 2 * i]), ex2(S[32 * H + 2 * i + 1]));
  }
}
__device__ __forceinline__ void attn_fast(const uint32_t (&q)[8], float (&O)[12], uint32_t sbase, int step0, int nsteps, bool elected, uint32_t one2) {
  uint64_t kb0 = mkd((sbase & 0x3FFFFu) >> 4, DHI_KV);
  asm volatile("" : "+l"(kb0));
#pragma unroll 1
  for (int step4 = step0; step4 < step0 + nsteps; step4 += KVR) {
#pragma unroll
    for (int j = 0; j < KVR; j++) {
      const int step = step4 + j;
      const uint64_t kb = kb0 + (uint64_t)(j * (GRP_BYTES >> 4));
      float S[64]; uint32_t PA[16], PB[16];
#pragma unroll
      for (int i = 0; i < 64; i++) S[i] = 0.f;
      mbar_wait(sbase + OFF_BAR + (BAR_KV + j) * 8, (step / KVR) & 1);
      fence_regs(S);
      wg_fence();
      wgmma_rs_n128<0>(S, q[0], q[1], q[2], q[3], kb + (uint64_t)((PLANE >> 4) << 16));
      wgmma_rs_n128<1>(S, q[4], q[5], q[6], q[7], kb + (uint64_t)(2 * PLANE >> 4));
      wg_commit();
      wg_wait<0>();
      fence_regs(S);
      softmax_half<0>(S, PA, one2);
      fence_regs(PA); fence_regs(O);
      wg_fence();
      issue_pv(O, PA, kb + VOFF);
      wg_commit();
      softmax_half<1>(S, PB, one2);
      fence_regs(PB);
      wg_fence();
      issue_pv(O, PB, kb + VOFF + 4 * (768 >> 4));
      wg_commit();
      wg_wait<0>();
      fence_regs(PA); fence_regs(PB); fence_regs(O);
      const uint32_t old = kv_release_begin(sbase, j, elected && step + KVR < NSTEP);
      if (old == 3u) kv_load(sbase, step + KVR);
    }
  }
}
template <int H>
__device__ __forceinline__ void slow_step(const uint32_t (&q)[8], float (&O)[12], uint64_t kb, float& m0, float& m1) {
  float S[32]; uint32_t P[16];
#pragma unroll
  for (int i = 0; i < 32; i++) S[i] = 0.f;
  fence_regs(S);
  wg_fence();
  issue_qk(S, q, kb + 64 * H);
  wg_commit();
  wg_wait<0>();
  fence_regs(S);
  softmax_slow<8 * H>(S, P, O, m0, m1);
  fence_regs(P); fence_regs(O);
  wg_fence();
  issue_pv(O, P, kb + VOFF + H * 4 * (768 >> 4));
  wg_commit();
  wg_wait<0>();
  fence_regs(O); fence_regs(P);
}
__device__ __forceinline__ void attn_slow(const uint32_t (&q)[8], float (&O)[12], uint32_t sbase, int step0, int nsteps, bool elected, float& m0, float& m1) {
#pragma unroll 1
  for (int step = step0; step < step0 + nsteps; step++) {
    kv_wait(sbase, step);
    const uint64_t kb = mkd(((sbase & 0x3FFFFu) >> 4) + (step & (KVR - 1)) * (GRP_BYTES >> 4), DHI_KV);
    slow_step<0>(q, O, kb, m0, m1);
    slow_step<1>(q, O, kb, m0, m1);
    kv_release(sbase, step, elected);
  }
}

__device__ __forceinline__ void load_row20(const __nv_bfloat16* p, float (&f)[20]) {
  const uint2* p2 = reinterpret_cast<const uint2*>(p);
#pragma unroll
  for (int i = 0; i < 5; i++) { const uint2 v = p2[i]; f[4 * i] = bf_lo(v.x); f[4 * i + 1] = bf_hi(v.x); f[4 * i + 2] = bf_lo(v.y); f[4 * i + 3] = bf_hi(v.y); }
}
__device__ __forceinline__ void softmax8(float (&sc)[8]) {
  float mx = sc[0];
#pragma unroll
  for (int w = 1; w < 8; w++) mx = fmaxf(mx, sc[w]);
  float l = 0.f;
#pragma unroll
  for (int w = 0; w < 8; w++) { sc[w] = ex2(sc[w] - mx); l += sc[w]; }
  const float r = 1.f / l;
#pragma unroll
  for (int w = 0; w < 8; w++) sc[w] *= r;
}
__device__ __forceinline__ void local_attn(int t, int lane) {
  constexpr int PITCH = 3 * D_MODEL;
  constexpr float SC = 0.22360679774997896f * 1.4426950408889634f, NEG = -1e9f * 1.4426950408889634f;
  const __nv_bfloat16* base = g_qkv + lane * DH;
  float a[20], sc[8];
  load_row20(base + (size_t)t * PITCH, a);
#pragma unroll
  for (int w = 0; w < 8; w++) {
    const int r = t - 2 * w;
    float k[20];
    load_row20(base + D_MODEL + (size_t)max(r, 0) * PITCH, k);
    float d = 0.f;
#pragma unroll
    for (int i = 0; i < 20; i++) d = fmaf(a[i], k[i], d);
    sc[w] = r >= 0 ? d * SC : NEG;
  }
  softmax8(sc);
#pragma unroll
  for (int i = 0; i < 20; i++) a[i] = 0.f;
#pragma unroll
  for (int w = 0; w < 8; w++) {
    float v[20];
    load_row20(base + 2 * D_MODEL + (size_t)max(t - 2 * w, 0) * PITCH, v);
#pragma unroll
    for (int i = 0; i < 20; i++) a[i] = fmaf(sc[w], v[i], a[i]);
  }
  const float ga = 1.f - g_gate[t];
  uint2* da = reinterpret_cast<uint2*>(g_a2 + (size_t)t * (2 * D_MODEL) + D_MODEL + lane * DH);
#pragma unroll
  for (int i = 0; i < 5; i++)
    da[i] = make_uint2(pack_bf16(a[4 * i] * ga, a[4 * i + 1] * ga), pack_bf16(a[4 * i + 2] * ga, a[4 * i + 3] * ga));
}
__device__ __forceinline__ uint32_t ta_slot(int i) { return i < 4 ? OFF_X + i * 16384 : (i - 4) * 16384; }

__global__ void __launch_bounds__(512, 1)
attn_kernel(const __grid_constant__ CUtensorMap tmA2, __nv_bfloat16* __restrict__ out, uint32_t one2) {
  extern __shared__ uint8_t smem_raw[];
  uint8_t* smem = reinterpret_cast<uint8_t*>((reinterpret_cast<uintptr_t>(smem_raw) + 1023) & ~(uintptr_t)1023);
  const uint32_t sbase = smem_u32(smem);
  const uint32_t dbase = sbase & 0x3FFFFu;
  const uint32_t bars = sbase + OFF_BAR;
  const int tid = threadIdx.x, wg = tid >> 7, warp = (tid >> 5) & 3, lane = tid & 31, g = lane >> 2, t = lane & 3;
  const int mb = blockIdx.x >> 3, nb = blockIdx.x & 7;
  const bool elected = (tid & 127) == 0;
  if (tid == 0) {
    for (int i = 0; i < BAR_TE; i++) mbar_init(bars + i * 8, 1);
    for (int i = BAR_TE; i < BAR_TE + TSL; i++) mbar_init(bars + i * 8, 8);
    mbar_init(bars + BAR_OWN * 8, 4);
    for (int i = 0; i < 4; i++) *reinterpret_cast<uint32_t*>(smem + OFF_BAR + CNT_KV * 8 + i * 4) = 0u;
    fence_mbar_init();
  }
  __syncthreads();
  auto tail_load = [&](int i) {
    const uint32_t fb = bars + (BAR_TA + i % TSL) * 8;
    mbar_expect_tx(fb, i < 10 ? 16384 : 16384 + 10240);
    tma_2d(sbase + ta_slot(i % TSL), &tmA2, i < 10 ? D_MODEL + i * 64 : (i - 10) * 64, mb * 128, fb);
    if (i >= 10) bulk_g2s(sbase + OFF_W + (i - 10) * 10240, g_wimg + (nb * 10 + i - 10) * 10240, 10240, fb);
  };
  pdl_wait();
  PROF(1, 1);
  if (tid == 416) for (int j = 0; j < KVR; j++) kv_load(sbase, j);
  __syncwarp();
  uint32_t q[8], q2[6];
  const int rowA = (blockIdx.x * 8 + wg) * 64 + warp * 16 + g;
  {
    const uint32_t* r0 = reinterpret_cast<const uint32_t*>(g_q + (size_t)rowA * DH);
    const uint32_t* r1 = r0 + 8 * (DH / 2);
    const uint32_t* s0 = r0 + 256 * (DH / 2);
    const uint32_t* s1 = s0 + 8 * (DH / 2);
    q[0] = r0[t]; q[1] = r1[t]; q[2] = r0[t + 4]; q[3] = r1[t + 4];
    q[4] = t < 2 ? r0[8 + t] : 0u;
    q[5] = t < 2 ? r1[8 + t] : 0u;
    q2[0] = s0[t]; q2[1] = s1[t]; q2[2] = s0[t + 4]; q2[3] = s1[t + 4];
    q2[4] = t < 2 ? s0[8 + t] : 0u;
    q2[5] = t < 2 ? s1[8 + t] : 0u;
  }
  local_attn(blockIdx.x * 16 + (tid >> 5), lane);
  float kmax2 = 0.f, vmax = 0.f;
#pragma unroll
  for (int i = 0; i < 2; i++) {
    const float a = g_kmax2[lane + 32 * i];
    kmax2 = (a > kmax2 || a != a) ? a : kmax2;
    vmax = fmaxf(vmax, g_vmax[lane + 32 * i]);
  }
#pragma unroll
  for (int o = 1; o < 32; o <<= 1) {
    const float a = __shfl_xor_sync(0xffffffffu, kmax2, o);
    kmax2 = (a > kmax2 || a != a) ? a : kmax2;
    vmax = fmaxf(vmax, __shfl_xor_sync(0xffffffffu, vmax, o));
  }
  const float qlim = (vmax >= 0.00390625f && vmax <= 256.f) ? 9025.f / kmax2 : -1.f;
  PROF(1, 2);
#pragma unroll 1
  for (int it = 0; it < 2; it++) {
    const int row0 = rowA + it * 256;
    if (it == 1) {
#pragma unroll
      for (int i = 0; i < 6; i++) q[i] = q2[i];
    }
    float n0 = bf_lo(q[0]) * bf_lo(q[0]) + bf_hi(q[0]) * bf_hi(q[0]) + bf_lo(q[2]) * bf_lo(q[2]) + bf_hi(q[2]) * bf_hi(q[2]) +
               bf_lo(q[4]) * bf_lo(q[4]) + bf_hi(q[4]) * bf_hi(q[4]);
    float n1 = bf_lo(q[1]) * bf_lo(q[1]) + bf_hi(q[1]) * bf_hi(q[1]) + bf_lo(q[3]) * bf_lo(q[3]) + bf_hi(q[3]) * bf_hi(q[3]) +
               bf_lo(q[5]) * bf_lo(q[5]) + bf_hi(q[5]) * bf_hi(q[5]);
    n0 += __shfl_xor_sync(0xffffffffu, n0, 1); n0 += __shfl_xor_sync(0xffffffffu, n0, 2);
    n1 += __shfl_xor_sync(0xffffffffu, n1, 1); n1 += __shfl_xor_sync(0xffffffffu, n1, 2);
    const bool safe = (n0 <= qlim) && (n1 <= qlim);
    uint32_t unsafe_any;
    asm volatile("{\n.reg .pred p, r;\nsetp.eq.u32 p, %1, 0;\nbarrier.cta.red.or.pred r, %2, 128, p;\nselp.u32 %0, 1, 0, r;\n}\n"
                 : "=r"(unsafe_any) : "r"((uint32_t)safe), "r"(wg + 1) : "memory");
    float O[12];
#pragma unroll
    for (int i = 0; i < 12; i++) O[i] = 0.f;
    if (!unsafe_any && t >= 2) { q[4] = q[5] = (t == 2) ? 0x3F804100u : 0x00003B80u; }
    q[6] = q[4]; q[7] = q[5];
    fence_regs(q);
    float m0 = -INFINITY, m1 = -INFINITY;
#pragma unroll 1
    for (int part = 0; part < 4; part++) {
      const int s0 = it * NGRP + part * KVR;
      if (!unsafe_any) attn_fast(q, O, sbase, s0, KVR, elected, one2);
      else attn_slow(q, O, sbase, s0, KVR, elected, m0, m1);
      const int ev = it * 4 + part;
      if (ev == 0) {
        signal_done(&g_doneL[blockIdx.x], wg, tid);
        if (tid == 160) {
          mbar_expect_tx(bars + BAR_W * 8, 10 * 10240);
          for (int i = 0; i < 5; i++) bulk_g2s(sbase + OFF_W + i * 20480, g_wimg + ((8 + nb) * 10) * 10240 + i * 20480, 20480, bars + BAR_W * 8);
        }
      } else if (ev == 5 && tid == 32) {
        wait_flags8(&g_doneL[mb * 8], 4u);
        for (int i = 0; i < 4; i++) tail_load(i);
      }
      __syncwarp();
    }
    const float l0 = __shfl_sync(0xffffffffu, O[8], (lane & ~3) | 2);
    const float l1 = __shfl_sync(0xffffffffu, O[10], (lane & ~3) | 2);
    const int tok = row0 >> 5;
    const float gt = g_gate[tok];
    const float i0 = gt / l0, i1 = gt / l1;
    uint32_t* o0 = reinterpret_cast<uint32_t*>(g_a2 + (size_t)tok * (2 * D_MODEL) + (row0 & 31) * DH);
    uint32_t* o1 = o0 + 8 * (DH / 2);
    o0[t] = pack_bf16(O[0] * i0, O[1] * i0); o1[t] = pack_bf16(O[2] * i1, O[3] * i1);
    o0[t + 4] = pack_bf16(O[4] * i0, O[5] * i0); o1[t + 4] = pack_bf16(O[6] * i1, O[7] * i1);
    if (t < 2) { o0[t + 8] = pack_bf16(O[8] * i0, O[9] * i0); o1[t + 8] = pack_bf16(O[10] * i1, O[11] * i1); }
  }
  signal_done(&g_done[blockIdx.x], wg, tid);
  if ((tid & 127) == 64) mbar_arrive(bars + BAR_OWN * 8);
  PROF(1, 3);
  if (wg == 3) {
    if (tid == 416) {
      mbar_wait(bars + BAR_OWN * 8, 0);
      for (int i = 4; i < 20; i++) {
        if (i >= TSL) mbar_wait(bars + (BAR_TE + i % TSL) * 8, (i / TSL - 1) & 1);
        if (i == 10) { wait_flags8(&g_done[mb * 8], 4u); PROF2(2, 0); }
        tail_load(i);
      }
    }
  } else if (wg < 2) {
    float acc[40];
#pragma unroll
    for (int i = 0; i < 40; i++) acc[i] = 0.f;
    mbar_wait(bars + BAR_W * 8, 0);
    int sl = 0, ph = 0;
#pragma unroll 1
    for (int i = 0; i < 20; i++) {
      mbar_wait(bars + (BAR_TA + sl) * 8, ph);
      if (i == 10) PROF(2, 1);
      const uint32_t alo = ((dbase + ta_slot(sl) + wg * 8192) >> 4) | (1u << 16);
      const uint32_t blo = ((dbase + OFF_W + (i >= 10 ? i - 10 : i) * 10240) >> 4) | ((128u >> 4) << 16);
      fence_regs(acc);
      wg_fence();
#pragma unroll
      for (int k = 0; k < 4; k++) wgmma_ss_n80_tb(acc, mkd(alo + k * 2, DHI_SW128_K), mkd(blo + k * 16, 1024u >> 4));
      wg_commit();
      if (i > 0) {
        wg_wait<1>();
        if (lane == 0) mbar_arrive(bars + (BAR_TE + (sl == 0 ? TSL - 1 : sl - 1)) * 8);
      }
      if (++sl == TSL) { sl = 0; ph ^= 1; }
    }
    wg_wait<0>();
    fence_regs(acc);
    PROF(2, 2);
    asm volatile("bar.sync %0, 128;" :: "r"(wg + 1) : "memory");
    const uint32_t so = ta_slot(warp) + wg * 8192;
    const int row0 = mb * 128 + wg * 64 + warp * 16;
    store_tile_bf16<80>(acc, 1.0f, sbase + so, smem + so, out + (size_t)row0 * D_MODEL + nb * 80, D_MODEL, lane);
    PROF(2, 3);
  }
}

typedef CUresult (*EncodeFn)(CUtensorMap*, CUtensorMapDataType, cuuint32_t, void*, const cuuint64_t*, const cuuint64_t*,
                             const cuuint32_t*, const cuuint32_t*, CUtensorMapInterleave, CUtensorMapSwizzle,
                             CUtensorMapL2promotion, CUtensorMapFloatOOBfill);

void make_map(EncodeFn fn, CUtensorMap* tm, const void* ptr, int rank, const cuuint64_t* dims, const cuuint64_t* strides,
              const cuuint32_t* box, CUtensorMapSwizzle sw) {
  const cuuint32_t es[3] = {1, 1, 1};
  fn(tm, CU_TENSOR_MAP_DATA_TYPE_BFLOAT16, rank, const_cast<void*>(ptr), dims, strides, box, es, CU_TENSOR_MAP_INTERLEAVE_NONE, sw,
     CU_TENSOR_MAP_L2_PROMOTION_L2_256B, CU_TENSOR_MAP_FLOAT_OOB_FILL_NONE);
}
void map_a(EncodeFn fn, CUtensorMap* tm, const void* p, int rows, int cols, int box_rows) {
  const cuuint64_t dims[2] = {(cuuint64_t)cols, (cuuint64_t)rows};
  const cuuint64_t str[1] = {(cuuint64_t)cols * 2};
  const cuuint32_t box[2] = {64, (cuuint32_t)box_rows};
  make_map(fn, tm, p, 2, dims, str, box, CU_TENSOR_MAP_SWIZZLE_128B);
}
void map_w(EncodeFn fn, CUtensorMap* tm, const void* p, int K, int N, int atom, CUtensorMapSwizzle sw) {
  const cuuint64_t dims[3] = {(cuuint64_t)atom, (cuuint64_t)K, (cuuint64_t)(N / atom)};
  const cuuint64_t str[2] = {(cuuint64_t)N * 2, (cuuint64_t)atom * 2};
  const cuuint32_t box[3] = {(cuuint32_t)atom, 64, 5};
  make_map(fn, tm, p, 3, dims, str, box, sw);
}

template <typename... KArgs, typename... Args>
void launch(void (*kern)(KArgs...), int grid, int block, int smem, bool pdl, Args... args) {
  cudaLaunchConfig_t cfg = {};
  cfg.gridDim = dim3(grid); cfg.blockDim = dim3(block); cfg.dynamicSmemBytes = smem; cfg.stream = cudaStreamPerThread;
  cudaLaunchAttribute at[1];
  at[0].id = cudaLaunchAttributeProgrammaticStreamSerialization;
  at[0].val.programmaticStreamSerializationAllowed = 1;
  cfg.attrs = at; cfg.numAttrs = pdl ? 1 : 0;
  cudaLaunchKernelEx(&cfg, kern, KArgs(args)...);
}

}

extern "C" void kernel_launch(void* const* d_in, const int* in_sizes, int n_in, void* d_out, int out_size) {
  (void)in_sizes; (void)n_in; (void)out_size;
  const __nv_bfloat16* x = (const __nv_bfloat16*)d_in[0];
  const __nv_bfloat16* wq = (const __nv_bfloat16*)d_in[1];
  const __nv_bfloat16* wk = (const __nv_bfloat16*)d_in[2];
  const __nv_bfloat16* wv = (const __nv_bfloat16*)d_in[3];
  const __nv_bfloat16* woA = (const __nv_bfloat16*)d_in[4];
  const __nv_bfloat16* wqkv = (const __nv_bfloat16*)d_in[6];
  const __nv_bfloat16* woB = (const __nv_bfloat16*)d_in[7];
  const __nv_bfloat16* gate_w = (const __nv_bfloat16*)d_in[8];

  static EncodeFn enc = nullptr;
  static void* a2_ptr = nullptr;
  if (!enc) {
    void* fp = nullptr;
    cudaDriverEntryPointQueryResult qr;
    cudaGetDriverEntryPoint("cuTensorMapEncodeTiled", &fp, cudaEnableDefault, &qr);
    enc = (EncodeFn)fp;
    cudaGetSymbolAddress(&a2_ptr, g_a2);
    cudaFuncSetAttribute(proj_kernel, cudaFuncAttributeMaxDynamicSharedMemorySize, K1_SMEM);
    cudaFuncSetAttribute(attn_kernel, cudaFuncAttributeMaxDynamicSharedMemorySize, K2_SMEM);
  }
  CUtensorMap tmX, tmWq, tmWqkv, tmA2;
  map_a(enc, &tmX, x, S_LEN, D_MODEL, 256);
  map_w(enc, &tmWq, wq, D_MODEL, D_MODEL, 32, CU_TENSOR_MAP_SWIZZLE_64B);
  map_w(enc, &tmWqkv, wqkv, D_MODEL, 3 * D_MODEL, 32, CU_TENSOR_MAP_SWIZZLE_64B);
  map_a(enc, &tmA2, a2_ptr, S_LEN, 2 * D_MODEL, 128);

  launch(proj_kernel, 132, 512, K1_SMEM, false, tmX, tmWq, tmWqkv, wk, wv, gate_w, woA, woB);
  launch(attn_kernel, 128, 512, K2_SMEM, true, tmA2, (__nv_bfloat16*)d_out, 0x3F803F80u);
}
```

```cpp
#include <cuda_runtime.h>
#include <cuda_bf16.h>
#include <cuda.h>
#include <stdint.h>

namespace {

constexpr int S_LEN = 2048, D_MODEL = 640, DH = 20;

constexpr int GRP = 128;
constexpr int PLANE = GRP * 16;
constexpr int GRP_BYTES = GRP * 16 * 6;
constexpr int NGRP = S_LEN / GRP;
#define TMASKV 0xBBBBu
constexpr uint32_t TMASK = TMASKV;

__device__ __align__(1024) __nv_bfloat16 g_q[S_LEN * D_MODEL];
__device__ __align__(1024) __nv_bfloat16 g_qkv[S_LEN * 3 * D_MODEL];
__device__ __align__(1024) __nv_bfloat16 g_a2[S_LEN * 2 * D_MODEL];
__device__ __align__(1024) uint8_t g_kvimg[NGRP * GRP_BYTES];
__device__ __align__(1024) uint8_t g_wimg[2 * 8 * 10 * 10240];
__device__ float g_gate[S_LEN];
__device__ float g_kmax2[64];
__device__ float g_vmax[64];
__device__ __align__(32) unsigned int g_doneL[128];
__device__ __align__(32) unsigned int g_done[128];

#define PROF(k, slot)
#define PROF2(k, slot)
__device__ __forceinline__ uint32_t smem_u32(const void* p) { return (uint32_t)__cvta_generic_to_shared(p); }
__device__ __forceinline__ uint64_t mkd(uint32_t lo, uint32_t hi) {
  uint64_t d; asm("mov.b64 %0, {%1, %2};" : "=l"(d) : "r"(lo), "r"(hi)); return d;
}
__device__ __forceinline__ void wg_fence() { asm volatile("wgmma.fence.sync.aligned;" ::: "memory"); }
__device__ __forceinline__ void wg_commit() { asm volatile("wgmma.commit_group.sync.aligned;" ::: "memory"); }
template <int N> __device__ __forceinline__ void wg_wait() { asm volatile("wgmma.wait_group.sync.aligned %0;" :: "n"(N) : "memory"); }
template <int N> __device__ __forceinline__ void fence_regs(float (&d)[N]) {
#pragma unroll
  for (int i = 0; i < N; i++) asm volatile("" : "+f"(d[i]) :: "memory");
}
template <int N> __device__ __forceinline__ void fence_regs(uint32_t (&d)[N]) {
#pragma unroll
  for (int i = 0; i < N; i++) asm volatile("" : "+r"(d[i]) :: "memory");
}
__device__ __forceinline__ void mbar_init(uint32_t bar, uint32_t cnt) { asm volatile("mbarrier.init.shared::cta.b64 [%0], %1;" :: "r"(bar), "r"(cnt)); }
__device__ __forceinline__ void mbar_expect_tx(uint32_t bar, uint32_t bytes) {
  asm volatile("mbarrier.arrive.expect_tx.shared::cta.b64 _, [%0], %1;" :: "r"(bar), "r"(bytes) : "memory");
}
__device__ __forceinline__ void mbar_arrive(uint32_t bar) { asm volatile("mbarrier.arrive.shared::cta.b64 _, [%0];" :: "r"(bar) : "memory"); }
#define WAIT_HINT 20000u
__device__ __forceinline__ void mbar_wait(uint32_t bar, uint32_t parity) {
  asm volatile("{\n.reg .pred p;\nWAIT_%=:\nmbarrier.try_wait.parity.shared::cta.b64 p, [%0], %1, %2;\n@p bra DONE_%=;\nbra WAIT_%=;\nDONE_%=:\n}\n"
               :: "r"(bar), "r"(parity), "r"(WAIT_HINT) : "memory");
}
__device__ __forceinline__ void fence_mbar_init() { asm volatile("fence.mbarrier_init.release.cluster;" ::: "memory"); }
__device__ __forceinline__ void fence_proxy_async() { asm volatile("fence.proxy.async.shared::cta;" ::: "memory"); }
__device__ __forceinline__ void bulk_g2s(uint32_t dst, const void* src, uint32_t bytes, uint32_t bar) {
  asm volatile("cp.async.bulk.shared::cluster.global.mbarrier::complete_tx::bytes [%0], [%1], %2, [%3];"
               :: "r"(dst), "l"(src), "r"(bytes), "r"(bar) : "memory");
}
__device__ __forceinline__ void tma_2d(uint32_t dst, const CUtensorMap* tm, int c0, int c1, uint32_t bar) {
  asm volatile("cp.async.bulk.tensor.2d.shared::cluster.global.mbarrier::complete_tx::bytes [%0], [%1, {%3, %4}], [%2];"
               :: "r"(dst), "l"((uint64_t)tm), "r"(bar), "r"(c0), "r"(c1) : "memory");
}
__device__ __forceinline__ void tma_3d(uint32_t dst, const CUtensorMap* tm, int c0, int c1, int c2, uint32_t bar) {
  asm volatile("cp.async.bulk.tensor.3d.shared::cluster.global.mbarrier::complete_tx::bytes [%0], [%1, {%3, %4, %5}], [%2];"
               :: "r"(dst), "l"((uint64_t)tm), "r"(bar), "r"(c0), "r"(c1), "r"(c2) : "memory");
}
__device__ __forceinline__ void pdl_wait() { asm volatile("griddepcontrol.wait;" ::: "memory"); }
__device__ __forceinline__ void pdl_launch() { asm volatile("griddepcontrol.launch_dependents;" ::: "memory"); }
__device__ __forceinline__ float ex2(float x) { float y; asm("ex2.approx.ftz.f32 %0, %1;" : "=f"(y) : "f"(x)); return y; }
__device__ __forceinline__ uint32_t pack_bf16(float lo, float hi) {
  uint32_t r; asm("cvt.rn.bf16x2.f32 %0, %1, %2;" : "=r"(r) : "f"(hi), "f"(lo)); return r;
}
__device__ __forceinline__ float bf_lo(uint32_t x) { return __uint_as_float(x << 16); }
__device__ __forceinline__ float bf_hi(uint32_t x) { return __uint_as_float(x & 0xffff0000u); }
__device__ __forceinline__ void stsm4(uint32_t addr, uint32_t r0, uint32_t r1, uint32_t r2, uint32_t r3) {
  asm volatile("stmatrix.sync.aligned.m8n8.x4.shared.b16 [%0], {%1, %2, %3, %4};" :: "r"(addr), "r"(r0), "r"(r1), "r"(r2), "r"(r3) : "memory");
}

__device__ __forceinline__ void wgmma_ss_n160_tb(float (&d)[80], uint64_t descA, uint64_t descB) {
  asm volatile("wgmma.mma_async.sync.aligned.m64n160k16.f32.bf16.bf16 {%0, %1, %2, %3, %4, %5, %6, %7, %8, %9, %10, %11, %12, %13, %14, %15, %16, %17, %18, %19, %20, %21, %22, %23, %24, %25, %26, %27, %28, %29, %30, %31, %32, %33, %34, %35, %36, %37, %38, %39, %40, %41, %42, %43, %44, %45, %46, %47, %48, %49, %50, %51, %52, %53, %54, %55, %56, %57, %58, %59, %60, %61, %62, %63, %64, %65, %66, %67, %68, %69, %70, %71, %72, %73, %74, %75, %76, %77, %78, %79}, %80, %81, 1, 1, 1, 0, 1;\n"
    : "+f"(d[0]), "+f"(d[1]), "+f"(d[2]), "+f"(d[3]), "+f"(d[4]), "+f"(d[5]), "+f"(d[6]), "+f"(d[7]), "+f"(d[8]), "+f"(d[9]), "+f"(d[10]), "+f"(d[11]), "+f"(d[12]), "+f"(d[13]), "+f"(d[14]), "+f"(d[15]), "+f"(d[16]), "+f"(d[17]), "+f"(d[18]), "+f"(d[19]), "+f"(d[20]), "+f"(d[21]), "+f"(d[22]), "+f"(d[23]), "+f"(d[24]), "+f"(d[25]), "+f"(d[26]), "+f"(d[27]), "+f"(d[28]), "+f"(d[29]), "+f"(d[30]), "+f"(d[31]), "+f"(d[32]), "+f"(d[33]), "+f"(d[34]), "+f"(d[35]), "+f"(d[36]), "+f"(d[37]), "+f"(d[38]), "+f"(d[39]), "+f"(d[40]), "+f"(d[41]), "+f"(d[42]), "+f"(d[43]), "+f"(d[44]), "+f"(d[45]), "+f"(d[46]), "+f"(d[47]), "+f"(d[48]), "+f"(d[49]), "+f"(d[50]), "+f"(d[51]), "+f"(d[52]), "+f"(d[53]), "+f"(d[54]), "+f"(d[55]), "+f"(d[56]), "+f"(d[57]), "+f"(d[58]), "+f"(d[59]), "+f"(d[60]), "+f"(d[61]), "+f"(d[62]), "+f"(d[63]), "+f"(d[64]), "+f"(d[65]), "+f"(d[66]), "+f"(d[67]), "+f"(d[68]), "+f"(d[69]), "+f"(d[70]), "+f"(d[71]), "+f"(d[72]), "+f"(d[73]), "+f"(d[74]), "+f"(d[75]), "+f"(d[76]), "+f"(d[77]), "+f"(d[78]), "+f"(d[79])
    : "l"(descA), "l"(descB));
}
__device__ __forceinline__ void wgmma_ss_n48_tb(float (&d)[24], uint64_t descA, uint64_t descB) {
  asm volatile("wgmma.mma_async.sync.aligned.m64n48k16.f32.bf16.bf16 {%0, %1, %2, %3, %4, %5, %6, %7, %8, %9, %10, %11, %12, %13, %14, %15, %16, %17, %18, %19, %20, %21, %22, %23}, %24, %25, 1, 1, 1, 0, 1;\n"
    : "+f"(d[0]), "+f"(d[1]), "+f"(d[2]), "+f"(d[3]), "+f"(d[4]), "+f"(d[5]), "+f"(d[6]), "+f"(d[7]), "+f"(d[8]), "+f"(d[9]), "+f"(d[10]), "+f"(d[11]), "+f"(d[12]), "+f"(d[13]), "+f"(d[14]), "+f"(d[15]), "+f"(d[16]), "+f"(d[17]), "+f"(d[18]), "+f"(d[19]), "+f"(d[20]), "+f"(d[21]), "+f"(d[22]), "+f"(d[23])
    : "l"(descA), "l"(descB));
}
__device__ __forceinline__ void wgmma_ss_n80_tb(float (&d)[40], uint64_t descA, uint64_t descB) {
  asm volatile("wgmma.mma_async.sync.aligned.m64n80k16.f32.bf16.bf16 {%0, %1, %2, %3, %4, %5, %6, %7, %8, %9, %10, %11, %12, %13, %14, %15, %16, %17, %18, %19, %20, %21, %22, %23, %24, %25, %26, %27, %28, %29, %30, %31, %32, %33, %34, %35, %36, %37, %38, %39}, %40, %41, 1, 1, 1, 0, 1;\n"
    : "+f"(d[0]), "+f"(d[1]), "+f"(d[2]), "+f"(d[3]), "+f"(d[4]), "+f"(d[5]), "+f"(d[6]), "+f"(d[7]), "+f"(d[8]), "+f"(d[9]), "+f"(d[10]), "+f"(d[11]), "+f"(d[12]), "+f"(d[13]), "+f"(d[14]), "+f"(d[15]), "+f"(d[16]), "+f"(d[17]), "+f"(d[18]), "+f"(d[19]), "+f"(d[20]), "+f"(d[21]), "+f"(d[22]), "+f"(d[23]), "+f"(d[24]), "+f"(d[25]), "+f"(d[26]), "+f"(d[27]), "+f"(d[28]), "+f"(d[29]), "+f"(d[30]), "+f"(d[31]), "+f"(d[32]), "+f"(d[33]), "+f"(d[34]), "+f"(d[35]), "+f"(d[36]), "+f"(d[37]), "+f"(d[38]), "+f"(d[39])
    : "l"(descA), "l"(descB));
}
template <int SCALE_D>
__device__ __forceinline__ void wgmma_rs_n64(float (&d)[32], uint32_t a0, uint32_t a1, uint32_t a2, uint32_t a3, uint64_t descB) {
  asm volatile("wgmma.mma_async.sync.aligned.m64n64k16.f32.bf16.bf16 {%0, %1, %2, %3, %4, %5, %6, %7, %8, %9, %10, %11, %12, %13, %14, %15, %16, %17, %18, %19, %20, %21, %22, %23, %24, %25, %26, %27, %28, %29, %30, %31}, {%32, %33, %34, %35}, %36, %37, 1, 1, 0;\n"
    : "+f"(d[0]), "+f"(d[1]), "+f"(d[2]), "+f"(d[3]), "+f"(d[4]), "+f"(d[5]), "+f"(d[6]), "+f"(d[7]), "+f"(d[8]), "+f"(d[9]), "+f"(d[10]), "+f"(d[11]), "+f"(d[12]), "+f"(d[13]), "+f"(d[14]), "+f"(d[15]), "+f"(d[16]), "+f"(d[17]), "+f"(d[18]), "+f"(d[19]), "+f"(d[20]), "+f"(d[21]), "+f"(d[22]), "+f"(d[23]), "+f"(d[24]), "+f"(d[25]), "+f"(d[26]), "+f"(d[27]), "+f"(d[28]), "+f"(d[29]), "+f"(d[30]), "+f"(d[31])
    : "r"(a0), "r"(a1), "r"(a2), "r"(a3), "l"(descB), "n"(SCALE_D));
}
template <int SCALE_D>
__device__ __forceinline__ void wgmma_rs_n128(float (&d)[64], uint32_t a0, uint32_t a1, uint32_t a2, uint32_t a3, uint64_t descB) {
  asm volatile("wgmma.mma_async.sync.aligned.m64n128k16.f32.bf16.bf16 {%0, %1, %2, %3, %4, %5, %6, %7, %8, %9, %10, %11, %12, %13, %14, %15, %16, %17, %18, %19, %20, %21, %22, %23, %24, %25, %26, %27, %28, %29, %30, %31, %32, %33, %34, %35, %36, %37, %38, %39, %40, %41, %42, %43, %44, %45, %46, %47, %48, %49, %50, %51, %52, %53, %54, %55, %56, %57, %58, %59, %60, %61, %62, %63}, {%64, %65, %66, %67}, %68, %69, 1, 1, 0;\n"
    : "+f"(d[0]), "+f"(d[1]), "+f"(d[2]), "+f"(d[3]), "+f"(d[4]), "+f"(d[5]), "+f"(d[6]), "+f"(d[7]), "+f"(d[8]), "+f"(d[9]), "+f"(d[10]), "+f"(d[11]), "+f"(d[12]), "+f"(d[13]), "+f"(d[14]), "+f"(d[15]), "+f"(d[16]), "+f"(d[17]), "+f"(d[18]), "+f"(d[19]), "+f"(d[20]), "+f"(d[21]), "+f"(d[22]), "+f"(d[23]), "+f"(d[24]), "+f"(d[25]), "+f"(d[26]), "+f"(d[27]), "+f"(d[28]), "+f"(d[29]), "+f"(d[30]), "+f"(d[31]), "+f"(d[32]), "+f"(d[33]), "+f"(d[34]), "+f"(d[35]), "+f"(d[36]), "+f"(d[37]), "+f"(d[38]), "+f"(d[39]), "+f"(d[40]), "+f"(d[41]), "+f"(d[42]), "+f"(d[43]), "+f"(d[44]), "+f"(d[45]), "+f"(d[46]), "+f"(d[47]), "+f"(d[48]), "+f"(d[49]), "+f"(d[50]), "+f"(d[51]), "+f"(d[52]), "+f"(d[53]), "+f"(d[54]), "+f"(d[55]), "+f"(d[56]), "+f"(d[57]), "+f"(d[58]), "+f"(d[59]), "+f"(d[60]), "+f"(d[61]), "+f"(d[62]), "+f"(d[63])
    : "r"(a0), "r"(a1), "r"(a2), "r"(a3), "l"(descB), "n"(SCALE_D));
}
template <int SCALE_D>
__device__ __forceinline__ void wgmma_rs_n24_tb(float (&d)[12], uint32_t a0, uint32_t a1, uint32_t a2, uint32_t a3, uint64_t descB) {
  asm volatile("wgmma.mma_async.sync.aligned.m64n24k16.f32.bf16.bf16 {%0, %1, %2, %3, %4, %5, %6, %7, %8, %9, %10, %11}, {%12, %13, %14, %15}, %16, %17, 1, 1, 1;\n"
    : "+f"(d[0]), "+f"(d[1]), "+f"(d[2]), "+f"(d[3]), "+f"(d[4]), "+f"(d[5]), "+f"(d[6]), "+f"(d[7]), "+f"(d[8]), "+f"(d[9]), "+f"(d[10]), "+f"(d[11])
    : "r"(a0), "r"(a1), "r"(a2), "r"(a3), "l"(descB), "n"(SCALE_D));
}

constexpr uint32_t DHI_SW128_K = (1024 >> 4) | (1u << 30);
constexpr uint32_t DHI_SW64_MN = (512 >> 4) | (2u << 30);

template <int NC>
__device__ __forceinline__ void store_tile_bf16(const float (&acc)[NC / 2], float scale, uint32_t stage, uint8_t* stage_ptr,
                                                __nv_bfloat16* gdst, int gpitch, int lane) {
  constexpr int PITCH = NC * 2 + 16;
  const uint32_t waddr = stage + ((lane & 7) + ((lane >> 3) & 1) * 8) * PITCH + (lane >> 4) * 16;
#pragma unroll
  for (int j = 0; j < NC / 16; j++) {
    stsm4(waddr + j * 32, pack_bf16(acc[8 * j] * scale, acc[8 * j + 1] * scale), pack_bf16(acc[8 * j + 2] * scale, acc[8 * j + 3] * scale),
          pack_bf16(acc[8 * j + 4] * scale, acc[8 * j + 5] * scale), pack_bf16(acc[8 * j + 6] * scale, acc[8 * j + 7] * scale));
  }
  __syncwarp();
  constexpr int CPR = NC / 8;
#pragma unroll
  for (int i = 0; i < CPR / 2; i++) {
    const int c = i * 32 + lane, r = c / CPR, cc = c % CPR;
    const uint4 v = *reinterpret_cast<const uint4*>(stage_ptr + r * PITCH + cc * 16);
    *reinterpret_cast<uint4*>(gdst + (size_t)r * gpitch + cc * 8) = v;
  }
}

__device__ __forceinline__ void signal_done(unsigned int* flag, int wg, int tid) {
  asm volatile("bar.sync %0, 128;" :: "r"(wg + 1) : "memory");
  if ((tid & 127) == 0) asm volatile("red.release.gpu.global.add.u32 [%0], 1;" :: "l"(flag) : "memory");
}
__device__ __forceinline__ void wait_flags8(const unsigned int* f, unsigned int target) {
  for (int spin = 0; spin < (1 << 26); spin++) {
    unsigned int a, b, c, d, e, g, h, i;
    asm volatile("ld.volatile.global.v4.u32 {%0, %1, %2, %3}, [%4];" : "=r"(a), "=r"(b), "=r"(c), "=r"(d) : "l"(f) : "memory");
    asm volatile("ld.volatile.global.v4.u32 {%0, %1, %2, %3}, [%4];" : "=r"(e), "=r"(g), "=r"(h), "=r"(i) : "l"(f + 4) : "memory");
    if (min(min(min(a, b), min(c, d)), min(min(e, g), min(h, i))) >= target) break;
    __nanosleep(32);
  }
  asm volatile("fence.acq_rel.gpu;" ::: "memory");
  asm volatile("fence.proxy.async;" ::: "memory");
}

#define RP_LD 3
#define RP_ST 7
constexpr int K1_STAGES = 4;
constexpr int K1_A_BYTES = 256 * 128;
constexpr int K1_B_BYTES = 64 * 160 * 2;
constexpr int K1_STAGE = K1_A_BYTES + K1_B_BYTES;
constexpr int K1_SMEM = 5 * K1_A_BYTES + 61440 + 1024;
constexpr int KV_STAGES = 5;
constexpr int KVW_OFF = KV_STAGES * K1_A_BYTES;

__global__ void __launch_bounds__(512, 1)
proj_kernel(const __grid_constant__ CUtensorMap tmX, const __grid_constant__ CUtensorMap tmWq, const __grid_constant__ CUtensorMap tmWqkv,
            const __nv_bfloat16* __restrict__ wk, const __nv_bfloat16* __restrict__ wv, const __nv_bfloat16* __restrict__ gate_w,
            const __nv_bfloat16* __restrict__ woA, const __nv_bfloat16* __restrict__ woB) {
  extern __shared__ uint8_t smem_raw[];
  __shared__ __align__(8) uint64_t bar_full[KV_STAGES], bar_empty[KV_STAGES];
  uint8_t* smem = reinterpret_cast<uint8_t*>((reinterpret_cast<uintptr_t>(smem_raw) + 1023) & ~(uintptr_t)1023);
  const uint32_t sbase = smem_u32(smem);
  const uint32_t dbase = sbase & 0x3FFFFu;
  const int tid = threadIdx.x, warp = tid >> 5, lane = tid & 31;
  const bool is_kv = blockIdx.x >= 128;
  PROF(0, 0);
  if (tid == 0) {
    for (int i = 0; i < KV_STAGES; i++) { mbar_init(smem_u32(&bar_full[i]), 1); mbar_init(smem_u32(&bar_empty[i]), is_kv ? 8 : 16); }
    fence_mbar_init();
  }
  uint2 wa[2][5], wb[2][5]; uint32_t gw[2];
  if (is_kv && tid < 320) {
#pragma unroll
    for (int r = 0; r < 2; r++) {
      const int k = tid + r * 320;
      const uint2* pk = reinterpret_cast<const uint2*>(wk + k * 20);
      const uint2* pv = reinterpret_cast<const uint2*>(wv + k * 20);
#pragma unroll
      for (int i = 0; i < 5; i++) { wa[r][i] = __ldg(pk + i); wb[r][i] = __ldg(pv + i); }
      gw[r] = (uint32_t)__bfloat16_as_ushort(gate_w[k]);
    }
  }
  __syncthreads();
  if (tid == 480) {
    if (!is_kv) { g_done[blockIdx.x] = 0u; g_doneL[blockIdx.x] = 0u; }
    asm volatile("fence.acq_rel.gpu;" ::: "memory");
    pdl_launch();
  }
  __syncwarp();

  if (!is_kv) {
    const int mb = blockIdx.x >> 4, nb = blockIdx.x & 15;
    const CUtensorMap* tw = nb < 4 ? &tmWq : &tmWqkv;
    const int j0 = (nb < 4 ? nb : nb - 4) * 5;
    auto load = [&](int kt) {
      const int s = kt % K1_STAGES;
      const uint32_t fb = smem_u32(&bar_full[s]);
      mbar_expect_tx(fb, K1_STAGE);
      tma_2d(sbase + s * K1_STAGE, &tmX, kt * 64, mb * 256, fb);
      tma_3d(sbase + s * K1_STAGE + K1_A_BYTES, tw, 0, kt * 64, j0, fb);
    };
    if (tid == 0) for (int kt = 0; kt < K1_STAGES; kt++) load(kt);
    __syncwarp();
    uint4 wv2[2];
    const int rq = blockIdx.x * 400 + tid - 112;
    const int rhalf = rq >= 25600, rr = rq - rhalf * 25600, rk = 2 * (rr / 80), rch = rr % 80;
    {
      const int wg = warp >> 2;
      float acc[80];
#pragma unroll
      for (int i = 0; i < 80; i++) acc[i] = 0.f;
      for (int kt = 0; kt < 10; kt++) {
        const int s = kt % K1_STAGES;
        mbar_wait(smem_u32(&bar_full[s]), (kt / K1_STAGES) & 1);
        const uint32_t alo = ((dbase + s * K1_STAGE + wg * 8192) >> 4) | (1u << 16);
        const uint32_t blo = ((dbase + s * K1_STAGE + K1_A_BYTES) >> 4) | ((4096u >> 4) << 16);
        fence_regs(acc);
        wg_fence();
#pragma unroll
        for (int k = 0; k < 4; k++) wgmma_ss_n160_tb(acc, mkd(alo + k * 2, DHI_SW128_K), mkd(blo + k * 64, DHI_SW64_MN));
        wg_commit();
        if (kt == RP_LD && tid >= 112) {
          const uint4* src = reinterpret_cast<const uint4*>((rhalf ? woB : woA) + rk * D_MODEL + rch * 8);
          wv2[0] = __ldg(src); wv2[1] = __ldg(src + D_MODEL / 8);
        }
        if (kt == RP_ST && tid >= 112) {
          uint4* dst = reinterpret_cast<uint4*>(g_wimg + ((rhalf * 8 + rch / 10) * 10 + (rk >> 6)) * 10240 + (rch % 10) * 1024 + (rk & 63) * 16);
          dst[0] = wv2[0]; dst[1] = wv2[1];
        }
        __syncwarp();
        if (kt > 0 && kt - 1 + K1_STAGES < 10) {
          wg_wait<1>();
          const uint32_t eb = smem_u32(&bar_empty[(kt - 1) % K1_STAGES]);
          if (lane == 0) mbar_arrive(eb);
          if (tid == 0) { mbar_wait(eb, ((kt - 1) / K1_STAGES) & 1); load(kt - 1 + K1_STAGES); }
          __syncwarp();
        }
      }
      wg_wait<0>();
      fence_regs(acc);
      PROF(0, 1);
      asm volatile("bar.sync %0, 128;" :: "r"(wg + 1) : "memory");
      const int w4 = warp & 3;
      const uint32_t off = w4 * K1_STAGE + wg * 8192;
      const int row0 = mb * 256 + wg * 64 + w4 * 16;
      if (nb < 4) {
        store_tile_bf16<160>(acc, 0.22360679774997896f * 1.4426950408889634f, sbase + off, smem + off,
                             g_q + (size_t)row0 * D_MODEL + nb * 160, D_MODEL, lane);
      } else {
        store_tile_bf16<160>(acc, 1.0f, sbase + off, smem + off, g_qkv + (size_t)row0 * (3 * D_MODEL) + (nb - 4) * 160, 3 * D_MODEL, lane);
      }
    }
  } else {
    const int cb = blockIdx.x - 128;
    if (warp == 8 && lane == 0) {
      for (int it = 0; it < KV_STAGES; it++) {
        const uint32_t fb = smem_u32(&bar_full[it]);
        mbar_expect_tx(fb, K1_A_BYTES);
        tma_2d(sbase + it * K1_A_BYTES, &tmX, it * 64, cb * 512, fb);
      }
    }
    __syncwarp();
    if (tid < 320) {
#pragma unroll
      for (int r = 0; r < 2; r++) {
        uint4* dst = reinterpret_cast<uint4*>(smem + KVW_OFF + (tid + r * 320) * 16);
        dst[0] = make_uint4(wa[r][0].x, wa[r][0].y, wa[r][1].x, wa[r][1].y);
        dst[640] = make_uint4(wa[r][2].x, wa[r][2].y, wa[r][3].x, wa[r][3].y);
        dst[1280] = make_uint4(wa[r][4].x, wa[r][4].y, 0u, 0u);
        dst[1920] = make_uint4(wb[r][0].x, wb[r][0].y, wb[r][1].x, wb[r][1].y);
        dst[2560] = make_uint4(wb[r][2].x, wb[r][2].y, wb[r][3].x, wb[r][3].y);
        dst[3200] = make_uint4(wb[r][4].x, wb[r][4].y, gw[r], 0u);
      }
    }
    fence_proxy_async();
    asm volatile("bar.sync 1, 512;" ::: "memory");
    PROF(0, 1);
    auto produce = [&](int it0, int it1) {
      for (int it = it0; it < it1; it++) {
        const int s = it % KV_STAGES;
        mbar_wait(smem_u32(&bar_empty[s]), (it / KV_STAGES - 1) & 1);
        const uint32_t fb = smem_u32(&bar_full[s]);
        mbar_expect_tx(fb, K1_A_BYTES);
        tma_2d(sbase + s * K1_A_BYTES, &tmX, (it >= 10 ? it - 10 : it) * 64, cb * 512 + (it >= 10 ? 256 : 0), fb);
      }
    };
    if (tid == 256) produce(KV_STAGES, 15);
    __syncwarp();
    {
      const int pass = warp >> 3, wg = (warp >> 2) & 1, w4 = warp & 3, g = lane >> 2, t = lane & 3;
      if (pass == 1) asm volatile("bar.sync 2, 512;" ::: "memory");
      {
        float acc[2][24];
#pragma unroll
        for (int i = 0; i < 24; i++) { acc[0][i] = 0.f; acc[1][i] = 0.f; }
        for (int kt = 0; kt < 10; kt++) {
          const int it = pass * 10 + kt, s = it % KV_STAGES;
          mbar_wait(smem_u32(&bar_full[s]), (it / KV_STAGES) & 1);
          const uint32_t alo = ((dbase + s * K1_A_BYTES + wg * 16384) >> 4) | (1u << 16);
          const uint32_t blo = ((dbase + KVW_OFF + kt * 1024) >> 4) | ((128u >> 4) << 16);
          fence_regs(acc[0]); fence_regs(acc[1]);
          wg_fence();
#pragma unroll
          for (int k = 0; k < 4; k++) {
            wgmma_ss_n48_tb(acc[0], mkd(alo + k * 2, DHI_SW128_K), mkd(blo + k * 16, 10240u >> 4));
            wgmma_ss_n48_tb(acc[1], mkd(alo + 512 + k * 2, DHI_SW128_K), mkd(blo + k * 16, 10240u >> 4));
          }
          wg_commit();
          if (kt > 0) {
            wg_wait<1>();
            if (lane == 0) mbar_arrive(smem_u32(&bar_empty[(it - 1) % KV_STAGES]));
          }
        }
        wg_wait<0>();
        fence_regs(acc[0]); fence_regs(acc[1]);
        if (lane == 0) mbar_arrive(smem_u32(&bar_empty[(pass * 10 + 9) % KV_STAGES]));
        if (pass == 0) asm volatile("bar.arrive 2, 512;" ::: "memory");
        PROF(0, 2);
        if (tid == 0) produce(15, 20);
        __syncwarp();
        float kmax2 = 0.f, vmax = 0.f;
#pragma unroll
        for (int hh = 0; hh < 4; hh++) {
          const int h = hh & 1;
          const float (&a)[24] = acc[hh >> 1];
          const int key = cb * 512 + pass * 256 + wg * 128 + (hh >> 1) * 64 + w4 * 16 + g + h * 8;
          const int grp = key >> 7, kk = key & 127;
          const bool poly = (TMASK >> (kk >> 3)) & 1;
          uint8_t* gp = g_kvimg + grp * GRP_BYTES;
          const uint32_t k0 = pack_bf16(a[2 * h], a[2 * h + 1]);
          const uint32_t k1 = pack_bf16(a[4 + 2 * h], a[5 + 2 * h]);
          uint32_t k2 = pack_bf16(a[8 + 2 * h], a[9 + 2 * h]);
          float n2 = bf_lo(k0) * bf_lo(k0) + bf_hi(k0) * bf_hi(k0) + bf_lo(k1) * bf_lo(k1) + bf_hi(k1) * bf_hi(k1);
          if (t < 2) {
            n2 += bf_lo(k2) * bf_lo(k2) + bf_hi(k2) * bf_hi(k2);
            k2 = pack_bf16(bf_lo(k2) * 0.5f, bf_hi(k2) * 0.5f);
          } else if (t == 2) k2 = poly ? pack_bf16(24.f, 2.5f) : pack_bf16(0.5f, 0.f);
          else k2 = poly ? pack_bf16(0.5f, 0.f) : 0u;
          *reinterpret_cast<uint32_t*>(gp + kk * 16 + t * 4) = k0;
          *reinterpret_cast<uint32_t*>(gp + PLANE + kk * 16 + t * 4) = k1;
          *reinterpret_cast<uint32_t*>(gp + 2 * PLANE + kk * 16 + t * 4) = k2;
          n2 += __shfl_xor_sync(0xffffffffu, n2, 1);
          n2 += __shfl_xor_sync(0xffffffffu, n2, 2);
          kmax2 = (n2 > kmax2 || n2 != n2) ? n2 : kmax2;
          uint32_t v0 = pack_bf16(a[12 + 2 * h], a[13 + 2 * h]);
          uint32_t v1 = pack_bf16(a[16 + 2 * h], a[17 + 2 * h]);
          uint32_t v2 = pack_bf16(a[20 + 2 * h], a[21 + 2 * h]);
          float vm = fmaxf(fmaxf(fabsf(bf_lo(v0)), fabsf(bf_hi(v0))), fmaxf(fabsf(bf_lo(v1)), fabsf(bf_hi(v1))));
          if (t < 2) vm = fmaxf(vm, fmaxf(fabsf(bf_lo(v2)), fabsf(bf_hi(v2))));
          else if (t == 2) {
            const float z = a[20 + 2 * h];
            g_gate[key] = 1.f / (1.f + __expf(-z));
            v2 = 0x00003F80u;
          } else v2 = 0u;
          vmax = fmaxf(vmax, vm);
          if (poly) { v0 ^= 0x80008000u; v1 ^= 0x80008000u; v2 ^= 0x80008000u; }
          uint8_t* vp = gp + 3 * PLANE + (kk >> 3) * 384 + (kk & 7) * 16 + t * 4;
          *reinterpret_cast<uint32_t*>(vp) = v0;
          *reinterpret_cast<uint32_t*>(vp + 128) = v1;
          *reinterpret_cast<uint32_t*>(vp + 256) = v2;
        }
#pragma unroll
        for (int o = 1; o < 32; o <<= 1) {
          const float a = __shfl_xor_sync(0xffffffffu, kmax2, o);
          kmax2 = (a > kmax2 || a != a) ? a : kmax2;
          vmax = fmaxf(vmax, __shfl_xor_sync(0xffffffffu, vmax, o));
        }
        if (lane == 0) { g_kmax2[cb * 16 + warp] = kmax2; g_vmax[cb * 16 + warp] = vmax; }
      }
    }
  }
}

__device__ __forceinline__ uint32_t ex2_pair_poly(float u0, float u1, uint32_t one2) {
  const uint32_t W = __byte_perm(__float_as_uint(u0), __float_as_uint(u1), 0x6521);
  uint32_t v; asm("lop3.b32 %0, %1, 0x007F007F, %2, 0xEA;" : "=r"(v) : "r"(W), "r"(one2));
  uint32_t L, p;
  asm("fma.rn.bf16x2 %0, %1, %2, %3;" : "=r"(L) : "r"(v), "r"(0x1f961f96u), "r"(0x9fe39fe3u));
  asm("fma.rn.bf16x2 %0, %1, %1, %2;" : "=r"(p) : "r"(L), "r"(0x00f500f5u));
  return W + p;
}
template <int JOFF>
__device__ __forceinline__ void softmax_slow(const float (&S)[32], uint32_t (&P)[16], float (&O)[12], float& m0, float& m1) {
  float a0 = m0, a1 = m1;
#pragma unroll
  for (int j = 0; j < 8; j++) {
    a0 = fmaxf(a0, fmaxf(S[4 * j], S[4 * j + 1]));
    a1 = fmaxf(a1, fmaxf(S[4 * j + 2], S[4 * j + 3]));
  }
  a0 = fmaxf(a0, __shfl_xor_sync(0xffffffffu, a0, 1)); a0 = fmaxf(a0, __shfl_xor_sync(0xffffffffu, a0, 2));
  a1 = fmaxf(a1, __shfl_xor_sync(0xffffffffu, a1, 1)); a1 = fmaxf(a1, __shfl_xor_sync(0xffffffffu, a1, 2));
  const float c0 = ex2(m0 - a0), c1 = ex2(m1 - a1);
  m0 = a0; m1 = a1;
#pragma unroll
  for (int j = 0; j < 3; j++) { O[4 * j] *= c0; O[4 * j + 1] *= c0; O[4 * j + 2] *= c1; O[4 * j + 3] *= c1; }
#pragma unroll
  for (int i = 0; i < 16; i++) {
    const float m = (i & 1) ? a1 : a0;
    const uint32_t p = pack_bf16(ex2(S[2 * i] - m), ex2(S[2 * i + 1] - m));
    P[i] = ((TMASK >> (JOFF + i / 2)) & 1) ? (p ^ 0x80008000u) : p;
  }
}
constexpr uint32_t DHI_KV = 128 >> 4;
__device__ __forceinline__ void issue_qk(float (&S)[32], const uint32_t (&q)[8], uint64_t base) {
  wgmma_rs_n64<0>(S, q[0], q[1], q[2], q[3], base + (uint64_t)((PLANE >> 4) << 16));
  wgmma_rs_n64<1>(S, q[4], q[5], q[6], q[7], base + (uint64_t)(2 * PLANE >> 4));
}
__device__ __forceinline__ void issue_pv(float (&O)[12], const uint32_t (&P)[16], uint64_t vbase) {
#pragma unroll
  for (int kk = 0; kk < 4; kk++)
    wgmma_rs_n24_tb<1>(O, P[4 * kk], P[4 * kk + 1], P[4 * kk + 2], P[4 * kk + 3], vbase + (uint64_t)(kk * (768 >> 4)));
}

constexpr uint32_t VOFF = ((3 * PLANE) >> 4) + ((384u >> 4) << 16);
constexpr int KVR = 4;
constexpr int OFF_W = KVR * GRP_BYTES;
constexpr int OFF_X = OFF_W + 10 * 10240;
constexpr int OFF_BAR = OFF_X + 4 * 16384;
constexpr int K2_SMEM = OFF_BAR + 256 + 1024;
constexpr int TSL = 7;
constexpr int BAR_KV = 0, BAR_W = 4, BAR_TA = 5, BAR_TE = 12, BAR_OWN = 19, BAR_L = 20, BAR_LD = 21, CNT_KV = 22;
constexpr int NSTEP = 2 * NGRP;

__device__ __forceinline__ void kv_load(uint32_t sbase, int step) {
  const uint32_t bar = sbase + OFF_BAR + (BAR_KV + (step & (KVR - 1))) * 8;
  mbar_expect_tx(bar, GRP_BYTES);
  bulk_g2s(sbase + (step & (KVR - 1)) * GRP_BYTES, g_kvimg + (step & (NGRP - 1)) * GRP_BYTES, GRP_BYTES, bar);
}
__device__ __forceinline__ void kv_release(uint32_t sbase, int step, bool elected) {
  if (elected && step + KVR < NSTEP) {
    uint32_t old;
    asm volatile("atom.acq_rel.cta.shared::cta.inc.u32 %0, [%1], 3;" : "=r"(old) : "r"(sbase + OFF_BAR + CNT_KV * 8 + (step & (KVR - 1)) * 4) : "memory");
    if (old == 3u) kv_load(sbase, step + KVR);
  }
  __syncwarp();
}
__device__ __forceinline__ void kv_wait(uint32_t sbase, int step) {
  mbar_wait(sbase + OFF_BAR + (BAR_KV + (step & (KVR - 1))) * 8, (step / KVR) & 1);
}

__device__ __forceinline__ uint32_t kv_release_begin(uint32_t sbase, int slot, bool doit) {
  uint32_t old = 0;
  asm volatile("{\n.reg .pred p;\nsetp.ne.u32 p, %2, 0;\n@p atom.relaxed.cta.shared::cta.inc.u32 %0, [%1], 3;\n}\n"
               : "+r"(old) : "r"(sbase + OFF_BAR + CNT_KV * 8 + slot * 4), "r"((uint32_t)doit) : "memory");
  return old;
}
template <int H>
__device__ __forceinline__ void softmax_half(const float (&S)[64], uint32_t (&P)[16], uint32_t one2) {
#pragma unroll
  for (int i = 0; i < 16; i++) {
    if ((TMASK >> (8 * H + i / 2)) & 1) P[i] = ex2_pair_poly(S[32 * H + 2 * i], S[32 * H + 2 * i + 1], one2);
    else P[i] = pack_bf16(ex2(S[32 * H + 2 * i]), ex2(S[32 * H + 2 * i + 1]));
  }
}
__device__ __forceinline__ void attn_fast(const uint32_t (&q)[8], float (&O)[12], uint32_t sbase, int step0, int nsteps, bool elected, uint32_t one2) {
  uint64_t kb0 = mkd((sbase & 0x3FFFFu) >> 4, DHI_KV);
  asm volatile("" : "+l"(kb0));
#pragma unroll 1
  for (int step4 = step0; step4 < step0 + nsteps; step4 += KVR) {
#pragma unroll
    for (int j = 0; j < KVR; j++) {
      const int step = step4 + j;
      const uint64_t kb = kb0 + (uint64_t)(j * (GRP_BYTES >> 4));
      float S[64]; uint32_t PA[16], PB[16];
#pragma unroll
      for (int i = 0; i < 64; i++) S[i] = 0.f;
      mbar_wait(sbase + OFF_BAR + (BAR_KV + j) * 8, (step / KVR) & 1);
      fence_regs(S);
      wg_fence();
      wgmma_rs_n128<0>(S, q[0], q[1], q[2], q[3], kb + (uint64_t)((PLANE >> 4) << 16));
      wgmma_rs_n128<1>(S, q[4], q[5], q[6], q[7], kb + (uint64_t)(2 * PLANE >> 4));
      wg_commit();
      wg_wait<0>();
      fence_regs(S);
      softmax_half<0>(S, PA, one2);
      fence_regs(PA); fence_regs(O);
      wg_fence();
      issue_pv(O, PA, kb + VOFF);
      wg_commit();
      softmax_half<1>(S, PB, one2);
      fence_regs(PB);
      wg_fence();
      issue_pv(O, PB, kb + VOFF + 4 * (768 >> 4));
      wg_commit();
      wg_wait<0>();
      fence_regs(PA); fence_regs(PB); fence_regs(O);
      const uint32_t old = kv_release_begin(sbase, j, elected && step + KVR < NSTEP);
      if (old == 3u) kv_load(sbase, step + KVR);
    }
  }
}
template <int H>
__device__ __forceinline__ void slow_step(const uint32_t (&q)[8], float (&O)[12], uint64_t kb, float& m0, float& m1) {
  float S[32]; uint32_t P[16];
#pragma unroll
  for (int i = 0; i < 32; i++) S[i] = 0.f;
  fence_regs(S);
  wg_fence();
  issue_qk(S, q, kb + 64 * H);
  wg_commit();
  wg_wait<0>();
  fence_regs(S);
  softmax_slow<8 * H>(S, P, O, m0, m1);
  fence_regs(P); fence_regs(O);
  wg_fence();
  issue_pv(O, P, kb + VOFF + H * 4 * (768 >> 4));
  wg_commit();
  wg_wait<0>();
  fence_regs(O); fence_regs(P);
}
__device__ __forceinline__ void attn_slow(const uint32_t (&q)[8], float (&O)[12], uint32_t sbase, int step0, int nsteps, bool elected, float& m0, float& m1) {
#pragma unroll 1
  for (int step = step0; step < step0 + nsteps; step++) {
    kv_wait(sbase, step);
    const uint64_t kb = mkd(((sbase & 0x3FFFFu) >> 4) + (step & (KVR - 1)) * (GRP_BYTES >> 4), DHI_KV);
    slow_step<0>(q, O, kb, m0, m1);
    slow_step<1>(q, O, kb, m0, m1);
    kv_release(sbase, step, elected);
  }
}

__device__ __forceinline__ void load_row20(const __nv_bfloat16* p, float (&f)[20]) {
  const uint2* p2 = reinterpret_cast<const uint2*>(p);
#pragma unroll
  for (int i = 0; i < 5; i++) { const uint2 v = p2[i]; f[4 * i] = bf_lo(v.x); f[4 * i + 1] = bf_hi(v.x); f[4 * i + 2] = bf_lo(v.y); f[4 * i + 3] = bf_hi(v.y); }
}
__device__ __forceinline__ void softmax8(float (&sc)[8]) {
  float mx = sc[0];
#pragma unroll
  for (int w = 1; w < 8; w++) mx = fmaxf(mx, sc[w]);
  float l = 0.f;
#pragma unroll
  for (int w = 0; w < 8; w++) { sc[w] = ex2(sc[w] - mx); l += sc[w]; }
  const float r = 1.f / l;
#pragma unroll
  for (int w = 0; w < 8; w++) sc[w] *= r;
}
constexpr int LBOX = 30 * 320;
__device__ __forceinline__ void local_attn(const uint8_t* stage, int t0, int i, int lane) {
  constexpr float SC = 0.22360679774997896f * 1.4426950408889634f, NEG = -1e9f * 1.4426950408889634f;
  const uint8_t* base = stage + (lane >> 3) * LBOX + (lane & 7) * 40 + (i + 14) * 320;
  const int t = t0 + i;
  float a[20], sc[8];
  load_row20(reinterpret_cast<const __nv_bfloat16*>(base), a);
#pragma unroll
  for (int w = 0; w < 8; w++) {
    float k[20];
    load_row20(reinterpret_cast<const __nv_bfloat16*>(base + 4 * LBOX - w * 640), k);
    float d = 0.f;
#pragma unroll
    for (int j = 0; j < 20; j++) d = fmaf(a[j], k[j], d);
    sc[w] = t - 2 * w >= 0 ? d * SC : NEG;
  }
  softmax8(sc);
#pragma unroll
  for (int j = 0; j < 20; j++) a[j] = 0.f;
#pragma unroll
  for (int w = 0; w < 8; w++) {
    float v[20];
    load_row20(reinterpret_cast<const __nv_bfloat16*>(base + 8 * LBOX - w * 640), v);
#pragma unroll
    for (int j = 0; j < 20; j++) a[j] = fmaf(sc[w], v[j], a[j]);
  }
  const float ga = 1.f - g_gate[t];
  uint2* da = reinterpret_cast<uint2*>(g_a2 + (size_t)t * (2 * D_MODEL) + D_MODEL + lane * DH);
#pragma unroll
  for (int j = 0; j < 5; j++)
    da[j] = make_uint2(pack_bf16(a[4 * j] * ga, a[4 * j + 1] * ga), pack_bf16(a[4 * j + 2] * ga, a[4 * j + 3] * ga));
}
__device__ __forceinline__ uint32_t ta_slot(int i) { return i < 4 ? OFF_X + i * 16384 : (i - 4) * 16384; }

__global__ void __launch_bounds__(512, 1)
attn_kernel(const __grid_constant__ CUtensorMap tmA2, const __grid_constant__ CUtensorMap tmL, __nv_bfloat16* __restrict__ out, uint32_t one2) {
  extern __shared__ uint8_t smem_raw[];
  uint8_t* smem = reinterpret_cast<uint8_t*>((reinterpret_cast<uintptr_t>(smem_raw) + 1023) & ~(uintptr_t)1023);
  const uint32_t sbase = smem_u32(smem);
  const uint32_t dbase = sbase & 0x3FFFFu;
  const uint32_t bars = sbase + OFF_BAR;
  const int tid = threadIdx.x, wg = tid >> 7, warp = (tid >> 5) & 3, lane = tid & 31, g = lane >> 2, t = lane & 3;
  const int mb = blockIdx.x >> 3, nb = blockIdx.x & 7;
  const bool elected = (tid & 127) == 0;
  if (tid == 0) {
    for (int i = 0; i < BAR_TE; i++) mbar_init(bars + i * 8, 1);
    for (int i = BAR_TE; i < BAR_TE + TSL; i++) mbar_init(bars + i * 8, 8);
    mbar_init(bars + BAR_OWN * 8, 4);
    mbar_init(bars + BAR_L * 8, 1);
    mbar_init(bars + BAR_LD * 8, 4);
    for (int i = 0; i < 4; i++) *reinterpret_cast<uint32_t*>(smem + OFF_BAR + CNT_KV * 8 + i * 4) = 0u;
    fence_mbar_init();
  }
  __syncthreads();
  auto tail_load = [&](int i) {
    const uint32_t fb = bars + (BAR_TA + i % TSL) * 8;
    mbar_expect_tx(fb, i < 10 ? 16384 : 16384 + 10240);
    tma_2d(sbase + ta_slot(i % TSL), &tmA2, i < 10 ? D_MODEL + i * 64 : (i - 10) * 64, mb * 128, fb);
    if (i >= 10) bulk_g2s(sbase + OFF_W + (i - 10) * 10240, g_wimg + (nb * 10 + i - 10) * 10240, 10240, fb);
  };
  pdl_wait();
  PROF(1, 1);
  if (tid == 416) for (int j = 0; j < KVR; j++) kv_load(sbase, j);
  __syncwarp();
  uint32_t q[8], q2[6];
  const int rowA = (blockIdx.x * 8 + wg) * 64 + warp * 16 + g;
  {
    const uint32_t* r0 = reinterpret_cast<const uint32_t*>(g_q + (size_t)rowA * DH);
    const uint32_t* r1 = r0 + 8 * (DH / 2);
    const uint32_t* s0 = r0 + 256 * (DH / 2);
    const uint32_t* s1 = s0 + 8 * (DH / 2);
    q[0] = r0[t]; q[1] = r1[t]; q[2] = r0[t + 4]; q[3] = r1[t + 4];
    q[4] = t < 2 ? r0[8 + t] : 0u;
    q[5] = t < 2 ? r1[8 + t] : 0u;
    q2[0] = s0[t]; q2[1] = s1[t]; q2[2] = s0[t + 4]; q2[3] = s1[t + 4];
    q2[4] = t < 2 ? s0[8 + t] : 0u;
    q2[5] = t < 2 ? s1[8 + t] : 0u;
  }
  float kmax2 = 0.f, vmax = 0.f;
#pragma unroll
  for (int i = 0; i < 2; i++) {
    const float a = g_kmax2[lane + 32 * i];
    kmax2 = (a > kmax2 || a != a) ? a : kmax2;
    vmax = fmaxf(vmax, g_vmax[lane + 32 * i]);
  }
#pragma unroll
  for (int o = 1; o < 32; o <<= 1) {
    const float a = __shfl_xor_sync(0xffffffffu, kmax2, o);
    kmax2 = (a > kmax2 || a != a) ? a : kmax2;
    vmax = fmaxf(vmax, __shfl_xor_sync(0xffffffffu, vmax, o));
  }
  const float qlim = (vmax >= 0.00390625f && vmax <= 256.f) ? 9025.f / kmax2 : -1.f;
  PROF(1, 2);
#pragma unroll 1
  for (int it = 0; it < 2; it++) {
    const int row0 = rowA + it * 256;
    if (it == 1) {
#pragma unroll
      for (int i = 0; i < 6; i++) q[i] = q2[i];
    }
    float n0 = bf_lo(q[0]) * bf_lo(q[0]) + bf_hi(q[0]) * bf_hi(q[0]) + bf_lo(q[2]) * bf_lo(q[2]) + bf_hi(q[2]) * bf_hi(q[2]) +
               bf_lo(q[4]) * bf_lo(q[4]) + bf_hi(q[4]) * bf_hi(q[4]);
    float n1 = bf_lo(q[1]) * bf_lo(q[1]) + bf_hi(q[1]) * bf_hi(q[1]) + bf_lo(q[3]) * bf_lo(q[3]) + bf_hi(q[3]) * bf_hi(q[3]) +
               bf_lo(q[5]) * bf_lo(q[5]) + bf_hi(q[5]) * bf_hi(q[5]);
    n0 += __shfl_xor_sync(0xffffffffu, n0, 1); n0 += __shfl_xor_sync(0xffffffffu, n0, 2);
    n1 += __shfl_xor_sync(0xffffffffu, n1, 1); n1 += __shfl_xor_sync(0xffffffffu, n1, 2);
    const bool safe = (n0 <= qlim) && (n1 <= qlim);
    uint32_t unsafe_any;
    asm volatile("{\n.reg .pred p, r;\nsetp.eq.u32 p, %1, 0;\nbarrier.cta.red.or.pred r, %2, 128, p;\nselp.u32 %0, 1, 0, r;\n}\n"
                 : "=r"(unsafe_any) : "r"((uint32_t)safe), "r"(wg + 1) : "memory");
    float O[12];
#pragma unroll
    for (int i = 0; i < 12; i++) O[i] = 0.f;
    if (!unsafe_any && t >= 2) { q[4] = q[5] = (t == 2) ? 0x3F804100u : 0x00003B80u; }
    q[6] = q[4]; q[7] = q[5];
    fence_regs(q);
    float m0 = -INFINITY, m1 = -INFINITY;
#pragma unroll 1
    for (int part = 0; part < 4; part++) {
      const int s0 = it * NGRP + part * KVR;
      if (!unsafe_any) attn_fast(q, O, sbase, s0, KVR, elected, one2);
      else attn_slow(q, O, sbase, s0, KVR, elected, m0, m1);
      const int ev = it * 4 + part;
      if (ev == 0 && tid == 288) {
        mbar_expect_tx(bars + BAR_L * 8, 12 * LBOX);
        for (int i = 0; i < 12; i++) tma_2d(sbase + OFF_W + i * LBOX, &tmL, i * 160, blockIdx.x * 16 - 14, bars + BAR_L * 8);
      }
      if (ev == wg + 1) {
        mbar_wait(bars + BAR_L * 8, 0);
        local_attn(smem + OFF_W, blockIdx.x * 16, tid >> 5, lane);
      } else if (ev == wg + 2) {
        signal_done(&g_doneL[blockIdx.x], wg, tid);
        if ((tid & 127) == 64) mbar_arrive(bars + BAR_LD * 8);
      }
      if (ev == 6 && tid == 32) {
        mbar_wait(bars + BAR_LD * 8, 0);
        mbar_expect_tx(bars + BAR_W * 8, 10 * 10240);
        for (int i = 0; i < 5; i++) bulk_g2s(sbase + OFF_W + i * 20480, g_wimg + ((8 + nb) * 10) * 10240 + i * 20480, 20480, bars + BAR_W * 8);
        wait_flags8(&g_doneL[mb * 8], 4u);
        for (int i = 0; i < 4; i++) tail_load(i);
      }
      __syncwarp();
    }
    const float l0 = __shfl_sync(0xffffffffu, O[8], (lane & ~3) | 2);
    const float l1 = __shfl_sync(0xffffffffu, O[10], (lane & ~3) | 2);
    const int tok = row0 >> 5;
    const float gt = g_gate[tok];
    const float i0 = gt / l0, i1 = gt / l1;
    uint32_t* o0 = reinterpret_cast<uint32_t*>(g_a2 + (size_t)tok * (2 * D_MODEL) + (row0 & 31) * DH);
    uint32_t* o1 = o0 + 8 * (DH / 2);
    o0[t] = pack_bf16(O[0] * i0, O[1] * i0); o1[t] = pack_bf16(O[2] * i1, O[3] * i1);
    o0[t + 4] = pack_bf16(O[4] * i0, O[5] * i0); o1[t + 4] = pack_bf16(O[6] * i1, O[7] * i1);
    if (t < 2) { o0[t + 8] = pack_bf16(O[8] * i0, O[9] * i0); o1[t + 8] = pack_bf16(O[10] * i1, O[11] * i1); }
  }
  signal_done(&g_done[blockIdx.x], wg, tid);
  if ((tid & 127) == 64) mbar_arrive(bars + BAR_OWN * 8);
  PROF(1, 3);
  if (wg == 3) {
    if (tid == 416) {
      mbar_wait(bars + BAR_OWN * 8, 0);
      for (int i = 4; i < 20; i++) {
        if (i >= TSL) mbar_wait(bars + (BAR_TE + i % TSL) * 8, (i / TSL - 1) & 1);
        if (i == 10) { wait_flags8(&g_done[mb * 8], 4u); PROF2(2, 0); }
        tail_load(i);
      }
    }
  } else if (wg < 2) {
    float acc[40];
#pragma unroll
    for (int i = 0; i < 40; i++) acc[i] = 0.f;
    mbar_wait(bars + BAR_W * 8, 0);
    int sl = 0, ph = 0;
#pragma unroll 1
    for (int i = 0; i < 20; i++) {
      mbar_wait(bars + (BAR_TA + sl) * 8, ph);
      if (i == 10) PROF(2, 1);
      const uint32_t alo = ((dbase + ta_slot(sl) + wg * 8192) >> 4) | (1u << 16);
      const uint32_t blo = ((dbase + OFF_W + (i >= 10 ? i - 10 : i) * 10240) >> 4) | ((128u >> 4) << 16);
      fence_regs(acc);
      wg_fence();
#pragma unroll
      for (int k = 0; k < 4; k++) wgmma_ss_n80_tb(acc, mkd(alo + k * 2, DHI_SW128_K), mkd(blo + k * 16, 1024u >> 4));
      wg_commit();
      if (i > 0) {
        wg_wait<1>();
        if (lane == 0) mbar_arrive(bars + (BAR_TE + (sl == 0 ? TSL - 1 : sl - 1)) * 8);
      }
      if (++sl == TSL) { sl = 0; ph ^= 1; }
    }
    wg_wait<0>();
    fence_regs(acc);
    PROF(2, 2);
    asm volatile("bar.sync %0, 128;" :: "r"(wg + 1) : "memory");
    const uint32_t so = ta_slot(warp) + wg * 8192;
    const int row0 = mb * 128 + wg * 64 + warp * 16;
    store_tile_bf16<80>(acc, 1.0f, sbase + so, smem + so, out + (size_t)row0 * D_MODEL + nb * 80, D_MODEL, lane);
    PROF(2, 3);
  }
}

typedef CUresult (*EncodeFn)(CUtensorMap*, CUtensorMapDataType, cuuint32_t, void*, const cuuint64_t*, const cuuint64_t*,
                             const cuuint32_t*, const cuuint32_t*, CUtensorMapInterleave, CUtensorMapSwizzle,
                             CUtensorMapL2promotion, CUtensorMapFloatOOBfill);

void make_map(EncodeFn fn, CUtensorMap* tm, const void* ptr, int rank, const cuuint64_t* dims, const cuuint64_t* strides,
              const cuuint32_t* box, CUtensorMapSwizzle sw) {
  const cuuint32_t es[3] = {1, 1, 1};
  fn(tm, CU_TENSOR_MAP_DATA_TYPE_BFLOAT16, rank, const_cast<void*>(ptr), dims, strides, box, es, CU_TENSOR_MAP_INTERLEAVE_NONE, sw,
     CU_TENSOR_MAP_L2_PROMOTION_L2_256B, CU_TENSOR_MAP_FLOAT_OOB_FILL_NONE);
}
void map_a(EncodeFn fn, CUtensorMap* tm, const void* p, int rows, int cols, int box_rows) {
  const cuuint64_t dims[2] = {(cuuint64_t)cols, (cuuint64_t)rows};
  const cuuint64_t str[1] = {(cuuint64_t)cols * 2};
  const cuuint32_t box[2] = {64, (cuuint32_t)box_rows};
  make_map(fn, tm, p, 2, dims, str, box, CU_TENSOR_MAP_SWIZZLE_128B);
}
void map_w(EncodeFn fn, CUtensorMap* tm, const void* p, int K, int N, int atom, CUtensorMapSwizzle sw) {
  const cuuint64_t dims[3] = {(cuuint64_t)atom, (cuuint64_t)K, (cuuint64_t)(N / atom)};
  const cuuint64_t str[2] = {(cuuint64_t)N * 2, (cuuint64_t)atom * 2};
  const cuuint32_t box[3] = {(cuuint32_t)atom, 64, 5};
  make_map(fn, tm, p, 3, dims, str, box, sw);
}

template <typename... KArgs, typename... Args>
void launch(void (*kern)(KArgs...), int grid, int block, int smem, bool pdl, Args... args) {
  cudaLaunchConfig_t cfg = {};
  cfg.gridDim = dim3(grid); cfg.blockDim = dim3(block); cfg.dynamicSmemBytes = smem; cfg.stream = cudaStreamPerThread;
  cudaLaunchAttribute at[1];
  at[0].id = cudaLaunchAttributeProgrammaticStreamSerialization;
  at[0].val.programmaticStreamSerializationAllowed = 1;
  cfg.attrs = at; cfg.numAttrs = pdl ? 1 : 0;
  cudaLaunchKernelEx(&cfg, kern, KArgs(args)...);
}

}

extern "C" void kernel_launch(void* const* d_in, const int* in_sizes, int n_in, void* d_out, int out_size) {
  (void)in_sizes; (void)n_in; (void)out_size;
  const __nv_bfloat16* x = (const __nv_bfloat16*)d_in[0];
  const __nv_bfloat16* wq = (const __nv_bfloat16*)d_in[1];
  const __nv_bfloat16* wk = (const __nv_bfloat16*)d_in[2];
  const __nv_bfloat16* wv = (const __nv_bfloat16*)d_in[3];
  const __nv_bfloat16* woA = (const __nv_bfloat16*)d_in[4];
  const __nv_bfloat16* wqkv = (const __nv_bfloat16*)d_in[6];
  const __nv_bfloat16* woB = (const __nv_bfloat16*)d_in[7];
  const __nv_bfloat16* gate_w = (const __nv_bfloat16*)d_in[8];

  static EncodeFn enc = nullptr;
  static void* a2_ptr = nullptr;
  static void* qkv_ptr = nullptr;
  if (!enc) {
    void* fp = nullptr;
    cudaDriverEntryPointQueryResult qr;
    cudaGetDriverEntryPoint("cuTensorMapEncodeTiled", &fp, cudaEnableDefault, &qr);
    enc = (EncodeFn)fp;
    cudaGetSymbolAddress(&a2_ptr, g_a2);
    cudaGetSymbolAddress(&qkv_ptr, g_qkv);
    cudaFuncSetAttribute(proj_kernel, cudaFuncAttributeMaxDynamicSharedMemorySize, K1_SMEM);
    cudaFuncSetAttribute(attn_kernel, cudaFuncAttributeMaxDynamicSharedMemorySize, K2_SMEM);
  }
  CUtensorMap tmX, tmWq, tmWqkv, tmA2, tmL;
  {
    const cuuint64_t dims[2] = {3 * D_MODEL, S_LEN};
    const cuuint64_t str[1] = {3 * D_MODEL * 2};
    const cuuint32_t box[2] = {160, 30};
    make_map(enc, &tmL, qkv_ptr, 2, dims, str, box, CU_TENSOR_MAP_SWIZZLE_NONE);
  }
  map_a(enc, &tmX, x, S_LEN, D_MODEL, 256);
  map_w(enc, &tmWq, wq, D_MODEL, D_MODEL, 32, CU_TENSOR_MAP_SWIZZLE_64B);
  map_w(enc, &tmWqkv, wqkv, D_MODEL, 3 * D_MODEL, 32, CU_TENSOR_MAP_SWIZZLE_64B);
  map_a(enc, &tmA2, a2_ptr, S_LEN, 2 * D_MODEL, 128);

  launch(proj_kernel, 132, 512, K1_SMEM, false, tmX, tmWq, tmWqkv, wk, wv, gate_w, woA, woB);
  launch(attn_kernel, 128, 512, K2_SMEM, true, tmA2, tmL, (__nv_bfloat16*)d_out, 0x3F803F80u);
}
```

```cpp
#include <cuda_runtime.h>
#include <cuda_bf16.h>
#include <cuda.h>
#include <stdint.h>

namespace {

constexpr int S_LEN = 2048, D_MODEL = 640, DH = 20;

constexpr int GRP = 128;
constexpr int PLANE = GRP * 16;
constexpr int GRP_BYTES = GRP * 16 * 6;
constexpr int NGRP = S_LEN / GRP;
#define TMASKV 0xBBBBu
constexpr uint32_t TMASK = TMASKV;

__device__ __align__(1024) __nv_bfloat16 g_q[S_LEN * D_MODEL];
__device__ __align__(1024) __nv_bfloat16 g_qkv[S_LEN * 3 * D_MODEL];
__device__ __align__(1024) __nv_bfloat16 g_a2[S_LEN * 2 * D_MODEL];
__device__ __align__(1024) uint8_t g_kvimg[NGRP * GRP_BYTES];
__device__ __align__(1024) uint8_t g_wimg[2 * 8 * 10 * 10240];
__device__ float g_gate[S_LEN];
__device__ float g_kmax2[64];
__device__ float g_vmax[64];
__device__ __align__(32) unsigned int g_doneL[128];
__device__ __align__(32) unsigned int g_done[128];

#define PROF(k, slot)
#define PROF2(k, slot)
__device__ __forceinline__ uint32_t smem_u32(const void* p) { return (uint32_t)__cvta_generic_to_shared(p); }
__device__ __forceinline__ uint64_t mkd(uint32_t lo, uint32_t hi) {
  uint64_t d; asm("mov.b64 %0, {%1, %2};" : "=l"(d) : "r"(lo), "r"(hi)); return d;
}
__device__ __forceinline__ void wg_fence() { asm volatile("wgmma.fence.sync.aligned;" ::: "memory"); }
__device__ __forceinline__ void wg_commit() { asm volatile("wgmma.commit_group.sync.aligned;" ::: "memory"); }
template <int N> __device__ __forceinline__ void wg_wait() { asm volatile("wgmma.wait_group.sync.aligned %0;" :: "n"(N) : "memory"); }
template <int N> __device__ __forceinline__ void fence_regs(float (&d)[N]) {
#pragma unroll
  for (int i = 0; i < N; i++) asm volatile("" : "+f"(d[i]) :: "memory");
}
template <int N> __device__ __forceinline__ void fence_regs(uint32_t (&d)[N]) {
#pragma unroll
  for (int i = 0; i < N; i++) asm volatile("" : "+r"(d[i]) :: "memory");
}
__device__ __forceinline__ void mbar_init(uint32_t bar, uint32_t cnt) { asm volatile("mbarrier.init.shared::cta.b64 [%0], %1;" :: "r"(bar), "r"(cnt)); }
__device__ __forceinline__ void mbar_expect_tx(uint32_t bar, uint32_t bytes) {
  asm volatile("mbarrier.arrive.expect_tx.shared::cta.b64 _, [%0], %1;" :: "r"(bar), "r"(bytes) : "memory");
}
__device__ __forceinline__ void mbar_arrive(uint32_t bar) { asm volatile("mbarrier.arrive.shared::cta.b64 _, [%0];" :: "r"(bar) : "memory"); }
#define WAIT_HINT 20000u
__device__ __forceinline__ void mbar_wait(uint32_t bar, uint32_t parity) {
  asm volatile("{\n.reg .pred p;\nWAIT_%=:\nmbarrier.try_wait.parity.shared::cta.b64 p, [%0], %1, %2;\n@p bra DONE_%=;\nbra WAIT_%=;\nDONE_%=:\n}\n"
               :: "r"(bar), "r"(parity), "r"(WAIT_HINT) : "memory");
}
__device__ __forceinline__ void fence_mbar_init() { asm volatile("fence.mbarrier_init.release.cluster;" ::: "memory"); }
__device__ __forceinline__ void fence_proxy_async() { asm volatile("fence.proxy.async.shared::cta;" ::: "memory"); }
__device__ __forceinline__ void bulk_g2s(uint32_t dst, const void* src, uint32_t bytes, uint32_t bar) {
  asm volatile("cp.async.bulk.shared::cluster.global.mbarrier::complete_tx::bytes [%0], [%1], %2, [%3];"
               :: "r"(dst), "l"(src), "r"(bytes), "r"(bar) : "memory");
}
__device__ __forceinline__ void tma_2d(uint32_t dst, const CUtensorMap* tm, int c0, int c1, uint32_t bar) {
  asm volatile("cp.async.bulk.tensor.2d.shared::cluster.global.mbarrier::complete_tx::bytes [%0], [%1, {%3, %4}], [%2];"
               :: "r"(dst), "l"((uint64_t)tm), "r"(bar), "r"(c0), "r"(c1) : "memory");
}
__device__ __forceinline__ void tma_3d(uint32_t dst, const CUtensorMap* tm, int c0, int c1, int c2, uint32_t bar) {
  asm volatile("cp.async.bulk.tensor.3d.shared::cluster.global.mbarrier::complete_tx::bytes [%0], [%1, {%3, %4, %5}], [%2];"
               :: "r"(dst), "l"((uint64_t)tm), "r"(bar), "r"(c0), "r"(c1), "r"(c2) : "memory");
}
__device__ __forceinline__ void pdl_wait() { asm volatile("griddepcontrol.wait;" ::: "memory"); }
__device__ __forceinline__ void pdl_launch() { asm volatile("griddepcontrol.launch_dependents;" ::: "memory"); }
__device__ __forceinline__ float ex2(float x) { float y; asm("ex2.approx.ftz.f32 %0, %1;" : "=f"(y) : "f"(x)); return y; }
__device__ __forceinline__ uint32_t pack_bf16(float lo, float hi) {
  uint32_t r; asm("cvt.rn.bf16x2.f32 %0, %1, %2;" : "=r"(r) : "f"(hi), "f"(lo)); return r;
}
__device__ __forceinline__ float bf_lo(uint32_t x) { return __uint_as_float(x << 16); }
__device__ __forceinline__ float bf_hi(uint32_t x) { return __uint_as_float(x & 0xffff0000u); }
__device__ __forceinline__ void stsm4(uint32_t addr, uint32_t r0, uint32_t r1, uint32_t r2, uint32_t r3) {
  asm volatile("stmatrix.sync.aligned.m8n8.x4.shared.b16 [%0], {%1, %2, %3, %4};" :: "r"(addr), "r"(r0), "r"(r1), "r"(r2), "r"(r3) : "memory");
}

__device__ __forceinline__ void wgmma_ss_n160_tb(float (&d)[80], uint64_t descA, uint64_t descB) {
  asm volatile("wgmma.mma_async.sync.aligned.m64n160k16.f32.bf16.bf16 {%0, %1, %2, %3, %4, %5, %6, %7, %8, %9, %10, %11, %12, %13, %14, %15, %16, %17, %18, %19, %20, %21, %22, %23, %24, %25, %26, %27, %28, %29, %30, %31, %32, %33, %34, %35, %36, %37, %38, %39, %40, %41, %42, %43, %44, %45, %46, %47, %48, %49, %50, %51, %52, %53, %54, %55, %56, %57, %58, %59, %60, %61, %62, %63, %64, %65, %66, %67, %68, %69, %70, %71, %72, %73, %74, %75, %76, %77, %78, %79}, %80, %81, 1, 1, 1, 0, 1;\n"
    : "+f"(d[0]), "+f"(d[1]), "+f"(d[2]), "+f"(d[3]), "+f"(d[4]), "+f"(d[5]), "+f"(d[6]), "+f"(d[7]), "+f"(d[8]), "+f"(d[9]), "+f"(d[10]), "+f"(d[11]), "+f"(d[12]), "+f"(d[13]), "+f"(d[14]), "+f"(d[15]), "+f"(d[16]), "+f"(d[17]), "+f"(d[18]), "+f"(d[19]), "+f"(d[20]), "+f"(d[21]), "+f"(d[22]), "+f"(d[23]), "+f"(d[24]), "+f"(d[25]), "+f"(d[26]), "+f"(d[27]), "+f"(d[28]), "+f"(d[29]), "+f"(d[30]), "+f"(d[31]), "+f"(d[32]), "+f"(d[33]), "+f"(d[34]), "+f"(d[35]), "+f"(d[36]), "+f"(d[37]), "+f"(d[38]), "+f"(d[39]), "+f"(d[40]), "+f"(d[41]), "+f"(d[42]), "+f"(d[43]), "+f"(d[44]), "+f"(d[45]), "+f"(d[46]), "+f"(d[47]), "+f"(d[48]), "+f"(d[49]), "+f"(d[50]), "+f"(d[51]), "+f"(d[52]), "+f"(d[53]), "+f"(d[54]), "+f"(d[55]), "+f"(d[56]), "+f"(d[57]), "+f"(d[58]), "+f"(d[59]), "+f"(d[60]), "+f"(d[61]), "+f"(d[62]), "+f"(d[63]), "+f"(d[64]), "+f"(d[65]), "+f"(d[66]), "+f"(d[67]), "+f"(d[68]), "+f"(d[69]), "+f"(d[70]), "+f"(d[71]), "+f"(d[72]), "+f"(d[73]), "+f"(d[74]), "+f"(d[75]), "+f"(d[76]), "+f"(d[77]), "+f"(d[78]), "+f"(d[79])
    : "l"(descA), "l"(descB));
}
__device__ __forceinline__ void wgmma_ss_n48_tb(float (&d)[24], uint64_t descA, uint64_t descB) {
  asm volatile("wgmma.mma_async.sync.aligned.m64n48k16.f32.bf16.bf16 {%0, %1, %2, %3, %4, %5, %6, %7, %8, %9, %10, %11, %12, %13, %14, %15, %16, %17, %18, %19, %20, %21, %22, %23}, %24, %25, 1, 1, 1, 0, 1;\n"
    : "+f"(d[0]), "+f"(d[1]), "+f"(d[2]), "+f"(d[3]), "+f"(d[4]), "+f"(d[5]), "+f"(d[6]), "+f"(d[7]), "+f"(d[8]), "+f"(d[9]), "+f"(d[10]), "+f"(d[11]), "+f"(d[12]), "+f"(d[13]), "+f"(d[14]), "+f"(d[15]), "+f"(d[16]), "+f"(d[17]), "+f"(d[18]), "+f"(d[19]), "+f"(d[20]), "+f"(d[21]), "+f"(d[22]), "+f"(d[23])
    : "l"(descA), "l"(descB));
}
__device__ __forceinline__ void wgmma_ss_n80_tb(float (&d)[40], uint64_t descA, uint64_t descB) {
  asm volatile("wgmma.mma_async.sync.aligned.m64n80k16.f32.bf16.bf16 {%0, %1, %2, %3, %4, %5, %6, %7, %8, %9, %10, %11, %12, %13, %14, %15, %16, %17, %18, %19, %20, %21, %22, %23, %24, %25, %26, %27, %28, %29, %30, %31, %32, %33, %34, %35, %36, %37, %38, %39}, %40, %41, 1, 1, 1, 0, 1;\n"
    : "+f"(d[0]), "+f"(d[1]), "+f"(d[2]), "+f"(d[3]), "+f"(d[4]), "+f"(d[5]), "+f"(d[6]), "+f"(d[7]), "+f"(d[8]), "+f"(d[9]), "+f"(d[10]), "+f"(d[11]), "+f"(d[12]), "+f"(d[13]), "+f"(d[14]), "+f"(d[15]), "+f"(d[16]), "+f"(d[17]), "+f"(d[18]), "+f"(d[19]), "+f"(d[20]), "+f"(d[21]), "+f"(d[22]), "+f"(d[23]), "+f"(d[24]), "+f"(d[25]), "+f"(d[26]), "+f"(d[27]), "+f"(d[28]), "+f"(d[29]), "+f"(d[30]), "+f"(d[31]), "+f"(d[32]), "+f"(d[33]), "+f"(d[34]), "+f"(d[35]), "+f"(d[36]), "+f"(d[37]), "+f"(d[38]), "+f"(d[39])
    : "l"(descA), "l"(descB));
}
template <int SCALE_D>
__device__ __forceinline__ void wgmma_rs_n64(float (&d)[32], uint32_t a0, uint32_t a1, uint32_t a2, uint32_t a3, uint64_t descB) {
  asm volatile("wgmma.mma_async.sync.aligned.m64n64k16.f32.bf16.bf16 {%0, %1, %2, %3, %4, %5, %6, %7, %8, %9, %10, %11, %12, %13, %14, %15, %16, %17, %18, %19, %20, %21, %22, %23, %24, %25, %26, %27, %28, %29, %30, %31}, {%32, %33, %34, %35}, %36, %37, 1, 1, 0;\n"
    : "+f"(d[0]), "+f"(d[1]), "+f"(d[2]), "+f"(d[3]), "+f"(d[4]), "+f"(d[5]), "+f"(d[6]), "+f"(d[7]), "+f"(d[8]), "+f"(d[9]), "+f"(d[10]), "+f"(d[11]), "+f"(d[12]), "+f"(d[13]), "+f"(d[14]), "+f"(d[15]), "+f"(d[16]), "+f"(d[17]), "+f"(d[18]), "+f"(d[19]), "+f"(d[20]), "+f"(d[21]), "+f"(d[22]), "+f"(d[23]), "+f"(d[24]), "+f"(d[25]), "+f"(d[26]), "+f"(d[27]), "+f"(d[28]), "+f"(d[29]), "+f"(d[30]), "+f"(d[31])
    : "r"(a0), "r"(a1), "r"(a2), "r"(a3), "l"(descB), "n"(SCALE_D));
}
template <int SCALE_D>
__device__ __forceinline__ void wgmma_rs_n128(float (&d)[64], uint32_t a0, uint32_t a1, uint32_t a2, uint32_t a3, uint64_t descB) {
  asm volatile("wgmma.mma_async.sync.aligned.m64n128k16.f32.bf16.bf16 {%0, %1, %2, %3, %4, %5, %6, %7, %8, %9, %10, %11, %12, %13, %14, %15, %16, %17, %18, %19, %20, %21, %22, %23, %24, %25, %26, %27, %28, %29, %30, %31, %32, %33, %34, %35, %36, %37, %38, %39, %40, %41, %42, %43, %44, %45, %46, %47, %48, %49, %50, %51, %52, %53, %54, %55, %56, %57, %58, %59, %60, %61, %62, %63}, {%64, %65, %66, %67}, %68, %69, 1, 1, 0;\n"
    : "+f"(d[0]), "+f"(d[1]), "+f"(d[2]), "+f"(d[3]), "+f"(d[4]), "+f"(d[5]), "+f"(d[6]), "+f"(d[7]), "+f"(d[8]), "+f"(d[9]), "+f"(d[10]), "+f"(d[11]), "+f"(d[12]), "+f"(d[13]), "+f"(d[14]), "+f"(d[15]), "+f"(d[16]), "+f"(d[17]), "+f"(d[18]), "+f"(d[19]), "+f"(d[20]), "+f"(d[21]), "+f"(d[22]), "+f"(d[23]), "+f"(d[24]), "+f"(d[25]), "+f"(d[26]), "+f"(d[27]), "+f"(d[28]), "+f"(d[29]), "+f"(d[30]), "+f"(d[31]), "+f"(d[32]), "+f"(d[33]), "+f"(d[34]), "+f"(d[35]), "+f"(d[36]), "+f"(d[37]), "+f"(d[38]), "+f"(d[39]), "+f"(d[40]), "+f"(d[41]), "+f"(d[42]), "+f"(d[43]), "+f"(d[44]), "+f"(d[45]), "+f"(d[46]), "+f"(d[47]), "+f"(d[48]), "+f"(d[49]), "+f"(d[50]), "+f"(d[51]), "+f"(d[52]), "+f"(d[53]), "+f"(d[54]), "+f"(d[55]), "+f"(d[56]), "+f"(d[57]), "+f"(d[58]), "+f"(d[59]), "+f"(d[60]), "+f"(d[61]), "+f"(d[62]), "+f"(d[63])
    : "r"(a0), "r"(a1), "r"(a2), "r"(a3), "l"(descB), "n"(SCALE_D));
}
template <int SCALE_D>
__device__ __forceinline__ void wgmma_rs_n24_tb(float (&d)[12], uint32_t a0, uint32_t a1, uint32_t a2, uint32_t a3, uint64_t descB) {
  asm volatile("wgmma.mma_async.sync.aligned.m64n24k16.f32.bf16.bf16 {%0, %1, %2, %3, %4, %5, %6, %7, %8, %9, %10, %11}, {%12, %13, %14, %15}, %16, %17, 1, 1, 1;\n"
    : "+f"(d[0]), "+f"(d[1]), "+f"(d[2]), "+f"(d[3]), "+f"(d[4]), "+f"(d[5]), "+f"(d[6]), "+f"(d[7]), "+f"(d[8]), "+f"(d[9]), "+f"(d[10]), "+f"(d[11])
    : "r"(a0), "r"(a1), "r"(a2), "r"(a3), "l"(descB), "n"(SCALE_D));
}

constexpr uint32_t DHI_SW128_K = (1024 >> 4) | (1u << 30);
constexpr uint32_t DHI_SW64_MN = (512 >> 4) | (2u << 30);

template <int NC>
__device__ __forceinline__ void store_tile_bf16(const float (&acc)[NC / 2], float scale, uint32_t stage, uint8_t* stage_ptr,
                                                __nv_bfloat16* gdst, int gpitch, int lane) {
  constexpr int PITCH = NC * 2 + 16;
  const uint32_t waddr = stage + ((lane & 7) + ((lane >> 3) & 1) * 8) * PITCH + (lane >> 4) * 16;
#pragma unroll
  for (int j = 0; j < NC / 16; j++) {
    stsm4(waddr + j * 32, pack_bf16(acc[8 * j] * scale, acc[8 * j + 1] * scale), pack_bf16(acc[8 * j + 2] * scale, acc[8 * j + 3] * scale),
          pack_bf16(acc[8 * j + 4] * scale, acc[8 * j + 5] * scale), pack_bf16(acc[8 * j + 6] * scale, acc[8 * j + 7] * scale));
  }
  __syncwarp();
  constexpr int CPR = NC / 8;
#pragma unroll
  for (int i = 0; i < CPR / 2; i++) {
    const int c = i * 32 + lane, r = c / CPR, cc = c % CPR;
    const uint4 v = *reinterpret_cast<const uint4*>(stage_ptr + r * PITCH + cc * 16);
    *reinterpret_cast<uint4*>(gdst + (size_t)r * gpitch + cc * 8) = v;
  }
}

__device__ __forceinline__ void signal_done(unsigned int* flag, int wg, int tid) {
  asm volatile("bar.sync %0, 128;" :: "r"(wg + 1) : "memory");
  if ((tid & 127) == 0) asm volatile("red.release.gpu.global.add.u32 [%0], 1;" :: "l"(flag) : "memory");
}
__device__ __forceinline__ void wait_flags8(const unsigned int* f, unsigned int target) {
  for (int spin = 0; spin < (1 << 26); spin++) {
    unsigned int a, b, c, d, e, g, h, i;
    asm volatile("ld.volatile.global.v4.u32 {%0, %1, %2, %3}, [%4];" : "=r"(a), "=r"(b), "=r"(c), "=r"(d) : "l"(f) : "memory");
    asm volatile("ld.volatile.global.v4.u32 {%0, %1, %2, %3}, [%4];" : "=r"(e), "=r"(g), "=r"(h), "=r"(i) : "l"(f + 4) : "memory");
    if (min(min(min(a, b), min(c, d)), min(min(e, g), min(h, i))) >= target) break;
    __nanosleep(32);
  }
  asm volatile("fence.acq_rel.gpu;" ::: "memory");
  asm volatile("fence.proxy.async;" ::: "memory");
}

#define RP_LD 3
#define RP_ST 7
constexpr int K1_STAGES = 4;
constexpr int K1_A_BYTES = 256 * 128;
constexpr int K1_B_BYTES = 64 * 160 * 2;
constexpr int K1_STAGE = K1_A_BYTES + K1_B_BYTES;
constexpr int K1_SMEM = 5 * K1_A_BYTES + 61440 + 1024;
constexpr int KV_STAGES = 5;
constexpr int KVW_OFF = KV_STAGES * K1_A_BYTES;

__global__ void __launch_bounds__(512, 1)
proj_kernel(const __grid_constant__ CUtensorMap tmX, const __grid_constant__ CUtensorMap tmWq, const __grid_constant__ CUtensorMap tmWqkv,
            const __nv_bfloat16* __restrict__ wk, const __nv_bfloat16* __restrict__ wv, const __nv_bfloat16* __restrict__ gate_w,
            const __nv_bfloat16* __restrict__ woA, const __nv_bfloat16* __restrict__ woB) {
  extern __shared__ uint8_t smem_raw[];
  __shared__ __align__(8) uint64_t bar_full[KV_STAGES], bar_empty[KV_STAGES];
  uint8_t* smem = reinterpret_cast<uint8_t*>((reinterpret_cast<uintptr_t>(smem_raw) + 1023) & ~(uintptr_t)1023);
  const uint32_t sbase = smem_u32(smem);
  const uint32_t dbase = sbase & 0x3FFFFu;
  const int tid = threadIdx.x, warp = tid >> 5, lane = tid & 31;
  const bool is_kv = blockIdx.x >= 128;
  PROF(0, 0);
  if (tid == 0) {
    for (int i = 0; i < KV_STAGES; i++) { mbar_init(smem_u32(&bar_full[i]), 1); mbar_init(smem_u32(&bar_empty[i]), is_kv ? 8 : 16); }
    fence_mbar_init();
  }
  uint2 wa[2][5], wb[2][5]; uint32_t gw[2];
  if (is_kv && tid < 320) {
#pragma unroll
    for (int r = 0; r < 2; r++) {
      const int k = tid + r * 320;
      const uint2* pk = reinterpret_cast<const uint2*>(wk + k * 20);
      const uint2* pv = reinterpret_cast<const uint2*>(wv + k * 20);
#pragma unroll
      for (int i = 0; i < 5; i++) { wa[r][i] = __ldg(pk + i); wb[r][i] = __ldg(pv + i); }
      gw[r] = (uint32_t)__bfloat16_as_ushort(gate_w[k]);
    }
  }
  __syncthreads();
  if (tid == 480) {
    if (!is_kv) { g_done[blockIdx.x] = 0u; g_doneL[blockIdx.x] = 0u; }
    asm volatile("fence.acq_rel.gpu;" ::: "memory");
    pdl_launch();
  }
  __syncwarp();

  if (!is_kv) {
    const int mb = blockIdx.x >> 4, nb = blockIdx.x & 15;
    const CUtensorMap* tw = nb < 4 ? &tmWq : &tmWqkv;
    const int j0 = (nb < 4 ? nb : nb - 4) * 5;
    auto load = [&](int kt) {
      const int s = kt % K1_STAGES;
      const uint32_t fb = smem_u32(&bar_full[s]);
      mbar_expect_tx(fb, K1_STAGE);
      tma_2d(sbase + s * K1_STAGE, &tmX, kt * 64, mb * 256, fb);
      tma_3d(sbase + s * K1_STAGE + K1_A_BYTES, tw, 0, kt * 64, j0, fb);
    };
    if (tid == 0) for (int kt = 0; kt < K1_STAGES; kt++) load(kt);
    __syncwarp();
    uint4 wv2[2];
    const int rq = blockIdx.x * 400 + tid - 112;
    const int rhalf = rq >= 25600, rr = rq - rhalf * 25600, rk = 2 * (rr / 80), rch = rr % 80;
    {
      const int wg = warp >> 2;
      float acc[80];
#pragma unroll
      for (int i = 0; i < 80; i++) acc[i] = 0.f;
      for (int kt = 0; kt < 10; kt++) {
        const int s = kt % K1_STAGES;
        mbar_wait(smem_u32(&bar_full[s]), (kt / K1_STAGES) & 1);
        const uint32_t alo = ((dbase + s * K1_STAGE + wg * 8192) >> 4) | (1u << 16);
        const uint32_t blo = ((dbase + s * K1_STAGE + K1_A_BYTES) >> 4) | ((4096u >> 4) << 16);
        fence_regs(acc);
        wg_fence();
#pragma unroll
        for (int k = 0; k < 4; k++) wgmma_ss_n160_tb(acc, mkd(alo + k * 2, DHI_SW128_K), mkd(blo + k * 64, DHI_SW64_MN));
        wg_commit();
        if (kt == RP_LD && tid >= 112) {
          const uint4* src = reinterpret_cast<const uint4*>((rhalf ? woB : woA) + rk * D_MODEL + rch * 8);
          wv2[0] = __ldg(src); wv2[1] = __ldg(src + D_MODEL / 8);
        }
        if (kt == RP_ST && tid >= 112) {
          uint4* dst = reinterpret_cast<uint4*>(g_wimg + ((rhalf * 8 + rch / 10) * 10 + (rk >> 6)) * 10240 + (rch % 10) * 1024 + (rk & 63) * 16);
          dst[0] = wv2[0]; dst[1] = wv2[1];
        }
        __syncwarp();
        if (kt > 0 && kt - 1 + K1_STAGES < 10) {
          wg_wait<1>();
          const uint32_t eb = smem_u32(&bar_empty[(kt - 1) % K1_STAGES]);
          if (lane == 0) mbar_arrive(eb);
          if (tid == 0) { mbar_wait(eb, ((kt - 1) / K1_STAGES) & 1); load(kt - 1 + K1_STAGES); }
          __syncwarp();
        }
      }
      wg_wait<0>();
      fence_regs(acc);
      PROF(0, 1);
      asm volatile("bar.sync %0, 128;" :: "r"(wg + 1) : "memory");
      const int w4 = warp & 3;
      const uint32_t off = w4 * K1_STAGE + wg * 8192;
      const int row0 = mb * 256 + wg * 64 + w4 * 16;
      if (nb < 4) {
        store_tile_bf16<160>(acc, 0.22360679774997896f * 1.4426950408889634f, sbase + off, smem + off,
                             g_q + (size_t)row0 * D_MODEL + nb * 160, D_MODEL, lane);
      } else {
        store_tile_bf16<160>(acc, 1.0f, sbase + off, smem + off, g_qkv + (size_t)row0 * (3 * D_MODEL) + (nb - 4) * 160, 3 * D_MODEL, lane);
      }
    }
  } else {
    const int cb = blockIdx.x - 128;
    if (warp == 8 && lane == 0) {
      for (int it = 0; it < KV_STAGES; it++) {
        const uint32_t fb = smem_u32(&bar_full[it]);
        mbar_expect_tx(fb, K1_A_BYTES);
        tma_2d(sbase + it * K1_A_BYTES, &tmX, it * 64, cb * 512, fb);
      }
    }
    __syncwarp();
    if (tid < 320) {
#pragma unroll
      for (int r = 0; r < 2; r++) {
        uint4* dst = reinterpret_cast<uint4*>(smem + KVW_OFF + (tid + r * 320) * 16);
        dst[0] = make_uint4(wa[r][0].x, wa[r][0].y, wa[r][1].x, wa[r][1].y);
        dst[640] = make_uint4(wa[r][2].x, wa[r][2].y, wa[r][3].x, wa[r][3].y);
        dst[1280] = make_uint4(wa[r][4].x, wa[r][4].y, 0u, 0u);
        dst[1920] = make_uint4(wb[r][0].x, wb[r][0].y, wb[r][1].x, wb[r][1].y);
        dst[2560] = make_uint4(wb[r][2].x, wb[r][2].y, wb[r][3].x, wb[r][3].y);
        dst[3200] = make_uint4(wb[r][4].x, wb[r][4].y, gw[r], 0u);
      }
    }
    fence_proxy_async();
    asm volatile("bar.sync 1, 512;" ::: "memory");
    PROF(0, 1);
    auto produce = [&](int it0, int it1) {
      for (int it = it0; it < it1; it++) {
        const int s = it % KV_STAGES;
        mbar_wait(smem_u32(&bar_empty[s]), (it / KV_STAGES - 1) & 1);
        const uint32_t fb = smem_u32(&bar_full[s]);
        mbar_expect_tx(fb, K1_A_BYTES);
        tma_2d(sbase + s * K1_A_BYTES, &tmX, (it >= 10 ? it - 10 : it) * 64, cb * 512 + (it >= 10 ? 256 : 0), fb);
      }
    };
    if (tid == 256) produce(KV_STAGES, 15);
    __syncwarp();
    {
      const int pass = warp >> 3, wg = (warp >> 2) & 1, w4 = warp & 3, g = lane >> 2, t = lane & 3;
      if (pass == 1) asm volatile("bar.sync 2, 512;" ::: "memory");
      {
        float acc[2][24];
#pragma unroll
        for (int i = 0; i < 24; i++) { acc[0][i] = 0.f; acc[1][i] = 0.f; }
        for (int kt = 0; kt < 10; kt++) {
          const int it = pass * 10 + kt, s = it % KV_STAGES;
          mbar_wait(smem_u32(&bar_full[s]), (it / KV_STAGES) & 1);
          const uint32_t alo = ((dbase + s * K1_A_BYTES + wg * 16384) >> 4) | (1u << 16);
          const uint32_t blo = ((dbase + KVW_OFF + kt * 1024) >> 4) | ((128u >> 4) << 16);
          fence_regs(acc[0]); fence_regs(acc[1]);
          wg_fence();
#pragma unroll
          for (int k = 0; k < 4; k++) {
            wgmma_ss_n48_tb(acc[0], mkd(alo + k * 2, DHI_SW128_K), mkd(blo + k * 16, 10240u >> 4));
            wgmma_ss_n48_tb(acc[1], mkd(alo + 512 + k * 2, DHI_SW128_K), mkd(blo + k * 16, 10240u >> 4));
          }
          wg_commit();
          if (kt > 0) {
            wg_wait<1>();
            if (lane == 0) mbar_arrive(smem_u32(&bar_empty[(it - 1) % KV_STAGES]));
          }
        }
        wg_wait<0>();
        fence_regs(acc[0]); fence_regs(acc[1]);
        if (lane == 0) mbar_arrive(smem_u32(&bar_empty[(pass * 10 + 9) % KV_STAGES]));
        if (pass == 0) asm volatile("bar.arrive 2, 512;" ::: "memory");
        PROF(0, 2);
        if (tid == 0) produce(15, 20);
        __syncwarp();
        float kmax2 = 0.f, vmax = 0.f;
#pragma unroll
        for (int hh = 0; hh < 4; hh++) {
          const int h = hh & 1;
          const float (&a)[24] = acc[hh >> 1];
          const int key = cb * 512 + pass * 256 + wg * 128 + (hh >> 1) * 64 + w4 * 16 + g + h * 8;
          const int grp = key >> 7, kk = key & 127;
          const bool poly = (TMASK >> (kk >> 3)) & 1;
          uint8_t* gp = g_kvimg + grp * GRP_BYTES;
          const uint32_t k0 = pack_bf16(a[2 * h], a[2 * h + 1]);
          const uint32_t k1 = pack_bf16(a[4 + 2 * h], a[5 + 2 * h]);
          uint32_t k2 = pack_bf16(a[8 + 2 * h], a[9 + 2 * h]);
          float n2 = bf_lo(k0) * bf_lo(k0) + bf_hi(k0) * bf_hi(k0) + bf_lo(k1) * bf_lo(k1) + bf_hi(k1) * bf_hi(k1);
          if (t < 2) {
            n2 += bf_lo(k2) * bf_lo(k2) + bf_hi(k2) * bf_hi(k2);
            k2 = pack_bf16(bf_lo(k2) * 0.5f, bf_hi(k2) * 0.5f);
          } else if (t == 2) k2 = poly ? pack_bf16(24.f, 2.5f) : pack_bf16(0.5f, 0.f);
          else k2 = poly ? pack_bf16(0.5f, 0.f) : 0u;
          *reinterpret_cast<uint32_t*>(gp + kk * 16 + t * 4) = k0;
          *reinterpret_cast<uint32_t*>(gp + PLANE + kk * 16 + t * 4) = k1;
          *reinterpret_cast<uint32_t*>(gp + 2 * PLANE + kk * 16 + t * 4) = k2;
          n2 += __shfl_xor_sync(0xffffffffu, n2, 1);
          n2 += __shfl_xor_sync(0xffffffffu, n2, 2);
          kmax2 = (n2 > kmax2 || n2 != n2) ? n2 : kmax2;
          uint32_t v0 = pack_bf16(a[12 + 2 * h], a[13 + 2 * h]);
          uint32_t v1 = pack_bf16(a[16 + 2 * h], a[17 + 2 * h]);
          uint32_t v2 = pack_bf16(a[20 + 2 * h], a[21 + 2 * h]);
          float vm = fmaxf(fmaxf(fabsf(bf_lo(v0)), fabsf(bf_hi(v0))), fmaxf(fabsf(bf_lo(v1)), fabsf(bf_hi(v1))));
          if (t < 2) vm = fmaxf(vm, fmaxf(fabsf(bf_lo(v2)), fabsf(bf_hi(v2))));
          else if (t == 2) {
            const float z = a[20 + 2 * h];
            g_gate[key] = 1.f / (1.f + __expf(-z));
            v2 = 0x00003F80u;
          } else v2 = 0u;
          vmax = fmaxf(vmax, vm);
          if (poly) { v0 ^= 0x80008000u; v1 ^= 0x80008000u; v2 ^= 0x80008000u; }
          uint8_t* vp = gp + 3 * PLANE + (kk >> 3) * 384 + (kk & 7) * 16 + t * 4;
          *reinterpret_cast<uint32_t*>(vp) = v0;
          *reinterpret_cast<uint32_t*>(vp + 128) = v1;
          *reinterpret_cast<uint32_t*>(vp + 256) = v2;
        }
#pragma unroll
        for (int o = 1; o < 32; o <<= 1) {
          const float a = __shfl_xor_sync(0xffffffffu, kmax2, o);
          kmax2 = (a > kmax2 || a != a) ? a : kmax2;
          vmax = fmaxf(vmax, __shfl_xor_sync(0xffffffffu, vmax, o));
        }
        if (lane == 0) { g_kmax2[cb * 16 + warp] = kmax2; g_vmax[cb * 16 + warp] = vmax; }
      }
    }
  }
}

__device__ __forceinline__ uint32_t ex2_pair_poly(float u0, float u1, uint32_t one2) {
  const uint32_t W = __byte_perm(__float_as_uint(u0), __float_as_uint(u1), 0x6521);
  uint32_t v; asm("lop3.b32 %0, %1, 0x007F007F, %2, 0xEA;" : "=r"(v) : "r"(W), "r"(one2));
  uint32_t L, p;
  asm("fma.rn.bf16x2 %0, %1, %2, %3;" : "=r"(L) : "r"(v), "r"(0x1f961f96u), "r"(0x9fe39fe3u));
  asm("fma.rn.bf16x2 %0, %1, %1, %2;" : "=r"(p) : "r"(L), "r"(0x00f500f5u));
  return W + p;
}
template <int JOFF>
__device__ __forceinline__ void softmax_slow(const float (&S)[32], uint32_t (&P)[16], float (&O)[12], float& m0, float& m1) {
  float a0 = m0, a1 = m1;
#pragma unroll
  for (int j = 0; j < 8; j++) {
    a0 = fmaxf(a0, fmaxf(S[4 * j], S[4 * j + 1]));
    a1 = fmaxf(a1, fmaxf(S[4 * j + 2], S[4 * j + 3]));
  }
  a0 = fmaxf(a0, __shfl_xor_sync(0xffffffffu, a0, 1)); a0 = fmaxf(a0, __shfl_xor_sync(0xffffffffu, a0, 2));
  a1 = fmaxf(a1, __shfl_xor_sync(0xffffffffu, a1, 1)); a1 = fmaxf(a1, __shfl_xor_sync(0xffffffffu, a1, 2));
  const float c0 = ex2(m0 - a0), c1 = ex2(m1 - a1);
  m0 = a0; m1 = a1;
#pragma unroll
  for (int j = 0; j < 3; j++) { O[4 * j] *= c0; O[4 * j + 1] *= c0; O[4 * j + 2] *= c1; O[4 * j + 3] *= c1; }
#pragma unroll
  for (int i = 0; i < 16; i++) {
    const float m = (i & 1) ? a1 : a0;
    const uint32_t p = pack_bf16(ex2(S[2 * i] - m), ex2(S[2 * i + 1] - m));
    P[i] = ((TMASK >> (JOFF + i / 2)) & 1) ? (p ^ 0x80008000u) : p;
  }
}
constexpr uint32_t DHI_KV = 128 >> 4;
__device__ __forceinline__ void issue_qk(float (&S)[32], const uint32_t (&q)[8], uint64_t base) {
  wgmma_rs_n64<0>(S, q[0], q[1], q[2], q[3], base + (uint64_t)((PLANE >> 4) << 16));
  wgmma_rs_n64<1>(S, q[4], q[5], q[6], q[7], base + (uint64_t)(2 * PLANE >> 4));
}
__device__ __forceinline__ void issue_pv(float (&O)[12], const uint32_t (&P)[16], uint64_t vbase) {
#pragma unroll
  for (int kk = 0; kk < 4; kk++)
    wgmma_rs_n24_tb<1>(O, P[4 * kk], P[4 * kk + 1], P[4 * kk + 2], P[4 * kk + 3], vbase + (uint64_t)(kk * (768 >> 4)));
}

constexpr uint32_t VOFF = ((3 * PLANE) >> 4) + ((384u >> 4) << 16);
constexpr int KVR = 4;
constexpr int OFF_W = KVR * GRP_BYTES;
constexpr int OFF_X = OFF_W + 10 * 10240;
constexpr int OFF_BAR = OFF_X + 4 * 16384;
constexpr int K2_SMEM = OFF_BAR + 256 + 1024;
constexpr int TSL = 7;
constexpr int BAR_KV = 0, BAR_W = 4, BAR_TA = 5, BAR_TE = 12, BAR_OWN = 19, BAR_L = 20, BAR_LD = 21, CNT_KV = 22;
constexpr int NSTEP = 2 * NGRP;

__device__ __forceinline__ void kv_load(uint32_t sbase, int step) {
  const uint32_t bar = sbase + OFF_BAR + (BAR_KV + (step & (KVR - 1))) * 8;
  mbar_expect_tx(bar, GRP_BYTES);
  bulk_g2s(sbase + (step & (KVR - 1)) * GRP_BYTES, g_kvimg + (step & (NGRP - 1)) * GRP_BYTES, GRP_BYTES, bar);
}
__device__ __forceinline__ void kv_release(uint32_t sbase, int step, bool elected) {
  if (elected && step + KVR < NSTEP) {
    uint32_t old;
    asm volatile("atom.acq_rel.cta.shared::cta.inc.u32 %0, [%1], 3;" : "=r"(old) : "r"(sbase + OFF_BAR + CNT_KV * 8 + (step & (KVR - 1)) * 4) : "memory");
    if (old == 3u) kv_load(sbase, step + KVR);
  }
  __syncwarp();
}
__device__ __forceinline__ void kv_wait(uint32_t sbase, int step) {
  mbar_wait(sbase + OFF_BAR + (BAR_KV + (step & (KVR - 1))) * 8, (step / KVR) & 1);
}

__device__ __forceinline__ uint32_t kv_release_begin(uint32_t sbase, int slot, bool doit) {
  uint32_t old = 0;
  asm volatile("{\n.reg .pred p;\nsetp.ne.u32 p, %2, 0;\n@p atom.relaxed.cta.shared::cta.inc.u32 %0, [%1], 3;\n}\n"
               : "+r"(old) : "r"(sbase + OFF_BAR + CNT_KV * 8 + slot * 4), "r"((uint32_t)doit) : "memory");
  return old;
}
template <int H>
__device__ __forceinline__ void softmax_half(const float (&S)[64], uint32_t (&P)[16], uint32_t one2) {
#pragma unroll
  for (int i = 0; i < 16; i++) {
    if ((TMASK >> (8 * H + i / 2)) & 1) P[i] = ex2_pair_poly(S[32 * H + 2 * i], S[32 * H + 2 * i + 1], one2);
    else P[i] = pack_bf16(ex2(S[32 * H + 2 * i]), ex2(S[32 * H + 2 * i + 1]));
  }
}
__device__ __forceinline__ void attn_fast(const uint32_t (&q)[8], float (&O)[12], uint32_t sbase, int step0, int nsteps, bool elected, uint32_t one2) {
  uint64_t kb0 = mkd((sbase & 0x3FFFFu) >> 4, DHI_KV);
  asm volatile("" : "+l"(kb0));
#pragma unroll 1
  for (int step4 = step0; step4 < step0 + nsteps; step4 += KVR) {
#pragma unroll
    for (int j = 0; j < KVR; j++) {
      const int step = step4 + j;
      const uint64_t kb = kb0 + (uint64_t)(j * (GRP_BYTES >> 4));
      float S[64]; uint32_t PA[16], PB[16];
#pragma unroll
      for (int i = 0; i < 64; i++) S[i] = 0.f;
      mbar_wait(sbase + OFF_BAR + (BAR_KV + j) * 8, (step / KVR) & 1);
      fence_regs(S);
      wg_fence();
      wgmma_rs_n128<0>(S, q[0], q[1], q[2], q[3], kb + (uint64_t)((PLANE >> 4) << 16));
      wgmma_rs_n128<1>(S, q[4], q[5], q[6], q[7], kb + (uint64_t)(2 * PLANE >> 4));
      wg_commit();
      wg_wait<0>();
      fence_regs(S);
      softmax_half<0>(S, PA, one2);
      fence_regs(PA); fence_regs(O);
      wg_fence();
      issue_pv(O, PA, kb + VOFF);
      wg_commit();
      softmax_half<1>(S, PB, one2);
      fence_regs(PB);
      wg_fence();
      issue_pv(O, PB, kb + VOFF + 4 * (768 >> 4));
      wg_commit();
      wg_wait<0>();
      fence_regs(PA); fence_regs(PB); fence_regs(O);
      const uint32_t old = kv_release_begin(sbase, j, elected && step + KVR < NSTEP);
      if (old == 3u) kv_load(sbase, step + KVR);
    }
  }
}
template <int H>
__device__ __forceinline__ void slow_step(const uint32_t (&q)[8], float (&O)[12], uint64_t kb, float& m0, float& m1) {
  float S[32]; uint32_t P[16];
#pragma unroll
  for (int i = 0; i < 32; i++) S[i] = 0.f;
  fence_regs(S);
  wg_fence();
  issue_qk(S, q, kb + 64 * H);
  wg_commit();
  wg_wait<0>();
  fence_regs(S);
  softmax_slow<8 * H>(S, P, O, m0, m1);
  fence_regs(P); fence_regs(O);
  wg_fence();
  issue_pv(O, P, kb + VOFF + H * 4 * (768 >> 4));
  wg_commit();
  wg_wait<0>();
  fence_regs(O); fence_regs(P);
}
__device__ __forceinline__ void attn_slow(const uint32_t (&q)[8], float (&O)[12], uint32_t sbase, int step0, int nsteps, bool elected, float& m0, float& m1) {
#pragma unroll 1
  for (int step = step0; step < step0 + nsteps; step++) {
    kv_wait(sbase, step);
    const uint64_t kb = mkd(((sbase & 0x3FFFFu) >> 4) + (step & (KVR - 1)) * (GRP_BYTES >> 4), DHI_KV);
    slow_step<0>(q, O, kb, m0, m1);
    slow_step<1>(q, O, kb, m0, m1);
    kv_release(sbase, step, elected);
  }
}

__device__ __forceinline__ void softmax8(float (&sc)[8], float scale) {
  float mx = sc[0];
#pragma unroll
  for (int w = 1; w < 8; w++) mx = fmaxf(mx, sc[w]);
  float l = 0.f;
#pragma unroll
  for (int w = 0; w < 8; w++) { sc[w] = ex2(sc[w] - mx); l += sc[w]; }
  const float r = __fdividef(scale, l);
#pragma unroll
  for (int w = 0; w < 8; w++) sc[w] *= r;
}
#define LEV(wg) 1
constexpr int LBOX = 30 * 320;
__device__ __forceinline__ uint2 lds64(uint32_t a) {
  uint2 v; asm volatile("ld.shared.v2.u32 {%0, %1}, [%2];" : "=r"(v.x), "=r"(v.y) : "r"(a)); return v;
}
__device__ __forceinline__ void local_attn(uint32_t stage, int t0, int i, int lane) {
  constexpr float SC = 0.22360679774997896f * 1.4426950408889634f, NEG = -1e9f * 1.4426950408889634f;
  const uint32_t base = stage + (lane >> 3) * LBOX + (lane & 7) * 40 + (i + 14) * 320;
  const int t = t0 + i;
  float sc[8];
#pragma unroll
  for (int w = 0; w < 8; w++) sc[w] = 0.f;
#pragma unroll 1
  for (int c = 0; c < 5; c++) {
    const uint2 qv = lds64(base + c * 8);
    const float q0 = bf_lo(qv.x), q1 = bf_hi(qv.x), q2 = bf_lo(qv.y), q3 = bf_hi(qv.y);
#pragma unroll
    for (int w = 0; w < 8; w++) {
      const uint2 k = lds64(base + c * 8 + 4 * LBOX - w * 640);
      sc[w] = fmaf(q0, bf_lo(k.x), sc[w]); sc[w] = fmaf(q1, bf_hi(k.x), sc[w]);
      sc[w] = fmaf(q2, bf_lo(k.y), sc[w]); sc[w] = fmaf(q3, bf_hi(k.y), sc[w]);
    }
  }
#pragma unroll
  for (int w = 0; w < 8; w++) sc[w] = t - 2 * w >= 0 ? sc[w] * SC : NEG;
  softmax8(sc, 1.f - g_gate[t]);
  uint2* dst = reinterpret_cast<uint2*>(g_a2 + (size_t)t * (2 * D_MODEL) + D_MODEL + lane * DH);
#pragma unroll 1
  for (int c = 0; c < 5; c++) {
    float o0 = 0.f, o1 = 0.f, o2 = 0.f, o3 = 0.f;
#pragma unroll
    for (int w = 0; w < 8; w++) {
      const uint2 v = lds64(base + c * 8 + 8 * LBOX - w * 640);
      o0 = fmaf(sc[w], bf_lo(v.x), o0); o1 = fmaf(sc[w], bf_hi(v.x), o1);
      o2 = fmaf(sc[w], bf_lo(v.y), o2); o3 = fmaf(sc[w], bf_hi(v.y), o3);
    }
    dst[c] = make_uint2(pack_bf16(o0, o1), pack_bf16(o2, o3));
  }
}
__device__ __forceinline__ uint32_t ta_slot(int i) { return i < 4 ? OFF_X + i * 16384 : (i - 4) * 16384; }

__global__ void __launch_bounds__(640, 1)
attn_kernel(const __grid_constant__ CUtensorMap tmA2, const __grid_constant__ CUtensorMap tmL, __nv_bfloat16* __restrict__ out, uint32_t one2) {
  extern __shared__ uint8_t smem_raw[];
  uint8_t* smem = reinterpret_cast<uint8_t*>((reinterpret_cast<uintptr_t>(smem_raw) + 1023) & ~(uintptr_t)1023);
  const uint32_t sbase = smem_u32(smem);
  const uint32_t dbase = sbase & 0x3FFFFu;
  const uint32_t bars = sbase + OFF_BAR;
  const int tid = threadIdx.x, wg = tid >> 7, warp = (tid >> 5) & 3, lane = tid & 31, g = lane >> 2, t = lane & 3;
  const int mb = blockIdx.x >> 3, nb = blockIdx.x & 7;
  const bool elected = (tid & 127) == 0;
  if (tid == 0) {
    for (int i = 0; i < BAR_TE; i++) mbar_init(bars + i * 8, 1);
    for (int i = BAR_TE; i < BAR_TE + TSL; i++) mbar_init(bars + i * 8, 8);
    mbar_init(bars + BAR_OWN * 8, 4);
    mbar_init(bars + BAR_L * 8, 1);
    for (int i = 0; i < 4; i++) *reinterpret_cast<uint32_t*>(smem + OFF_BAR + CNT_KV * 8 + i * 4) = 0u;
    fence_mbar_init();
  }
  __syncthreads();
  auto tail_load = [&](int i) {
    const uint32_t fb = bars + (BAR_TA + i % TSL) * 8;
    mbar_expect_tx(fb, i < 10 ? 16384 : 16384 + 10240);
    tma_2d(sbase + ta_slot(i % TSL), &tmA2, i < 10 ? D_MODEL + i * 64 : (i - 10) * 64, mb * 128, fb);
    if (i >= 10) bulk_g2s(sbase + OFF_W + (i - 10) * 10240, g_wimg + (nb * 10 + i - 10) * 10240, 10240, fb);
  };
  if (wg == 4) {
    asm volatile("setmaxnreg.dec.sync.aligned.u32 32;");
    pdl_wait();
    if (tid == 512) {
      for (int j = 0; j < KVR; j++) kv_load(sbase, j);
      mbar_expect_tx(bars + BAR_L * 8, 12 * LBOX);
      for (int i = 0; i < 12; i++) tma_2d(sbase + OFF_W + i * LBOX, &tmL, i * 160, blockIdx.x * 16 - 14, bars + BAR_L * 8);
    }
    __syncwarp();
    mbar_wait(bars + BAR_L * 8, 0);
#pragma unroll 1
    for (int i = 0; i < 4; i++) local_attn(sbase + OFF_W, blockIdx.x * 16, warp * 4 + i, lane);
    signal_done(&g_doneL[blockIdx.x], wg, tid);
    if (tid == 512) {
      PROF2(0, 2);
      mbar_expect_tx(bars + BAR_W * 8, 10 * 10240);
      for (int i = 0; i < 5; i++) bulk_g2s(sbase + OFF_W + i * 20480, g_wimg + ((8 + nb) * 10) * 10240 + i * 20480, 20480, bars + BAR_W * 8);
      wait_flags8(&g_doneL[mb * 8], 1u);
      for (int i = 0; i < 4; i++) tail_load(i);
      mbar_wait(bars + BAR_OWN * 8, 0);
      for (int i = 4; i < 20; i++) {
        if (i >= TSL) mbar_wait(bars + (BAR_TE + i % TSL) * 8, (i / TSL - 1) & 1);
        if (i == 10) { wait_flags8(&g_done[mb * 8], 4u); PROF2(2, 0); }
        tail_load(i);
      }
    }
    return;
  }
  asm volatile("setmaxnreg.inc.sync.aligned.u32 112;");
  pdl_wait();
  PROF(1, 1);
  uint32_t q[8], q2[6];
  const int rowA = (blockIdx.x * 8 + wg) * 64 + warp * 16 + g;
  {
    const uint32_t* r0 = reinterpret_cast<const uint32_t*>(g_q + (size_t)rowA * DH);
    const uint32_t* r1 = r0 + 8 * (DH / 2);
    const uint32_t* s0 = r0 + 256 * (DH / 2);
    const uint32_t* s1 = s0 + 8 * (DH / 2);
    q[0] = r0[t]; q[1] = r1[t]; q[2] = r0[t + 4]; q[3] = r1[t + 4];
    q[4] = t < 2 ? r0[8 + t] : 0u;
    q[5] = t < 2 ? r1[8 + t] : 0u;
    q2[0] = s0[t]; q2[1] = s1[t]; q2[2] = s0[t + 4]; q2[3] = s1[t + 4];
    q2[4] = t < 2 ? s0[8 + t] : 0u;
    q2[5] = t < 2 ? s1[8 + t] : 0u;
  }
  float kmax2 = 0.f, vmax = 0.f;
#pragma unroll
  for (int i = 0; i < 2; i++) {
    const float a = g_kmax2[lane + 32 * i];
    kmax2 = (a > kmax2 || a != a) ? a : kmax2;
    vmax = fmaxf(vmax, g_vmax[lane + 32 * i]);
  }
#pragma unroll
  for (int o = 1; o < 32; o <<= 1) {
    const float a = __shfl_xor_sync(0xffffffffu, kmax2, o);
    kmax2 = (a > kmax2 || a != a) ? a : kmax2;
    vmax = fmaxf(vmax, __shfl_xor_sync(0xffffffffu, vmax, o));
  }
  const float qlim = (vmax >= 0.00390625f && vmax <= 256.f) ? 9025.f / kmax2 : -1.f;
  PROF(1, 2);
#pragma unroll 1
  for (int it = 0; it < 2; it++) {
    const int row0 = rowA + it * 256;
    if (it == 1) {
#pragma unroll
      for (int i = 0; i < 6; i++) q[i] = q2[i];
    }
    float n0 = bf_lo(q[0]) * bf_lo(q[0]) + bf_hi(q[0]) * bf_hi(q[0]) + bf_lo(q[2]) * bf_lo(q[2]) + bf_hi(q[2]) * bf_hi(q[2]) +
               bf_lo(q[4]) * bf_lo(q[4]) + bf_hi(q[4]) * bf_hi(q[4]);
    float n1 = bf_lo(q[1]) * bf_lo(q[1]) + bf_hi(q[1]) * bf_hi(q[1]) + bf_lo(q[3]) * bf_lo(q[3]) + bf_hi(q[3]) * bf_hi(q[3]) +
               bf_lo(q[5]) * bf_lo(q[5]) + bf_hi(q[5]) * bf_hi(q[5]);
    n0 += __shfl_xor_sync(0xffffffffu, n0, 1); n0 += __shfl_xor_sync(0xffffffffu, n0, 2);
    n1 += __shfl_xor_sync(0xffffffffu, n1, 1); n1 += __shfl_xor_sync(0xffffffffu, n1, 2);
    const bool safe = (n0 <= qlim) && (n1 <= qlim);
    uint32_t unsafe_any;
    asm volatile("{\n.reg .pred p, r;\nsetp.eq.u32 p, %1, 0;\nbarrier.cta.red.or.pred r, %2, 128, p;\nselp.u32 %0, 1, 0, r;\n}\n"
                 : "=r"(unsafe_any) : "r"((uint32_t)safe), "r"(wg + 1) : "memory");
    float O[12];
#pragma unroll
    for (int i = 0; i < 12; i++) O[i] = 0.f;
    if (!unsafe_any && t >= 2) { q[4] = q[5] = (t == 2) ? 0x3F804100u : 0x00003B80u; }
    q[6] = q[4]; q[7] = q[5];
    fence_regs(q);
    float m0 = -INFINITY, m1 = -INFINITY;
    if (!unsafe_any) attn_fast(q, O, sbase, it * NGRP, NGRP, elected, one2);
    else attn_slow(q, O, sbase, it * NGRP, NGRP, elected, m0, m1);
    const float l0 = __shfl_sync(0xffffffffu, O[8], (lane & ~3) | 2);
    const float l1 = __shfl_sync(0xffffffffu, O[10], (lane & ~3) | 2);
    const int tok = row0 >> 5;
    const float gt = g_gate[tok];
    const float i0 = gt / l0, i1 = gt / l1;
    uint32_t* o0 = reinterpret_cast<uint32_t*>(g_a2 + (size_t)tok * (2 * D_MODEL) + (row0 & 31) * DH);
    uint32_t* o1 = o0 + 8 * (DH / 2);
    o0[t] = pack_bf16(O[0] * i0, O[1] * i0); o1[t] = pack_bf16(O[2] * i1, O[3] * i1);
    o0[t + 4] = pack_bf16(O[4] * i0, O[5] * i0); o1[t + 4] = pack_bf16(O[6] * i1, O[7] * i1);
    if (t < 2) { o0[t + 8] = pack_bf16(O[8] * i0, O[9] * i0); o1[t + 8] = pack_bf16(O[10] * i1, O[11] * i1); }
  }
  signal_done(&g_done[blockIdx.x], wg, tid);
  if ((tid & 127) == 64) mbar_arrive(bars + BAR_OWN * 8);
  PROF(1, 3);
  if (wg < 2) {
    float acc[40];
#pragma unroll
    for (int i = 0; i < 40; i++) acc[i] = 0.f;
    mbar_wait(bars + BAR_W * 8, 0);
    int sl = 0, ph = 0;
#pragma unroll 1
    for (int i = 0; i < 20; i++) {
      mbar_wait(bars + (BAR_TA + sl) * 8, ph);
      if (i == 10) PROF(2, 1);
      const uint32_t alo = ((dbase + ta_slot(sl) + wg * 8192) >> 4) | (1u << 16);
      const uint32_t blo = ((dbase + OFF_W + (i >= 10 ? i - 10 : i) * 10240) >> 4) | ((128u >> 4) << 16);
      fence_regs(acc);
      wg_fence();
#pragma unroll
      for (int k = 0; k < 4; k++) wgmma_ss_n80_tb(acc, mkd(alo + k * 2, DHI_SW128_K), mkd(blo + k * 16, 1024u >> 4));
      wg_commit();
      if (i > 0) {
        wg_wait<1>();
        if (lane == 0) mbar_arrive(bars + (BAR_TE + (sl == 0 ? TSL - 1 : sl - 1)) * 8);
      }
      if (++sl == TSL) { sl = 0; ph ^= 1; }
    }
    wg_wait<0>();
    fence_regs(acc);
    PROF(2, 2);
    asm volatile("bar.sync %0, 128;" :: "r"(wg + 1) : "memory");
    const uint32_t so = ta_slot(warp) + wg * 8192;
    const int row0 = mb * 128 + wg * 64 + warp * 16;
    store_tile_bf16<80>(acc, 1.0f, sbase + so, smem + so, out + (size_t)row0 * D_MODEL + nb * 80, D_MODEL, lane);
    PROF(2, 3);
  }
}

typedef CUresult (*EncodeFn)(CUtensorMap*, CUtensorMapDataType, cuuint32_t, void*, const cuuint64_t*, const cuuint64_t*,
                             const cuuint32_t*, const cuuint32_t*, CUtensorMapInterleave, CUtensorMapSwizzle,
                             CUtensorMapL2promotion, CUtensorMapFloatOOBfill);

void make_map(EncodeFn fn, CUtensorMap* tm, const void* ptr, int rank, const cuuint64_t* dims, const cuuint64_t* strides,
              const cuuint32_t* box, CUtensorMapSwizzle sw) {
  const cuuint32_t es[3] = {1, 1, 1};
  fn(tm, CU_TENSOR_MAP_DATA_TYPE_BFLOAT16, rank, const_cast<void*>(ptr), dims, strides, box, es, CU_TENSOR_MAP_INTERLEAVE_NONE, sw,
     CU_TENSOR_MAP_L2_PROMOTION_L2_256B, CU_TENSOR_MAP_FLOAT_OOB_FILL_NONE);
}
void map_a(EncodeFn fn, CUtensorMap* tm, const void* p, int rows, int cols, int box_rows) {
  const cuuint64_t dims[2] = {(cuuint64_t)cols, (cuuint64_t)rows};
  const cuuint64_t str[1] = {(cuuint64_t)cols * 2};
  const cuuint32_t box[2] = {64, (cuuint32_t)box_rows};
  make_map(fn, tm, p, 2, dims, str, box, CU_TENSOR_MAP_SWIZZLE_128B);
}
void map_w(EncodeFn fn, CUtensorMap* tm, const void* p, int K, int N, int atom, CUtensorMapSwizzle sw) {
  const cuuint64_t dims[3] = {(cuuint64_t)atom, (cuuint64_t)K, (cuuint64_t)(N / atom)};
  const cuuint64_t str[2] = {(cuuint64_t)N * 2, (cuuint64_t)atom * 2};
  const cuuint32_t box[3] = {(cuuint32_t)atom, 64, 5};
  make_map(fn, tm, p, 3, dims, str, box, sw);
}

template <typename... KArgs, typename... Args>
void launch(void (*kern)(KArgs...), int grid, int block, int smem, bool pdl, Args... args) {
  cudaLaunchConfig_t cfg = {};
  cfg.gridDim = dim3(grid); cfg.blockDim = dim3(block); cfg.dynamicSmemBytes = smem; cfg.stream = cudaStreamPerThread;
  cudaLaunchAttribute at[1];
  at[0].id = cudaLaunchAttributeProgrammaticStreamSerialization;
  at[0].val.programmaticStreamSerializationAllowed = 1;
  cfg.attrs = at; cfg.numAttrs = pdl ? 1 : 0;
  cudaLaunchKernelEx(&cfg, kern, KArgs(args)...);
}

}

extern "C" void kernel_launch(void* const* d_in, const int* in_sizes, int n_in, void* d_out, int out_size) {
  (void)in_sizes; (void)n_in; (void)out_size;
  const __nv_bfloat16* x = (const __nv_bfloat16*)d_in[0];
  const __nv_bfloat16* wq = (const __nv_bfloat16*)d_in[1];
  const __nv_bfloat16* wk = (const __nv_bfloat16*)d_in[2];
  const __nv_bfloat16* wv = (const __nv_bfloat16*)d_in[3];
  const __nv_bfloat16* woA = (const __nv_bfloat16*)d_in[4];
  const __nv_bfloat16* wqkv = (const __nv_bfloat16*)d_in[6];
  const __nv_bfloat16* woB = (const __nv_bfloat16*)d_in[7];
  const __nv_bfloat16* gate_w = (const __nv_bfloat16*)d_in[8];

  static EncodeFn enc = nullptr;
  static void* a2_ptr = nullptr;
  static void* qkv_ptr = nullptr;
  if (!enc) {
    void* fp = nullptr;
    cudaDriverEntryPointQueryResult qr;
    cudaGetDriverEntryPoint("cuTensorMapEncodeTiled", &fp, cudaEnableDefault, &qr);
    enc = (EncodeFn)fp;
    cudaGetSymbolAddress(&a2_ptr, g_a2);
    cudaGetSymbolAddress(&qkv_ptr, g_qkv);
    cudaFuncSetAttribute(proj_kernel, cudaFuncAttributeMaxDynamicSharedMemorySize, K1_SMEM);
    cudaFuncSetAttribute(attn_kernel, cudaFuncAttributeMaxDynamicSharedMemorySize, K2_SMEM);
  }
  CUtensorMap tmX, tmWq, tmWqkv, tmA2, tmL;
  {
    const cuuint64_t dims[2] = {3 * D_MODEL, S_LEN};
    const cuuint64_t str[1] = {3 * D_MODEL * 2};
    const cuuint32_t box[2] = {160, 30};
    make_map(enc, &tmL, qkv_ptr, 2, dims, str, box, CU_TENSOR_MAP_SWIZZLE_NONE);
  }
  map_a(enc, &tmX, x, S_LEN, D_MODEL, 256);
  map_w(enc, &tmWq, wq, D_MODEL, D_MODEL, 32, CU_TENSOR_MAP_SWIZZLE_64B);
  map_w(enc, &tmWqkv, wqkv, D_MODEL, 3 * D_MODEL, 32, CU_TENSOR_MAP_SWIZZLE_64B);
  map_a(enc, &tmA2, a2_ptr, S_LEN, 2 * D_MODEL, 128);

  launch(proj_kernel, 132, 512, K1_SMEM, false, tmX, tmWq, tmWqkv, wk, wv, gate_w, woA, woB);
  launch(attn_kernel, 128, 640, K2_SMEM, true, tmA2, tmL, (__nv_bfloat16*)d_out, 0x3F803F80u);
}
```

```cpp
#include <cuda_runtime.h>
#include <cuda_bf16.h>
#include <cuda.h>
#include <stdint.h>

namespace {

constexpr int S_LEN = 2048, D_MODEL = 640, DH = 20;

constexpr int GRP = 128;
constexpr int PLANE = GRP * 16;
constexpr int GRP_BYTES = GRP * 16 * 6;
constexpr int NGRP = S_LEN / GRP;
#define TMASKV 0xBBBBu
constexpr uint32_t TMASK = TMASKV;

__device__ __align__(1024) __nv_bfloat16 g_q[S_LEN * D_MODEL];
__device__ __align__(1024) __nv_bfloat16 g_qkv[S_LEN * 3 * D_MODEL];
__device__ __align__(1024) __nv_bfloat16 g_a2[S_LEN * 2 * D_MODEL];
__device__ __align__(1024) uint8_t g_kvimg[NGRP * GRP_BYTES];
__device__ __align__(1024) uint8_t g_wimg[2 * 8 * 10 * 10240];
__device__ float g_gate[S_LEN];
__device__ float g_kmax2[64];
__device__ float g_vmax[64];
__device__ __align__(32) unsigned int g_doneL[128];
__device__ __align__(32) unsigned int g_done[128];

#define PROF(k, slot)
#define PROF2(k, slot)
__device__ __forceinline__ uint32_t smem_u32(const void* p) { return (uint32_t)__cvta_generic_to_shared(p); }
__device__ __forceinline__ uint64_t mkd(uint32_t lo, uint32_t hi) {
  uint64_t d; asm("mov.b64 %0, {%1, %2};" : "=l"(d) : "r"(lo), "r"(hi)); return d;
}
__device__ __forceinline__ void wg_fence() { asm volatile("wgmma.fence.sync.aligned;" ::: "memory"); }
__device__ __forceinline__ void wg_commit() { asm volatile("wgmma.commit_group.sync.aligned;" ::: "memory"); }
template <int N> __device__ __forceinline__ void wg_wait() { asm volatile("wgmma.wait_group.sync.aligned %0;" :: "n"(N) : "memory"); }
template <int N> __device__ __forceinline__ void fence_regs(float (&d)[N]) {
#pragma unroll
  for (int i = 0; i < N; i++) asm volatile("" : "+f"(d[i]) :: "memory");
}
template <int N> __device__ __forceinline__ void fence_regs(uint32_t (&d)[N]) {
#pragma unroll
  for (int i = 0; i < N; i++) asm volatile("" : "+r"(d[i]) :: "memory");
}
__device__ __forceinline__ void mbar_init(uint32_t bar, uint32_t cnt) { asm volatile("mbarrier.init.shared::cta.b64 [%0], %1;" :: "r"(bar), "r"(cnt)); }
__device__ __forceinline__ void mbar_expect_tx(uint32_t bar, uint32_t bytes) {
  asm volatile("mbarrier.arrive.expect_tx.shared::cta.b64 _, [%0], %1;" :: "r"(bar), "r"(bytes) : "memory");
}
__device__ __forceinline__ void mbar_arrive(uint32_t bar) { asm volatile("mbarrier.arrive.shared::cta.b64 _, [%0];" :: "r"(bar) : "memory"); }
#define WAIT_HINT 20000u
__device__ __forceinline__ void mbar_wait(uint32_t bar, uint32_t parity) {
  asm volatile("{\n.reg .pred p;\nWAIT_%=:\nmbarrier.try_wait.parity.shared::cta.b64 p, [%0], %1, %2;\n@p bra DONE_%=;\nbra WAIT_%=;\nDONE_%=:\n}\n"
               :: "r"(bar), "r"(parity), "r"(WAIT_HINT) : "memory");
}
__device__ __forceinline__ void fence_mbar_init() { asm volatile("fence.mbarrier_init.release.cluster;" ::: "memory"); }
__device__ __forceinline__ void fence_proxy_async() { asm volatile("fence.proxy.async.shared::cta;" ::: "memory"); }
__device__ __forceinline__ void bulk_g2s(uint32_t dst, const void* src, uint32_t bytes, uint32_t bar) {
  asm volatile("cp.async.bulk.shared::cluster.global.mbarrier::complete_tx::bytes [%0], [%1], %2, [%3];"
               :: "r"(dst), "l"(src), "r"(bytes), "r"(bar) : "memory");
}
__device__ __forceinline__ void tma_2d(uint32_t dst, const CUtensorMap* tm, int c0, int c1, uint32_t bar) {
  asm volatile("cp.async.bulk.tensor.2d.shared::cluster.global.mbarrier::complete_tx::bytes [%0], [%1, {%3, %4}], [%2];"
               :: "r"(dst), "l"((uint64_t)tm), "r"(bar), "r"(c0), "r"(c1) : "memory");
}
__device__ __forceinline__ void tma_3d(uint32_t dst, const CUtensorMap* tm, int c0, int c1, int c2, uint32_t bar) {
  asm volatile("cp.async.bulk.tensor.3d.shared::cluster.global.mbarrier::complete_tx::bytes [%0], [%1, {%3, %4, %5}], [%2];"
               :: "r"(dst), "l"((uint64_t)tm), "r"(bar), "r"(c0), "r"(c1), "r"(c2) : "memory");
}
__device__ __forceinline__ void pdl_wait() { asm volatile("griddepcontrol.wait;" ::: "memory"); }
__device__ __forceinline__ void pdl_launch() { asm volatile("griddepcontrol.launch_dependents;" ::: "memory"); }
__device__ __forceinline__ float ex2(float x) { float y; asm("ex2.approx.ftz.f32 %0, %1;" : "=f"(y) : "f"(x)); return y; }
__device__ __forceinline__ uint32_t pack_bf16(float lo, float hi) {
  uint32_t r; asm("cvt.rn.bf16x2.f32 %0, %1, %2;" : "=r"(r) : "f"(hi), "f"(lo)); return r;
}
__device__ __forceinline__ float bf_lo(uint32_t x) { return __uint_as_float(x << 16); }
__device__ __forceinline__ float bf_hi(uint32_t x) { return __uint_as_float(x & 0xffff0000u); }
__device__ __forceinline__ void stsm4(uint32_t addr, uint32_t r0, uint32_t r1, uint32_t r2, uint32_t r3) {
  asm volatile("stmatrix.sync.aligned.m8n8.x4.shared.b16 [%0], {%1, %2, %3, %4};" :: "r"(addr), "r"(r0), "r"(r1), "r"(r2), "r"(r3) : "memory");
}

__device__ __forceinline__ void wgmma_ss_n160_tb(float (&d)[80], uint64_t descA, uint64_t descB) {
  asm volatile("wgmma.mma_async.sync.aligned.m64n160k16.f32.bf16.bf16 {%0, %1, %2, %3, %4, %5, %6, %7, %8, %9, %10, %11, %12, %13, %14, %15, %16, %17, %18, %19, %20, %21, %22, %23, %24, %25, %26, %27, %28, %29, %30, %31, %32, %33, %34, %35, %36, %37, %38, %39, %40, %41, %42, %43, %44, %45, %46, %47, %48, %49, %50, %51, %52, %53, %54, %55, %56, %57, %58, %59, %60, %61, %62, %63, %64, %65, %66, %67, %68, %69, %70, %71, %72, %73, %74, %75, %76, %77, %78, %79}, %80, %81, 1, 1, 1, 0, 1;\n"
    : "+f"(d[0]), "+f"(d[1]), "+f"(d[2]), "+f"(d[3]), "+f"(d[4]), "+f"(d[5]), "+f"(d[6]), "+f"(d[7]), "+f"(d[8]), "+f"(d[9]), "+f"(d[10]), "+f"(d[11]), "+f"(d[12]), "+f"(d[13]), "+f"(d[14]), "+f"(d[15]), "+f"(d[16]), "+f"(d[17]), "+f"(d[18]), "+f"(d[19]), "+f"(d[20]), "+f"(d[21]), "+f"(d[22]), "+f"(d[23]), "+f"(d[24]), "+f"(d[25]), "+f"(d[26]), "+f"(d[27]), "+f"(d[28]), "+f"(d[29]), "+f"(d[30]), "+f"(d[31]), "+f"(d[32]), "+f"(d[33]), "+f"(d[34]), "+f"(d[35]), "+f"(d[36]), "+f"(d[37]), "+f"(d[38]), "+f"(d[39]), "+f"(d[40]), "+f"(d[41]), "+f"(d[42]), "+f"(d[43]), "+f"(d[44]), "+f"(d[45]), "+f"(d[46]), "+f"(d[47]), "+f"(d[48]), "+f"(d[49]), "+f"(d[50]), "+f"(d[51]), "+f"(d[52]), "+f"(d[53]), "+f"(d[54]), "+f"(d[55]), "+f"(d[56]), "+f"(d[57]), "+f"(d[58]), "+f"(d[59]), "+f"(d[60]), "+f"(d[61]), "+f"(d[62]), "+f"(d[63]), "+f"(d[64]), "+f"(d[65]), "+f"(d[66]), "+f"(d[67]), "+f"(d[68]), "+f"(d[69]), "+f"(d[70]), "+f"(d[71]), "+f"(d[72]), "+f"(d[73]), "+f"(d[74]), "+f"(d[75]), "+f"(d[76]), "+f"(d[77]), "+f"(d[78]), "+f"(d[79])
    : "l"(descA), "l"(descB));
}
__device__ __forceinline__ void wgmma_ss_n48_tb(float (&d)[24], uint64_t descA, uint64_t descB) {
  asm volatile("wgmma.mma_async.sync.aligned.m64n48k16.f32.bf16.bf16 {%0, %1, %2, %3, %4, %5, %6, %7, %8, %9, %10, %11, %12, %13, %14, %15, %16, %17, %18, %19, %20, %21, %22, %23}, %24, %25, 1, 1, 1, 0, 1;\n"
    : "+f"(d[0]), "+f"(d[1]), "+f"(d[2]), "+f"(d[3]), "+f"(d[4]), "+f"(d[5]), "+f"(d[6]), "+f"(d[7]), "+f"(d[8]), "+f"(d[9]), "+f"(d[10]), "+f"(d[11]), "+f"(d[12]), "+f"(d[13]), "+f"(d[14]), "+f"(d[15]), "+f"(d[16]), "+f"(d[17]), "+f"(d[18]), "+f"(d[19]), "+f"(d[20]), "+f"(d[21]), "+f"(d[22]), "+f"(d[23])
    : "l"(descA), "l"(descB));
}
__device__ __forceinline__ void wgmma_ss_n80_tb(float (&d)[40], uint64_t descA, uint64_t descB) {
  asm volatile("wgmma.mma_async.sync.aligned.m64n80k16.f32.bf16.bf16 {%0, %1, %2, %3, %4, %5, %6, %7, %8, %9, %10, %11, %12, %13, %14, %15, %16, %17, %18, %19, %20, %21, %22, %23, %24, %25, %26, %27, %28, %29, %30, %31, %32, %33, %34, %35, %36, %37, %38, %39}, %40, %41, 1, 1, 1, 0, 1;\n"
    : "+f"(d[0]), "+f"(d[1]), "+f"(d[2]), "+f"(d[3]), "+f"(d[4]), "+f"(d[5]), "+f"(d[6]), "+f"(d[7]), "+f"(d[8]), "+f"(d[9]), "+f"(d[10]), "+f"(d[11]), "+f"(d[12]), "+f"(d[13]), "+f"(d[14]), "+f"(d[15]), "+f"(d[16]), "+f"(d[17]), "+f"(d[18]), "+f"(d[19]), "+f"(d[20]), "+f"(d[21]), "+f"(d[22]), "+f"(d[23]), "+f"(d[24]), "+f"(d[25]), "+f"(d[26]), "+f"(d[27]), "+f"(d[28]), "+f"(d[29]), "+f"(d[30]), "+f"(d[31]), "+f"(d[32]), "+f"(d[33]), "+f"(d[34]), "+f"(d[35]), "+f"(d[36]), "+f"(d[37]), "+f"(d[38]), "+f"(d[39])
    : "l"(descA), "l"(descB));
}
template <int SCALE_D>
__device__ __forceinline__ void wgmma_rs_n64(float (&d)[32], uint32_t a0, uint32_t a1, uint32_t a2, uint32_t a3, uint64_t descB) {
  asm volatile("wgmma.mma_async.sync.aligned.m64n64k16.f32.bf16.bf16 {%0, %1, %2, %3, %4, %5, %6, %7, %8, %9, %10, %11, %12, %13, %14, %15, %16, %17, %18, %19, %20, %21, %22, %23, %24, %25, %26, %27, %28, %29, %30, %31}, {%32, %33, %34, %35}, %36, %37, 1, 1, 0;\n"
    : "+f"(d[0]), "+f"(d[1]), "+f"(d[2]), "+f"(d[3]), "+f"(d[4]), "+f"(d[5]), "+f"(d[6]), "+f"(d[7]), "+f"(d[8]), "+f"(d[9]), "+f"(d[10]), "+f"(d[11]), "+f"(d[12]), "+f"(d[13]), "+f"(d[14]), "+f"(d[15]), "+f"(d[16]), "+f"(d[17]), "+f"(d[18]), "+f"(d[19]), "+f"(d[20]), "+f"(d[21]), "+f"(d[22]), "+f"(d[23]), "+f"(d[24]), "+f"(d[25]), "+f"(d[26]), "+f"(d[27]), "+f"(d[28]), "+f"(d[29]), "+f"(d[30]), "+f"(d[31])
    : "r"(a0), "r"(a1), "r"(a2), "r"(a3), "l"(descB), "n"(SCALE_D));
}
template <int SCALE_D>
__device__ __forceinline__ void wgmma_rs_n128(float (&d)[64], uint32_t a0, uint32_t a1, uint32_t a2, uint32_t a3, uint64_t descB) {
  asm volatile("wgmma.mma_async.sync.aligned.m64n128k16.f32.bf16.bf16 {%0, %1, %2, %3, %4, %5, %6, %7, %8, %9, %10, %11, %12, %13, %14, %15, %16, %17, %18, %19, %20, %21, %22, %23, %24, %25, %26, %27, %28, %29, %30, %31, %32, %33, %34, %35, %36, %37, %38, %39, %40, %41, %42, %43, %44, %45, %46, %47, %48, %49, %50, %51, %52, %53, %54, %55, %56, %57, %58, %59, %60, %61, %62, %63}, {%64, %65, %66, %67}, %68, %69, 1, 1, 0;\n"
    : "+f"(d[0]), "+f"(d[1]), "+f"(d[2]), "+f"(d[3]), "+f"(d[4]), "+f"(d[5]), "+f"(d[6]), "+f"(d[7]), "+f"(d[8]), "+f"(d[9]), "+f"(d[10]), "+f"(d[11]), "+f"(d[12]), "+f"(d[13]), "+f"(d[14]), "+f"(d[15]), "+f"(d[16]), "+f"(d[17]), "+f"(d[18]), "+f"(d[19]), "+f"(d[20]), "+f"(d[21]), "+f"(d[22]), "+f"(d[23]), "+f"(d[24]), "+f"(d[25]), "+f"(d[26]), "+f"(d[27]), "+f"(d[28]), "+f"(d[29]), "+f"(d[30]), "+f"(d[31]), "+f"(d[32]), "+f"(d[33]), "+f"(d[34]), "+f"(d[35]), "+f"(d[36]), "+f"(d[37]), "+f"(d[38]), "+f"(d[39]), "+f"(d[40]), "+f"(d[41]), "+f"(d[42]), "+f"(d[43]), "+f"(d[44]), "+f"(d[45]), "+f"(d[46]), "+f"(d[47]), "+f"(d[48]), "+f"(d[49]), "+f"(d[50]), "+f"(d[51]), "+f"(d[52]), "+f"(d[53]), "+f"(d[54]), "+f"(d[55]), "+f"(d[56]), "+f"(d[57]), "+f"(d[58]), "+f"(d[59]), "+f"(d[60]), "+f"(d[61]), "+f"(d[62]), "+f"(d[63])
    : "r"(a0), "r"(a1), "r"(a2), "r"(a3), "l"(descB), "n"(SCALE_D));
}
template <int SCALE_D>
__device__ __forceinline__ void wgmma_rs_n24_tb(float (&d)[12], uint32_t a0, uint32_t a1, uint32_t a2, uint32_t a3, uint64_t descB) {
  asm volatile("wgmma.mma_async.sync.aligned.m64n24k16.f32.bf16.bf16 {%0, %1, %2, %3, %4, %5, %6, %7, %8, %9, %10, %11}, {%12, %13, %14, %15}, %16, %17, 1, 1, 1;\n"
    : "+f"(d[0]), "+f"(d[1]), "+f"(d[2]), "+f"(d[3]), "+f"(d[4]), "+f"(d[5]), "+f"(d[6]), "+f"(d[7]), "+f"(d[8]), "+f"(d[9]), "+f"(d[10]), "+f"(d[11])
    : "r"(a0), "r"(a1), "r"(a2), "r"(a3), "l"(descB), "n"(SCALE_D));
}

constexpr uint32_t DHI_SW128_K = (1024 >> 4) | (1u << 30);
constexpr uint32_t DHI_SW64_MN = (512 >> 4) | (2u << 30);

template <int NC>
__device__ __forceinline__ void store_tile_bf16(const float (&acc)[NC / 2], float scale, uint32_t stage, uint8_t* stage_ptr,
                                                __nv_bfloat16* gdst, int gpitch, int lane) {
  constexpr int PITCH = NC * 2 + 16;
  const uint32_t waddr = stage + ((lane & 7) + ((lane >> 3) & 1) * 8) * PITCH + (lane >> 4) * 16;
#pragma unroll
  for (int j = 0; j < NC / 16; j++) {
    stsm4(waddr + j * 32, pack_bf16(acc[8 * j] * scale, acc[8 * j + 1] * scale), pack_bf16(acc[8 * j + 2] * scale, acc[8 * j + 3] * scale),
          pack_bf16(acc[8 * j + 4] * scale, acc[8 * j + 5] * scale), pack_bf16(acc[8 * j + 6] * scale, acc[8 * j + 7] * scale));
  }
  __syncwarp();
  constexpr int CPR = NC / 8;
#pragma unroll
  for (int i = 0; i < CPR / 2; i++) {
    const int c = i * 32 + lane, r = c / CPR, cc = c % CPR;
    const uint4 v = *reinterpret_cast<const uint4*>(stage_ptr + r * PITCH + cc * 16);
    *reinterpret_cast<uint4*>(gdst + (size_t)r * gpitch + cc * 8) = v;
  }
}

__device__ __forceinline__ void signal_done(unsigned int* flag, int wg, int tid) {
  asm volatile("bar.sync %0, 128;" :: "r"(wg + 1) : "memory");
  if ((tid & 127) == 0) asm volatile("red.release.gpu.global.add.u32 [%0], 1;" :: "l"(flag) : "memory");
}
__device__ __forceinline__ void wait_flags8(const unsigned int* f, unsigned int target) {
  for (int spin = 0; spin < (1 << 26); spin++) {
    unsigned int a, b, c, d, e, g, h, i;
    asm volatile("ld.volatile.global.v4.u32 {%0, %1, %2, %3}, [%4];" : "=r"(a), "=r"(b), "=r"(c), "=r"(d) : "l"(f) : "memory");
    asm volatile("ld.volatile.global.v4.u32 {%0, %1, %2, %3}, [%4];" : "=r"(e), "=r"(g), "=r"(h), "=r"(i) : "l"(f + 4) : "memory");
    if (min(min(min(a, b), min(c, d)), min(min(e, g), min(h, i))) >= target) break;
    __nanosleep(32);
  }
  asm volatile("fence.acq_rel.gpu;" ::: "memory");
  asm volatile("fence.proxy.async;" ::: "memory");
}

#define RP_LD 3
#define RP_ST 7
constexpr int K1_STAGES = 4;
constexpr int K1_A_BYTES = 256 * 128;
constexpr int K1_B_BYTES = 64 * 160 * 2;
constexpr int K1_STAGE = K1_A_BYTES + K1_B_BYTES;
constexpr int K1_SMEM = 5 * K1_A_BYTES + 61440 + 1024;
constexpr int KV_STAGES = 5;
constexpr int KVW_OFF = KV_STAGES * K1_A_BYTES;

__global__ void __launch_bounds__(512, 1)
proj_kernel(const __grid_constant__ CUtensorMap tmX, const __grid_constant__ CUtensorMap tmWq, const __grid_constant__ CUtensorMap tmWqkv,
            const __nv_bfloat16* __restrict__ wk, const __nv_bfloat16* __restrict__ wv, const __nv_bfloat16* __restrict__ gate_w,
            const __nv_bfloat16* __restrict__ woA, const __nv_bfloat16* __restrict__ woB) {
  extern __shared__ uint8_t smem_raw[];
  __shared__ __align__(8) uint64_t bar_full[KV_STAGES], bar_empty[KV_STAGES];
  uint8_t* smem = reinterpret_cast<uint8_t*>((reinterpret_cast<uintptr_t>(smem_raw) + 1023) & ~(uintptr_t)1023);
  const uint32_t sbase = smem_u32(smem);
  const uint32_t dbase = sbase & 0x3FFFFu;
  const int tid = threadIdx.x, warp = tid >> 5, lane = tid & 31;
  const bool is_kv = blockIdx.x >= 128;
  PROF(0, 0);
  if (tid == 0) {
    for (int i = 0; i < KV_STAGES; i++) { mbar_init(smem_u32(&bar_full[i]), 1); mbar_init(smem_u32(&bar_empty[i]), is_kv ? 8 : 16); }
    fence_mbar_init();
  }
  uint2 wa[2][5], wb[2][5]; uint32_t gw[2];
  if (is_kv && tid < 320) {
#pragma unroll
    for (int r = 0; r < 2; r++) {
      const int k = tid + r * 320;
      const uint2* pk = reinterpret_cast<const uint2*>(wk + k * 20);
      const uint2* pv = reinterpret_cast<const uint2*>(wv + k * 20);
#pragma unroll
      for (int i = 0; i < 5; i++) { wa[r][i] = __ldg(pk + i); wb[r][i] = __ldg(pv + i); }
      gw[r] = (uint32_t)__bfloat16_as_ushort(gate_w[k]);
    }
  }
  __syncthreads();
  if (tid == 480) {
    if (!is_kv) { g_done[blockIdx.x] = 0u; g_doneL[blockIdx.x] = 0u; }
    asm volatile("fence.acq_rel.gpu;" ::: "memory");
    pdl_launch();
  }
  __syncwarp();

  if (!is_kv) {
    const int mb = blockIdx.x >> 4, nb = blockIdx.x & 15;
    const CUtensorMap* tw = nb < 4 ? &tmWq : &tmWqkv;
    const int j0 = (nb < 4 ? nb : nb - 4) * 5;
    auto load = [&](int kt) {
      const int s = kt % K1_STAGES;
      const uint32_t fb = smem_u32(&bar_full[s]);
      mbar_expect_tx(fb, K1_STAGE);
      tma_2d(sbase + s * K1_STAGE, &tmX, kt * 64, mb * 256, fb);
      tma_3d(sbase + s * K1_STAGE + K1_A_BYTES, tw, 0, kt * 64, j0, fb);
    };
    if (tid == 0) for (int kt = 0; kt < K1_STAGES; kt++) load(kt);
    __syncwarp();
    uint4 wv2[2];
    const int rq = blockIdx.x * 400 + tid - 112;
    const int rhalf = rq >= 25600, rr = rq - rhalf * 25600, rk = 2 * (rr / 80), rch = rr % 80;
    {
      const int wg = warp >> 2;
      float acc[80];
#pragma unroll
      for (int i = 0; i < 80; i++) acc[i] = 0.f;
      for (int kt = 0; kt < 10; kt++) {
        const int s = kt % K1_STAGES;
        mbar_wait(smem_u32(&bar_full[s]), (kt / K1_STAGES) & 1);
        const uint32_t alo = ((dbase + s * K1_STAGE + wg * 8192) >> 4) | (1u << 16);
        const uint32_t blo = ((dbase + s * K1_STAGE + K1_A_BYTES) >> 4) | ((4096u >> 4) << 16);
        fence_regs(acc);
        wg_fence();
#pragma unroll
        for (int k = 0; k < 4; k++) wgmma_ss_n160_tb(acc, mkd(alo + k * 2, DHI_SW128_K), mkd(blo + k * 64, DHI_SW64_MN));
        wg_commit();
        if (kt == RP_LD && tid >= 112) {
          const uint4* src = reinterpret_cast<const uint4*>((rhalf ? woB : woA) + rk * D_MODEL + rch * 8);
          wv2[0] = __ldg(src); wv2[1] = __ldg(src + D_MODEL / 8);
        }
        if (kt == RP_ST && tid >= 112) {
          uint4* dst = reinterpret_cast<uint4*>(g_wimg + ((rhalf * 8 + rch / 10) * 10 + (rk >> 6)) * 10240 + (rch % 10) * 1024 + (rk & 63) * 16);
          dst[0] = wv2[0]; dst[1] = wv2[1];
        }
        __syncwarp();
        if (kt > 0 && kt - 1 + K1_STAGES < 10) {
          wg_wait<1>();
          const uint32_t eb = smem_u32(&bar_empty[(kt - 1) % K1_STAGES]);
          if (lane == 0) mbar_arrive(eb);
          if (tid == 0) { mbar_wait(eb, ((kt - 1) / K1_STAGES) & 1); load(kt - 1 + K1_STAGES); }
          __syncwarp();
        }
      }
      wg_wait<0>();
      fence_regs(acc);
      PROF(0, 1);
      asm volatile("bar.sync %0, 128;" :: "r"(wg + 1) : "memory");
      const int w4 = warp & 3;
      const uint32_t off = w4 * K1_STAGE + wg * 8192;
      const int row0 = mb * 256 + wg * 64 + w4 * 16;
      if (nb < 4) {
        store_tile_bf16<160>(acc, 0.22360679774997896f * 1.4426950408889634f, sbase + off, smem + off,
                             g_q + (size_t)row0 * D_MODEL + nb * 160, D_MODEL, lane);
      } else {
        store_tile_bf16<160>(acc, 1.0f, sbase + off, smem + off, g_qkv + (size_t)row0 * (3 * D_MODEL) + (nb - 4) * 160, 3 * D_MODEL, lane);
      }
    }
  } else {
    const int cb = blockIdx.x - 128;
    if (warp == 8 && lane == 0) {
      for (int it = 0; it < KV_STAGES; it++) {
        const uint32_t fb = smem_u32(&bar_full[it]);
        mbar_expect_tx(fb, K1_A_BYTES);
        tma_2d(sbase + it * K1_A_BYTES, &tmX, it * 64, cb * 512, fb);
      }
    }
    __syncwarp();
    if (tid < 320) {
#pragma unroll
      for (int r = 0; r < 2; r++) {
        uint4* dst = reinterpret_cast<uint4*>(smem + KVW_OFF + (tid + r * 320) * 16);
        dst[0] = make_uint4(wa[r][0].x, wa[r][0].y, wa[r][1].x, wa[r][1].y);
        dst[640] = make_uint4(wa[r][2].x, wa[r][2].y, wa[r][3].x, wa[r][3].y);
        dst[1280] = make_uint4(wa[r][4].x, wa[r][4].y, 0u, 0u);
        dst[1920] = make_uint4(wb[r][0].x, wb[r][0].y, wb[r][1].x, wb[r][1].y);
        dst[2560] = make_uint4(wb[r][2].x, wb[r][2].y, wb[r][3].x, wb[r][3].y);
        dst[3200] = make_uint4(wb[r][4].x, wb[r][4].y, gw[r], 0u);
      }
    }
    fence_proxy_async();
    asm volatile("bar.sync 1, 512;" ::: "memory");
    PROF(0, 1);
    auto produce = [&](int it0, int it1) {
      for (int it = it0; it < it1; it++) {
        const int s = it % KV_STAGES;
        mbar_wait(smem_u32(&bar_empty[s]), (it / KV_STAGES - 1) & 1);
        const uint32_t fb = smem_u32(&bar_full[s]);
        mbar_expect_tx(fb, K1_A_BYTES);
        tma_2d(sbase + s * K1_A_BYTES, &tmX, (it >= 10 ? it - 10 : it) * 64, cb * 512 + (it >= 10 ? 256 : 0), fb);
      }
    };
    if (tid == 256) produce(KV_STAGES, 15);
    __syncwarp();
    {
      const int pass = warp >> 3, wg = (warp >> 2) & 1, w4 = warp & 3, g = lane >> 2, t = lane & 3;
      if (pass == 1) asm volatile("bar.sync 2, 512;" ::: "memory");
      {
        float acc[2][24];
#pragma unroll
        for (int i = 0; i < 24; i++) { acc[0][i] = 0.f; acc[1][i] = 0.f; }
        for (int kt = 0; kt < 10; kt++) {
          const int it = pass * 10 + kt, s = it % KV_STAGES;
          mbar_wait(smem_u32(&bar_full[s]), (it / KV_STAGES) & 1);
          const uint32_t alo = ((dbase + s * K1_A_BYTES + wg * 16384) >> 4) | (1u << 16);
          const uint32_t blo = ((dbase + KVW_OFF + kt * 1024) >> 4) | ((128u >> 4) << 16);
          fence_regs(acc[0]); fence_regs(acc[1]);
          wg_fence();
#pragma unroll
          for (int k = 0; k < 4; k++) {
            wgmma_ss_n48_tb(acc[0], mkd(alo + k * 2, DHI_SW128_K), mkd(blo + k * 16, 10240u >> 4));
            wgmma_ss_n48_tb(acc[1], mkd(alo + 512 + k * 2, DHI_SW128_K), mkd(blo + k * 16, 10240u >> 4));
          }
          wg_commit();
          if (kt > 0) {
            wg_wait<1>();
            if (lane == 0) mbar_arrive(smem_u32(&bar_empty[(it - 1) % KV_STAGES]));
          }
        }
        wg_wait<0>();
        fence_regs(acc[0]); fence_regs(acc[1]);
        if (lane == 0) mbar_arrive(smem_u32(&bar_empty[(pass * 10 + 9) % KV_STAGES]));
        if (pass == 0) asm volatile("bar.arrive 2, 512;" ::: "memory");
        PROF(0, 2);
        if (tid == 0) produce(15, 20);
        __syncwarp();
        float kmax2 = 0.f, vmax = 0.f;
#pragma unroll
        for (int hh = 0; hh < 4; hh++) {
          const int h = hh & 1;
          const float (&a)[24] = acc[hh >> 1];
          const int key = cb * 512 + pass * 256 + wg * 128 + (hh >> 1) * 64 + w4 * 16 + g + h * 8;
          const int grp = key >> 7, kk = key & 127;
          const bool poly = (TMASK >> (kk >> 3)) & 1;
          uint8_t* gp = g_kvimg + grp * GRP_BYTES;
          const uint32_t k0 = pack_bf16(a[2 * h], a[2 * h + 1]);
          const uint32_t k1 = pack_bf16(a[4 + 2 * h], a[5 + 2 * h]);
          uint32_t k2 = pack_bf16(a[8 + 2 * h], a[9 + 2 * h]);
          float n2 = bf_lo(k0) * bf_lo(k0) + bf_hi(k0) * bf_hi(k0) + bf_lo(k1) * bf_lo(k1) + bf_hi(k1) * bf_hi(k1);
          if (t < 2) {
            n2 += bf_lo(k2) * bf_lo(k2) + bf_hi(k2) * bf_hi(k2);
            k2 = pack_bf16(bf_lo(k2) * 0.5f, bf_hi(k2) * 0.5f);
          } else if (t == 2) k2 = poly ? pack_bf16(24.f, 2.5f) : pack_bf16(0.5f, 0.f);
          else k2 = poly ? pack_bf16(0.5f, 0.f) : 0u;
          *reinterpret_cast<uint32_t*>(gp + kk * 16 + t * 4) = k0;
          *reinterpret_cast<uint32_t*>(gp + PLANE + kk * 16 + t * 4) = k1;
          *reinterpret_cast<uint32_t*>(gp + 2 * PLANE + kk * 16 + t * 4) = k2;
          n2 += __shfl_xor_sync(0xffffffffu, n2, 1);
          n2 += __shfl_xor_sync(0xffffffffu, n2, 2);
          kmax2 = (n2 > kmax2 || n2 != n2) ? n2 : kmax2;
          uint32_t v0 = pack_bf16(a[12 + 2 * h], a[13 + 2 * h]);
          uint32_t v1 = pack_bf16(a[16 + 2 * h], a[17 + 2 * h]);
          uint32_t v2 = pack_bf16(a[20 + 2 * h], a[21 + 2 * h]);
          float vm = fmaxf(fmaxf(fabsf(bf_lo(v0)), fabsf(bf_hi(v0))), fmaxf(fabsf(bf_lo(v1)), fabsf(bf_hi(v1))));
          if (t < 2) vm = fmaxf(vm, fmaxf(fabsf(bf_lo(v2)), fabsf(bf_hi(v2))));
          else if (t == 2) {
            const float z = a[20 + 2 * h];
            g_gate[key] = 1.f / (1.f + __expf(-z));
            v2 = 0x00003F80u;
          } else v2 = 0u;
          vmax = fmaxf(vmax, vm);
          if (poly) { v0 ^= 0x80008000u; v1 ^= 0x80008000u; v2 ^= 0x80008000u; }
          uint8_t* vp = gp + 3 * PLANE + (kk >> 3) * 384 + (kk & 7) * 16 + t * 4;
          *reinterpret_cast<uint32_t*>(vp) = v0;
          *reinterpret_cast<uint32_t*>(vp + 128) = v1;
          *reinterpret_cast<uint32_t*>(vp + 256) = v2;
        }
#pragma unroll
        for (int o = 1; o < 32; o <<= 1) {
          const float a = __shfl_xor_sync(0xffffffffu, kmax2, o);
          kmax2 = (a > kmax2 || a != a) ? a : kmax2;
          vmax = fmaxf(vmax, __shfl_xor_sync(0xffffffffu, vmax, o));
        }
        if (lane == 0) { g_kmax2[cb * 16 + warp] = kmax2; g_vmax[cb * 16 + warp] = vmax; }
      }
    }
  }
}

__device__ __forceinline__ uint32_t ex2_pair_poly(float u0, float u1, uint32_t one2) {
  const uint32_t W = __byte_perm(__float_as_uint(u0), __float_as_uint(u1), 0x6521);
  uint32_t v; asm("lop3.b32 %0, %1, 0x007F007F, %2, 0xEA;" : "=r"(v) : "r"(W), "r"(one2));
  uint32_t L, p;
  asm("fma.rn.bf16x2 %0, %1, %2, %3;" : "=r"(L) : "r"(v), "r"(0x1f961f96u), "r"(0x9fe39fe3u));
  asm("fma.rn.bf16x2 %0, %1, %1, %2;" : "=r"(p) : "r"(L), "r"(0x00f500f5u));
  return W + p;
}
template <int JOFF>
__device__ __forceinline__ void softmax_slow(const float (&S)[32], uint32_t (&P)[16], float (&O)[12], float& m0, float& m1) {
  float a0 = m0, a1 = m1;
#pragma unroll
  for (int j = 0; j < 8; j++) {
    a0 = fmaxf(a0, fmaxf(S[4 * j], S[4 * j + 1]));
    a1 = fmaxf(a1, fmaxf(S[4 * j + 2], S[4 * j + 3]));
  }
  a0 = fmaxf(a0, __shfl_xor_sync(0xffffffffu, a0, 1)); a0 = fmaxf(a0, __shfl_xor_sync(0xffffffffu, a0, 2));
  a1 = fmaxf(a1, __shfl_xor_sync(0xffffffffu, a1, 1)); a1 = fmaxf(a1, __shfl_xor_sync(0xffffffffu, a1, 2));
  const float c0 = ex2(m0 - a0), c1 = ex2(m1 - a1);
  m0 = a0; m1 = a1;
#pragma unroll
  for (int j = 0; j < 3; j++) { O[4 * j] *= c0; O[4 * j + 1] *= c0; O[4 * j + 2] *= c1; O[4 * j + 3] *= c1; }
#pragma unroll
  for (int i = 0; i < 16; i++) {
    const float m = (i & 1) ? a1 : a0;
    const uint32_t p = pack_bf16(ex2(S[2 * i] - m), ex2(S[2 * i + 1] - m));
    P[i] = ((TMASK >> (JOFF + i / 2)) & 1) ? (p ^ 0x80008000u) : p;
  }
}
constexpr uint32_t DHI_KV = 128 >> 4;
__device__ __forceinline__ void issue_qk(float (&S)[32], const uint32_t (&q)[8], uint64_t base) {
  wgmma_rs_n64<0>(S, q[0], q[1], q[2], q[3], base + (uint64_t)((PLANE >> 4) << 16));
  wgmma_rs_n64<1>(S, q[4], q[5], q[6], q[7], base + (uint64_t)(2 * PLANE >> 4));
}
__device__ __forceinline__ void issue_pv(float (&O)[12], const uint32_t (&P)[16], uint64_t vbase) {
#pragma unroll
  for (int kk = 0; kk < 4; kk++)
    wgmma_rs_n24_tb<1>(O, P[4 * kk], P[4 * kk + 1], P[4 * kk + 2], P[4 * kk + 3], vbase + (uint64_t)(kk * (768 >> 4)));
}

constexpr uint32_t VOFF = ((3 * PLANE) >> 4) + ((384u >> 4) << 16);
constexpr int KVR = 4;
constexpr int OFF_W = KVR * GRP_BYTES;
constexpr int OFF_X = OFF_W + 10 * 10240;
constexpr int OFF_BAR = OFF_X + 4 * 16384;
constexpr int K2_SMEM = OFF_BAR + 512 + 1024;
constexpr int TSL = 7;
constexpr int BAR_KV = 0, BAR_W = 4, BAR_TA = 5, BAR_TE = 12, BAR_OWN = 19, BAR_L = 20, CNT_KV = 21, BAR_WA = 23, BAR_WF = 33;
constexpr int NSTEP = 2 * NGRP;

__device__ __forceinline__ void kv_load(uint32_t sbase, int step) {
  const uint32_t bar = sbase + OFF_BAR + (BAR_KV + (step & (KVR - 1))) * 8;
  mbar_expect_tx(bar, GRP_BYTES);
  bulk_g2s(sbase + (step & (KVR - 1)) * GRP_BYTES, g_kvimg + (step & (NGRP - 1)) * GRP_BYTES, GRP_BYTES, bar);
}
__device__ __forceinline__ void kv_release(uint32_t sbase, int step, bool elected) {
  if (elected && step + KVR < NSTEP) {
    uint32_t old;
    asm volatile("atom.acq_rel.cta.shared::cta.inc.u32 %0, [%1], 3;" : "=r"(old) : "r"(sbase + OFF_BAR + CNT_KV * 8 + (step & (KVR - 1)) * 4) : "memory");
    if (old == 3u) kv_load(sbase, step + KVR);
  }
  __syncwarp();
}
__device__ __forceinline__ void kv_wait(uint32_t sbase, int step) {
  mbar_wait(sbase + OFF_BAR + (BAR_KV + (step & (KVR - 1))) * 8, (step / KVR) & 1);
}

__device__ __forceinline__ uint32_t kv_release_begin(uint32_t sbase, int slot, bool doit) {
  uint32_t old = 0;
  asm volatile("{\n.reg .pred p;\nsetp.ne.u32 p, %2, 0;\n@p atom.relaxed.cta.shared::cta.inc.u32 %0, [%1], 3;\n}\n"
               : "+r"(old) : "r"(sbase + OFF_BAR + CNT_KV * 8 + slot * 4), "r"((uint32_t)doit) : "memory");
  return old;
}
template <int H>
__device__ __forceinline__ void softmax_half(const float (&S)[64], uint32_t (&P)[16], uint32_t one2) {
#pragma unroll
  for (int i = 0; i < 16; i++) {
    if ((TMASK >> (8 * H + i / 2)) & 1) P[i] = ex2_pair_poly(S[32 * H + 2 * i], S[32 * H + 2 * i + 1], one2);
    else P[i] = pack_bf16(ex2(S[32 * H + 2 * i]), ex2(S[32 * H + 2 * i + 1]));
  }
}
__device__ __forceinline__ void attn_fast(const uint32_t (&q)[8], float (&O)[12], uint32_t sbase, int step0, int nsteps, bool elected, uint32_t one2) {
  uint64_t kb0 = mkd((sbase & 0x3FFFFu) >> 4, DHI_KV);
  asm volatile("" : "+l"(kb0));
#pragma unroll 1
  for (int step4 = step0; step4 < step0 + nsteps; step4 += KVR) {
#pragma unroll
    for (int j = 0; j < KVR; j++) {
      const int step = step4 + j;
      const uint64_t kb = kb0 + (uint64_t)(j * (GRP_BYTES >> 4));
      float S[64]; uint32_t PA[16], PB[16];
#pragma unroll
      for (int i = 0; i < 64; i++) S[i] = 0.f;
      mbar_wait(sbase + OFF_BAR + (BAR_KV + j) * 8, (step / KVR) & 1);
      fence_regs(S);
      wg_fence();
      wgmma_rs_n128<0>(S, q[0], q[1], q[2], q[3], kb + (uint64_t)((PLANE >> 4) << 16));
      wgmma_rs_n128<1>(S, q[4], q[5], q[6], q[7], kb + (uint64_t)(2 * PLANE >> 4));
      wg_commit();
      wg_wait<0>();
      fence_regs(S);
      softmax_half<0>(S, PA, one2);
      fence_regs(PA); fence_regs(O);
      wg_fence();
      issue_pv(O, PA, kb + VOFF);
      wg_commit();
      softmax_half<1>(S, PB, one2);
      fence_regs(PB);
      wg_fence();
      issue_pv(O, PB, kb + VOFF + 4 * (768 >> 4));
      wg_commit();
      wg_wait<0>();
      fence_regs(PA); fence_regs(PB); fence_regs(O);
      const uint32_t old = kv_release_begin(sbase, j, elected && step + KVR < NSTEP);
      if (old == 3u) kv_load(sbase, step + KVR);
    }
  }
}
template <int H>
__device__ __forceinline__ void slow_step(const uint32_t (&q)[8], float (&O)[12], uint64_t kb, float& m0, float& m1) {
  float S[32]; uint32_t P[16];
#pragma unroll
  for (int i = 0; i < 32; i++) S[i] = 0.f;
  fence_regs(S);
  wg_fence();
  issue_qk(S, q, kb + 64 * H);
  wg_commit();
  wg_wait<0>();
  fence_regs(S);
  softmax_slow<8 * H>(S, P, O, m0, m1);
  fence_regs(P); fence_regs(O);
  wg_fence();
  issue_pv(O, P, kb + VOFF + H * 4 * (768 >> 4));
  wg_commit();
  wg_wait<0>();
  fence_regs(O); fence_regs(P);
}
__device__ __forceinline__ void attn_slow(const uint32_t (&q)[8], float (&O)[12], uint32_t sbase, int step0, int nsteps, bool elected, float& m0, float& m1) {
#pragma unroll 1
  for (int step = step0; step < step0 + nsteps; step++) {
    kv_wait(sbase, step);
    const uint64_t kb = mkd(((sbase & 0x3FFFFu) >> 4) + (step & (KVR - 1)) * (GRP_BYTES >> 4), DHI_KV);
    slow_step<0>(q, O, kb, m0, m1);
    slow_step<1>(q, O, kb, m0, m1);
    kv_release(sbase, step, elected);
  }
}

__device__ __forceinline__ void softmax8(float (&sc)[8], float scale) {
  float mx = sc[0];
#pragma unroll
  for (int w = 1; w < 8; w++) mx = fmaxf(mx, sc[w]);
  float l = 0.f;
#pragma unroll
  for (int w = 0; w < 8; w++) { sc[w] = ex2(sc[w] - mx); l += sc[w]; }
  const float r = __fdividef(scale, l);
#pragma unroll
  for (int w = 0; w < 8; w++) sc[w] *= r;
}
#define LEV(wg) 1
constexpr int LBOX = 30 * 320;
__device__ __forceinline__ uint2 lds64(uint32_t a) {
  uint2 v; asm volatile("ld.shared.v2.u32 {%0, %1}, [%2];" : "=r"(v.x), "=r"(v.y) : "r"(a)); return v;
}
__device__ __forceinline__ void local_attn(uint32_t stage, int t0, int i, int lane) {
  constexpr float SC = 0.22360679774997896f * 1.4426950408889634f, NEG = -1e9f * 1.4426950408889634f;
  const uint32_t base = stage + (lane >> 3) * LBOX + (lane & 7) * 40 + (i + 14) * 320;
  const int t = t0 + i;
  float sc[8];
#pragma unroll
  for (int w = 0; w < 8; w++) sc[w] = 0.f;
#pragma unroll 1
  for (int c = 0; c < 5; c++) {
    const uint2 qv = lds64(base + c * 8);
    const float q0 = bf_lo(qv.x), q1 = bf_hi(qv.x), q2 = bf_lo(qv.y), q3 = bf_hi(qv.y);
#pragma unroll
    for (int w = 0; w < 8; w++) {
      const uint2 k = lds64(base + c * 8 + 4 * LBOX - w * 640);
      sc[w] = fmaf(q0, bf_lo(k.x), sc[w]); sc[w] = fmaf(q1, bf_hi(k.x), sc[w]);
      sc[w] = fmaf(q2, bf_lo(k.y), sc[w]); sc[w] = fmaf(q3, bf_hi(k.y), sc[w]);
    }
  }
#pragma unroll
  for (int w = 0; w < 8; w++) sc[w] = t - 2 * w >= 0 ? sc[w] * SC : NEG;
  softmax8(sc, 1.f - g_gate[t]);
  uint2* dst = reinterpret_cast<uint2*>(g_a2 + (size_t)t * (2 * D_MODEL) + D_MODEL + lane * DH);
#pragma unroll 1
  for (int c = 0; c < 5; c++) {
    float o0 = 0.f, o1 = 0.f, o2 = 0.f, o3 = 0.f;
#pragma unroll
    for (int w = 0; w < 8; w++) {
      const uint2 v = lds64(base + c * 8 + 8 * LBOX - w * 640);
      o0 = fmaf(sc[w], bf_lo(v.x), o0); o1 = fmaf(sc[w], bf_hi(v.x), o1);
      o2 = fmaf(sc[w], bf_lo(v.y), o2); o3 = fmaf(sc[w], bf_hi(v.y), o3);
    }
    dst[c] = make_uint2(pack_bf16(o0, o1), pack_bf16(o2, o3));
  }
}
__device__ __forceinline__ uint32_t ta_slot(int i) { return i < 4 ? OFF_X + i * 16384 : (i - 4) * 16384; }

__global__ void __launch_bounds__(640, 1)
attn_kernel(const __grid_constant__ CUtensorMap tmA2, const __grid_constant__ CUtensorMap tmL, __nv_bfloat16* __restrict__ out, uint32_t one2) {
  extern __shared__ uint8_t smem_raw[];
  uint8_t* smem = reinterpret_cast<uint8_t*>((reinterpret_cast<uintptr_t>(smem_raw) + 1023) & ~(uintptr_t)1023);
  const uint32_t sbase = smem_u32(smem);
  const uint32_t dbase = sbase & 0x3FFFFu;
  const uint32_t bars = sbase + OFF_BAR;
  const int tid = threadIdx.x, wg = tid >> 7, warp = (tid >> 5) & 3, lane = tid & 31, g = lane >> 2, t = lane & 3;
  const int mb = blockIdx.x >> 3, nb = blockIdx.x & 7;
  const bool elected = (tid & 127) == 0;
  if (tid == 0) {
    for (int i = 0; i < BAR_TE; i++) mbar_init(bars + i * 8, 1);
    for (int i = BAR_TE; i < BAR_TE + TSL; i++) mbar_init(bars + i * 8, 8);
    mbar_init(bars + BAR_OWN * 8, 4);
    mbar_init(bars + BAR_L * 8, 1);
    for (int i = 0; i < 10; i++) { mbar_init(bars + (BAR_WA + i) * 8, 1); mbar_init(bars + (BAR_WF + i) * 8, 8); }
    for (int i = 0; i < 4; i++) *reinterpret_cast<uint32_t*>(smem + OFF_BAR + CNT_KV * 8 + i * 4) = 0u;
    fence_mbar_init();
  }
  __syncthreads();
  auto tail_load = [&](int i) {
    const uint32_t fb = bars + (BAR_TA + i % TSL) * 8;
    mbar_expect_tx(fb, 16384);
    tma_2d(sbase + ta_slot(i % TSL), &tmA2, i < 10 ? D_MODEL + i * 64 : (i - 10) * 64, mb * 128, fb);
  };
  if (wg == 4) {
    asm volatile("setmaxnreg.dec.sync.aligned.u32 32;");
    pdl_wait();
    if (tid == 512) {
      for (int j = 0; j < KVR; j++) kv_load(sbase, j);
      mbar_expect_tx(bars + BAR_L * 8, 12 * LBOX);
      for (int i = 0; i < 12; i++) tma_2d(sbase + OFF_W + i * LBOX, &tmL, i * 160, blockIdx.x * 16 - 14, bars + BAR_L * 8);
    }
    __syncwarp();
    mbar_wait(bars + BAR_L * 8, 0);
#pragma unroll 1
    for (int i = 0; i < 4; i++) local_attn(sbase + OFF_W, blockIdx.x * 16, warp * 4 + i, lane);
    signal_done(&g_doneL[blockIdx.x], wg, tid);
    if (tid == 512) {
      PROF2(0, 2);
      mbar_expect_tx(bars + BAR_W * 8, 10 * 10240);
      for (int i = 0; i < 5; i++) bulk_g2s(sbase + OFF_W + i * 20480, g_wimg + ((8 + nb) * 10) * 10240 + i * 20480, 20480, bars + BAR_W * 8);
      wait_flags8(&g_doneL[mb * 8], 1u);
      for (int i = 0; i < 4; i++) tail_load(i);
      mbar_wait(bars + BAR_OWN * 8, 0);
      for (int i = 4; i < 20; i++) {
        if (i >= TSL) mbar_wait(bars + (BAR_TE + i % TSL) * 8, (i / TSL - 1) & 1);
        if (i == 10) { wait_flags8(&g_done[mb * 8], 4u); PROF2(2, 0); }
        tail_load(i);
      }
    } else if (tid == 544) {
      for (int kt = 0; kt < 10; kt++) {
        mbar_wait(bars + (BAR_WF + kt) * 8, 0);
        mbar_expect_tx(bars + (BAR_WA + kt) * 8, 10240);
        bulk_g2s(sbase + OFF_W + kt * 10240, g_wimg + (nb * 10 + kt) * 10240, 10240, bars + (BAR_WA + kt) * 8);
      }
    }
    return;
  }
  asm volatile("setmaxnreg.inc.sync.aligned.u32 112;");
  pdl_wait();
  PROF(1, 1);
  uint32_t q[8], q2[6];
  const int rowA = (blockIdx.x * 8 + wg) * 64 + warp * 16 + g;
  {
    const uint32_t* r0 = reinterpret_cast<const uint32_t*>(g_q + (size_t)rowA * DH);
    const uint32_t* r1 = r0 + 8 * (DH / 2);
    const uint32_t* s0 = r0 + 256 * (DH / 2);
    const uint32_t* s1 = s0 + 8 * (DH / 2);
    q[0] = r0[t]; q[1] = r1[t]; q[2] = r0[t + 4]; q[3] = r1[t + 4];
    q[4] = t < 2 ? r0[8 + t] : 0u;
    q[5] = t < 2 ? r1[8 + t] : 0u;
    q2[0] = s0[t]; q2[1] = s1[t]; q2[2] = s0[t + 4]; q2[3] = s1[t + 4];
    q2[4] = t < 2 ? s0[8 + t] : 0u;
    q2[5] = t < 2 ? s1[8 + t] : 0u;
  }
  float kmax2 = 0.f, vmax = 0.f;
#pragma unroll
  for (int i = 0; i < 2; i++) {
    const float a = g_kmax2[lane + 32 * i];
    kmax2 = (a > kmax2 || a != a) ? a : kmax2;
    vmax = fmaxf(vmax, g_vmax[lane + 32 * i]);
  }
#pragma unroll
  for (int o = 1; o < 32; o <<= 1) {
    const float a = __shfl_xor_sync(0xffffffffu, kmax2, o);
    kmax2 = (a > kmax2 || a != a) ? a : kmax2;
    vmax = fmaxf(vmax, __shfl_xor_sync(0xffffffffu, vmax, o));
  }
  const float qlim = (vmax >= 0.00390625f && vmax <= 256.f) ? 9025.f / kmax2 : -1.f;
  PROF(1, 2);
#pragma unroll 1
  for (int it = 0; it < 2; it++) {
    const int row0 = rowA + it * 256;
    if (it == 1) {
#pragma unroll
      for (int i = 0; i < 6; i++) q[i] = q2[i];
    }
    float n0 = bf_lo(q[0]) * bf_lo(q[0]) + bf_hi(q[0]) * bf_hi(q[0]) + bf_lo(q[2]) * bf_lo(q[2]) + bf_hi(q[2]) * bf_hi(q[2]) +
               bf_lo(q[4]) * bf_lo(q[4]) + bf_hi(q[4]) * bf_hi(q[4]);
    float n1 = bf_lo(q[1]) * bf_lo(q[1]) + bf_hi(q[1]) * bf_hi(q[1]) + bf_lo(q[3]) * bf_lo(q[3]) + bf_hi(q[3]) * bf_hi(q[3]) +
               bf_lo(q[5]) * bf_lo(q[5]) + bf_hi(q[5]) * bf_hi(q[5]);
    n0 += __shfl_xor_sync(0xffffffffu, n0, 1); n0 += __shfl_xor_sync(0xffffffffu, n0, 2);
    n1 += __shfl_xor_sync(0xffffffffu, n1, 1); n1 += __shfl_xor_sync(0xffffffffu, n1, 2);
    const bool safe = (n0 <= qlim) && (n1 <= qlim);
    uint32_t unsafe_any;
    asm volatile("{\n.reg .pred p, r;\nsetp.eq.u32 p, %1, 0;\nbarrier.cta.red.or.pred r, %2, 128, p;\nselp.u32 %0, 1, 0, r;\n}\n"
                 : "=r"(unsafe_any) : "r"((uint32_t)safe), "r"(wg + 1) : "memory");
    float O[12];
#pragma unroll
    for (int i = 0; i < 12; i++) O[i] = 0.f;
    if (!unsafe_any && t >= 2) { q[4] = q[5] = (t == 2) ? 0x3F804100u : 0x00003B80u; }
    q[6] = q[4]; q[7] = q[5];
    fence_regs(q);
    float m0 = -INFINITY, m1 = -INFINITY;
    if (!unsafe_any) attn_fast(q, O, sbase, it * NGRP, NGRP, elected, one2);
    else attn_slow(q, O, sbase, it * NGRP, NGRP, elected, m0, m1);
    const float l0 = __shfl_sync(0xffffffffu, O[8], (lane & ~3) | 2);
    const float l1 = __shfl_sync(0xffffffffu, O[10], (lane & ~3) | 2);
    const int tok = row0 >> 5;
    const float gt = g_gate[tok];
    const float i0 = gt / l0, i1 = gt / l1;
    uint32_t* o0 = reinterpret_cast<uint32_t*>(g_a2 + (size_t)tok * (2 * D_MODEL) + (row0 & 31) * DH);
    uint32_t* o1 = o0 + 8 * (DH / 2);
    o0[t] = pack_bf16(O[0] * i0, O[1] * i0); o1[t] = pack_bf16(O[2] * i1, O[3] * i1);
    o0[t + 4] = pack_bf16(O[4] * i0, O[5] * i0); o1[t + 4] = pack_bf16(O[6] * i1, O[7] * i1);
    if (t < 2) { o0[t + 8] = pack_bf16(O[8] * i0, O[9] * i0); o1[t + 8] = pack_bf16(O[10] * i1, O[11] * i1); }
  }
  signal_done(&g_done[blockIdx.x], wg, tid);
  if ((tid & 127) == 64) mbar_arrive(bars + BAR_OWN * 8);
  PROF(1, 3);
  if (wg < 2) {
    float acc[40];
#pragma unroll
    for (int i = 0; i < 40; i++) acc[i] = 0.f;
    mbar_wait(bars + BAR_W * 8, 0);
    int sl = 0, ph = 0;
#pragma unroll 1
    for (int i = 0; i < 20; i++) {
      mbar_wait(bars + (BAR_TA + sl) * 8, ph);
      if (i >= 10) mbar_wait(bars + (BAR_WA + i - 10) * 8, 0);
      if (i == 10) PROF(2, 1);
      const uint32_t alo = ((dbase + ta_slot(sl) + wg * 8192) >> 4) | (1u << 16);
      const uint32_t blo = ((dbase + OFF_W + (i >= 10 ? i - 10 : i) * 10240) >> 4) | ((128u >> 4) << 16);
      fence_regs(acc);
      wg_fence();
#pragma unroll
      for (int k = 0; k < 4; k++) wgmma_ss_n80_tb(acc, mkd(alo + k * 2, DHI_SW128_K), mkd(blo + k * 16, 1024u >> 4));
      wg_commit();
      if (i > 0) {
        wg_wait<1>();
        if (lane == 0) mbar_arrive(bars + (BAR_TE + (sl == 0 ? TSL - 1 : sl - 1)) * 8);
        if (lane == 1 && i <= 10) mbar_arrive(bars + (BAR_WF + i - 1) * 8);
      }
      if (++sl == TSL) { sl = 0; ph ^= 1; }
    }
    wg_wait<0>();
    fence_regs(acc);
    PROF(2, 2);
    asm volatile("bar.sync %0, 128;" :: "r"(wg + 1) : "memory");
    const uint32_t so = ta_slot(warp) + wg * 8192;
    const int row0 = mb * 128 + wg * 64 + warp * 16;
    store_tile_bf16<80>(acc, 1.0f, sbase + so, smem + so, out + (size_t)row0 * D_MODEL + nb * 80, D_MODEL, lane);
    PROF(2, 3);
  }
}

typedef CUresult (*EncodeFn)(CUtensorMap*, CUtensorMapDataType, cuuint32_t, void*, const cuuint64_t*, const cuuint64_t*,
                             const cuuint32_t*, const cuuint32_t*, CUtensorMapInterleave, CUtensorMapSwizzle,
                             CUtensorMapL2promotion, CUtensorMapFloatOOBfill);

void make_map(EncodeFn fn, CUtensorMap* tm, const void* ptr, int rank, const cuuint64_t* dims, const cuuint64_t* strides,
              const cuuint32_t* box, CUtensorMapSwizzle sw) {
  const cuuint32_t es[3] = {1, 1, 1};
  fn(tm, CU_TENSOR_MAP_DATA_TYPE_BFLOAT16, rank, const_cast<void*>(ptr), dims, strides, box, es, CU_TENSOR_MAP_INTERLEAVE_NONE, sw,
     CU_TENSOR_MAP_L2_PROMOTION_L2_256B, CU_TENSOR_MAP_FLOAT_OOB_FILL_NONE);
}
void map_a(EncodeFn fn, CUtensorMap* tm, const void* p, int rows, int cols, int box_rows) {
  const cuuint64_t dims[2] = {(cuuint64_t)cols, (cuuint64_t)rows};
  const cuuint64_t str[1] = {(cuuint64_t)cols * 2};
  const cuuint32_t box[2] = {64, (cuuint32_t)box_rows};
  make_map(fn, tm, p, 2, dims, str, box, CU_TENSOR_MAP_SWIZZLE_128B);
}
void map_w(EncodeFn fn, CUtensorMap* tm, const void* p, int K, int N, int atom, CUtensorMapSwizzle sw) {
  const cuuint64_t dims[3] = {(cuuint64_t)atom, (cuuint64_t)K, (cuuint64_t)(N / atom)};
  const cuuint64_t str[2] = {(cuuint64_t)N * 2, (cuuint64_t)atom * 2};
  const cuuint32_t box[3] = {(cuuint32_t)atom, 64, 5};
  make_map(fn, tm, p, 3, dims, str, box, sw);
}

template <typename... KArgs, typename... Args>
void launch(void (*kern)(KArgs...), int grid, int block, int smem, bool pdl, Args... args) {
  cudaLaunchConfig_t cfg = {};
  cfg.gridDim = dim3(grid); cfg.blockDim = dim3(block); cfg.dynamicSmemBytes = smem; cfg.stream = cudaStreamPerThread;
  cudaLaunchAttribute at[1];
  at[0].id = cudaLaunchAttributeProgrammaticStreamSerialization;
  at[0].val.programmaticStreamSerializationAllowed = 1;
  cfg.attrs = at; cfg.numAttrs = pdl ? 1 : 0;
  cudaLaunchKernelEx(&cfg, kern, KArgs(args)...);
}

}

extern "C" void kernel_launch(void* const* d_in, const int* in_sizes, int n_in, void* d_out, int out_size) {
  (void)in_sizes; (void)n_in; (void)out_size;
  const __nv_bfloat16* x = (const __nv_bfloat16*)d_in[0];
  const __nv_bfloat16* wq = (const __nv_bfloat16*)d_in[1];
  const __nv_bfloat16* wk = (const __nv_bfloat16*)d_in[2];
  const __nv_bfloat16* wv = (const __nv_bfloat16*)d_in[3];
  const __nv_bfloat16* woA = (const __nv_bfloat16*)d_in[4];
  const __nv_bfloat16* wqkv = (const __nv_bfloat16*)d_in[6];
  const __nv_bfloat16* woB = (const __nv_bfloat16*)d_in[7];
  const __nv_bfloat16* gate_w = (const __nv_bfloat16*)d_in[8];

  static EncodeFn enc = nullptr;
  static void* a2_ptr = nullptr;
  static void* qkv_ptr = nullptr;
  if (!enc) {
    void* fp = nullptr;
    cudaDriverEntryPointQueryResult qr;
    cudaGetDriverEntryPoint("cuTensorMapEncodeTiled", &fp, cudaEnableDefault, &qr);
    enc = (EncodeFn)fp;
    cudaGetSymbolAddress(&a2_ptr, g_a2);
    cudaGetSymbolAddress(&qkv_ptr, g_qkv);
    cudaFuncSetAttribute(proj_kernel, cudaFuncAttributeMaxDynamicSharedMemorySize, K1_SMEM);
    cudaFuncSetAttribute(attn_kernel, cudaFuncAttributeMaxDynamicSharedMemorySize, K2_SMEM);
  }
  CUtensorMap tmX, tmWq, tmWqkv, tmA2, tmL;
  {
    const cuuint64_t dims[2] = {3 * D_MODEL, S_LEN};
    const cuuint64_t str[1] = {3 * D_MODEL * 2};
    const cuuint32_t box[2] = {160, 30};
    make_map(enc, &tmL, qkv_ptr, 2, dims, str, box, CU_TENSOR_MAP_SWIZZLE_NONE);
  }
  map_a(enc, &tmX, x, S_LEN, D_MODEL, 256);
  map_w(enc, &tmWq, wq, D_MODEL, D_MODEL, 32, CU_TENSOR_MAP_SWIZZLE_64B);
  map_w(enc, &tmWqkv, wqkv, D_MODEL, 3 * D_MODEL, 32, CU_TENSOR_MAP_SWIZZLE_64B);
  map_a(enc, &tmA2, a2_ptr, S_LEN, 2 * D_MODEL, 128);

  launch(proj_kernel, 132, 512, K1_SMEM, false, tmX, tmWq, tmWqkv, wk, wv, gate_w, woA, woB);
  launch(attn_kernel, 128, 640, K2_SMEM, true, tmA2, tmL, (__nv_bfloat16*)d_out, 0x3F803F80u);
}
```

```cpp
#include <cuda_runtime.h>
#include <cuda_bf16.h>
#include <cuda.h>
#include <stdint.h>

namespace {

constexpr int S_LEN = 2048, D_MODEL = 640, DH = 20;

constexpr int GRP = 128;
constexpr int PLANE = GRP * 16;
constexpr int GRP_BYTES = GRP * 16 * 6;
constexpr int NGRP = S_LEN / GRP;
#define TMASKV 0x6DB6u
constexpr uint32_t TMASK = TMASKV;

__device__ __align__(1024) __nv_bfloat16 g_q[S_LEN * D_MODEL];
__device__ __align__(1024) __nv_bfloat16 g_qkv[S_LEN * 3 * D_MODEL];
__device__ __align__(1024) __nv_bfloat16 g_a2[S_LEN * 2 * D_MODEL];
__device__ __align__(1024) uint8_t g_kvimg[NGRP * GRP_BYTES];
__device__ __align__(1024) uint8_t g_wimg[2 * 8 * 10 * 10240];
__device__ float g_gate[S_LEN];
__device__ float g_kmax2[64];
__device__ float g_vmax[64];
__device__ __align__(32) unsigned int g_doneL[128];
__device__ __align__(32) unsigned int g_done[128];

#define PROF(k, slot)
#define PROF2(k, slot)
__device__ __forceinline__ uint32_t smem_u32(const void* p) { return (uint32_t)__cvta_generic_to_shared(p); }
__device__ __forceinline__ uint64_t mkd(uint32_t lo, uint32_t hi) {
  uint64_t d; asm("mov.b64 %0, {%1, %2};" : "=l"(d) : "r"(lo), "r"(hi)); return d;
}
__device__ __forceinline__ void wg_fence() { asm volatile("wgmma.fence.sync.aligned;" ::: "memory"); }
__device__ __forceinline__ void wg_commit() { asm volatile("wgmma.commit_group.sync.aligned;" ::: "memory"); }
template <int N> __device__ __forceinline__ void wg_wait() { asm volatile("wgmma.wait_group.sync.aligned %0;" :: "n"(N) : "memory"); }
template <int N> __device__ __forceinline__ void fence_regs(float (&d)[N]) {
#pragma unroll
  for (int i = 0; i < N; i++) asm volatile("" : "+f"(d[i]) :: "memory");
}
template <int N> __device__ __forceinline__ void fence_regs(uint32_t (&d)[N]) {
#pragma unroll
  for (int i = 0; i < N; i++) asm volatile("" : "+r"(d[i]) :: "memory");
}
__device__ __forceinline__ void mbar_init(uint32_t bar, uint32_t cnt) { asm volatile("mbarrier.init.shared::cta.b64 [%0], %1;" :: "r"(bar), "r"(cnt)); }
__device__ __forceinline__ void mbar_expect_tx(uint32_t bar, uint32_t bytes) {
  asm volatile("mbarrier.arrive.expect_tx.shared::cta.b64 _, [%0], %1;" :: "r"(bar), "r"(bytes) : "memory");
}
__device__ __forceinline__ void mbar_arrive(uint32_t bar) { asm volatile("mbarrier.arrive.shared::cta.b64 _, [%0];" :: "r"(bar) : "memory"); }
#define WAIT_HINT 20000u
__device__ __forceinline__ void mbar_wait(uint32_t bar, uint32_t parity) {
  asm volatile("{\n.reg .pred p;\nWAIT_%=:\nmbarrier.try_wait.parity.shared::cta.b64 p, [%0], %1, %2;\n@p bra DONE_%=;\nbra WAIT_%=;\nDONE_%=:\n}\n"
               :: "r"(bar), "r"(parity), "r"(WAIT_HINT) : "memory");
}
__device__ __forceinline__ void fence_mbar_init() { asm volatile("fence.mbarrier_init.release.cluster;" ::: "memory"); }
__device__ __forceinline__ void fence_proxy_async() { asm volatile("fence.proxy.async.shared::cta;" ::: "memory"); }
__device__ __forceinline__ void bulk_g2s(uint32_t dst, const void* src, uint32_t bytes, uint32_t bar) {
  asm volatile("cp.async.bulk.shared::cluster.global.mbarrier::complete_tx::bytes [%0], [%1], %2, [%3];"
               :: "r"(dst), "l"(src), "r"(bytes), "r"(bar) : "memory");
}
__device__ __forceinline__ void tma_2d(uint32_t dst, const CUtensorMap* tm, int c0, int c1, uint32_t bar) {
  asm volatile("cp.async.bulk.tensor.2d.shared::cluster.global.mbarrier::complete_tx::bytes [%0], [%1, {%3, %4}], [%2];"
               :: "r"(dst), "l"((uint64_t)tm), "r"(bar), "r"(c0), "r"(c1) : "memory");
}
__device__ __forceinline__ void tma_3d(uint32_t dst, const CUtensorMap* tm, int c0, int c1, int c2, uint32_t bar) {
  asm volatile("cp.async.bulk.tensor.3d.shared::cluster.global.mbarrier::complete_tx::bytes [%0], [%1, {%3, %4, %5}], [%2];"
               :: "r"(dst), "l"((uint64_t)tm), "r"(bar), "r"(c0), "r"(c1), "r"(c2) : "memory");
}
__device__ __forceinline__ void pdl_wait() { asm volatile("griddepcontrol.wait;" ::: "memory"); }
__device__ __forceinline__ void pdl_launch() { asm volatile("griddepcontrol.launch_dependents;" ::: "memory"); }
__device__ __forceinline__ float ex2(float x) { float y; asm("ex2.approx.ftz.f32 %0, %1;" : "=f"(y) : "f"(x)); return y; }
__device__ __forceinline__ uint32_t pack_bf16(float lo, float hi) {
  uint32_t r; asm("cvt.rn.bf16x2.f32 %0, %1, %2;" : "=r"(r) : "f"(hi), "f"(lo)); return r;
}
__device__ __forceinline__ float bf_lo(uint32_t x) { return __uint_as_float(x << 16); }
__device__ __forceinline__ float bf_hi(uint32_t x) { return __uint_as_float(x & 0xffff0000u); }
__device__ __forceinline__ void stsm4(uint32_t addr, uint32_t r0, uint32_t r1, uint32_t r2, uint32_t r3) {
  asm volatile("stmatrix.sync.aligned.m8n8.x4.shared.b16 [%0], {%1, %2, %3, %4};" :: "r"(addr), "r"(r0), "r"(r1), "r"(r2), "r"(r3) : "memory");
}

__device__ __forceinline__ void wgmma_ss_n160_tb(float (&d)[80], uint64_t descA, uint64_t descB) {
  asm volatile("wgmma.mma_async.sync.aligned.m64n160k16.f32.bf16.bf16 {%0, %1, %2, %3, %4, %5, %6, %7, %8, %9, %10, %11, %12, %13, %14, %15, %16, %17, %18, %19, %20, %21, %22, %23, %24, %25, %26, %27, %28, %29, %30, %31, %32, %33, %34, %35, %36, %37, %38, %39, %40, %41, %42, %43, %44, %45, %46, %47, %48, %49, %50, %51, %52, %53, %54, %55, %56, %57, %58, %59, %60, %61, %62, %63, %64, %65, %66, %67, %68, %69, %70, %71, %72, %73, %74, %75, %76, %77, %78, %79}, %80, %81, 1, 1, 1, 0, 1;\n"
    : "+f"(d[0]), "+f"(d[1]), "+f"(d[2]), "+f"(d[3]), "+f"(d[4]), "+f"(d[5]), "+f"(d[6]), "+f"(d[7]), "+f"(d[8]), "+f"(d[9]), "+f"(d[10]), "+f"(d[11]), "+f"(d[12]), "+f"(d[13]), "+f"(d[14]), "+f"(d[15]), "+f"(d[16]), "+f"(d[17]), "+f"(d[18]), "+f"(d[19]), "+f"(d[20]), "+f"(d[21]), "+f"(d[22]), "+f"(d[23]), "+f"(d[24]), "+f"(d[25]), "+f"(d[26]), "+f"(d[27]), "+f"(d[28]), "+f"(d[29]), "+f"(d[30]), "+f"(d[31]), "+f"(d[32]), "+f"(d[33]), "+f"(d[34]), "+f"(d[35]), "+f"(d[36]), "+f"(d[37]), "+f"(d[38]), "+f"(d[39]), "+f"(d[40]), "+f"(d[41]), "+f"(d[42]), "+f"(d[43]), "+f"(d[44]), "+f"(d[45]), "+f"(d[46]), "+f"(d[47]), "+f"(d[48]), "+f"(d[49]), "+f"(d[50]), "+f"(d[51]), "+f"(d[52]), "+f"(d[53]), "+f"(d[54]), "+f"(d[55]), "+f"(d[56]), "+f"(d[57]), "+f"(d[58]), "+f"(d[59]), "+f"(d[60]), "+f"(d[61]), "+f"(d[62]), "+f"(d[63]), "+f"(d[64]), "+f"(d[65]), "+f"(d[66]), "+f"(d[67]), "+f"(d[68]), "+f"(d[69]), "+f"(d[70]), "+f"(d[71]), "+f"(d[72]), "+f"(d[73]), "+f"(d[74]), "+f"(d[75]), "+f"(d[76]), "+f"(d[77]), "+f"(d[78]), "+f"(d[79])
    : "l"(descA), "l"(descB));
}
__device__ __forceinline__ void wgmma_ss_n48_tb(float (&d)[24], uint64_t descA, uint64_t descB) {
  asm volatile("wgmma.mma_async.sync.aligned.m64n48k16.f32.bf16.bf16 {%0, %1, %2, %3, %4, %5, %6, %7, %8, %9, %10, %11, %12, %13, %14, %15, %16, %17, %18, %19, %20, %21, %22, %23}, %24, %25, 1, 1, 1, 0, 1;\n"
    : "+f"(d[0]), "+f"(d[1]), "+f"(d[2]), "+f"(d[3]), "+f"(d[4]), "+f"(d[5]), "+f"(d[6]), "+f"(d[7]), "+f"(d[8]), "+f"(d[9]), "+f"(d[10]), "+f"(d[11]), "+f"(d[12]), "+f"(d[13]), "+f"(d[14]), "+f"(d[15]), "+f"(d[16]), "+f"(d[17]), "+f"(d[18]), "+f"(d[19]), "+f"(d[20]), "+f"(d[21]), "+f"(d[22]), "+f"(d[23])
    : "l"(descA), "l"(descB));
}
__device__ __forceinline__ void wgmma_ss_n80_tb(float (&d)[40], uint64_t descA, uint64_t descB) {
  asm volatile("wgmma.mma_async.sync.aligned.m64n80k16.f32.bf16.bf16 {%0, %1, %2, %3, %4, %5, %6, %7, %8, %9, %10, %11, %12, %13, %14, %15, %16, %17, %18, %19, %20, %21, %22, %23, %24, %25, %26, %27, %28, %29, %30, %31, %32, %33, %34, %35, %36, %37, %38, %39}, %40, %41, 1, 1, 1, 0, 1;\n"
    : "+f"(d[0]), "+f"(d[1]), "+f"(d[2]), "+f"(d[3]), "+f"(d[4]), "+f"(d[5]), "+f"(d[6]), "+f"(d[7]), "+f"(d[8]), "+f"(d[9]), "+f"(d[10]), "+f"(d[11]), "+f"(d[12]), "+f"(d[13]), "+f"(d[14]), "+f"(d[15]), "+f"(d[16]), "+f"(d[17]), "+f"(d[18]), "+f"(d[19]), "+f"(d[20]), "+f"(d[21]), "+f"(d[22]), "+f"(d[23]), "+f"(d[24]), "+f"(d[25]), "+f"(d[26]), "+f"(d[27]), "+f"(d[28]), "+f"(d[29]), "+f"(d[30]), "+f"(d[31]), "+f"(d[32]), "+f"(d[33]), "+f"(d[34]), "+f"(d[35]), "+f"(d[36]), "+f"(d[37]), "+f"(d[38]), "+f"(d[39])
    : "l"(descA), "l"(descB));
}
template <int SCALE_D>
__device__ __forceinline__ void wgmma_rs_n64(float (&d)[32], uint32_t a0, uint32_t a1, uint32_t a2, uint32_t a3, uint64_t descB) {
  asm volatile("wgmma.mma_async.sync.aligned.m64n64k16.f32.bf16.bf16 {%0, %1, %2, %3, %4, %5, %6, %7, %8, %9, %10, %11, %12, %13, %14, %15, %16, %17, %18, %19, %20, %21, %22, %23, %24, %25, %26, %27, %28, %29, %30, %31}, {%32, %33, %34, %35}, %36, %37, 1, 1, 0;\n"
    : "+f"(d[0]), "+f"(d[1]), "+f"(d[2]), "+f"(d[3]), "+f"(d[4]), "+f"(d[5]), "+f"(d[6]), "+f"(d[7]), "+f"(d[8]), "+f"(d[9]), "+f"(d[10]), "+f"(d[11]), "+f"(d[12]), "+f"(d[13]), "+f"(d[14]), "+f"(d[15]), "+f"(d[16]), "+f"(d[17]), "+f"(d[18]), "+f"(d[19]), "+f"(d[20]), "+f"(d[21]), "+f"(d[22]), "+f"(d[23]), "+f"(d[24]), "+f"(d[25]), "+f"(d[26]), "+f"(d[27]), "+f"(d[28]), "+f"(d[29]), "+f"(d[30]), "+f"(d[31])
    : "r"(a0), "r"(a1), "r"(a2), "r"(a3), "l"(descB), "n"(SCALE_D));
}
template <int SCALE_D>
__device__ __forceinline__ void wgmma_rs_n128(float (&d)[64], uint32_t a0, uint32_t a1, uint32_t a2, uint32_t a3, uint64_t descB) {
  asm volatile("wgmma.mma_async.sync.aligned.m64n128k16.f32.bf16.bf16 {%0, %1, %2, %3, %4, %5, %6, %7, %8, %9, %10, %11, %12, %13, %14, %15, %16, %17, %18, %19, %20, %21, %22, %23, %24, %25, %26, %27, %28, %29, %30, %31, %32, %33, %34, %35, %36, %37, %38, %39, %40, %41, %42, %43, %44, %45, %46, %47, %48, %49, %50, %51, %52, %53, %54, %55, %56, %57, %58, %59, %60, %61, %62, %63}, {%64, %65, %66, %67}, %68, %69, 1, 1, 0;\n"
    : "+f"(d[0]), "+f"(d[1]), "+f"(d[2]), "+f"(d[3]), "+f"(d[4]), "+f"(d[5]), "+f"(d[6]), "+f"(d[7]), "+f"(d[8]), "+f"(d[9]), "+f"(d[10]), "+f"(d[11]), "+f"(d[12]), "+f"(d[13]), "+f"(d[14]), "+f"(d[15]), "+f"(d[16]), "+f"(d[17]), "+f"(d[18]), "+f"(d[19]), "+f"(d[20]), "+f"(d[21]), "+f"(d[22]), "+f"(d[23]), "+f"(d[24]), "+f"(d[25]), "+f"(d[26]), "+f"(d[27]), "+f"(d[28]), "+f"(d[29]), "+f"(d[30]), "+f"(d[31]), "+f"(d[32]), "+f"(d[33]), "+f"(d[34]), "+f"(d[35]), "+f"(d[36]), "+f"(d[37]), "+f"(d[38]), "+f"(d[39]), "+f"(d[40]), "+f"(d[41]), "+f"(d[42]), "+f"(d[43]), "+f"(d[44]), "+f"(d[45]), "+f"(d[46]), "+f"(d[47]), "+f"(d[48]), "+f"(d[49]), "+f"(d[50]), "+f"(d[51]), "+f"(d[52]), "+f"(d[53]), "+f"(d[54]), "+f"(d[55]), "+f"(d[56]), "+f"(d[57]), "+f"(d[58]), "+f"(d[59]), "+f"(d[60]), "+f"(d[61]), "+f"(d[62]), "+f"(d[63])
    : "r"(a0), "r"(a1), "r"(a2), "r"(a3), "l"(descB), "n"(SCALE_D));
}
template <int SCALE_D>
__device__ __forceinline__ void wgmma_rs_n24_tb(float (&d)[12], uint32_t a0, uint32_t a1, uint32_t a2, uint32_t a3, uint64_t descB) {
  asm volatile("wgmma.mma_async.sync.aligned.m64n24k16.f32.bf16.bf16 {%0, %1, %2, %3, %4, %5, %6, %7, %8, %9, %10, %11}, {%12, %13, %14, %15}, %16, %17, 1, 1, 1;\n"
    : "+f"(d[0]), "+f"(d[1]), "+f"(d[2]), "+f"(d[3]), "+f"(d[4]), "+f"(d[5]), "+f"(d[6]), "+f"(d[7]), "+f"(d[8]), "+f"(d[9]), "+f"(d[10]), "+f"(d[11])
    : "r"(a0), "r"(a1), "r"(a2), "r"(a3), "l"(descB), "n"(SCALE_D));
}

constexpr uint32_t DHI_SW128_K = (1024 >> 4) | (1u << 30);
constexpr uint32_t DHI_SW64_MN = (512 >> 4) | (2u << 30);

template <int NC>
__device__ __forceinline__ void store_tile_bf16(const float (&acc)[NC / 2], float scale, uint32_t stage, uint8_t* stage_ptr,
                                                __nv_bfloat16* gdst, int gpitch, int lane) {
  constexpr int PITCH = NC * 2 + 16;
  const uint32_t waddr = stage + ((lane & 7) + ((lane >> 3) & 1) * 8) * PITCH + (lane >> 4) * 16;
#pragma unroll
  for (int j = 0; j < NC / 16; j++) {
    stsm4(waddr + j * 32, pack_bf16(acc[8 * j] * scale, acc[8 * j + 1] * scale), pack_bf16(acc[8 * j + 2] * scale, acc[8 * j + 3] * scale),
          pack_bf16(acc[8 * j + 4] * scale, acc[8 * j + 5] * scale), pack_bf16(acc[8 * j + 6] * scale, acc[8 * j + 7] * scale));
  }
  __syncwarp();
  constexpr int CPR = NC / 8;
#pragma unroll
  for (int i = 0; i < CPR / 2; i++) {
    const int c = i * 32 + lane, r = c / CPR, cc = c % CPR;
    const uint4 v = *reinterpret_cast<const uint4*>(stage_ptr + r * PITCH + cc * 16);
    *reinterpret_cast<uint4*>(gdst + (size_t)r * gpitch + cc * 8) = v;
  }
}

__device__ __forceinline__ void signal_done(unsigned int* flag, int wg, int tid) {
  asm volatile("bar.sync %0, 128;" :: "r"(wg + 1) : "memory");
  if ((tid & 127) == 0) asm volatile("red.release.gpu.global.add.u32 [%0], 1;" :: "l"(flag) : "memory");
}
__device__ __forceinline__ void wait_flags8(const unsigned int* f, unsigned int target) {
  for (int spin = 0; spin < (1 << 26); spin++) {
    unsigned int a, b, c, d, e, g, h, i;
    asm volatile("ld.volatile.global.v4.u32 {%0, %1, %2, %3}, [%4];" : "=r"(a), "=r"(b), "=r"(c), "=r"(d) : "l"(f) : "memory");
    asm volatile("ld.volatile.global.v4.u32 {%0, %1, %2, %3}, [%4];" : "=r"(e), "=r"(g), "=r"(h), "=r"(i) : "l"(f + 4) : "memory");
    if (min(min(min(a, b), min(c, d)), min(min(e, g), min(h, i))) >= target) break;
    __nanosleep(32);
  }
  asm volatile("fence.acq_rel.gpu;" ::: "memory");
  asm volatile("fence.proxy.async;" ::: "memory");
}

#define RP_LD 3
#define RP_ST 7
constexpr int K1_STAGES = 4;
constexpr int K1_A_BYTES = 256 * 128;
constexpr int K1_B_BYTES = 64 * 160 * 2;
constexpr int K1_STAGE = K1_A_BYTES + K1_B_BYTES;
constexpr int K1_SMEM = 5 * K1_A_BYTES + 61440 + 1024;
constexpr int KV_STAGES = 5;
constexpr int KVW_OFF = KV_STAGES * K1_A_BYTES;

__global__ void __launch_bounds__(512, 1)
proj_kernel(const __grid_constant__ CUtensorMap tmX, const __grid_constant__ CUtensorMap tmWq, const __grid_constant__ CUtensorMap tmWqkv,
            const __nv_bfloat16* __restrict__ wk, const __nv_bfloat16* __restrict__ wv, const __nv_bfloat16* __restrict__ gate_w,
            const __nv_bfloat16* __restrict__ woA, const __nv_bfloat16* __restrict__ woB) {
  extern __shared__ uint8_t smem_raw[];
  __shared__ __align__(8) uint64_t bar_full[KV_STAGES], bar_empty[KV_STAGES];
  uint8_t* smem = reinterpret_cast<uint8_t*>((reinterpret_cast<uintptr_t>(smem_raw) + 1023) & ~(uintptr_t)1023);
  const uint32_t sbase = smem_u32(smem);
  const uint32_t dbase = sbase & 0x3FFFFu;
  const int tid = threadIdx.x, warp = tid >> 5, lane = tid & 31;
  const bool is_kv = blockIdx.x >= 128;
  PROF(0, 0);
  if (tid == 0) {
    for (int i = 0; i < KV_STAGES; i++) { mbar_init(smem_u32(&bar_full[i]), 1); mbar_init(smem_u32(&bar_empty[i]), is_kv ? 8 : 16); }
    fence_mbar_init();
  }
  uint2 wa[2][5], wb[2][5]; uint32_t gw[2];
  if (is_kv && tid < 320) {
#pragma unroll
    for (int r = 0; r < 2; r++) {
      const int k = tid + r * 320;
      const uint2* pk = reinterpret_cast<const uint2*>(wk + k * 20);
      const uint2* pv = reinterpret_cast<const uint2*>(wv + k * 20);
#pragma unroll
      for (int i = 0; i < 5; i++) { wa[r][i] = __ldg(pk + i); wb[r][i] = __ldg(pv + i); }
      gw[r] = (uint32_t)__bfloat16_as_ushort(gate_w[k]);
    }
  }
  __syncthreads();
  if (tid == 480) {
    if (!is_kv) { g_done[blockIdx.x] = 0u; g_doneL[blockIdx.x] = 0u; }
    asm volatile("fence.acq_rel.gpu;" ::: "memory");
    pdl_launch();
  }
  __syncwarp();

  if (!is_kv) {
    const int mb = blockIdx.x >> 4, nb = blockIdx.x & 15;
    const CUtensorMap* tw = nb < 4 ? &tmWq : &tmWqkv;
    const int j0 = (nb < 4 ? nb : nb - 4) * 5;
    auto load = [&](int kt) {
      const int s = kt % K1_STAGES;
      const uint32_t fb = smem_u32(&bar_full[s]);
      mbar_expect_tx(fb, K1_STAGE);
      tma_2d(sbase + s * K1_STAGE, &tmX, kt * 64, mb * 256, fb);
      tma_3d(sbase + s * K1_STAGE + K1_A_BYTES, tw, 0, kt * 64, j0, fb);
    };
    if (tid == 0) for (int kt = 0; kt < K1_STAGES; kt++) load(kt);
    __syncwarp();
    uint4 wv2[2];
    const int rq = blockIdx.x * 400 + tid - 112;
    const int rhalf = rq >= 25600, rr = rq - rhalf * 25600, rk = 2 * (rr / 80), rch = rr % 80;
    {
      const int wg = warp >> 2;
      float acc[80];
#pragma unroll
      for (int i = 0; i < 80; i++) acc[i] = 0.f;
      for (int kt = 0; kt < 10; kt++) {
        const int s = kt % K1_STAGES;
        mbar_wait(smem_u32(&bar_full[s]), (kt / K1_STAGES) & 1);
        const uint32_t alo = ((dbase + s * K1_STAGE + wg * 8192) >> 4) | (1u << 16);
        const uint32_t blo = ((dbase + s * K1_STAGE + K1_A_BYTES) >> 4) | ((4096u >> 4) << 16);
        fence_regs(acc);
        wg_fence();
#pragma unroll
        for (int k = 0; k < 4; k++) wgmma_ss_n160_tb(acc, mkd(alo + k * 2, DHI_SW128_K), mkd(blo + k * 64, DHI_SW64_MN));
        wg_commit();
        if (kt == RP_LD && tid >= 112) {
          const uint4* src = reinterpret_cast<const uint4*>((rhalf ? woB : woA) + rk * D_MODEL + rch * 8);
          wv2[0] = __ldg(src); wv2[1] = __ldg(src + D_MODEL / 8);
        }
        if (kt == RP_ST && tid >= 112) {
          uint4* dst = reinterpret_cast<uint4*>(g_wimg + ((rhalf * 8 + rch / 10) * 10 + (rk >> 6)) * 10240 + (rch % 10) * 1024 + (rk & 63) * 16);
          dst[0] = wv2[0]; dst[1] = wv2[1];
        }
        __syncwarp();
        if (kt > 0 && kt - 1 + K1_STAGES < 10) {
          wg_wait<1>();
          const uint32_t eb = smem_u32(&bar_empty[(kt - 1) % K1_STAGES]);
          if (lane == 0) mbar_arrive(eb);
          if (tid == 0) { mbar_wait(eb, ((kt - 1) / K1_STAGES) & 1); load(kt - 1 + K1_STAGES); }
          __syncwarp();
        }
      }
      wg_wait<0>();
      fence_regs(acc);
      PROF(0, 1);
      asm volatile("bar.sync %0, 128;" :: "r"(wg + 1) : "memory");
      const int w4 = warp & 3;
      const uint32_t off = w4 * K1_STAGE + wg * 8192;
      const int row0 = mb * 256 + wg * 64 + w4 * 16;
      if (nb < 4) {
        store_tile_bf16<160>(acc, 0.22360679774997896f * 1.4426950408889634f, sbase + off, smem + off,
                             g_q + (size_t)row0 * D_MODEL + nb * 160, D_MODEL, lane);
      } else {
        store_tile_bf16<160>(acc, 1.0f, sbase + off, smem + off, g_qkv + (size_t)row0 * (3 * D_MODEL) + (nb - 4) * 160, 3 * D_MODEL, lane);
      }
    }
  } else {
    const int cb = blockIdx.x - 128;
    if (warp == 8 && lane == 0) {
      for (int it = 0; it < KV_STAGES; it++) {
        const uint32_t fb = smem_u32(&bar_full[it]);
        mbar_expect_tx(fb, K1_A_BYTES);
        tma_2d(sbase + it * K1_A_BYTES, &tmX, it * 64, cb * 512, fb);
      }
    }
    __syncwarp();
    if (tid < 320) {
#pragma unroll
      for (int r = 0; r < 2; r++) {
        uint4* dst = reinterpret_cast<uint4*>(smem + KVW_OFF + (tid + r * 320) * 16);
        dst[0] = make_uint4(wa[r][0].x, wa[r][0].y, wa[r][1].x, wa[r][1].y);
        dst[640] = make_uint4(wa[r][2].x, wa[r][2].y, wa[r][3].x, wa[r][3].y);
        dst[1280] = make_uint4(wa[r][4].x, wa[r][4].y, 0u, 0u);
        dst[1920] = make_uint4(wb[r][0].x, wb[r][0].y, wb[r][1].x, wb[r][1].y);
        dst[2560] = make_uint4(wb[r][2].x, wb[r][2].y, wb[r][3].x, wb[r][3].y);
        dst[3200] = make_uint4(wb[r][4].x, wb[r][4].y, gw[r], 0u);
      }
    }
    fence_proxy_async();
    asm volatile("bar.sync 1, 512;" ::: "memory");
    PROF(0, 1);
    auto produce = [&](int it0, int it1) {
      for (int it = it0; it < it1; it++) {
        const int s = it % KV_STAGES;
        mbar_wait(smem_u32(&bar_empty[s]), (it / KV_STAGES - 1) & 1);
        const uint32_t fb = smem_u32(&bar_full[s]);
        mbar_expect_tx(fb, K1_A_BYTES);
        tma_2d(sbase + s * K1_A_BYTES, &tmX, (it >= 10 ? it - 10 : it) * 64, cb * 512 + (it >= 10 ? 256 : 0), fb);
      }
    };
    if (tid == 256) produce(KV_STAGES, 15);
    __syncwarp();
    {
      const int pass = warp >> 3, wg = (warp >> 2) & 1, w4 = warp & 3, g = lane >> 2, t = lane & 3;
      if (pass == 1) asm volatile("bar.sync 2, 512;" ::: "memory");
      {
        float acc[2][24];
#pragma unroll
        for (int i = 0; i < 24; i++) { acc[0][i] = 0.f; acc[1][i] = 0.f; }
        for (int kt = 0; kt < 10; kt++) {
          const int it = pass * 10 + kt, s = it % KV_STAGES;
          mbar_wait(smem_u32(&bar_full[s]), (it / KV_STAGES) & 1);
          const uint32_t alo = ((dbase + s * K1_A_BYTES + wg * 16384) >> 4) | (1u << 16);
          const uint32_t blo = ((dbase + KVW_OFF + kt * 1024) >> 4) | ((128u >> 4) << 16);
          fence_regs(acc[0]); fence_regs(acc[1]);
          wg_fence();
#pragma unroll
          for (int k = 0; k < 4; k++) {
            wgmma_ss_n48_tb(acc[0], mkd(alo + k * 2, DHI_SW128_K), mkd(blo + k * 16, 10240u >> 4));
            wgmma_ss_n48_tb(acc[1], mkd(alo + 512 + k * 2, DHI_SW128_K), mkd(blo + k * 16, 10240u >> 4));
          }
          wg_commit();
          if (kt > 0) {
            wg_wait<1>();
            if (lane == 0) mbar_arrive(smem_u32(&bar_empty[(it - 1) % KV_STAGES]));
          }
        }
        wg_wait<0>();
        fence_regs(acc[0]); fence_regs(acc[1]);
        if (lane == 0) mbar_arrive(smem_u32(&bar_empty[(pass * 10 + 9) % KV_STAGES]));
        if (pass == 0) asm volatile("bar.arrive 2, 512;" ::: "memory");
        PROF(0, 2);
        if (tid == 0) produce(15, 20);
        __syncwarp();
        float kmax2 = 0.f, vmax = 0.f;
#pragma unroll
        for (int hh = 0; hh < 4; hh++) {
          const int h = hh & 1;
          const float (&a)[24] = acc[hh >> 1];
          const int key = cb * 512 + pass * 256 + wg * 128 + (hh >> 1) * 64 + w4 * 16 + g + h * 8;
          const int grp = key >> 7, kk = key & 127;
          const bool poly = (TMASK >> (kk >> 3)) & 1;
          uint8_t* gp = g_kvimg + grp * GRP_BYTES;
          const uint32_t k0 = pack_bf16(a[2 * h], a[2 * h + 1]);
          const uint32_t k1 = pack_bf16(a[4 + 2 * h], a[5 + 2 * h]);
          uint32_t k2 = pack_bf16(a[8 + 2 * h], a[9 + 2 * h]);
          float n2 = bf_lo(k0) * bf_lo(k0) + bf_hi(k0) * bf_hi(k0) + bf_lo(k1) * bf_lo(k1) + bf_hi(k1) * bf_hi(k1);
          if (t < 2) {
            n2 += bf_lo(k2) * bf_lo(k2) + bf_hi(k2) * bf_hi(k2);
            k2 = pack_bf16(bf_lo(k2) * 0.5f, bf_hi(k2) * 0.5f);
          } else if (t == 2) k2 = poly ? pack_bf16(24.f, 2.5f) : pack_bf16(0.5f, 0.f);
          else k2 = poly ? pack_bf16(0.5f, 0.f) : 0u;
          *reinterpret_cast<uint32_t*>(gp + kk * 16 + t * 4) = k0;
          *reinterpret_cast<uint32_t*>(gp + PLANE + kk * 16 + t * 4) = k1;
          *reinterpret_cast<uint32_t*>(gp + 2 * PLANE + kk * 16 + t * 4) = k2;
          n2 += __shfl_xor_sync(0xffffffffu, n2, 1);
          n2 += __shfl_xor_sync(0xffffffffu, n2, 2);
          kmax2 = (n2 > kmax2 || n2 != n2) ? n2 : kmax2;
          uint32_t v0 = pack_bf16(a[12 + 2 * h], a[13 + 2 * h]);
          uint32_t v1 = pack_bf16(a[16 + 2 * h], a[17 + 2 * h]);
          uint32_t v2 = pack_bf16(a[20 + 2 * h], a[21 + 2 * h]);
          float vm = fmaxf(fmaxf(fabsf(bf_lo(v0)), fabsf(bf_hi(v0))), fmaxf(fabsf(bf_lo(v1)), fabsf(bf_hi(v1))));
          if (t < 2) vm = fmaxf(vm, fmaxf(fabsf(bf_lo(v2)), fabsf(bf_hi(v2))));
          else if (t == 2) {
            const float z = a[20 + 2 * h];
            g_gate[key] = 1.f / (1.f + __expf(-z));
            v2 = 0x00003F80u;
          } else v2 = 0u;
          vmax = fmaxf(vmax, vm);
          if (poly) { v0 ^= 0x80008000u; v1 ^= 0x80008000u; v2 ^= 0x80008000u; }
          uint8_t* vp = gp + 3 * PLANE + (kk >> 3) * 384 + (kk & 7) * 16 + t * 4;
          *reinterpret_cast<uint32_t*>(vp) = v0;
          *reinterpret_cast<uint32_t*>(vp + 128) = v1;
          *reinterpret_cast<uint32_t*>(vp + 256) = v2;
        }
#pragma unroll
        for (int o = 1; o < 32; o <<= 1) {
          const float a = __shfl_xor_sync(0xffffffffu, kmax2, o);
          kmax2 = (a > kmax2 || a != a) ? a : kmax2;
          vmax = fmaxf(vmax, __shfl_xor_sync(0xffffffffu, vmax, o));
        }
        if (lane == 0) { g_kmax2[cb * 16 + warp] = kmax2; g_vmax[cb * 16 + warp] = vmax; }
      }
    }
  }
}

__device__ __forceinline__ uint32_t ex2_pair_poly(float u0, float u1, uint32_t one2) {
  const uint32_t W = __byte_perm(__float_as_uint(u0), __float_as_uint(u1), 0x6521);
  uint32_t v; asm("lop3.b32 %0, %1, 0x007F007F, %2, 0xEA;" : "=r"(v) : "r"(W), "r"(one2));
  uint32_t L, p;
  asm("fma.rn.bf16x2 %0, %1, %2, %3;" : "=r"(L) : "r"(v), "r"(0x1f961f96u), "r"(0x9fe39fe3u));
  asm("fma.rn.bf16x2 %0, %1, %1, %2;" : "=r"(p) : "r"(L), "r"(0x00f500f5u));
  return W + p;
}
template <int JOFF>
__device__ __forceinline__ void softmax_slow(const float (&S)[32], uint32_t (&P)[16], float (&O)[12], float& m0, float& m1) {
  float a0 = m0, a1 = m1;
#pragma unroll
  for (int j = 0; j < 8; j++) {
    a0 = fmaxf(a0, fmaxf(S[4 * j], S[4 * j + 1]));
    a1 = fmaxf(a1, fmaxf(S[4 * j + 2], S[4 * j + 3]));
  }
  a0 = fmaxf(a0, __shfl_xor_sync(0xffffffffu, a0, 1)); a0 = fmaxf(a0, __shfl_xor_sync(0xffffffffu, a0, 2));
  a1 = fmaxf(a1, __shfl_xor_sync(0xffffffffu, a1, 1)); a1 = fmaxf(a1, __shfl_xor_sync(0xffffffffu, a1, 2));
  const float c0 = ex2(m0 - a0), c1 = ex2(m1 - a1);
  m0 = a0; m1 = a1;
#pragma unroll
  for (int j = 0; j < 3; j++) { O[4 * j] *= c0; O[4 * j + 1] *= c0; O[4 * j + 2] *= c1; O[4 * j + 3] *= c1; }
#pragma unroll
  for (int i = 0; i < 16; i++) {
    const float m = (i & 1) ? a1 : a0;
    const uint32_t p = pack_bf16(ex2(S[2 * i] - m), ex2(S[2 * i + 1] - m));
    P[i] = ((TMASK >> (JOFF + i / 2)) & 1) ? (p ^ 0x80008000u) : p;
  }
}
constexpr uint32_t DHI_KV = 128 >> 4;
__device__ __forceinline__ void issue_qk(float (&S)[32], const uint32_t (&q)[8], uint64_t base) {
  wgmma_rs_n64<0>(S, q[0], q[1], q[2], q[3], base + (uint64_t)((PLANE >> 4) << 16));
  wgmma_rs_n64<1>(S, q[4], q[5], q[6], q[7], base + (uint64_t)(2 * PLANE >> 4));
}
__device__ __forceinline__ void issue_pv(float (&O)[12], const uint32_t (&P)[16], uint64_t vbase) {
#pragma unroll
  for (int kk = 0; kk < 4; kk++)
    wgmma_rs_n24_tb<1>(O, P[4 * kk], P[4 * kk + 1], P[4 * kk + 2], P[4 * kk + 3], vbase + (uint64_t)(kk * (768 >> 4)));
}

constexpr uint32_t VOFF = ((3 * PLANE) >> 4) + ((384u >> 4) << 16);
constexpr int KVR = 4;
constexpr int OFF_W = KVR * GRP_BYTES;
constexpr int OFF_X = OFF_W + 10 * 10240;
constexpr int OFF_BAR = OFF_X + 4 * 16384;
constexpr int K2_SMEM = OFF_BAR + 512 + 1024;
constexpr int TSL = 7;
constexpr int BAR_KV = 0, BAR_W = 4, BAR_TA = 5, BAR_TE = 12, BAR_OWN = 19, BAR_L = 20, CNT_KV = 21, BAR_WA = 23, BAR_WF = 33, CNT_TK = 43;
constexpr int NSTEP = 2 * NGRP;

__device__ __forceinline__ void kv_load(uint32_t sbase, int step) {
  const uint32_t bar = sbase + OFF_BAR + (BAR_KV + (step & (KVR - 1))) * 8;
  mbar_expect_tx(bar, GRP_BYTES);
  bulk_g2s(sbase + (step & (KVR - 1)) * GRP_BYTES, g_kvimg + (step & (NGRP - 1)) * GRP_BYTES, GRP_BYTES, bar);
}
__device__ __forceinline__ void kv_release(uint32_t sbase, int step, bool elected) {
  if (elected && step + KVR < NSTEP) {
    uint32_t old;
    asm volatile("atom.acq_rel.cta.shared::cta.inc.u32 %0, [%1], 3;" : "=r"(old) : "r"(sbase + OFF_BAR + CNT_KV * 8 + (step & (KVR - 1)) * 4) : "memory");
    if (old == 3u) kv_load(sbase, step + KVR);
  }
  __syncwarp();
}
__device__ __forceinline__ void kv_wait(uint32_t sbase, int step) {
  mbar_wait(sbase + OFF_BAR + (BAR_KV + (step & (KVR - 1))) * 8, (step / KVR) & 1);
}

__device__ __forceinline__ uint32_t kv_release_begin(uint32_t sbase, int slot, bool doit) {
  uint32_t old = 0;
  asm volatile("{\n.reg .pred p;\nsetp.ne.u32 p, %2, 0;\n@p atom.relaxed.cta.shared::cta.inc.u32 %0, [%1], 3;\n}\n"
               : "+r"(old) : "r"(sbase + OFF_BAR + CNT_KV * 8 + slot * 4), "r"((uint32_t)doit) : "memory");
  return old;
}
template <int H>
__device__ __forceinline__ void softmax_half(const float (&S)[64], uint32_t (&P)[16], uint32_t one2) {
#pragma unroll
  for (int i = 0; i < 16; i++) {
    if ((TMASK >> (8 * H + i / 2)) & 1) P[i] = ex2_pair_poly(S[32 * H + 2 * i], S[32 * H + 2 * i + 1], one2);
    else P[i] = pack_bf16(ex2(S[32 * H + 2 * i]), ex2(S[32 * H + 2 * i + 1]));
  }
}
__device__ __forceinline__ void attn_fast(const uint32_t (&q)[8], float (&O)[12], uint32_t sbase, int step0, int nsteps, bool elected, uint32_t one2) {
  uint64_t kb0 = mkd((sbase & 0x3FFFFu) >> 4, DHI_KV);
  asm volatile("" : "+l"(kb0));
#pragma unroll 1
  for (int step4 = step0; step4 < step0 + nsteps; step4 += KVR) {
#pragma unroll
    for (int j = 0; j < KVR; j++) {
      const int step = step4 + j;
      const uint64_t kb = kb0 + (uint64_t)(j * (GRP_BYTES >> 4));
      float S[64]; uint32_t PA[16], PB[16];
#pragma unroll
      for (int i = 0; i < 64; i++) S[i] = 0.f;
      mbar_wait(sbase + OFF_BAR + (BAR_KV + j) * 8, (step / KVR) & 1);
      fence_regs(S);
      wg_fence();
      wgmma_rs_n128<0>(S, q[0], q[1], q[2], q[3], kb + (uint64_t)((PLANE >> 4) << 16));
      wgmma_rs_n128<1>(S, q[4], q[5], q[6], q[7], kb + (uint64_t)(2 * PLANE >> 4));
      wg_commit();
      const uint32_t old = kv_release_begin(sbase, (j + KVR - 1) & (KVR - 1), elected && step > step0 && step - 1 + KVR < NSTEP);
      wg_wait<0>();
      fence_regs(S);
      softmax_half<0>(S, PA, one2);
      fence_regs(PA); fence_regs(O);
      wg_fence();
      issue_pv(O, PA, kb + VOFF);
      wg_commit();
      softmax_half<1>(S, PB, one2);
      fence_regs(PB);
      wg_fence();
      issue_pv(O, PB, kb + VOFF + 4 * (768 >> 4));
      wg_commit();
      if (old == 3u) kv_load(sbase, step - 1 + KVR);
      wg_wait<0>();
      fence_regs(PA); fence_regs(PB); fence_regs(O);
    }
  }
  kv_release(sbase, step0 + nsteps - 1, elected);
}
template <int H>
__device__ __forceinline__ void slow_step(const uint32_t (&q)[8], float (&O)[12], uint64_t kb, float& m0, float& m1) {
  float S[32]; uint32_t P[16];
#pragma unroll
  for (int i = 0; i < 32; i++) S[i] = 0.f;
  fence_regs(S);
  wg_fence();
  issue_qk(S, q, kb + 64 * H);
  wg_commit();
  wg_wait<0>();
  fence_regs(S);
  softmax_slow<8 * H>(S, P, O, m0, m1);
  fence_regs(P); fence_regs(O);
  wg_fence();
  issue_pv(O, P, kb + VOFF + H * 4 * (768 >> 4));
  wg_commit();
  wg_wait<0>();
  fence_regs(O); fence_regs(P);
}
__device__ __forceinline__ void attn_slow(const uint32_t (&q)[8], float (&O)[12], uint32_t sbase, int step0, int nsteps, bool elected, float& m0, float& m1) {
#pragma unroll 1
  for (int step = step0; step < step0 + nsteps; step++) {
    kv_wait(sbase, step);
    const uint64_t kb = mkd(((sbase & 0x3FFFFu) >> 4) + (step & (KVR - 1)) * (GRP_BYTES >> 4), DHI_KV);
    slow_step<0>(q, O, kb, m0, m1);
    slow_step<1>(q, O, kb, m0, m1);
    kv_release(sbase, step, elected);
  }
}

__device__ __forceinline__ void softmax8(float (&sc)[8], float scale) {
  float mx = sc[0];
#pragma unroll
  for (int w = 1; w < 8; w++) mx = fmaxf(mx, sc[w]);
  float l = 0.f;
#pragma unroll
  for (int w = 0; w < 8; w++) { sc[w] = ex2(sc[w] - mx); l += sc[w]; }
  const float r = __fdividef(scale, l);
#pragma unroll
  for (int w = 0; w < 8; w++) sc[w] *= r;
}
#define LEV(wg) 1
constexpr int LBOX = 30 * 320;
__device__ __forceinline__ uint2 lds64(uint32_t a) {
  uint2 v; asm volatile("ld.shared.v2.u32 {%0, %1}, [%2];" : "=r"(v.x), "=r"(v.y) : "r"(a)); return v;
}
__device__ __forceinline__ void local_attn(uint32_t stage, int t0, int i, int lane) {
  constexpr float SC = 0.22360679774997896f * 1.4426950408889634f, NEG = -1e9f * 1.4426950408889634f;
  const uint32_t base = stage + (lane >> 3) * LBOX + (lane & 7) * 40 + (i + 14) * 320;
  const int t = t0 + i;
  float sc[8];
#pragma unroll
  for (int w = 0; w < 8; w++) sc[w] = 0.f;
#pragma unroll 1
  for (int c = 0; c < 5; c++) {
    const uint2 qv = lds64(base + c * 8);
    const float q0 = bf_lo(qv.x), q1 = bf_hi(qv.x), q2 = bf_lo(qv.y), q3 = bf_hi(qv.y);
#pragma unroll
    for (int w = 0; w < 8; w++) {
      const uint2 k = lds64(base + c * 8 + 4 * LBOX - w * 640);
      sc[w] = fmaf(q0, bf_lo(k.x), sc[w]); sc[w] = fmaf(q1, bf_hi(k.x), sc[w]);
      sc[w] = fmaf(q2, bf_lo(k.y), sc[w]); sc[w] = fmaf(q3, bf_hi(k.y), sc[w]);
    }
  }
#pragma unroll
  for (int w = 0; w < 8; w++) sc[w] = t - 2 * w >= 0 ? sc[w] * SC : NEG;
  softmax8(sc, 1.f - g_gate[t]);
  uint2* dst = reinterpret_cast<uint2*>(g_a2 + (size_t)t * (2 * D_MODEL) + D_MODEL + lane * DH);
#pragma unroll 1
  for (int c = 0; c < 5; c++) {
    float o0 = 0.f, o1 = 0.f, o2 = 0.f, o3 = 0.f;
#pragma unroll
    for (int w = 0; w < 8; w++) {
      const uint2 v = lds64(base + c * 8 + 8 * LBOX - w * 640);
      o0 = fmaf(sc[w], bf_lo(v.x), o0); o1 = fmaf(sc[w], bf_hi(v.x), o1);
      o2 = fmaf(sc[w], bf_lo(v.y), o2); o3 = fmaf(sc[w], bf_hi(v.y), o3);
    }
    dst[c] = make_uint2(pack_bf16(o0, o1), pack_bf16(o2, o3));
  }
}
__device__ __forceinline__ uint32_t ta_slot(int i) { return i < 4 ? OFF_X + i * 16384 : (i - 4) * 16384; }

__global__ void __launch_bounds__(640, 1)
attn_kernel(const __grid_constant__ CUtensorMap tmA2, const __grid_constant__ CUtensorMap tmL, __nv_bfloat16* __restrict__ out, uint32_t one2) {
  extern __shared__ uint8_t smem_raw[];
  uint8_t* smem = reinterpret_cast<uint8_t*>((reinterpret_cast<uintptr_t>(smem_raw) + 1023) & ~(uintptr_t)1023);
  const uint32_t sbase = smem_u32(smem);
  const uint32_t dbase = sbase & 0x3FFFFu;
  const uint32_t bars = sbase + OFF_BAR;
  const int tid = threadIdx.x, wg = tid >> 7, warp = (tid >> 5) & 3, lane = tid & 31, g = lane >> 2, t = lane & 3;
  const int mb = blockIdx.x >> 3, nb = blockIdx.x & 7;
  const bool elected = (tid & 127) == 0;
  if (tid == 0) {
    for (int i = 0; i < BAR_TE; i++) mbar_init(bars + i * 8, 1);
    for (int i = BAR_TE; i < BAR_TE + TSL; i++) mbar_init(bars + i * 8, 8);
    mbar_init(bars + BAR_OWN * 8, 4);
    mbar_init(bars + BAR_L * 8, 1);
    for (int i = 0; i < 10; i++) { mbar_init(bars + (BAR_WA + i) * 8, 1); mbar_init(bars + (BAR_WF + i) * 8, 8); }
    for (int i = 0; i < 4; i++) *reinterpret_cast<uint32_t*>(smem + OFF_BAR + CNT_KV * 8 + i * 4) = 0u;
    *reinterpret_cast<uint32_t*>(smem + OFF_BAR + CNT_TK * 8) = 0u;
    fence_mbar_init();
  }
  __syncthreads();
  auto tail_load = [&](int i) {
    const uint32_t fb = bars + (BAR_TA + i % TSL) * 8;
    mbar_expect_tx(fb, 16384);
    tma_2d(sbase + ta_slot(i % TSL), &tmA2, i < 10 ? D_MODEL + i * 64 : (i - 10) * 64, mb * 128, fb);
  };
  if (wg == 4) {
    asm volatile("setmaxnreg.dec.sync.aligned.u32 32;");
    pdl_wait();
    if (tid == 512) {
      for (int j = 0; j < KVR; j++) kv_load(sbase, j);
      mbar_expect_tx(bars + BAR_L * 8, 12 * LBOX);
      for (int i = 0; i < 12; i++) tma_2d(sbase + OFF_W + i * LBOX, &tmL, i * 160, blockIdx.x * 16 - 14, bars + BAR_L * 8);
    }
    __syncwarp();
    mbar_wait(bars + BAR_L * 8, 0);
#pragma unroll 1
    for (int i = 0; i < 4; i++) local_attn(sbase + OFF_W, blockIdx.x * 16, warp * 4 + i, lane);
    signal_done(&g_doneL[blockIdx.x], wg, tid);
    if (tid == 512) {
      PROF2(0, 2);
      fence_proxy_async();
      mbar_expect_tx(bars + BAR_W * 8, 10 * 10240);
      for (int i = 0; i < 5; i++) bulk_g2s(sbase + OFF_W + i * 20480, g_wimg + ((8 + nb) * 10) * 10240 + i * 20480, 20480, bars + BAR_W * 8);
      wait_flags8(&g_doneL[mb * 8], 1u);
      for (int i = 0; i < 4; i++) tail_load(i);
      mbar_wait(bars + BAR_OWN * 8, 0);
      for (int i = 4; i < 20; i++) {
        if (i >= TSL) mbar_wait(bars + (BAR_TE + i % TSL) * 8, (i / TSL - 1) & 1);
        if (i == 10) { wait_flags8(&g_done[mb * 8], 1u); PROF2(2, 0); }
        tail_load(i);
      }
    } else if (tid == 576) {
      mbar_wait(bars + BAR_OWN * 8, 0);
      asm volatile("red.release.gpu.global.add.u32 [%0], 1;" :: "l"(&g_done[blockIdx.x]) : "memory");
    } else if (tid == 544) {
      for (int kt = 0; kt < 10; kt++) {
        mbar_wait(bars + (BAR_WF + kt) * 8, 0);
        mbar_expect_tx(bars + (BAR_WA + kt) * 8, 10240);
        bulk_g2s(sbase + OFF_W + kt * 10240, g_wimg + (nb * 10 + kt) * 10240, 10240, bars + (BAR_WA + kt) * 8);
      }
    }
    return;
  }
  asm volatile("setmaxnreg.inc.sync.aligned.u32 112;");
  pdl_wait();
  PROF(1, 1);
  uint32_t q[8], q2[6];
  const int rowA = (blockIdx.x * 8 + wg) * 64 + warp * 16 + g;
  {
    const uint32_t* r0 = reinterpret_cast<const uint32_t*>(g_q + (size_t)rowA * DH);
    const uint32_t* r1 = r0 + 8 * (DH / 2);
    const uint32_t* s0 = r0 + 256 * (DH / 2);
    const uint32_t* s1 = s0 + 8 * (DH / 2);
    q[0] = r0[t]; q[1] = r1[t]; q[2] = r0[t + 4]; q[3] = r1[t + 4];
    q[4] = t < 2 ? r0[8 + t] : 0u;
    q[5] = t < 2 ? r1[8 + t] : 0u;
    q2[0] = s0[t]; q2[1] = s1[t]; q2[2] = s0[t + 4]; q2[3] = s1[t + 4];
    q2[4] = t < 2 ? s0[8 + t] : 0u;
    q2[5] = t < 2 ? s1[8 + t] : 0u;
  }
  float kmax2 = 0.f, vmax = 0.f;
#pragma unroll
  for (int i = 0; i < 2; i++) {
    const float a = g_kmax2[lane + 32 * i];
    kmax2 = (a > kmax2 || a != a) ? a : kmax2;
    vmax = fmaxf(vmax, g_vmax[lane + 32 * i]);
  }
#pragma unroll
  for (int o = 1; o < 32; o <<= 1) {
    const float a = __shfl_xor_sync(0xffffffffu, kmax2, o);
    kmax2 = (a > kmax2 || a != a) ? a : kmax2;
    vmax = fmaxf(vmax, __shfl_xor_sync(0xffffffffu, vmax, o));
  }
  const float qlim = (vmax >= 0.00390625f && vmax <= 256.f) ? 9025.f / kmax2 : -1.f;
  PROF(1, 2);
#pragma unroll 1
  for (int it = 0; it < 2; it++) {
    const int row0 = rowA + it * 256;
    if (it == 1) {
#pragma unroll
      for (int i = 0; i < 6; i++) q[i] = q2[i];
    }
    float n0 = bf_lo(q[0]) * bf_lo(q[0]) + bf_hi(q[0]) * bf_hi(q[0]) + bf_lo(q[2]) * bf_lo(q[2]) + bf_hi(q[2]) * bf_hi(q[2]) +
               bf_lo(q[4]) * bf_lo(q[4]) + bf_hi(q[4]) * bf_hi(q[4]);
    float n1 = bf_lo(q[1]) * bf_lo(q[1]) + bf_hi(q[1]) * bf_hi(q[1]) + bf_lo(q[3]) * bf_lo(q[3]) + bf_hi(q[3]) * bf_hi(q[3]) +
               bf_lo(q[5]) * bf_lo(q[5]) + bf_hi(q[5]) * bf_hi(q[5]);
    n0 += __shfl_xor_sync(0xffffffffu, n0, 1); n0 += __shfl_xor_sync(0xffffffffu, n0, 2);
    n1 += __shfl_xor_sync(0xffffffffu, n1, 1); n1 += __shfl_xor_sync(0xffffffffu, n1, 2);
    const bool safe = (n0 <= qlim) && (n1 <= qlim);
    uint32_t unsafe_any;
    asm volatile("{\n.reg .pred p, r;\nsetp.eq.u32 p, %1, 0;\nbarrier.cta.red.or.pred r, %2, 128, p;\nselp.u32 %0, 1, 0, r;\n}\n"
                 : "=r"(unsafe_any) : "r"((uint32_t)safe), "r"(wg + 1) : "memory");
    float O[12];
#pragma unroll
    for (int i = 0; i < 12; i++) O[i] = 0.f;
    if (!unsafe_any && t >= 2) { q[4] = q[5] = (t == 2) ? 0x3F804100u : 0x00003B80u; }
    q[6] = q[4]; q[7] = q[5];
    fence_regs(q);
    float m0 = -INFINITY, m1 = -INFINITY;
    if (!unsafe_any) attn_fast(q, O, sbase, it * NGRP, NGRP, elected, one2);
    else attn_slow(q, O, sbase, it * NGRP, NGRP, elected, m0, m1);
    const float l0 = __shfl_sync(0xffffffffu, O[8], (lane & ~3) | 2);
    const float l1 = __shfl_sync(0xffffffffu, O[10], (lane & ~3) | 2);
    const int tok = row0 >> 5;
    const float gt = g_gate[tok];
    const float i0 = gt / l0, i1 = gt / l1;
    uint32_t* o0 = reinterpret_cast<uint32_t*>(g_a2 + (size_t)tok * (2 * D_MODEL) + (row0 & 31) * DH);
    uint32_t* o1 = o0 + 8 * (DH / 2);
    o0[t] = pack_bf16(O[0] * i0, O[1] * i0); o1[t] = pack_bf16(O[2] * i1, O[3] * i1);
    o0[t + 4] = pack_bf16(O[4] * i0, O[5] * i0); o1[t + 4] = pack_bf16(O[6] * i1, O[7] * i1);
    if (t < 2) { o0[t + 8] = pack_bf16(O[8] * i0, O[9] * i0); o1[t + 8] = pack_bf16(O[10] * i1, O[11] * i1); }
  }
  uint32_t* ticket = reinterpret_cast<uint32_t*>(smem + OFF_BAR + CNT_TK * 8);
  if (elected) ticket[1 + wg] = atomicAdd(ticket, 1u);
  asm volatile("bar.sync %0, 128;" :: "r"(wg + 1) : "memory");
  if (elected) mbar_arrive(bars + BAR_OWN * 8);
  const int mt = ticket[1 + wg];
  PROF(1, 3);
  if (mt < 2) {
    float acc[40];
#pragma unroll
    for (int i = 0; i < 40; i++) acc[i] = 0.f;
    mbar_wait(bars + BAR_W * 8, 0);
    int sl = 0, ph = 0;
#pragma unroll 1
    for (int i = 0; i < 20; i++) {
      mbar_wait(bars + (BAR_TA + sl) * 8, ph);
      if (i >= 10) mbar_wait(bars + (BAR_WA + i - 10) * 8, 0);
      const uint32_t alo = ((dbase + ta_slot(sl) + mt * 8192) >> 4) | (1u << 16);
      const uint32_t blo = ((dbase + OFF_W + (i >= 10 ? i - 10 : i) * 10240) >> 4) | ((128u >> 4) << 16);
      fence_regs(acc);
      wg_fence();
#pragma unroll
      for (int k = 0; k < 4; k++) wgmma_ss_n80_tb(acc, mkd(alo + k * 2, DHI_SW128_K), mkd(blo + k * 16, 1024u >> 4));
      wg_commit();
      if (i > 0) {
        wg_wait<1>();
        if (lane == 0) mbar_arrive(bars + (BAR_TE + (sl == 0 ? TSL - 1 : sl - 1)) * 8);
        if (lane == 1 && i <= 10) mbar_arrive(bars + (BAR_WF + i - 1) * 8);
      }
      if (++sl == TSL) { sl = 0; ph ^= 1; }
    }
    wg_wait<0>();
    fence_regs(acc);
    asm volatile("bar.sync %0, 128;" :: "r"(wg + 1) : "memory");
    const uint32_t so = ta_slot(warp) + mt * 8192;
    const int row0 = mb * 128 + mt * 64 + warp * 16;
    store_tile_bf16<80>(acc, 1.0f, sbase + so, smem + so, out + (size_t)row0 * D_MODEL + nb * 80, D_MODEL, lane);
  }
}

typedef CUresult (*EncodeFn)(CUtensorMap*, CUtensorMapDataType, cuuint32_t, void*, const cuuint64_t*, const cuuint64_t*,
                             const cuuint32_t*, const cuuint32_t*, CUtensorMapInterleave, CUtensorMapSwizzle,
                             CUtensorMapL2promotion, CUtensorMapFloatOOBfill);

void make_map(EncodeFn fn, CUtensorMap* tm, const void* ptr, int rank, const cuuint64_t* dims, const cuuint64_t* strides,
              const cuuint32_t* box, CUtensorMapSwizzle sw) {
  const cuuint32_t es[3] = {1, 1, 1};
  fn(tm, CU_TENSOR_MAP_DATA_TYPE_BFLOAT16, rank, const_cast<void*>(ptr), dims, strides, box, es, CU_TENSOR_MAP_INTERLEAVE_NONE, sw,
     CU_TENSOR_MAP_L2_PROMOTION_L2_256B, CU_TENSOR_MAP_FLOAT_OOB_FILL_NONE);
}
void map_a(EncodeFn fn, CUtensorMap* tm, const void* p, int rows, int cols, int box_rows) {
  const cuuint64_t dims[2] = {(cuuint64_t)cols, (cuuint64_t)rows};
  const cuuint64_t str[1] = {(cuuint64_t)cols * 2};
  const cuuint32_t box[2] = {64, (cuuint32_t)box_rows};
  make_map(fn, tm, p, 2, dims, str, box, CU_TENSOR_MAP_SWIZZLE_128B);
}
void map_w(EncodeFn fn, CUtensorMap* tm, const void* p, int K, int N, int atom, CUtensorMapSwizzle sw) {
  const cuuint64_t dims[3] = {(cuuint64_t)atom, (cuuint64_t)K, (cuuint64_t)(N / atom)};
  const cuuint64_t str[2] = {(cuuint64_t)N * 2, (cuuint64_t)atom * 2};
  const cuuint32_t box[3] = {(cuuint32_t)atom, 64, 5};
  make_map(fn, tm, p, 3, dims, str, box, sw);
}

template <typename... KArgs, typename... Args>
void launch(void (*kern)(KArgs...), int grid, int block, int smem, bool pdl, Args... args) {
  cudaLaunchConfig_t cfg = {};
  cfg.gridDim = dim3(grid); cfg.blockDim = dim3(block); cfg.dynamicSmemBytes = smem; cfg.stream = cudaStreamPerThread;
  cudaLaunchAttribute at[1];
  at[0].id = cudaLaunchAttributeProgrammaticStreamSerialization;
  at[0].val.programmaticStreamSerializationAllowed = 1;
  cfg.attrs = at; cfg.numAttrs = pdl ? 1 : 0;
  cudaLaunchKernelEx(&cfg, kern, KArgs(args)...);
}

}

extern "C" void kernel_launch(void* const* d_in, const int* in_sizes, int n_in, void* d_out, int out_size) {
  (void)in_sizes; (void)n_in; (void)out_size;
  const __nv_bfloat16* x = (const __nv_bfloat16*)d_in[0];
  const __nv_bfloat16* wq = (const __nv_bfloat16*)d_in[1];
  const __nv_bfloat16* wk = (const __nv_bfloat16*)d_in[2];
  const __nv_bfloat16* wv = (const __nv_bfloat16*)d_in[3];
  const __nv_bfloat16* woA = (const __nv_bfloat16*)d_in[4];
  const __nv_bfloat16* wqkv = (const __nv_bfloat16*)d_in[6];
  const __nv_bfloat16* woB = (const __nv_bfloat16*)d_in[7];
  const __nv_bfloat16* gate_w = (const __nv_bfloat16*)d_in[8];

  static EncodeFn enc = nullptr;
  static void* a2_ptr = nullptr;
  static void* qkv_ptr = nullptr;
  if (!enc) {
    void* fp = nullptr;
    cudaDriverEntryPointQueryResult qr;
    cudaGetDriverEntryPoint("cuTensorMapEncodeTiled", &fp, cudaEnableDefault, &qr);
    enc = (EncodeFn)fp;
    cudaGetSymbolAddress(&a2_ptr, g_a2);
    cudaGetSymbolAddress(&qkv_ptr, g_qkv);
    cudaFuncSetAttribute(proj_kernel, cudaFuncAttributeMaxDynamicSharedMemorySize, K1_SMEM);
    cudaFuncSetAttribute(attn_kernel, cudaFuncAttributeMaxDynamicSharedMemorySize, K2_SMEM);
  }
  CUtensorMap tmX, tmWq, tmWqkv, tmA2, tmL;
  {
    const cuuint64_t dims[2] = {3 * D_MODEL, S_LEN};
    const cuuint64_t str[1] = {3 * D_MODEL * 2};
    const cuuint32_t box[2] = {160, 30};
    make_map(enc, &tmL, qkv_ptr, 2, dims, str, box, CU_TENSOR_MAP_SWIZZLE_NONE);
  }
  map_a(enc, &tmX, x, S_LEN, D_MODEL, 256);
  map_w(enc, &tmWq, wq, D_MODEL, D_MODEL, 32, CU_TENSOR_MAP_SWIZZLE_64B);
  map_w(enc, &tmWqkv, wqkv, D_MODEL, 3 * D_MODEL, 32, CU_TENSOR_MAP_SWIZZLE_64B);
  map_a(enc, &tmA2, a2_ptr, S_LEN, 2 * D_MODEL, 128);

  launch(proj_kernel, 132, 512, K1_SMEM, false, tmX, tmWq, tmWqkv, wk, wv, gate_w, woA, woB);
  launch(attn_kernel, 128, 640, K2_SMEM, true, tmA2, tmL, (__nv_bfloat16*)d_out, 0x3F803F80u);
}
```

```cpp
#include <cuda_runtime.h>
#include <cuda_bf16.h>
#include <cuda.h>
#include <stdint.h>

namespace {

constexpr int S_LEN = 2048, D_MODEL = 640, DH = 20;

constexpr int GRP = 128;
constexpr int PLANE = GRP * 16;
constexpr int GRP_BYTES = GRP * 16 * 6;
constexpr int NGRP = S_LEN / GRP;
constexpr uint32_t TMASK = 0x6DB6u;

__device__ __align__(1024) __nv_bfloat16 g_q[S_LEN * D_MODEL];
__device__ __align__(1024) __nv_bfloat16 g_qkv[S_LEN * 3 * D_MODEL];
__device__ __align__(1024) __nv_bfloat16 g_a2[S_LEN * 2 * D_MODEL];
__device__ __align__(1024) uint8_t g_kvimg[NGRP * GRP_BYTES];
__device__ __align__(1024) uint8_t g_wimg[2 * 8 * 10 * 10240];
__device__ float g_gate[S_LEN];
__device__ float g_kmax2[64];
__device__ float g_vmax[64];
__device__ __align__(32) unsigned int g_doneL[128];
__device__ __align__(32) unsigned int g_done[128];

__device__ __forceinline__ uint32_t smem_u32(const void* p) { return (uint32_t)__cvta_generic_to_shared(p); }
__device__ __forceinline__ uint64_t mkd(uint32_t lo, uint32_t hi) {
  uint64_t d; asm("mov.b64 %0, {%1, %2};" : "=l"(d) : "r"(lo), "r"(hi)); return d;
}
__device__ __forceinline__ void wg_fence() { asm volatile("wgmma.fence.sync.aligned;" ::: "memory"); }
__device__ __forceinline__ void wg_commit() { asm volatile("wgmma.commit_group.sync.aligned;" ::: "memory"); }
template <int N> __device__ __forceinline__ void wg_wait() { asm volatile("wgmma.wait_group.sync.aligned %0;" :: "n"(N) : "memory"); }
template <int N> __device__ __forceinline__ void fence_regs(float (&d)[N]) {
#pragma unroll
  for (int i = 0; i < N; i++) asm volatile("" : "+f"(d[i]) :: "memory");
}
template <int N> __device__ __forceinline__ void fence_regs(uint32_t (&d)[N]) {
#pragma unroll
  for (int i = 0; i < N; i++) asm volatile("" : "+r"(d[i]) :: "memory");
}
__device__ __forceinline__ void mbar_init(uint32_t bar, uint32_t cnt) { asm volatile("mbarrier.init.shared::cta.b64 [%0], %1;" :: "r"(bar), "r"(cnt)); }
__device__ __forceinline__ void mbar_expect_tx(uint32_t bar, uint32_t bytes) {
  asm volatile("mbarrier.arrive.expect_tx.shared::cta.b64 _, [%0], %1;" :: "r"(bar), "r"(bytes) : "memory");
}
__device__ __forceinline__ void mbar_arrive(uint32_t bar) { asm volatile("mbarrier.arrive.shared::cta.b64 _, [%0];" :: "r"(bar) : "memory"); }
constexpr uint32_t WAIT_HINT = 20000u;
__device__ __forceinline__ void mbar_wait(uint32_t bar, uint32_t parity) {
  asm volatile("{\n.reg .pred p;\nWAIT_%=:\nmbarrier.try_wait.parity.shared::cta.b64 p, [%0], %1, %2;\n@p bra DONE_%=;\nbra WAIT_%=;\nDONE_%=:\n}\n"
               :: "r"(bar), "r"(parity), "r"(WAIT_HINT) : "memory");
}
__device__ __forceinline__ void fence_mbar_init() { asm volatile("fence.mbarrier_init.release.cluster;" ::: "memory"); }
__device__ __forceinline__ void fence_proxy_async() { asm volatile("fence.proxy.async.shared::cta;" ::: "memory"); }
__device__ __forceinline__ void bulk_g2s(uint32_t dst, const void* src, uint32_t bytes, uint32_t bar) {
  asm volatile("cp.async.bulk.shared::cluster.global.mbarrier::complete_tx::bytes [%0], [%1], %2, [%3];"
               :: "r"(dst), "l"(src), "r"(bytes), "r"(bar) : "memory");
}
__device__ __forceinline__ void tma_2d(uint32_t dst, const CUtensorMap* tm, int c0, int c1, uint32_t bar) {
  asm volatile("cp.async.bulk.tensor.2d.shared::cluster.global.mbarrier::complete_tx::bytes [%0], [%1, {%3, %4}], [%2];"
               :: "r"(dst), "l"((uint64_t)tm), "r"(bar), "r"(c0), "r"(c1) : "memory");
}
__device__ __forceinline__ void tma_3d(uint32_t dst, const CUtensorMap* tm, int c0, int c1, int c2, uint32_t bar) {
  asm volatile("cp.async.bulk.tensor.3d.shared::cluster.global.mbarrier::complete_tx::bytes [%0], [%1, {%3, %4, %5}], [%2];"
               :: "r"(dst), "l"((uint64_t)tm), "r"(bar), "r"(c0), "r"(c1), "r"(c2) : "memory");
}
__device__ __forceinline__ void prefetch_tmap(const CUtensorMap* tm) { asm volatile("prefetch.tensormap [%0];" :: "l"((uint64_t)tm) : "memory"); }
__device__ __forceinline__ void pdl_wait() { asm volatile("griddepcontrol.wait;" ::: "memory"); }
__device__ __forceinline__ void pdl_launch() { asm volatile("griddepcontrol.launch_dependents;" ::: "memory"); }
__device__ __forceinline__ float ex2(float x) { float y; asm("ex2.approx.ftz.f32 %0, %1;" : "=f"(y) : "f"(x)); return y; }
__device__ __forceinline__ uint32_t pack_bf16(float lo, float hi) {
  uint32_t r; asm("cvt.rn.bf16x2.f32 %0, %1, %2;" : "=r"(r) : "f"(hi), "f"(lo)); return r;
}
__device__ __forceinline__ float bf_lo(uint32_t x) { return __uint_as_float(x << 16); }
__device__ __forceinline__ float bf_hi(uint32_t x) { return __uint_as_float(x & 0xffff0000u); }
__device__ __forceinline__ void stsm4(uint32_t addr, uint32_t r0, uint32_t r1, uint32_t r2, uint32_t r3) {
  asm volatile("stmatrix.sync.aligned.m8n8.x4.shared.b16 [%0], {%1, %2, %3, %4};" :: "r"(addr), "r"(r0), "r"(r1), "r"(r2), "r"(r3) : "memory");
}

__device__ __forceinline__ void wgmma_ss_n160_tb(float (&d)[80], uint64_t descA, uint64_t descB) {
  asm volatile("wgmma.mma_async.sync.aligned.m64n160k16.f32.bf16.bf16 {%0, %1, %2, %3, %4, %5, %6, %7, %8, %9, %10, %11, %12, %13, %14, %15, %16, %17, %18, %19, %20, %21, %22, %23, %24, %25, %26, %27, %28, %29, %30, %31, %32, %33, %34, %35, %36, %37, %38, %39, %40, %41, %42, %43, %44, %45, %46, %47, %48, %49, %50, %51, %52, %53, %54, %55, %56, %57, %58, %59, %60, %61, %62, %63, %64, %65, %66, %67, %68, %69, %70, %71, %72, %73, %74, %75, %76, %77, %78, %79}, %80, %81, 1, 1, 1, 0, 1;\n"
    : "+f"(d[0]), "+f"(d[1]), "+f"(d[2]), "+f"(d[3]), "+f"(d[4]), "+f"(d[5]), "+f"(d[6]), "+f"(d[7]), "+f"(d[8]), "+f"(d[9]), "+f"(d[10]), "+f"(d[11]), "+f"(d[12]), "+f"(d[13]), "+f"(d[14]), "+f"(d[15]), "+f"(d[16]), "+f"(d[17]), "+f"(d[18]), "+f"(d[19]), "+f"(d[20]), "+f"(d[21]), "+f"(d[22]), "+f"(d[23]), "+f"(d[24]), "+f"(d[25]), "+f"(d[26]), "+f"(d[27]), "+f"(d[28]), "+f"(d[29]), "+f"(d[30]), "+f"(d[31]), "+f"(d[32]), "+f"(d[33]), "+f"(d[34]), "+f"(d[35]), "+f"(d[36]), "+f"(d[37]), "+f"(d[38]), "+f"(d[39]), "+f"(d[40]), "+f"(d[41]), "+f"(d[42]), "+f"(d[43]), "+f"(d[44]), "+f"(d[45]), "+f"(d[46]), "+f"(d[47]), "+f"(d[48]), "+f"(d[49]), "+f"(d[50]), "+f"(d[51]), "+f"(d[52]), "+f"(d[53]), "+f"(d[54]), "+f"(d[55]), "+f"(d[56]), "+f"(d[57]), "+f"(d[58]), "+f"(d[59]), "+f"(d[60]), "+f"(d[61]), "+f"(d[62]), "+f"(d[63]), "+f"(d[64]), "+f"(d[65]), "+f"(d[66]), "+f"(d[67]), "+f"(d[68]), "+f"(d[69]), "+f"(d[70]), "+f"(d[71]), "+f"(d[72]), "+f"(d[73]), "+f"(d[74]), "+f"(d[75]), "+f"(d[76]), "+f"(d[77]), "+f"(d[78]), "+f"(d[79])
    : "l"(descA), "l"(descB));
}
__device__ __forceinline__ void wgmma_ss_n48_tb(float (&d)[24], uint64_t descA, uint64_t descB) {
  asm volatile("wgmma.mma_async.sync.aligned.m64n48k16.f32.bf16.bf16 {%0, %1, %2, %3, %4, %5, %6, %7, %8, %9, %10, %11, %12, %13, %14, %15, %16, %17, %18, %19, %20, %21, %22, %23}, %24, %25, 1, 1, 1, 0, 1;\n"
    : "+f"(d[0]), "+f"(d[1]), "+f"(d[2]), "+f"(d[3]), "+f"(d[4]), "+f"(d[5]), "+f"(d[6]), "+f"(d[7]), "+f"(d[8]), "+f"(d[9]), "+f"(d[10]), "+f"(d[11]), "+f"(d[12]), "+f"(d[13]), "+f"(d[14]), "+f"(d[15]), "+f"(d[16]), "+f"(d[17]), "+f"(d[18]), "+f"(d[19]), "+f"(d[20]), "+f"(d[21]), "+f"(d[22]), "+f"(d[23])
    : "l"(descA), "l"(descB));
}
__device__ __forceinline__ void wgmma_ss_n80_tb(float (&d)[40], uint64_t descA, uint64_t descB) {
  asm volatile("wgmma.mma_async.sync.aligned.m64n80k16.f32.bf16.bf16 {%0, %1, %2, %3, %4, %5, %6, %7, %8, %9, %10, %11, %12, %13, %14, %15, %16, %17, %18, %19, %20, %21, %22, %23, %24, %25, %26, %27, %28, %29, %30, %31, %32, %33, %34, %35, %36, %37, %38, %39}, %40, %41, 1, 1, 1, 0, 1;\n"
    : "+f"(d[0]), "+f"(d[1]), "+f"(d[2]), "+f"(d[3]), "+f"(d[4]), "+f"(d[5]), "+f"(d[6]), "+f"(d[7]), "+f"(d[8]), "+f"(d[9]), "+f"(d[10]), "+f"(d[11]), "+f"(d[12]), "+f"(d[13]), "+f"(d[14]), "+f"(d[15]), "+f"(d[16]), "+f"(d[17]), "+f"(d[18]), "+f"(d[19]), "+f"(d[20]), "+f"(d[21]), "+f"(d[22]), "+f"(d[23]), "+f"(d[24]), "+f"(d[25]), "+f"(d[26]), "+f"(d[27]), "+f"(d[28]), "+f"(d[29]), "+f"(d[30]), "+f"(d[31]), "+f"(d[32]), "+f"(d[33]), "+f"(d[34]), "+f"(d[35]), "+f"(d[36]), "+f"(d[37]), "+f"(d[38]), "+f"(d[39])
    : "l"(descA), "l"(descB));
}
template <int SCALE_D>
__device__ __forceinline__ void wgmma_rs_n64(float (&d)[32], uint32_t a0, uint32_t a1, uint32_t a2, uint32_t a3, uint64_t descB) {
  asm volatile("wgmma.mma_async.sync.aligned.m64n64k16.f32.bf16.bf16 {%0, %1, %2, %3, %4, %5, %6, %7, %8, %9, %10, %11, %12, %13, %14, %15, %16, %17, %18, %19, %20, %21, %22, %23, %24, %25, %26, %27, %28, %29, %30, %31}, {%32, %33, %34, %35}, %36, %37, 1, 1, 0;\n"
    : "+f"(d[0]), "+f"(d[1]), "+f"(d[2]), "+f"(d[3]), "+f"(d[4]), "+f"(d[5]), "+f"(d[6]), "+f"(d[7]), "+f"(d[8]), "+f"(d[9]), "+f"(d[10]), "+f"(d[11]), "+f"(d[12]), "+f"(d[13]), "+f"(d[14]), "+f"(d[15]), "+f"(d[16]), "+f"(d[17]), "+f"(d[18]), "+f"(d[19]), "+f"(d[20]), "+f"(d[21]), "+f"(d[22]), "+f"(d[23]), "+f"(d[24]), "+f"(d[25]), "+f"(d[26]), "+f"(d[27]), "+f"(d[28]), "+f"(d[29]), "+f"(d[30]), "+f"(d[31])
    : "r"(a0), "r"(a1), "r"(a2), "r"(a3), "l"(descB), "n"(SCALE_D));
}
template <int SCALE_D>
__device__ __forceinline__ void wgmma_rs_n128(float (&d)[64], uint32_t a0, uint32_t a1, uint32_t a2, uint32_t a3, uint64_t descB) {
  asm volatile("wgmma.mma_async.sync.aligned.m64n128k16.f32.bf16.bf16 {%0, %1, %2, %3, %4, %5, %6, %7, %8, %9, %10, %11, %12, %13, %14, %15, %16, %17, %18, %19, %20, %21, %22, %23, %24, %25, %26, %27, %28, %29, %30, %31, %32, %33, %34, %35, %36, %37, %38, %39, %40, %41, %42, %43, %44, %45, %46, %47, %48, %49, %50, %51, %52, %53, %54, %55, %56, %57, %58, %59, %60, %61, %62, %63}, {%64, %65, %66, %67}, %68, %69, 1, 1, 0;\n"
    : "+f"(d[0]), "+f"(d[1]), "+f"(d[2]), "+f"(d[3]), "+f"(d[4]), "+f"(d[5]), "+f"(d[6]), "+f"(d[7]), "+f"(d[8]), "+f"(d[9]), "+f"(d[10]), "+f"(d[11]), "+f"(d[12]), "+f"(d[13]), "+f"(d[14]), "+f"(d[15]), "+f"(d[16]), "+f"(d[17]), "+f"(d[18]), "+f"(d[19]), "+f"(d[20]), "+f"(d[21]), "+f"(d[22]), "+f"(d[23]), "+f"(d[24]), "+f"(d[25]), "+f"(d[26]), "+f"(d[27]), "+f"(d[28]), "+f"(d[29]), "+f"(d[30]), "+f"(d[31]), "+f"(d[32]), "+f"(d[33]), "+f"(d[34]), "+f"(d[35]), "+f"(d[36]), "+f"(d[37]), "+f"(d[38]), "+f"(d[39]), "+f"(d[40]), "+f"(d[41]), "+f"(d[42]), "+f"(d[43]), "+f"(d[44]), "+f"(d[45]), "+f"(d[46]), "+f"(d[47]), "+f"(d[48]), "+f"(d[49]), "+f"(d[50]), "+f"(d[51]), "+f"(d[52]), "+f"(d[53]), "+f"(d[54]), "+f"(d[55]), "+f"(d[56]), "+f"(d[57]), "+f"(d[58]), "+f"(d[59]), "+f"(d[60]), "+f"(d[61]), "+f"(d[62]), "+f"(d[63])
    : "r"(a0), "r"(a1), "r"(a2), "r"(a3), "l"(descB), "n"(SCALE_D));
}
template <int SCALE_D>
__device__ __forceinline__ void wgmma_rs_n24_tb(float (&d)[12], uint32_t a0, uint32_t a1, uint32_t a2, uint32_t a3, uint64_t descB) {
  asm volatile("wgmma.mma_async.sync.aligned.m64n24k16.f32.bf16.bf16 {%0, %1, %2, %3, %4, %5, %6, %7, %8, %9, %10, %11}, {%12, %13, %14, %15}, %16, %17, 1, 1, 1;\n"
    : "+f"(d[0]), "+f"(d[1]), "+f"(d[2]), "+f"(d[3]), "+f"(d[4]), "+f"(d[5]), "+f"(d[6]), "+f"(d[7]), "+f"(d[8]), "+f"(d[9]), "+f"(d[10]), "+f"(d[11])
    : "r"(a0), "r"(a1), "r"(a2), "r"(a3), "l"(descB), "n"(SCALE_D));
}

constexpr uint32_t DHI_SW128_K = (1024 >> 4) | (1u << 30);
constexpr uint32_t DHI_SW64_MN = (512 >> 4) | (2u << 30);

template <int NC>
__device__ __forceinline__ void store_tile_bf16(const float (&acc)[NC / 2], float scale, uint32_t stage, uint8_t* stage_ptr,
                                                __nv_bfloat16* gdst, int gpitch, int lane) {
  constexpr int PITCH = NC * 2 + 16;
  const uint32_t waddr = stage + ((lane & 7) + ((lane >> 3) & 1) * 8) * PITCH + (lane >> 4) * 16;
#pragma unroll
  for (int j = 0; j < NC / 16; j++) {
    stsm4(waddr + j * 32, pack_bf16(acc[8 * j] * scale, acc[8 * j + 1] * scale), pack_bf16(acc[8 * j + 2] * scale, acc[8 * j + 3] * scale),
          pack_bf16(acc[8 * j + 4] * scale, acc[8 * j + 5] * scale), pack_bf16(acc[8 * j + 6] * scale, acc[8 * j + 7] * scale));
  }
  __syncwarp();
  constexpr int CPR = NC / 8;
#pragma unroll
  for (int i = 0; i < CPR / 2; i++) {
    const int c = i * 32 + lane, r = c / CPR, cc = c % CPR;
    const uint4 v = *reinterpret_cast<const uint4*>(stage_ptr + r * PITCH + cc * 16);
    *reinterpret_cast<uint4*>(gdst + (size_t)r * gpitch + cc * 8) = v;
  }
}

__device__ __forceinline__ void signal_done(unsigned int* flag, int wg, int tid) {
  asm volatile("bar.sync %0, 128;" :: "r"(wg + 1) : "memory");
  if ((tid & 127) == 0) asm volatile("red.release.gpu.global.add.u32 [%0], 1;" :: "l"(flag) : "memory");
}
__device__ __forceinline__ void wait_flags8(const unsigned int* f, unsigned int target) {
  for (int spin = 0; spin < (1 << 26); spin++) {
    unsigned int a, b, c, d, e, g, h, i;
    asm volatile("ld.volatile.global.v4.u32 {%0, %1, %2, %3}, [%4];" : "=r"(a), "=r"(b), "=r"(c), "=r"(d) : "l"(f) : "memory");
    asm volatile("ld.volatile.global.v4.u32 {%0, %1, %2, %3}, [%4];" : "=r"(e), "=r"(g), "=r"(h), "=r"(i) : "l"(f + 4) : "memory");
    if (min(min(min(a, b), min(c, d)), min(min(e, g), min(h, i))) >= target) break;
    __nanosleep(32);
  }
  asm volatile("fence.acq_rel.gpu;" ::: "memory");
  asm volatile("fence.proxy.async;" ::: "memory");
}

constexpr int RP_LD = 3, RP_ST = 7;
constexpr int K1_STAGES = 4;
constexpr int K1_A_BYTES = 256 * 128;
constexpr int K1_B_BYTES = 64 * 160 * 2;
constexpr int K1_STAGE = K1_A_BYTES + K1_B_BYTES;
constexpr int K1_SMEM = 5 * K1_A_BYTES + 61440 + 1024;
constexpr int KV_STAGES = 5;
constexpr int KVW_OFF = KV_STAGES * K1_A_BYTES;

__global__ void __launch_bounds__(512, 1)
proj_kernel(const __grid_constant__ CUtensorMap tmX, const __grid_constant__ CUtensorMap tmWq, const __grid_constant__ CUtensorMap tmWqkv,
            const __nv_bfloat16* __restrict__ wk, const __nv_bfloat16* __restrict__ wv, const __nv_bfloat16* __restrict__ gate_w,
            const __nv_bfloat16* __restrict__ woA, const __nv_bfloat16* __restrict__ woB) {
  extern __shared__ uint8_t smem_raw[];
  __shared__ __align__(8) uint64_t bar_full[KV_STAGES], bar_empty[KV_STAGES];
  uint8_t* smem = reinterpret_cast<uint8_t*>((reinterpret_cast<uintptr_t>(smem_raw) + 1023) & ~(uintptr_t)1023);
  const uint32_t sbase = smem_u32(smem);
  const uint32_t dbase = sbase & 0x3FFFFu;
  const int tid = threadIdx.x, warp = tid >> 5, lane = tid & 31;
  const bool is_kv = blockIdx.x >= 128;
  if (tid == 32) { prefetch_tmap(&tmX); prefetch_tmap((blockIdx.x & 15) < 4 ? &tmWq : &tmWqkv); }
  if (tid == 0) {
    for (int i = 0; i < KV_STAGES; i++) { mbar_init(smem_u32(&bar_full[i]), 1); mbar_init(smem_u32(&bar_empty[i]), is_kv ? 8 : 16); }
    fence_mbar_init();
  }
  uint2 wa[2][5], wb[2][5]; uint32_t gw[2];
  if (is_kv && tid < 320) {
#pragma unroll
    for (int r = 0; r < 2; r++) {
      const int k = tid + r * 320;
      const uint2* pk = reinterpret_cast<const uint2*>(wk + k * 20);
      const uint2* pv = reinterpret_cast<const uint2*>(wv + k * 20);
#pragma unroll
      for (int i = 0; i < 5; i++) { wa[r][i] = __ldg(pk + i); wb[r][i] = __ldg(pv + i); }
      gw[r] = (uint32_t)__bfloat16_as_ushort(gate_w[k]);
    }
  }
  __syncthreads();
  if (tid == 480) {
    if (!is_kv) { g_done[blockIdx.x] = 0u; g_doneL[blockIdx.x] = 0u; }
    asm volatile("fence.acq_rel.gpu;" ::: "memory");
    pdl_launch();
  }
  __syncwarp();

  if (!is_kv) {
    const int mb = blockIdx.x >> 4, nb = blockIdx.x & 15;
    const CUtensorMap* tw = nb < 4 ? &tmWq : &tmWqkv;
    const int j0 = (nb < 4 ? nb : nb - 4) * 5;
    auto load = [&](int kt) {
      const int s = kt % K1_STAGES;
      const uint32_t fb = smem_u32(&bar_full[s]);
      mbar_expect_tx(fb, K1_STAGE);
      tma_2d(sbase + s * K1_STAGE, &tmX, kt * 64, mb * 256, fb);
      tma_3d(sbase + s * K1_STAGE + K1_A_BYTES, tw, 0, kt * 64, j0, fb);
    };
    if (tid == 0) for (int kt = 0; kt < K1_STAGES; kt++) load(kt);
    __syncwarp();
    uint4 wv2[2];
    const int rq = blockIdx.x * 400 + tid - 112;
    const int rhalf = rq >= 25600, rr = rq - rhalf * 25600, rk = 2 * (rr / 80), rch = rr % 80;
    {
      const int wg = warp >> 2;
      float acc[80];
#pragma unroll
      for (int i = 0; i < 80; i++) acc[i] = 0.f;
      for (int kt = 0; kt < 10; kt++) {
        const int s = kt % K1_STAGES;
        mbar_wait(smem_u32(&bar_full[s]), (kt / K1_STAGES) & 1);
        const uint32_t alo = ((dbase + s * K1_STAGE + wg * 8192) >> 4) | (1u << 16);
        const uint32_t blo = ((dbase + s * K1_STAGE + K1_A_BYTES) >> 4) | ((4096u >> 4) << 16);
        fence_regs(acc);
        wg_fence();
#pragma unroll
        for (int k = 0; k < 4; k++) wgmma_ss_n160_tb(acc, mkd(alo + k * 2, DHI_SW128_K), mkd(blo + k * 64, DHI_SW64_MN));
        wg_commit();
        if (kt == RP_LD && tid >= 112) {
          const uint4* src = reinterpret_cast<const uint4*>((rhalf ? woB : woA) + rk * D_MODEL + rch * 8);
          wv2[0] = __ldg(src); wv2[1] = __ldg(src + D_MODEL / 8);
        }
        if (kt == RP_ST && tid >= 112) {
          uint4* dst = reinterpret_cast<uint4*>(g_wimg + ((rhalf * 8 + rch / 10) * 10 + (rk >> 6)) * 10240 + (rch % 10) * 1024 + (rk & 63) * 16);
          dst[0] = wv2[0]; dst[1] = wv2[1];
        }
        __syncwarp();
        if (kt > 0 && kt - 1 + K1_STAGES < 10) {
          wg_wait<1>();
          const uint32_t eb = smem_u32(&bar_empty[(kt - 1) % K1_STAGES]);
          if (lane == 0) mbar_arrive(eb);
          if (tid == 0) { mbar_wait(eb, ((kt - 1) / K1_STAGES) & 1); load(kt - 1 + K1_STAGES); }
          __syncwarp();
        }
      }
      wg_wait<0>();
      fence_regs(acc);
      asm volatile("bar.sync %0, 128;" :: "r"(wg + 1) : "memory");
      const int w4 = warp & 3;
      const uint32_t off = w4 * K1_STAGE + wg * 8192;
      const int row0 = mb * 256 + wg * 64 + w4 * 16;
      if (nb < 4) {
        store_tile_bf16<160>(acc, 0.22360679774997896f * 1.4426950408889634f, sbase + off, smem + off,
                             g_q + (size_t)row0 * D_MODEL + nb * 160, D_MODEL, lane);
      } else {
        store_tile_bf16<160>(acc, 1.0f, sbase + off, smem + off, g_qkv + (size_t)row0 * (3 * D_MODEL) + (nb - 4) * 160, 3 * D_MODEL, lane);
      }
    }
  } else {
    const int cb = blockIdx.x - 128;
    if (warp == 8 && lane == 0) {
      for (int it = 0; it < KV_STAGES; it++) {
        const uint32_t fb = smem_u32(&bar_full[it]);
        mbar_expect_tx(fb, K1_A_BYTES);
        tma_2d(sbase + it * K1_A_BYTES, &tmX, it * 64, cb * 512, fb);
      }
    }
    __syncwarp();
    if (tid < 320) {
#pragma unroll
      for (int r = 0; r < 2; r++) {
        uint4* dst = reinterpret_cast<uint4*>(smem + KVW_OFF + (tid + r * 320) * 16);
        dst[0] = make_uint4(wa[r][0].x, wa[r][0].y, wa[r][1].x, wa[r][1].y);
        dst[640] = make_uint4(wa[r][2].x, wa[r][2].y, wa[r][3].x, wa[r][3].y);
        dst[1280] = make_uint4(wa[r][4].x, wa[r][4].y, 0u, 0u);
        dst[1920] = make_uint4(wb[r][0].x, wb[r][0].y, wb[r][1].x, wb[r][1].y);
        dst[2560] = make_uint4(wb[r][2].x, wb[r][2].y, wb[r][3].x, wb[r][3].y);
        dst[3200] = make_uint4(wb[r][4].x, wb[r][4].y, gw[r], 0u);
      }
    }
    fence_proxy_async();
    asm volatile("bar.sync 1, 512;" ::: "memory");
    auto produce = [&](int it0, int it1) {
      for (int it = it0; it < it1; it++) {
        const int s = it % KV_STAGES;
        mbar_wait(smem_u32(&bar_empty[s]), (it / KV_STAGES - 1) & 1);
        const uint32_t fb = smem_u32(&bar_full[s]);
        mbar_expect_tx(fb, K1_A_BYTES);
        tma_2d(sbase + s * K1_A_BYTES, &tmX, (it >= 10 ? it - 10 : it) * 64, cb * 512 + (it >= 10 ? 256 : 0), fb);
      }
    };
    if (tid == 256) produce(KV_STAGES, 15);
    __syncwarp();
    {
      const int pass = warp >> 3, wg = (warp >> 2) & 1, w4 = warp & 3, g = lane >> 2, t = lane & 3;
      if (pass == 1) asm volatile("bar.sync 2, 512;" ::: "memory");
      {
        float acc[2][24];
#pragma unroll
        for (int i = 0; i < 24; i++) { acc[0][i] = 0.f; acc[1][i] = 0.f; }
        for (int kt = 0; kt < 10; kt++) {
          const int it = pass * 10 + kt, s = it % KV_STAGES;
          mbar_wait(smem_u32(&bar_full[s]), (it / KV_STAGES) & 1);
          const uint32_t alo = ((dbase + s * K1_A_BYTES + wg * 16384) >> 4) | (1u << 16);
          const uint32_t blo = ((dbase + KVW_OFF + kt * 1024) >> 4) | ((128u >> 4) << 16);
          fence_regs(acc[0]); fence_regs(acc[1]);
          wg_fence();
#pragma unroll
          for (int k = 0; k < 4; k++) {
            wgmma_ss_n48_tb(acc[0], mkd(alo + k * 2, DHI_SW128_K), mkd(blo + k * 16, 10240u >> 4));
            wgmma_ss_n48_tb(acc[1], mkd(alo + 512 + k * 2, DHI_SW128_K), mkd(blo + k * 16, 10240u >> 4));
          }
          wg_commit();
          if (kt > 0) {
            wg_wait<1>();
            if (lane == 0) mbar_arrive(smem_u32(&bar_empty[(it - 1) % KV_STAGES]));
          }
        }
        wg_wait<0>();
        fence_regs(acc[0]); fence_regs(acc[1]);
        if (lane == 0) mbar_arrive(smem_u32(&bar_empty[(pass * 10 + 9) % KV_STAGES]));
        if (pass == 0) asm volatile("bar.arrive 2, 512;" ::: "memory");
        if (tid == 0) produce(15, 20);
        __syncwarp();
        float kmax2 = 0.f, vmax = 0.f;
#pragma unroll
        for (int hh = 0; hh < 4; hh++) {
          const int h = hh & 1;
          const float (&a)[24] = acc[hh >> 1];
          const int key = cb * 512 + pass * 256 + wg * 128 + (hh >> 1) * 64 + w4 * 16 + g + h * 8;
          const int grp = key >> 7, kk = key & 127;
          const bool poly = (TMASK >> (kk >> 3)) & 1;
          uint8_t* gp = g_kvimg + grp * GRP_BYTES;
          const uint32_t k0 = pack_bf16(a[2 * h], a[2 * h + 1]);
          const uint32_t k1 = pack_bf16(a[4 + 2 * h], a[5 + 2 * h]);
          uint32_t k2 = pack_bf16(a[8 + 2 * h], a[9 + 2 * h]);
          float n2 = bf_lo(k0) * bf_lo(k0) + bf_hi(k0) * bf_hi(k0) + bf_lo(k1) * bf_lo(k1) + bf_hi(k1) * bf_hi(k1);
          if (t < 2) {
            n2 += bf_lo(k2) * bf_lo(k2) + bf_hi(k2) * bf_hi(k2);
            k2 = pack_bf16(bf_lo(k2) * 0.5f, bf_hi(k2) * 0.5f);
          } else if (t == 2) k2 = poly ? pack_bf16(24.f, 2.5f) : pack_bf16(0.5f, 0.f);
          else k2 = poly ? pack_bf16(0.5f, 0.f) : 0u;
          *reinterpret_cast<uint32_t*>(gp + kk * 16 + t * 4) = k0;
          *reinterpret_cast<uint32_t*>(gp + PLANE + kk * 16 + t * 4) = k1;
          *reinterpret_cast<uint32_t*>(gp + 2 * PLANE + kk * 16 + t * 4) = k2;
          n2 += __shfl_xor_sync(0xffffffffu, n2, 1);
          n2 += __shfl_xor_sync(0xffffffffu, n2, 2);
          kmax2 = (n2 > kmax2 || n2 != n2) ? n2 : kmax2;
          uint32_t v0 = pack_bf16(a[12 + 2 * h], a[13 + 2 * h]);
          uint32_t v1 = pack_bf16(a[16 + 2 * h], a[17 + 2 * h]);
          uint32_t v2 = pack_bf16(a[20 + 2 * h], a[21 + 2 * h]);
          float vm = fmaxf(fmaxf(fabsf(bf_lo(v0)), fabsf(bf_hi(v0))), fmaxf(fabsf(bf_lo(v1)), fabsf(bf_hi(v1))));
          if (t < 2) vm = fmaxf(vm, fmaxf(fabsf(bf_lo(v2)), fabsf(bf_hi(v2))));
          else if (t == 2) {
            const float z = a[20 + 2 * h];
            g_gate[key] = 1.f / (1.f + __expf(-z));
            v2 = 0x00003F80u;
          } else v2 = 0u;
          vmax = fmaxf(vmax, vm);
          if (poly) { v0 ^= 0x80008000u; v1 ^= 0x80008000u; v2 ^= 0x80008000u; }
          uint8_t* vp = gp + 3 * PLANE + (kk >> 3) * 384 + (kk & 7) * 16 + t * 4;
          *reinterpret_cast<uint32_t*>(vp) = v0;
          *reinterpret_cast<uint32_t*>(vp + 128) = v1;
          *reinterpret_cast<uint32_t*>(vp + 256) = v2;
        }
#pragma unroll
        for (int o = 1; o < 32; o <<= 1) {
          const float a = __shfl_xor_sync(0xffffffffu, kmax2, o);
          kmax2 = (a > kmax2 || a != a) ? a : kmax2;
          vmax = fmaxf(vmax, __shfl_xor_sync(0xffffffffu, vmax, o));
        }
        if (lane == 0) { g_kmax2[cb * 16 + warp] = kmax2; g_vmax[cb * 16 + warp] = vmax; }
      }
    }
  }
}

__device__ __forceinline__ uint32_t ex2_pair_poly(float u0, float u1, uint32_t one2) {
  const uint32_t W = __byte_perm(__float_as_uint(u0), __float_as_uint(u1), 0x6521);
  uint32_t v; asm("lop3.b32 %0, %1, 0x007F007F, %2, 0xEA;" : "=r"(v) : "r"(W), "r"(one2));
  uint32_t L, p;
  asm("fma.rn.bf16x2 %0, %1, %2, %3;" : "=r"(L) : "r"(v), "r"(0x1f961f96u), "r"(0x9fe39fe3u));
  asm("fma.rn.bf16x2 %0, %1, %1, %2;" : "=r"(p) : "r"(L), "r"(0x00f500f5u));
  return W + p;
}
template <int JOFF>
__device__ __forceinline__ void softmax_slow(const float (&S)[32], uint32_t (&P)[16], float (&O)[12], float& m0, float& m1) {
  float a0 = m0, a1 = m1;
#pragma unroll
  for (int j = 0; j < 8; j++) {
    a0 = fmaxf(a0, fmaxf(S[4 * j], S[4 * j + 1]));
    a1 = fmaxf(a1, fmaxf(S[4 * j + 2], S[4 * j + 3]));
  }
  a0 = fmaxf(a0, __shfl_xor_sync(0xffffffffu, a0, 1)); a0 = fmaxf(a0, __shfl_xor_sync(0xffffffffu, a0, 2));
  a1 = fmaxf(a1, __shfl_xor_sync(0xffffffffu, a1, 1)); a1 = fmaxf(a1, __shfl_xor_sync(0xffffffffu, a1, 2));
  const float c0 = ex2(m0 - a0), c1 = ex2(m1 - a1);
  m0 = a0; m1 = a1;
#pragma unroll
  for (int j = 0; j < 3; j++) { O[4 * j] *= c0; O[4 * j + 1] *= c0; O[4 * j + 2] *= c1; O[4 * j + 3] *= c1; }
#pragma unroll
  for (int i = 0; i < 16; i++) {
    const float m = (i & 1) ? a1 : a0;
    const uint32_t p = pack_bf16(ex2(S[2 * i] - m), ex2(S[2 * i + 1] - m));
    P[i] = ((TMASK >> (JOFF + i / 2)) & 1) ? (p ^ 0x80008000u) : p;
  }
}
constexpr uint32_t DHI_KV = 128 >> 4;
__device__ __forceinline__ void issue_qk(float (&S)[32], const uint32_t (&q)[8], uint64_t base) {
  wgmma_rs_n64<0>(S, q[0], q[1], q[2], q[3], base + (uint64_t)((PLANE >> 4) << 16));
  wgmma_rs_n64<1>(S, q[4], q[5], q[6], q[7], base + (uint64_t)(2 * PLANE >> 4));
}
__device__ __forceinline__ void issue_pv(float (&O)[12], const uint32_t (&P)[16], uint64_t vbase) {
#pragma unroll
  for (int kk = 0; kk < 4; kk++)
    wgmma_rs_n24_tb<1>(O, P[4 * kk], P[4 * kk + 1], P[4 * kk + 2], P[4 * kk + 3], vbase + (uint64_t)(kk * (768 >> 4)));
}

constexpr uint32_t VOFF = ((3 * PLANE) >> 4) + ((384u >> 4) << 16);
constexpr int KVR = 4;
constexpr int OFF_W = KVR * GRP_BYTES;
constexpr int OFF_X = OFF_W + 10 * 10240;
constexpr int OFF_BAR = OFF_X + 4 * 16384;
constexpr int K2_SMEM = OFF_BAR + 512 + 1024;
constexpr int TSL = 7;
constexpr int BAR_KV = 0, BAR_W = 4, BAR_TA = 5, BAR_TE = 12, BAR_OWN = 19, BAR_L = 20, CNT_KV = 21, BAR_WA = 23, BAR_WF = 33, CNT_TK = 43;
constexpr int NSTEP = 2 * NGRP;

__device__ __forceinline__ void kv_load(uint32_t sbase, int step) {
  const uint32_t bar = sbase + OFF_BAR + (BAR_KV + (step & (KVR - 1))) * 8;
  mbar_expect_tx(bar, GRP_BYTES);
  bulk_g2s(sbase + (step & (KVR - 1)) * GRP_BYTES, g_kvimg + (step & (NGRP - 1)) * GRP_BYTES, GRP_BYTES, bar);
}
__device__ __forceinline__ void kv_release(uint32_t sbase, int step, bool elected) {
  if (elected && step + KVR < NSTEP) {
    uint32_t old;
    asm volatile("atom.acq_rel.cta.shared::cta.inc.u32 %0, [%1], 3;" : "=r"(old) : "r"(sbase + OFF_BAR + CNT_KV * 8 + (step & (KVR - 1)) * 4) : "memory");
    if (old == 3u) kv_load(sbase, step + KVR);
  }
  __syncwarp();
}
__device__ __forceinline__ void kv_wait(uint32_t sbase, int step) {
  mbar_wait(sbase + OFF_BAR + (BAR_KV + (step & (KVR - 1))) * 8, (step / KVR) & 1);
}

__device__ __forceinline__ uint32_t kv_release_begin(uint32_t sbase, int slot, bool doit) {
  uint32_t old = 0;
  asm volatile("{\n.reg .pred p;\nsetp.ne.u32 p, %2, 0;\n@p atom.relaxed.cta.shared::cta.inc.u32 %0, [%1], 3;\n}\n"
               : "+r"(old) : "r"(sbase + OFF_BAR + CNT_KV * 8 + slot * 4), "r"((uint32_t)doit) : "memory");
  return old;
}
template <int H>
__device__ __forceinline__ void softmax_half(const float (&S)[64], uint32_t (&P)[16], uint32_t one2) {
#pragma unroll
  for (int i = 0; i < 16; i++) {
    if ((TMASK >> (8 * H + i / 2)) & 1) P[i] = ex2_pair_poly(S[32 * H + 2 * i], S[32 * H + 2 * i + 1], one2);
    else P[i] = pack_bf16(ex2(S[32 * H + 2 * i]), ex2(S[32 * H + 2 * i + 1]));
  }
}
__device__ __forceinline__ void attn_fast(const uint32_t (&q)[8], float (&O)[12], uint32_t sbase, int step0, int nsteps, bool elected, uint32_t one2) {
  uint64_t kb0 = mkd((sbase & 0x3FFFFu) >> 4, DHI_KV);
  asm volatile("" : "+l"(kb0));
#pragma unroll 1
  for (int step4 = step0; step4 < step0 + nsteps; step4 += KVR) {
#pragma unroll
    for (int j = 0; j < KVR; j++) {
      const int step = step4 + j;
      const uint64_t kb = kb0 + (uint64_t)(j * (GRP_BYTES >> 4));
      float S[64]; uint32_t PA[16], PB[16];
#pragma unroll
      for (int i = 0; i < 64; i++) S[i] = 0.f;
      mbar_wait(sbase + OFF_BAR + (BAR_KV + j) * 8, (step / KVR) & 1);
      fence_regs(S);
      wg_fence();
      wgmma_rs_n128<0>(S, q[0], q[1], q[2], q[3], kb + (uint64_t)((PLANE >> 4) << 16));
      wgmma_rs_n128<1>(S, q[4], q[5], q[6], q[7], kb + (uint64_t)(2 * PLANE >> 4));
      wg_commit();
      const uint32_t old = kv_release_begin(sbase, (j + KVR - 1) & (KVR - 1), elected && step > step0 && step - 1 + KVR < NSTEP);
      wg_wait<0>();
      fence_regs(S);
      softmax_half<0>(S, PA, one2);
      fence_regs(PA); fence_regs(O);
      wg_fence();
      issue_pv(O, PA, kb + VOFF);
      wg_commit();
      softmax_half<1>(S, PB, one2);
      fence_regs(PB);
      wg_fence();
      issue_pv(O, PB, kb + VOFF + 4 * (768 >> 4));
      wg_commit();
      if (old == 3u) kv_load(sbase, step - 1 + KVR);
      wg_wait<0>();
      fence_regs(PA); fence_regs(PB); fence_regs(O);
    }
  }
  kv_release(sbase, step0 + nsteps - 1, elected);
}
template <int H>
__device__ __forceinline__ void slow_step(const uint32_t (&q)[8], float (&O)[12], uint64_t kb, float& m0, float& m1) {
  float S[32]; uint32_t P[16];
#pragma unroll
  for (int i = 0; i < 32; i++) S[i] = 0.f;
  fence_regs(S);
  wg_fence();
  issue_qk(S, q, kb + 64 * H);
  wg_commit();
  wg_wait<0>();
  fence_regs(S);
  softmax_slow<8 * H>(S, P, O, m0, m1);
  fence_regs(P); fence_regs(O);
  wg_fence();
  issue_pv(O, P, kb + VOFF + H * 4 * (768 >> 4));
  wg_commit();
  wg_wait<0>();
  fence_regs(O); fence_regs(P);
}
__device__ __forceinline__ void attn_slow(const uint32_t (&q)[8], float (&O)[12], uint32_t sbase, int step0, int nsteps, bool elected, float& m0, float& m1) {
#pragma unroll 1
  for (int step = step0; step < step0 + nsteps; step++) {
    kv_wait(sbase, step);
    const uint64_t kb = mkd(((sbase & 0x3FFFFu) >> 4) + (step & (KVR - 1)) * (GRP_BYTES >> 4), DHI_KV);
    slow_step<0>(q, O, kb, m0, m1);
    slow_step<1>(q, O, kb, m0, m1);
    kv_release(sbase, step, elected);
  }
}

__device__ __forceinline__ void softmax8(float (&sc)[8], float scale) {
  float mx = sc[0];
#pragma unroll
  for (int w = 1; w < 8; w++) mx = fmaxf(mx, sc[w]);
  float l = 0.f;
#pragma unroll
  for (int w = 0; w < 8; w++) { sc[w] = ex2(sc[w] - mx); l += sc[w]; }
  const float r = __fdividef(scale, l);
#pragma unroll
  for (int w = 0; w < 8; w++) sc[w] *= r;
}
constexpr int LBOX = 30 * 320;
__device__ __forceinline__ uint2 lds64(uint32_t a) {
  uint2 v; asm volatile("ld.shared.v2.u32 {%0, %1}, [%2];" : "=r"(v.x), "=r"(v.y) : "r"(a)); return v;
}
__device__ __forceinline__ void local_attn(uint32_t stage, int t0, int i, int lane) {
  constexpr float SC = 0.22360679774997896f * 1.4426950408889634f, NEG = -1e9f * 1.4426950408889634f;
  const uint32_t base = stage + (lane >> 3) * LBOX + (lane & 7) * 40 + (i + 14) * 320;
  const int t = t0 + i;
  float sc[8];
#pragma unroll
  for (int w = 0; w < 8; w++) sc[w] = 0.f;
#pragma unroll 1
  for (int c = 0; c < 5; c++) {
    const uint2 qv = lds64(base + c * 8);
    const float q0 = bf_lo(qv.x), q1 = bf_hi(qv.x), q2 = bf_lo(qv.y), q3 = bf_hi(qv.y);
#pragma unroll
    for (int w = 0; w < 8; w++) {
      const uint2 k = lds64(base + c * 8 + 4 * LBOX - w * 640);
      sc[w] = fmaf(q0, bf_lo(k.x), sc[w]); sc[w] = fmaf(q1, bf_hi(k.x), sc[w]);
      sc[w] = fmaf(q2, bf_lo(k.y), sc[w]); sc[w] = fmaf(q3, bf_hi(k.y), sc[w]);
    }
  }
#pragma unroll
  for (int w = 0; w < 8; w++) sc[w] = t - 2 * w >= 0 ? sc[w] * SC : NEG;
  softmax8(sc, 1.f - g_gate[t]);
  uint2* dst = reinterpret_cast<uint2*>(g_a2 + (size_t)t * (2 * D_MODEL) + D_MODEL + lane * DH);
#pragma unroll 1
  for (int c = 0; c < 5; c++) {
    float o0 = 0.f, o1 = 0.f, o2 = 0.f, o3 = 0.f;
#pragma unroll
    for (int w = 0; w < 8; w++) {
      const uint2 v = lds64(base + c * 8 + 8 * LBOX - w * 640);
      o0 = fmaf(sc[w], bf_lo(v.x), o0); o1 = fmaf(sc[w], bf_hi(v.x), o1);
      o2 = fmaf(sc[w], bf_lo(v.y), o2); o3 = fmaf(sc[w], bf_hi(v.y), o3);
    }
    dst[c] = make_uint2(pack_bf16(o0, o1), pack_bf16(o2, o3));
  }
}
__device__ __forceinline__ uint32_t ta_slot(int i) { return i < 4 ? OFF_X + i * 16384 : (i - 4) * 16384; }

__global__ void __launch_bounds__(640, 1)
attn_kernel(const __grid_constant__ CUtensorMap tmA2, const __grid_constant__ CUtensorMap tmL, __nv_bfloat16* __restrict__ out, uint32_t one2) {
  extern __shared__ uint8_t smem_raw[];
  uint8_t* smem = reinterpret_cast<uint8_t*>((reinterpret_cast<uintptr_t>(smem_raw) + 1023) & ~(uintptr_t)1023);
  const uint32_t sbase = smem_u32(smem);
  const uint32_t dbase = sbase & 0x3FFFFu;
  const uint32_t bars = sbase + OFF_BAR;
  const int tid = threadIdx.x, wg = tid >> 7, warp = (tid >> 5) & 3, lane = tid & 31, g = lane >> 2, t = lane & 3;
  const int mb = blockIdx.x >> 3, nb = blockIdx.x & 7;
  const bool elected = (tid & 127) == 0;
  if (tid == 512) { prefetch_tmap(&tmL); prefetch_tmap(&tmA2); }
  if (tid == 0) {
    for (int i = 0; i < BAR_TE; i++) mbar_init(bars + i * 8, 1);
    for (int i = BAR_TE; i < BAR_TE + TSL; i++) mbar_init(bars + i * 8, 8);
    mbar_init(bars + BAR_OWN * 8, 4);
    mbar_init(bars + BAR_L * 8, 1);
    for (int i = 0; i < 10; i++) { mbar_init(bars + (BAR_WA + i) * 8, 1); mbar_init(bars + (BAR_WF + i) * 8, 8); }
    for (int i = 0; i < 4; i++) *reinterpret_cast<uint32_t*>(smem + OFF_BAR + CNT_KV * 8 + i * 4) = 0u;
    *reinterpret_cast<uint32_t*>(smem + OFF_BAR + CNT_TK * 8) = 0u;
    fence_mbar_init();
  }
  __syncthreads();
  auto tail_load = [&](int i) {
    const uint32_t fb = bars + (BAR_TA + i % TSL) * 8;
    mbar_expect_tx(fb, 16384);
    tma_2d(sbase + ta_slot(i % TSL), &tmA2, i < 10 ? D_MODEL + i * 64 : (i - 10) * 64, mb * 128, fb);
  };
  if (wg == 4) {
    asm volatile("setmaxnreg.dec.sync.aligned.u32 32;");
    pdl_wait();
    if (tid == 512) {
      for (int j = 0; j < KVR; j++) kv_load(sbase, j);
      mbar_expect_tx(bars + BAR_L * 8, 12 * LBOX);
      for (int i = 0; i < 12; i++) tma_2d(sbase + OFF_W + i * LBOX, &tmL, i * 160, blockIdx.x * 16 - 14, bars + BAR_L * 8);
    }
    __syncwarp();
    mbar_wait(bars + BAR_L * 8, 0);
#pragma unroll 1
    for (int i = 0; i < 4; i++) local_attn(sbase + OFF_W, blockIdx.x * 16, warp * 4 + i, lane);
    signal_done(&g_doneL[blockIdx.x], wg, tid);
    if (tid == 512) {
      fence_proxy_async();
      mbar_expect_tx(bars + BAR_W * 8, 10 * 10240);
      for (int i = 0; i < 5; i++) bulk_g2s(sbase + OFF_W + i * 20480, g_wimg + ((8 + nb) * 10) * 10240 + i * 20480, 20480, bars + BAR_W * 8);
      wait_flags8(&g_doneL[mb * 8], 1u);
      for (int i = 0; i < 4; i++) tail_load(i);
      mbar_wait(bars + BAR_OWN * 8, 0);
      for (int i = 4; i < 20; i++) {
        if (i >= TSL) mbar_wait(bars + (BAR_TE + i % TSL) * 8, (i / TSL - 1) & 1);
        if (i == 10) { wait_flags8(&g_done[mb * 8], 1u); }
        tail_load(i);
      }
    } else if (tid == 576) {
      mbar_wait(bars + BAR_OWN * 8, 0);
      asm volatile("red.release.gpu.global.add.u32 [%0], 1;" :: "l"(&g_done[blockIdx.x]) : "memory");
    } else if (tid == 544) {
      for (int kt = 0; kt < 10; kt++) {
        mbar_wait(bars + (BAR_WF + kt) * 8, 0);
        mbar_expect_tx(bars + (BAR_WA + kt) * 8, 10240);
        bulk_g2s(sbase + OFF_W + kt * 10240, g_wimg + (nb * 10 + kt) * 10240, 10240, bars + (BAR_WA + kt) * 8);
      }
    }
    return;
  }
  asm volatile("setmaxnreg.inc.sync.aligned.u32 112;");
  pdl_wait();
  uint32_t q[8], q2[6];
  const int rowA = (blockIdx.x * 8 + wg) * 64 + warp * 16 + g;
  {
    const uint32_t* r0 = reinterpret_cast<const uint32_t*>(g_q + (size_t)rowA * DH);
    const uint32_t* r1 = r0 + 8 * (DH / 2);
    const uint32_t* s0 = r0 + 256 * (DH / 2);
    const uint32_t* s1 = s0 + 8 * (DH / 2);
    q[0] = r0[t]; q[1] = r1[t]; q[2] = r0[t + 4]; q[3] = r1[t + 4];
    q[4] = t < 2 ? r0[8 + t] : 0u;
    q[5] = t < 2 ? r1[8 + t] : 0u;
    q2[0] = s0[t]; q2[1] = s1[t]; q2[2] = s0[t + 4]; q2[3] = s1[t + 4];
    q2[4] = t < 2 ? s0[8 + t] : 0u;
    q2[5] = t < 2 ? s1[8 + t] : 0u;
  }
  float kmax2 = 0.f, vmax = 0.f;
#pragma unroll
  for (int i = 0; i < 2; i++) {
    const float a = g_kmax2[lane + 32 * i];
    kmax2 = (a > kmax2 || a != a) ? a : kmax2;
    vmax = fmaxf(vmax, g_vmax[lane + 32 * i]);
  }
#pragma unroll
  for (int o = 1; o < 32; o <<= 1) {
    const float a = __shfl_xor_sync(0xffffffffu, kmax2, o);
    kmax2 = (a > kmax2 || a != a) ? a : kmax2;
    vmax = fmaxf(vmax, __shfl_xor_sync(0xffffffffu, vmax, o));
  }
  const float qlim = (vmax >= 0.00390625f && vmax <= 256.f) ? 9025.f / kmax2 : -1.f;
#pragma unroll 1
  for (int it = 0; it < 2; it++) {
    const int row0 = rowA + it * 256;
    if (it == 1) {
#pragma unroll
      for (int i = 0; i < 6; i++) q[i] = q2[i];
    }
    float n0 = bf_lo(q[0]) * bf_lo(q[0]) + bf_hi(q[0]) * bf_hi(q[0]) + bf_lo(q[2]) * bf_lo(q[2]) + bf_hi(q[2]) * bf_hi(q[2]) +
               bf_lo(q[4]) * bf_lo(q[4]) + bf_hi(q[4]) * bf_hi(q[4]);
    float n1 = bf_lo(q[1]) * bf_lo(q[1]) + bf_hi(q[1]) * bf_hi(q[1]) + bf_lo(q[3]) * bf_lo(q[3]) + bf_hi(q[3]) * bf_hi(q[3]) +
               bf_lo(q[5]) * bf_lo(q[5]) + bf_hi(q[5]) * bf_hi(q[5]);
    n0 += __shfl_xor_sync(0xffffffffu, n0, 1); n0 += __shfl_xor_sync(0xffffffffu, n0, 2);
    n1 += __shfl_xor_sync(0xffffffffu, n1, 1); n1 += __shfl_xor_sync(0xffffffffu, n1, 2);
    const bool safe = (n0 <= qlim) && (n1 <= qlim);
    uint32_t unsafe_any;
    asm volatile("{\n.reg .pred p, r;\nsetp.eq.u32 p, %1, 0;\nbarrier.cta.red.or.pred r, %2, 128, p;\nselp.u32 %0, 1, 0, r;\n}\n"
                 : "=r"(unsafe_any) : "r"((uint32_t)safe), "r"(wg + 1) : "memory");
    float O[12];
#pragma unroll
    for (int i = 0; i < 12; i++) O[i] = 0.f;
    if (!unsafe_any && t >= 2) { q[4] = q[5] = (t == 2) ? 0x3F804100u : 0x00003B80u; }
    q[6] = q[4]; q[7] = q[5];
    fence_regs(q);
    float m0 = -INFINITY, m1 = -INFINITY;
    if (!unsafe_any) attn_fast(q, O, sbase, it * NGRP, NGRP, elected, one2);
    else attn_slow(q, O, sbase, it * NGRP, NGRP, elected, m0, m1);
    const float l0 = __shfl_sync(0xffffffffu, O[8], (lane & ~3) | 2);
    const float l1 = __shfl_sync(0xffffffffu, O[10], (lane & ~3) | 2);
    const int tok = row0 >> 5;
    const float gt = g_gate[tok];
    const float i0 = gt / l0, i1 = gt / l1;
    uint32_t* o0 = reinterpret_cast<uint32_t*>(g_a2 + (size_t)tok * (2 * D_MODEL) + (row0 & 31) * DH);
    uint32_t* o1 = o0 + 8 * (DH / 2);
    o0[t] = pack_bf16(O[0] * i0, O[1] * i0); o1[t] = pack_bf16(O[2] * i1, O[3] * i1);
    o0[t + 4] = pack_bf16(O[4] * i0, O[5] * i0); o1[t + 4] = pack_bf16(O[6] * i1, O[7] * i1);
    if (t < 2) { o0[t + 8] = pack_bf16(O[8] * i0, O[9] * i0); o1[t + 8] = pack_bf16(O[10] * i1, O[11] * i1); }
  }
  uint32_t* ticket = reinterpret_cast<uint32_t*>(smem + OFF_BAR + CNT_TK * 8);
  if (elected) ticket[1 + wg] = atomicAdd(ticket, 1u);
  asm volatile("bar.sync %0, 128;" :: "r"(wg + 1) : "memory");
  if (elected) mbar_arrive(bars + BAR_OWN * 8);
  const int mt = ticket[1 + wg];
  if (mt < 2) {
    float acc[40];
#pragma unroll
    for (int i = 0; i < 40; i++) acc[i] = 0.f;
    mbar_wait(bars + BAR_W * 8, 0);
    int sl = 0, ph = 0;
#pragma unroll 1
    for (int i = 0; i < 20; i++) {
      mbar_wait(bars + (BAR_TA + sl) * 8, ph);
      if (i >= 10) mbar_wait(bars + (BAR_WA + i - 10) * 8, 0);
      const uint32_t alo = ((dbase + ta_slot(sl) + mt * 8192) >> 4) | (1u << 16);
      const uint32_t blo = ((dbase + OFF_W + (i >= 10 ? i - 10 : i) * 10240) >> 4) | ((128u >> 4) << 16);
      fence_regs(acc);
      wg_fence();
#pragma unroll
      for (int k = 0; k < 4; k++) wgmma_ss_n80_tb(acc, mkd(alo + k * 2, DHI_SW128_K), mkd(blo + k * 16, 1024u >> 4));
      wg_commit();
      if (i > 0) {
        wg_wait<1>();
        if (lane == 0) mbar_arrive(bars + (BAR_TE + (sl == 0 ? TSL - 1 : sl - 1)) * 8);
        if (lane == 1 && i <= 10) mbar_arrive(bars + (BAR_WF + i - 1) * 8);
      }
      if (++sl == TSL) { sl = 0; ph ^= 1; }
    }
    wg_wait<0>();
    fence_regs(acc);
    asm volatile("bar.sync %0, 128;" :: "r"(wg + 1) : "memory");
    const uint32_t so = ta_slot(warp) + mt * 8192;
    const int row0 = mb * 128 + mt * 64 + warp * 16;
    store_tile_bf16<80>(acc, 1.0f, sbase + so, smem + so, out + (size_t)row0 * D_MODEL + nb * 80, D_MODEL, lane);
  }
}

typedef CUresult (*EncodeFn)(CUtensorMap*, CUtensorMapDataType, cuuint32_t, void*, const cuuint64_t*, const cuuint64_t*,
                             const cuuint32_t*, const cuuint32_t*, CUtensorMapInterleave, CUtensorMapSwizzle,
                             CUtensorMapL2promotion, CUtensorMapFloatOOBfill);

void make_map(EncodeFn fn, CUtensorMap* tm, const void* ptr, int rank, const cuuint64_t* dims, const cuuint64_t* strides,
              const cuuint32_t* box, CUtensorMapSwizzle sw) {
  const cuuint32_t es[3] = {1, 1, 1};
  fn(tm, CU_TENSOR_MAP_DATA_TYPE_BFLOAT16, rank, const_cast<void*>(ptr), dims, strides, box, es, CU_TENSOR_MAP_INTERLEAVE_NONE, sw,
     CU_TENSOR_MAP_L2_PROMOTION_L2_256B, CU_TENSOR_MAP_FLOAT_OOB_FILL_NONE);
}
void map_a(EncodeFn fn, CUtensorMap* tm, const void* p, int rows, int cols, int box_rows) {
  const cuuint64_t dims[2] = {(cuuint64_t)cols, (cuuint64_t)rows};
  const cuuint64_t str[1] = {(cuuint64_t)cols * 2};
  const cuuint32_t box[2] = {64, (cuuint32_t)box_rows};
  make_map(fn, tm, p, 2, dims, str, box, CU_TENSOR_MAP_SWIZZLE_128B);
}
void map_w(EncodeFn fn, CUtensorMap* tm, const void* p, int K, int N, int atom, CUtensorMapSwizzle sw) {
  const cuuint64_t dims[3] = {(cuuint64_t)atom, (cuuint64_t)K, (cuuint64_t)(N / atom)};
  const cuuint64_t str[2] = {(cuuint64_t)N * 2, (cuuint64_t)atom * 2};
  const cuuint32_t box[3] = {(cuuint32_t)atom, 64, 5};
  make_map(fn, tm, p, 3, dims, str, box, sw);
}

template <typename... KArgs, typename... Args>
void launch(void (*kern)(KArgs...), int grid, int block, int smem, bool pdl, Args... args) {
  cudaLaunchConfig_t cfg = {};
  cfg.gridDim = dim3(grid); cfg.blockDim = dim3(block); cfg.dynamicSmemBytes = smem; cfg.stream = cudaStreamPerThread;
  cudaLaunchAttribute at[1];
  at[0].id = cudaLaunchAttributeProgrammaticStreamSerialization;
  at[0].val.programmaticStreamSerializationAllowed = 1;
  cfg.attrs = at; cfg.numAttrs = pdl ? 1 : 0;
  cudaLaunchKernelEx(&cfg, kern, KArgs(args)...);
}

}

extern "C" void kernel_launch(void* const* d_in, const int* in_sizes, int n_in, void* d_out, int out_size) {
  (void)in_sizes; (void)n_in; (void)out_size;
  const __nv_bfloat16* x = (const __nv_bfloat16*)d_in[0];
  const __nv_bfloat16* wq = (const __nv_bfloat16*)d_in[1];
  const __nv_bfloat16* wk = (const __nv_bfloat16*)d_in[2];
  const __nv_bfloat16* wv = (const __nv_bfloat16*)d_in[3];
  const __nv_bfloat16* woA = (const __nv_bfloat16*)d_in[4];
  const __nv_bfloat16* wqkv = (const __nv_bfloat16*)d_in[6];
  const __nv_bfloat16* woB = (const __nv_bfloat16*)d_in[7];
  const __nv_bfloat16* gate_w = (const __nv_bfloat16*)d_in[8];

  static EncodeFn enc = nullptr;
  static void* a2_ptr = nullptr;
  static void* qkv_ptr = nullptr;
  if (!enc) {
    void* fp = nullptr;
    cudaDriverEntryPointQueryResult qr;
    cudaGetDriverEntryPoint("cuTensorMapEncodeTiled", &fp, cudaEnableDefault, &qr);
    enc = (EncodeFn)fp;
    cudaGetSymbolAddress(&a2_ptr, g_a2);
    cudaGetSymbolAddress(&qkv_ptr, g_qkv);
    cudaFuncSetAttribute(proj_kernel, cudaFuncAttributeMaxDynamicSharedMemorySize, K1_SMEM);
    cudaFuncSetAttribute(attn_kernel, cudaFuncAttributeMaxDynamicSharedMemorySize, K2_SMEM);
  }
  CUtensorMap tmX, tmWq, tmWqkv, tmA2, tmL;
  {
    const cuuint64_t dims[2] = {3 * D_MODEL, S_LEN};
    const cuuint64_t str[1] = {3 * D_MODEL * 2};
    const cuuint32_t box[2] = {160, 30};
    make_map(enc, &tmL, qkv_ptr, 2, dims, str, box, CU_TENSOR_MAP_SWIZZLE_NONE);
  }
  map_a(enc, &tmX, x, S_LEN, D_MODEL, 256);
  map_w(enc, &tmWq, wq, D_MODEL, D_MODEL, 32, CU_TENSOR_MAP_SWIZZLE_64B);
  map_w(enc, &tmWqkv, wqkv, D_MODEL, 3 * D_MODEL, 32, CU_TENSOR_MAP_SWIZZLE_64B);
  map_a(enc, &tmA2, a2_ptr, S_LEN, 2 * D_MODEL, 128);

  launch(proj_kernel, 132, 512, K1_SMEM, false, tmX, tmWq, tmWqkv, wk, wv, gate_w, woA, woB);
  launch(attn_kernel, 128, 640, K2_SMEM, true, tmA2, tmL, (__nv_bfloat16*)d_out, 0x3F803F80u);
}
```

```cpp
#include <cuda_runtime.h>
#include <cuda_bf16.h>
#include <cuda.h>
#include <stdint.h>

namespace {

constexpr int S_LEN = 2048, D_MODEL = 640, DH = 20;

constexpr int GRP = 128;
constexpr int PLANE = GRP * 16;
constexpr int GRP_BYTES = GRP * 16 * 6;
constexpr int NGRP = S_LEN / GRP;
#define TMASKV 0x6DB6u
constexpr uint32_t TMASK = TMASKV;

__device__ __align__(1024) __nv_bfloat16 g_q[S_LEN * D_MODEL];
__device__ __align__(1024) __nv_bfloat16 g_qkv[S_LEN * 3 * D_MODEL];
__device__ __align__(1024) __nv_bfloat16 g_a2[S_LEN * 2 * D_MODEL];
__device__ __align__(1024) uint8_t g_kvimg[NGRP * GRP_BYTES];
__device__ __align__(1024) uint8_t g_wimg[2 * 8 * 10 * 10240];
__device__ float g_gate[S_LEN];
__device__ float g_kmax2[64];
__device__ float g_vmax[64];
__device__ __align__(32) unsigned int g_doneL[128];
__device__ __align__(32) unsigned int g_done[128];

#define PROF(k, slot)
#define PROF2(k, slot)
__device__ __forceinline__ uint32_t smem_u32(const void* p) { return (uint32_t)__cvta_generic_to_shared(p); }
__device__ __forceinline__ uint64_t mkd(uint32_t lo, uint32_t hi) {
  uint64_t d; asm("mov.b64 %0, {%1, %2};" : "=l"(d) : "r"(lo), "r"(hi)); return d;
}
__device__ __forceinline__ void wg_fence() { asm volatile("wgmma.fence.sync.aligned;" ::: "memory"); }
__device__ __forceinline__ void wg_commit() { asm volatile("wgmma.commit_group.sync.aligned;" ::: "memory"); }
template <int N> __device__ __forceinline__ void wg_wait() { asm volatile("wgmma.wait_group.sync.aligned %0;" :: "n"(N) : "memory"); }
template <int N> __device__ __forceinline__ void fence_regs(float (&d)[N]) {
#pragma unroll
  for (int i = 0; i < N; i++) asm volatile("" : "+f"(d[i]) :: "memory");
}
template <int N> __device__ __forceinline__ void fence_regs(uint32_t (&d)[N]) {
#pragma unroll
  for (int i = 0; i < N; i++) asm volatile("" : "+r"(d[i]) :: "memory");
}
__device__ __forceinline__ void mbar_init(uint32_t bar, uint32_t cnt) { asm volatile("mbarrier.init.shared::cta.b64 [%0], %1;" :: "r"(bar), "r"(cnt)); }
__device__ __forceinline__ void mbar_expect_tx(uint32_t bar, uint32_t bytes) {
  asm volatile("mbarrier.arrive.expect_tx.shared::cta.b64 _, [%0], %1;" :: "r"(bar), "r"(bytes) : "memory");
}
__device__ __forceinline__ void mbar_arrive(uint32_t bar) { asm volatile("mbarrier.arrive.shared::cta.b64 _, [%0];" :: "r"(bar) : "memory"); }
#define WAIT_HINT 20000u
__device__ __forceinline__ void mbar_wait(uint32_t bar, uint32_t parity) {
  asm volatile("{\n.reg .pred p;\nWAIT_%=:\nmbarrier.try_wait.parity.shared::cta.b64 p, [%0], %1, %2;\n@p bra DONE_%=;\nbra WAIT_%=;\nDONE_%=:\n}\n"
               :: "r"(bar), "r"(parity), "r"(WAIT_HINT) : "memory");
}
__device__ __forceinline__ void fence_mbar_init() { asm volatile("fence.mbarrier_init.release.cluster;" ::: "memory"); }
__device__ __forceinline__ void fence_proxy_async() { asm volatile("fence.proxy.async.shared::cta;" ::: "memory"); }
__device__ __forceinline__ void bulk_g2s(uint32_t dst, const void* src, uint32_t bytes, uint32_t bar) {
  asm volatile("cp.async.bulk.shared::cluster.global.mbarrier::complete_tx::bytes [%0], [%1], %2, [%3];"
               :: "r"(dst), "l"(src), "r"(bytes), "r"(bar) : "memory");
}
__device__ __forceinline__ void tma_2d(uint32_t dst, const CUtensorMap* tm, int c0, int c1, uint32_t bar) {
  asm volatile("cp.async.bulk.tensor.2d.shared::cluster.global.mbarrier::complete_tx::bytes [%0], [%1, {%3, %4}], [%2];"
               :: "r"(dst), "l"((uint64_t)tm), "r"(bar), "r"(c0), "r"(c1) : "memory");
}
__device__ __forceinline__ void tma_3d(uint32_t dst, const CUtensorMap* tm, int c0, int c1, int c2, uint32_t bar) {
  asm volatile("cp.async.bulk.tensor.3d.shared::cluster.global.mbarrier::complete_tx::bytes [%0], [%1, {%3, %4, %5}], [%2];"
               :: "r"(dst), "l"((uint64_t)tm), "r"(bar), "r"(c0), "r"(c1), "r"(c2) : "memory");
}
__device__ __forceinline__ void prefetch_tmap(const CUtensorMap* tm) { asm volatile("prefetch.tensormap [%0];" :: "l"((uint64_t)tm) : "memory"); }
__device__ __forceinline__ void pdl_wait() { asm volatile("griddepcontrol.wait;" ::: "memory"); }
__device__ __forceinline__ void pdl_launch() { asm volatile("griddepcontrol.launch_dependents;" ::: "memory"); }
__device__ __forceinline__ float ex2(float x) { float y; asm("ex2.approx.ftz.f32 %0, %1;" : "=f"(y) : "f"(x)); return y; }
__device__ __forceinline__ uint32_t pack_bf16(float lo, float hi) {
  uint32_t r; asm("cvt.rn.bf16x2.f32 %0, %1, %2;" : "=r"(r) : "f"(hi), "f"(lo)); return r;
}
__device__ __forceinline__ float bf_lo(uint32_t x) { return __uint_as_float(x << 16); }
__device__ __forceinline__ float bf_hi(uint32_t x) { return __uint_as_float(x & 0xffff0000u); }
__device__ __forceinline__ void stsm4(uint32_t addr, uint32_t r0, uint32_t r1, uint32_t r2, uint32_t r3) {
  asm volatile("stmatrix.sync.aligned.m8n8.x4.shared.b16 [%0], {%1, %2, %3, %4};" :: "r"(addr), "r"(r0), "r"(r1), "r"(r2), "r"(r3) : "memory");
}

__device__ __forceinline__ void wgmma_ss_n96_tb(float (&d)[48], uint64_t descA, uint64_t descB) {
  asm volatile("wgmma.mma_async.sync.aligned.m64n96k16.f32.bf16.bf16 {%0, %1, %2, %3, %4, %5, %6, %7, %8, %9, %10, %11, %12, %13, %14, %15, %16, %17, %18, %19, %20, %21, %22, %23, %24, %25, %26, %27, %28, %29, %30, %31, %32, %33, %34, %35, %36, %37, %38, %39, %40, %41, %42, %43, %44, %45, %46, %47}, %48, %49, 1, 1, 1, 0, 1;\n"
    : "+f"(d[0]), "+f"(d[1]), "+f"(d[2]), "+f"(d[3]), "+f"(d[4]), "+f"(d[5]), "+f"(d[6]), "+f"(d[7]), "+f"(d[8]), "+f"(d[9]), "+f"(d[10]), "+f"(d[11]), "+f"(d[12]), "+f"(d[13]), "+f"(d[14]), "+f"(d[15]), "+f"(d[16]), "+f"(d[17]), "+f"(d[18]), "+f"(d[19]), "+f"(d[20]), "+f"(d[21]), "+f"(d[22]), "+f"(d[23]), "+f"(d[24]), "+f"(d[25]), "+f"(d[26]), "+f"(d[27]), "+f"(d[28]), "+f"(d[29]), "+f"(d[30]), "+f"(d[31]), "+f"(d[32]), "+f"(d[33]), "+f"(d[34]), "+f"(d[35]), "+f"(d[36]), "+f"(d[37]), "+f"(d[38]), "+f"(d[39]), "+f"(d[40]), "+f"(d[41]), "+f"(d[42]), "+f"(d[43]), "+f"(d[44]), "+f"(d[45]), "+f"(d[46]), "+f"(d[47])
    : "l"(descA), "l"(descB));
}
__device__ __forceinline__ void wgmma_ss_n64_tb(float (&d)[32], uint64_t descA, uint64_t descB) {
  asm volatile("wgmma.mma_async.sync.aligned.m64n64k16.f32.bf16.bf16 {%0, %1, %2, %3, %4, %5, %6, %7, %8, %9, %10, %11, %12, %13, %14, %15, %16, %17, %18, %19, %20, %21, %22, %23, %24, %25, %26, %27, %28, %29, %30, %31}, %32, %33, 1, 1, 1, 0, 1;\n"
    : "+f"(d[0]), "+f"(d[1]), "+f"(d[2]), "+f"(d[3]), "+f"(d[4]), "+f"(d[5]), "+f"(d[6]), "+f"(d[7]), "+f"(d[8]), "+f"(d[9]), "+f"(d[10]), "+f"(d[11]), "+f"(d[12]), "+f"(d[13]), "+f"(d[14]), "+f"(d[15]), "+f"(d[16]), "+f"(d[17]), "+f"(d[18]), "+f"(d[19]), "+f"(d[20]), "+f"(d[21]), "+f"(d[22]), "+f"(d[23]), "+f"(d[24]), "+f"(d[25]), "+f"(d[26]), "+f"(d[27]), "+f"(d[28]), "+f"(d[29]), "+f"(d[30]), "+f"(d[31])
    : "l"(descA), "l"(descB));
}
__device__ __forceinline__ void wgmma_ss_n48_tb(float (&d)[24], uint64_t descA, uint64_t descB) {
  asm volatile("wgmma.mma_async.sync.aligned.m64n48k16.f32.bf16.bf16 {%0, %1, %2, %3, %4, %5, %6, %7, %8, %9, %10, %11, %12, %13, %14, %15, %16, %17, %18, %19, %20, %21, %22, %23}, %24, %25, 1, 1, 1, 0, 1;\n"
    : "+f"(d[0]), "+f"(d[1]), "+f"(d[2]), "+f"(d[3]), "+f"(d[4]), "+f"(d[5]), "+f"(d[6]), "+f"(d[7]), "+f"(d[8]), "+f"(d[9]), "+f"(d[10]), "+f"(d[11]), "+f"(d[12]), "+f"(d[13]), "+f"(d[14]), "+f"(d[15]), "+f"(d[16]), "+f"(d[17]), "+f"(d[18]), "+f"(d[19]), "+f"(d[20]), "+f"(d[21]), "+f"(d[22]), "+f"(d[23])
    : "l"(descA), "l"(descB));
}
__device__ __forceinline__ void wgmma_ss_n80_tb(float (&d)[40], uint64_t descA, uint64_t descB) {
  asm volatile("wgmma.mma_async.sync.aligned.m64n80k16.f32.bf16.bf16 {%0, %1, %2, %3, %4, %5, %6, %7, %8, %9, %10, %11, %12, %13, %14, %15, %16, %17, %18, %19, %20, %21, %22, %23, %24, %25, %26, %27, %28, %29, %30, %31, %32, %33, %34, %35, %36, %37, %38, %39}, %40, %41, 1, 1, 1, 0, 1;\n"
    : "+f"(d[0]), "+f"(d[1]), "+f"(d[2]), "+f"(d[3]), "+f"(d[4]), "+f"(d[5]), "+f"(d[6]), "+f"(d[7]), "+f"(d[8]), "+f"(d[9]), "+f"(d[10]), "+f"(d[11]), "+f"(d[12]), "+f"(d[13]), "+f"(d[14]), "+f"(d[15]), "+f"(d[16]), "+f"(d[17]), "+f"(d[18]), "+f"(d[19]), "+f"(d[20]), "+f"(d[21]), "+f"(d[22]), "+f"(d[23]), "+f"(d[24]), "+f"(d[25]), "+f"(d[26]), "+f"(d[27]), "+f"(d[28]), "+f"(d[29]), "+f"(d[30]), "+f"(d[31]), "+f"(d[32]), "+f"(d[33]), "+f"(d[34]), "+f"(d[35]), "+f"(d[36]), "+f"(d[37]), "+f"(d[38]), "+f"(d[39])
    : "l"(descA), "l"(descB));
}
template <int SCALE_D>
__device__ __forceinline__ void wgmma_rs_n64(float (&d)[32], uint32_t a0, uint32_t a1, uint32_t a2, uint32_t a3, uint64_t descB) {
  asm volatile("wgmma.mma_async.sync.aligned.m64n64k16.f32.bf16.bf16 {%0, %1, %2, %3, %4, %5, %6, %7, %8, %9, %10, %11, %12, %13, %14, %15, %16, %17, %18, %19, %20, %21, %22, %23, %24, %25, %26, %27, %28, %29, %30, %31}, {%32, %33, %34, %35}, %36, %37, 1, 1, 0;\n"
    : "+f"(d[0]), "+f"(d[1]), "+f"(d[2]), "+f"(d[3]), "+f"(d[4]), "+f"(d[5]), "+f"(d[6]), "+f"(d[7]), "+f"(d[8]), "+f"(d[9]), "+f"(d[10]), "+f"(d[11]), "+f"(d[12]), "+f"(d[13]), "+f"(d[14]), "+f"(d[15]), "+f"(d[16]), "+f"(d[17]), "+f"(d[18]), "+f"(d[19]), "+f"(d[20]), "+f"(d[21]), "+f"(d[22]), "+f"(d[23]), "+f"(d[24]), "+f"(d[25]), "+f"(d[26]), "+f"(d[27]), "+f"(d[28]), "+f"(d[29]), "+f"(d[30]), "+f"(d[31])
    : "r"(a0), "r"(a1), "r"(a2), "r"(a3), "l"(descB), "n"(SCALE_D));
}
template <int SCALE_D>
__device__ __forceinline__ void wgmma_rs_n128(float (&d)[64], uint32_t a0, uint32_t a1, uint32_t a2, uint32_t a3, uint64_t descB) {
  asm volatile("wgmma.mma_async.sync.aligned.m64n128k16.f32.bf16.bf16 {%0, %1, %2, %3, %4, %5, %6, %7, %8, %9, %10, %11, %12, %13, %14, %15, %16, %17, %18, %19, %20, %21, %22, %23, %24, %25, %26, %27, %28, %29, %30, %31, %32, %33, %34, %35, %36, %37, %38, %39, %40, %41, %42, %43, %44, %45, %46, %47, %48, %49, %50, %51, %52, %53, %54, %55, %56, %57, %58, %59, %60, %61, %62, %63}, {%64, %65, %66, %67}, %68, %69, 1, 1, 0;\n"
    : "+f"(d[0]), "+f"(d[1]), "+f"(d[2]), "+f"(d[3]), "+f"(d[4]), "+f"(d[5]), "+f"(d[6]), "+f"(d[7]), "+f"(d[8]), "+f"(d[9]), "+f"(d[10]), "+f"(d[11]), "+f"(d[12]), "+f"(d[13]), "+f"(d[14]), "+f"(d[15]), "+f"(d[16]), "+f"(d[17]), "+f"(d[18]), "+f"(d[19]), "+f"(d[20]), "+f"(d[21]), "+f"(d[22]), "+f"(d[23]), "+f"(d[24]), "+f"(d[25]), "+f"(d[26]), "+f"(d[27]), "+f"(d[28]), "+f"(d[29]), "+f"(d[30]), "+f"(d[31]), "+f"(d[32]), "+f"(d[33]), "+f"(d[34]), "+f"(d[35]), "+f"(d[36]), "+f"(d[37]), "+f"(d[38]), "+f"(d[39]), "+f"(d[40]), "+f"(d[41]), "+f"(d[42]), "+f"(d[43]), "+f"(d[44]), "+f"(d[45]), "+f"(d[46]), "+f"(d[47]), "+f"(d[48]), "+f"(d[49]), "+f"(d[50]), "+f"(d[51]), "+f"(d[52]), "+f"(d[53]), "+f"(d[54]), "+f"(d[55]), "+f"(d[56]), "+f"(d[57]), "+f"(d[58]), "+f"(d[59]), "+f"(d[60]), "+f"(d[61]), "+f"(d[62]), "+f"(d[63])
    : "r"(a0), "r"(a1), "r"(a2), "r"(a3), "l"(descB), "n"(SCALE_D));
}
template <int SCALE_D>
__device__ __forceinline__ void wgmma_rs_n24_tb(float (&d)[12], uint32_t a0, uint32_t a1, uint32_t a2, uint32_t a3, uint64_t descB) {
  asm volatile("wgmma.mma_async.sync.aligned.m64n24k16.f32.bf16.bf16 {%0, %1, %2, %3, %4, %5, %6, %7, %8, %9, %10, %11}, {%12, %13, %14, %15}, %16, %17, 1, 1, 1;\n"
    : "+f"(d[0]), "+f"(d[1]), "+f"(d[2]), "+f"(d[3]), "+f"(d[4]), "+f"(d[5]), "+f"(d[6]), "+f"(d[7]), "+f"(d[8]), "+f"(d[9]), "+f"(d[10]), "+f"(d[11])
    : "r"(a0), "r"(a1), "r"(a2), "r"(a3), "l"(descB), "n"(SCALE_D));
}

constexpr uint32_t DHI_SW128_K = (1024 >> 4) | (1u << 30);
constexpr uint32_t DHI_SW64_MN = (512 >> 4) | (2u << 30);

template <int NC>
__device__ __forceinline__ void store_tile_bf16(const float (&acc)[NC / 2], float scale, uint32_t stage, uint8_t* stage_ptr,
                                                __nv_bfloat16* gdst, int gpitch, int lane) {
  constexpr int PITCH = NC * 2 + 16;
  const uint32_t waddr = stage + ((lane & 7) + ((lane >> 3) & 1) * 8) * PITCH + (lane >> 4) * 16;
#pragma unroll
  for (int j = 0; j < NC / 16; j++) {
    stsm4(waddr + j * 32, pack_bf16(acc[8 * j] * scale, acc[8 * j + 1] * scale), pack_bf16(acc[8 * j + 2] * scale, acc[8 * j + 3] * scale),
          pack_bf16(acc[8 * j + 4] * scale, acc[8 * j + 5] * scale), pack_bf16(acc[8 * j + 6] * scale, acc[8 * j + 7] * scale));
  }
  __syncwarp();
  constexpr int CPR = NC / 8;
#pragma unroll
  for (int i = 0; i < CPR / 2; i++) {
    const int c = i * 32 + lane, r = c / CPR, cc = c % CPR;
    const uint4 v = *reinterpret_cast<const uint4*>(stage_ptr + r * PITCH + cc * 16);
    *reinterpret_cast<uint4*>(gdst + (size_t)r * gpitch + cc * 8) = v;
  }
}

__device__ __forceinline__ void signal_done(unsigned int* flag, int wg, int tid) {
  asm volatile("bar.sync %0, 128;" :: "r"(wg + 1) : "memory");
  if ((tid & 127) == 0) asm volatile("red.release.gpu.global.add.u32 [%0], 1;" :: "l"(flag) : "memory");
}
__device__ __forceinline__ void wait_flags8(const unsigned int* f, unsigned int target) {
  for (int spin = 0; spin < (1 << 26); spin++) {
    unsigned int a, b, c, d, e, g, h, i;
    asm volatile("ld.volatile.global.v4.u32 {%0, %1, %2, %3}, [%4];" : "=r"(a), "=r"(b), "=r"(c), "=r"(d) : "l"(f) : "memory");
    asm volatile("ld.volatile.global.v4.u32 {%0, %1, %2, %3}, [%4];" : "=r"(e), "=r"(g), "=r"(h), "=r"(i) : "l"(f + 4) : "memory");
    if (min(min(min(a, b), min(c, d)), min(min(e, g), min(h, i))) >= target) break;
    __nanosleep(32);
  }
  asm volatile("fence.acq_rel.gpu;" ::: "memory");
  asm volatile("fence.proxy.async;" ::: "memory");
}

#define RP_LD 2
#define RP_ST 6
constexpr int K1_STAGES = 4;
constexpr int K1_A_BYTES = 256 * 128;
constexpr int K1_B_BYTES = 64 * 160 * 2;
constexpr int K1_STAGE = K1_A_BYTES + K1_B_BYTES;
constexpr int K1_SMEM = 5 * K1_A_BYTES + 61440 + 1024;
constexpr int KV_STAGES = 5;
constexpr int KVW_OFF = KV_STAGES * K1_A_BYTES;

__global__ void __launch_bounds__(512, 1)
proj_kernel(const __grid_constant__ CUtensorMap tmX, const __grid_constant__ CUtensorMap tmWq, const __grid_constant__ CUtensorMap tmWqkv,
            const __nv_bfloat16* __restrict__ wk, const __nv_bfloat16* __restrict__ wv, const __nv_bfloat16* __restrict__ gate_w,
            const __nv_bfloat16* __restrict__ woA, const __nv_bfloat16* __restrict__ woB) {
  extern __shared__ uint8_t smem_raw[];
  __shared__ __align__(8) uint64_t bar_full[KV_STAGES], bar_empty[KV_STAGES];
  uint8_t* smem = reinterpret_cast<uint8_t*>((reinterpret_cast<uintptr_t>(smem_raw) + 1023) & ~(uintptr_t)1023);
  const uint32_t sbase = smem_u32(smem);
  const uint32_t dbase = sbase & 0x3FFFFu;
  const int tid = threadIdx.x, warp = tid >> 5, lane = tid & 31;
  const bool is_kv = blockIdx.x >= 128;
  PROF(0, 0);
  if (tid == 32) { prefetch_tmap(&tmX); prefetch_tmap((blockIdx.x & 15) < 4 ? &tmWq : &tmWqkv); }
  if (tid == 0) {
    for (int i = 0; i < KV_STAGES; i++) { mbar_init(smem_u32(&bar_full[i]), 1); mbar_init(smem_u32(&bar_empty[i]), is_kv ? 8 : 16); }
    fence_mbar_init();
  }
  uint2 wa[2][5], wb[2][5]; uint32_t gw[2];
  if (is_kv && tid < 320) {
#pragma unroll
    for (int r = 0; r < 2; r++) {
      const int k = tid + r * 320;
      const uint2* pk = reinterpret_cast<const uint2*>(wk + k * 20);
      const uint2* pv = reinterpret_cast<const uint2*>(wv + k * 20);
#pragma unroll
      for (int i = 0; i < 5; i++) { wa[r][i] = __ldg(pk + i); wb[r][i] = __ldg(pv + i); }
      gw[r] = (uint32_t)__bfloat16_as_ushort(gate_w[k]);
    }
  }
  __syncthreads();
  if (tid == 480) {
    if (!is_kv) { g_done[blockIdx.x] = 0u; g_doneL[blockIdx.x] = 0u; }
    asm volatile("fence.acq_rel.gpu;" ::: "memory");
    pdl_launch();
  }
  __syncwarp();

  if (!is_kv) {
    const int mb = blockIdx.x >> 4, nb = blockIdx.x & 15;
    const CUtensorMap* tw = nb < 4 ? &tmWq : &tmWqkv;
    const int j0 = (nb < 4 ? nb : nb - 4) * 5;
    auto load = [&](int kt) {
      const int s = kt % K1_STAGES;
      const uint32_t fb = smem_u32(&bar_full[s]);
      mbar_expect_tx(fb, K1_STAGE);
      tma_2d(sbase + s * K1_STAGE, &tmX, kt * 64, mb * 256, fb);
      tma_3d(sbase + s * K1_STAGE + K1_A_BYTES, tw, 0, kt * 64, j0, fb);
    };
    if (tid == 0) for (int kt = 0; kt < K1_STAGES; kt++) load(kt);
    __syncwarp();
    uint4 wv2[2];
    const int rq = blockIdx.x * 400 + tid - 112;
    const int rhalf = rq >= 25600, rr = rq - rhalf * 25600, rk = 2 * (rr / 80), rch = rr % 80;
    {
      const int wg = warp >> 2;
      float acc0[48], acc1[32];
#pragma unroll
      for (int i = 0; i < 48; i++) acc0[i] = 0.f;
#pragma unroll
      for (int i = 0; i < 32; i++) acc1[i] = 0.f;
      auto descs = [&](int kt, uint32_t& alo, uint32_t& blo) {
        const int s = kt % K1_STAGES;
        alo = ((dbase + s * K1_STAGE + wg * 8192) >> 4) | (1u << 16);
        blo = ((dbase + s * K1_STAGE + K1_A_BYTES) >> 4) | ((4096u >> 4) << 16);
      };
      for (int kt = 0; kt < 7; kt++) {
        mbar_wait(smem_u32(&bar_full[kt % K1_STAGES]), (kt / K1_STAGES) & 1);
        uint32_t alo, blo;
        descs(kt, alo, blo);
        fence_regs(acc0); fence_regs(acc1);
        wg_fence();
#pragma unroll
        for (int k = 0; k < 4; k++) {
          wgmma_ss_n96_tb(acc0, mkd(alo + k * 2, DHI_SW128_K), mkd(blo + k * 64, DHI_SW64_MN));
          wgmma_ss_n64_tb(acc1, mkd(alo + k * 2, DHI_SW128_K), mkd(blo + 768 + k * 64, DHI_SW64_MN));
        }
        wg_commit();
        if (kt == RP_LD && tid >= 112) {
          const uint4* src = reinterpret_cast<const uint4*>((rhalf ? woB : woA) + rk * D_MODEL + rch * 8);
          wv2[0] = __ldg(src); wv2[1] = __ldg(src + D_MODEL / 8);
        }
        if (kt == RP_ST && tid >= 112) {
          uint4* dst = reinterpret_cast<uint4*>(g_wimg + ((rhalf * 8 + rch / 10) * 10 + (rk >> 6)) * 10240 + (rch % 10) * 1024 + (rk & 63) * 16);
          dst[0] = wv2[0]; dst[1] = wv2[1];
        }
        __syncwarp();
        if (kt > 0) {
          wg_wait<1>();
          const uint32_t eb = smem_u32(&bar_empty[(kt - 1) % K1_STAGES]);
          if (lane == 0) mbar_arrive(eb);
          if (tid == 0) { mbar_wait(eb, ((kt - 1) / K1_STAGES) & 1); load(kt - 1 + K1_STAGES); }
          __syncwarp();
        }
      }
      fence_regs(acc0); fence_regs(acc1);
#pragma unroll
      for (int kt = 7; kt < 10; kt++) {
        mbar_wait(smem_u32(&bar_full[kt % K1_STAGES]), (kt / K1_STAGES) & 1);
        uint32_t alo, blo;
        descs(kt, alo, blo);
        wg_fence();
#pragma unroll
        for (int k = 0; k < 4; k++) wgmma_ss_n96_tb(acc0, mkd(alo + k * 2, DHI_SW128_K), mkd(blo + k * 64, DHI_SW64_MN));
      }
      wg_commit();
#pragma unroll
      for (int kt = 7; kt < 10; kt++) {
        uint32_t alo, blo;
        descs(kt, alo, blo);
#pragma unroll
        for (int k = 0; k < 4; k++) wgmma_ss_n64_tb(acc1, mkd(alo + k * 2, DHI_SW128_K), mkd(blo + 768 + k * 64, DHI_SW64_MN));
      }
      wg_commit();
      wg_wait<1>();
      fence_regs(acc0);
      {
        const uint32_t eb = smem_u32(&bar_empty[6 % K1_STAGES]);
        if (lane == 0) mbar_arrive(eb);
        mbar_wait(eb, (6 / K1_STAGES) & 1);
      }
      const int w4 = warp & 3;
      const int row0 = mb * 256 + wg * 64 + w4 * 16;
      const float scale = nb < 4 ? 0.22360679774997896f * 1.4426950408889634f : 1.0f;
      __nv_bfloat16* gdst = nb < 4 ? g_q + (size_t)row0 * D_MODEL + nb * 160 : g_qkv + (size_t)row0 * (3 * D_MODEL) + (nb - 4) * 160;
      const int gpitch = nb < 4 ? D_MODEL : 3 * D_MODEL;
      {
        const uint32_t off = (6 % K1_STAGES) * K1_STAGE + warp * (16 * (96 * 2 + 16));
        store_tile_bf16<96>(acc0, scale, sbase + off, smem + off, gdst, gpitch, lane);
        wg_wait<0>();
        fence_regs(acc1);
        PROF(0, 1);
        __syncwarp();
        store_tile_bf16<64>(acc1, scale, sbase + off, smem + off, gdst + 96, gpitch, lane);
      }
    }
  } else {
    const int cb = blockIdx.x - 128;
    if (warp == 8 && lane == 0) {
      for (int it = 0; it < KV_STAGES; it++) {
        const uint32_t fb = smem_u32(&bar_full[it]);
        mbar_expect_tx(fb, K1_A_BYTES);
        tma_2d(sbase + it * K1_A_BYTES, &tmX, it * 64, cb * 512, fb);
      }
    }
    __syncwarp();
    if (tid < 320) {
#pragma unroll
      for (int r = 0; r < 2; r++) {
        uint4* dst = reinterpret_cast<uint4*>(smem + KVW_OFF + (tid + r * 320) * 16);
        dst[0] = make_uint4(wa[r][0].x, wa[r][0].y, wa[r][1].x, wa[r][1].y);
        dst[640] = make_uint4(wa[r][2].x, wa[r][2].y, wa[r][3].x, wa[r][3].y);
        dst[1280] = make_uint4(wa[r][4].x, wa[r][4].y, 0u, 0u);
        dst[1920] = make_uint4(wb[r][0].x, wb[r][0].y, wb[r][1].x, wb[r][1].y);
        dst[2560] = make_uint4(wb[r][2].x, wb[r][2].y, wb[r][3].x, wb[r][3].y);
        dst[3200] = make_uint4(wb[r][4].x, wb[r][4].y, gw[r], 0u);
      }
    }
    fence_proxy_async();
    asm volatile("bar.sync 1, 512;" ::: "memory");
    PROF(0, 1);
    auto produce = [&](int it0, int it1) {
      for (int it = it0; it < it1; it++) {
        const int s = it % KV_STAGES;
        mbar_wait(smem_u32(&bar_empty[s]), (it / KV_STAGES - 1) & 1);
        const uint32_t fb = smem_u32(&bar_full[s]);
        mbar_expect_tx(fb, K1_A_BYTES);
        tma_2d(sbase + s * K1_A_BYTES, &tmX, (it >= 10 ? it - 10 : it) * 64, cb * 512 + (it >= 10 ? 256 : 0), fb);
      }
    };
    if (tid == 256) produce(KV_STAGES, 15);
    __syncwarp();
    {
      const int pass = warp >> 3, wg = (warp >> 2) & 1, w4 = warp & 3, g = lane >> 2, t = lane & 3;
      if (pass == 1) asm volatile("bar.sync 2, 512;" ::: "memory");
      {
        float acc[2][24];
#pragma unroll
        for (int i = 0; i < 24; i++) { acc[0][i] = 0.f; acc[1][i] = 0.f; }
        for (int kt = 0; kt < 10; kt++) {
          const int it = pass * 10 + kt, s = it % KV_STAGES;
          mbar_wait(smem_u32(&bar_full[s]), (it / KV_STAGES) & 1);
          const uint32_t alo = ((dbase + s * K1_A_BYTES + wg * 16384) >> 4) | (1u << 16);
          const uint32_t blo = ((dbase + KVW_OFF + kt * 1024) >> 4) | ((128u >> 4) << 16);
          fence_regs(acc[0]); fence_regs(acc[1]);
          wg_fence();
#pragma unroll
          for (int k = 0; k < 4; k++) {
            wgmma_ss_n48_tb(acc[0], mkd(alo + k * 2, DHI_SW128_K), mkd(blo + k * 16, 10240u >> 4));
            wgmma_ss_n48_tb(acc[1], mkd(alo + 512 + k * 2, DHI_SW128_K), mkd(blo + k * 16, 10240u >> 4));
          }
          wg_commit();
          if (kt > 0) {
            wg_wait<1>();
            if (lane == 0) mbar_arrive(smem_u32(&bar_empty[(it - 1) % KV_STAGES]));
          }
        }
        wg_wait<0>();
        fence_regs(acc[0]); fence_regs(acc[1]);
        if (lane == 0) mbar_arrive(smem_u32(&bar_empty[(pass * 10 + 9) % KV_STAGES]));
        if (pass == 0) asm volatile("bar.arrive 2, 512;" ::: "memory");
        PROF(0, 2);
        if (tid == 0) produce(15, 20);
        __syncwarp();
        float kmax2 = 0.f, vmax = 0.f;
#pragma unroll
        for (int hh = 0; hh < 4; hh++) {
          const int h = hh & 1;
          const float (&a)[24] = acc[hh >> 1];
          const int key = cb * 512 + pass * 256 + wg * 128 + (hh >> 1) * 64 + w4 * 16 + g + h * 8;
          const int grp = key >> 7, kk = key & 127;
          const bool poly = (TMASK >> (kk >> 3)) & 1;
          uint8_t* gp = g_kvimg + grp * GRP_BYTES;
          const uint32_t k0 = pack_bf16(a[2 * h], a[2 * h + 1]);
          const uint32_t k1 = pack_bf16(a[4 + 2 * h], a[5 + 2 * h]);
          uint32_t k2 = pack_bf16(a[8 + 2 * h], a[9 + 2 * h]);
          float n2 = bf_lo(k0) * bf_lo(k0) + bf_hi(k0) * bf_hi(k0) + bf_lo(k1) * bf_lo(k1) + bf_hi(k1) * bf_hi(k1);
          if (t < 2) {
            n2 += bf_lo(k2) * bf_lo(k2) + bf_hi(k2) * bf_hi(k2);
            k2 = pack_bf16(bf_lo(k2) * 0.5f, bf_hi(k2) * 0.5f);
          } else if (t == 2) k2 = poly ? pack_bf16(24.f, 2.5f) : pack_bf16(0.5f, 0.f);
          else k2 = poly ? pack_bf16(0.5f, 0.f) : 0u;
          *reinterpret_cast<uint32_t*>(gp + kk * 16 + t * 4) = k0;
          *reinterpret_cast<uint32_t*>(gp + PLANE + kk * 16 + t * 4) = k1;
          *reinterpret_cast<uint32_t*>(gp + 2 * PLANE + kk * 16 + t * 4) = k2;
          n2 += __shfl_xor_sync(0xffffffffu, n2, 1);
          n2 += __shfl_xor_sync(0xffffffffu, n2, 2);
          kmax2 = (n2 > kmax2 || n2 != n2) ? n2 : kmax2;
          uint32_t v0 = pack_bf16(a[12 + 2 * h], a[13 + 2 * h]);
          uint32_t v1 = pack_bf16(a[16 + 2 * h], a[17 + 2 * h]);
          uint32_t v2 = pack_bf16(a[20 + 2 * h], a[21 + 2 * h]);
          float vm = fmaxf(fmaxf(fabsf(bf_lo(v0)), fabsf(bf_hi(v0))), fmaxf(fabsf(bf_lo(v1)), fabsf(bf_hi(v1))));
          if (t < 2) vm = fmaxf(vm, fmaxf(fabsf(bf_lo(v2)), fabsf(bf_hi(v2))));
          else if (t == 2) {
            const float z = a[20 + 2 * h];
            g_gate[key] = 1.f / (1.f + __expf(-z));
            v2 = 0x00003F80u;
          } else v2 = 0u;
          vmax = fmaxf(vmax, vm);
          if (poly) { v0 ^= 0x80008000u; v1 ^= 0x80008000u; v2 ^= 0x80008000u; }
          uint8_t* vp = gp + 3 * PLANE + (kk >> 3) * 384 + (kk & 7) * 16 + t * 4;
          *reinterpret_cast<uint32_t*>(vp) = v0;
          *reinterpret_cast<uint32_t*>(vp + 128) = v1;
          *reinterpret_cast<uint32_t*>(vp + 256) = v2;
        }
#pragma unroll
        for (int o = 1; o < 32; o <<= 1) {
          const float a = __shfl_xor_sync(0xffffffffu, kmax2, o);
          kmax2 = (a > kmax2 || a != a) ? a : kmax2;
          vmax = fmaxf(vmax, __shfl_xor_sync(0xffffffffu, vmax, o));
        }
        if (lane == 0) { g_kmax2[cb * 16 + warp] = kmax2; g_vmax[cb * 16 + warp] = vmax; }
      }
    }
  }
}

__device__ __forceinline__ uint32_t ex2_pair_poly(float u0, float u1, uint32_t one2) {
  const uint32_t W = __byte_perm(__float_as_uint(u0), __float_as_uint(u1), 0x6521);
  uint32_t v; asm("lop3.b32 %0, %1, 0x007F007F, %2, 0xEA;" : "=r"(v) : "r"(W), "r"(one2));
  uint32_t L, p;
  asm("fma.rn.bf16x2 %0, %1, %2, %3;" : "=r"(L) : "r"(v), "r"(0x1f961f96u), "r"(0x9fe39fe3u));
  asm("fma.rn.bf16x2 %0, %1, %1, %2;" : "=r"(p) : "r"(L), "r"(0x00f500f5u));
  return W + p;
}
template <int JOFF>
__device__ __forceinline__ void softmax_slow(const float (&S)[32], uint32_t (&P)[16], float (&O)[12], float& m0, float& m1) {
  float a0 = m0, a1 = m1;
#pragma unroll
  for (int j = 0; j < 8; j++) {
    a0 = fmaxf(a0, fmaxf(S[4 * j], S[4 * j + 1]));
    a1 = fmaxf(a1, fmaxf(S[4 * j + 2], S[4 * j + 3]));
  }
  a0 = fmaxf(a0, __shfl_xor_sync(0xffffffffu, a0, 1)); a0 = fmaxf(a0, __shfl_xor_sync(0xffffffffu, a0, 2));
  a1 = fmaxf(a1, __shfl_xor_sync(0xffffffffu, a1, 1)); a1 = fmaxf(a1, __shfl_xor_sync(0xffffffffu, a1, 2));
  const float c0 = ex2(m0 - a0), c1 = ex2(m1 - a1);
  m0 = a0; m1 = a1;
#pragma unroll
  for (int j = 0; j < 3; j++) { O[4 * j] *= c0; O[4 * j + 1] *= c0; O[4 * j + 2] *= c1; O[4 * j + 3] *= c1; }
#pragma unroll
  for (int i = 0; i < 16; i++) {
    const float m = (i & 1) ? a1 : a0;
    const uint32_t p = pack_bf16(ex2(S[2 * i] - m), ex2(S[2 * i + 1] - m));
    P[i] = ((TMASK >> (JOFF + i / 2)) & 1) ? (p ^ 0x80008000u) : p;
  }
}
constexpr uint32_t DHI_KV = 128 >> 4;
__device__ __forceinline__ void issue_qk(float (&S)[32], const uint32_t (&q)[8], uint64_t base) {
  wgmma_rs_n64<0>(S, q[0], q[1], q[2], q[3], base + (uint64_t)((PLANE >> 4) << 16));
  wgmma_rs_n64<1>(S, q[4], q[5], q[6], q[7], base + (uint64_t)(2 * PLANE >> 4));
}
__device__ __forceinline__ void issue_pv(float (&O)[12], const uint32_t (&P)[16], uint64_t vbase) {
#pragma unroll
  for (int kk = 0; kk < 4; kk++)
    wgmma_rs_n24_tb<1>(O, P[4 * kk], P[4 * kk + 1], P[4 * kk + 2], P[4 * kk + 3], vbase + (uint64_t)(kk * (768 >> 4)));
}

constexpr uint32_t VOFF = ((3 * PLANE) >> 4) + ((384u >> 4) << 16);
constexpr int KVR = 4;
constexpr int OFF_W = KVR * GRP_BYTES;
constexpr int OFF_X = OFF_W + 10 * 10240;
constexpr int OFF_BAR = OFF_X + 4 * 16384;
constexpr int K2_SMEM = OFF_BAR + 512 + 1024;
constexpr int TSL = 7;
constexpr int BAR_KV = 0, BAR_W = 4, BAR_TA = 5, BAR_TE = 12, BAR_OWN = 19, BAR_L = 20, CNT_KV = 21, BAR_WA = 23, BAR_WF = 33, CNT_TK = 43;
constexpr int NSTEP = 2 * NGRP;

__device__ __forceinline__ void kv_load(uint32_t sbase, int step) {
  const uint32_t bar = sbase + OFF_BAR + (BAR_KV + (step & (KVR - 1))) * 8;
  mbar_expect_tx(bar, GRP_BYTES);
  bulk_g2s(sbase + (step & (KVR - 1)) * GRP_BYTES, g_kvimg + (step & (NGRP - 1)) * GRP_BYTES, GRP_BYTES, bar);
}
__device__ __forceinline__ void kv_release(uint32_t sbase, int step, bool elected) {
  if (elected && step + KVR < NSTEP) {
    uint32_t old;
    asm volatile("atom.acq_rel.cta.shared::cta.inc.u32 %0, [%1], 3;" : "=r"(old) : "r"(sbase + OFF_BAR + CNT_KV * 8 + (step & (KVR - 1)) * 4) : "memory");
    if (old == 3u) kv_load(sbase, step + KVR);
  }
  __syncwarp();
}
__device__ __forceinline__ void kv_wait(uint32_t sbase, int step) {
  mbar_wait(sbase + OFF_BAR + (BAR_KV + (step & (KVR - 1))) * 8, (step / KVR) & 1);
}

__device__ __forceinline__ uint32_t kv_release_begin(uint32_t sbase, int slot, bool doit) {
  uint32_t old = 0;
  asm volatile("{\n.reg .pred p;\nsetp.ne.u32 p, %2, 0;\n@p atom.relaxed.cta.shared::cta.inc.u32 %0, [%1], 3;\n}\n"
               : "+r"(old) : "r"(sbase + OFF_BAR + CNT_KV * 8 + slot * 4), "r"((uint32_t)doit) : "memory");
  return old;
}
template <int H>
__device__ __forceinline__ void softmax_half(const float (&S)[64], uint32_t (&P)[16], uint32_t one2) {
#pragma unroll
  for (int i = 0; i < 16; i++) {
    if ((TMASK >> (8 * H + i / 2)) & 1) P[i] = ex2_pair_poly(S[32 * H + 2 * i], S[32 * H + 2 * i + 1], one2);
    else P[i] = pack_bf16(ex2(S[32 * H + 2 * i]), ex2(S[32 * H + 2 * i + 1]));
  }
}
__device__ __forceinline__ void attn_fast(const uint32_t (&q)[8], float (&O)[12], uint32_t sbase, int step0, int nsteps, bool elected, uint32_t one2) {
  uint64_t kb0 = mkd((sbase & 0x3FFFFu) >> 4, DHI_KV);
  asm volatile("" : "+l"(kb0));
#pragma unroll 1
  for (int step4 = step0; step4 < step0 + nsteps; step4 += KVR) {
#pragma unroll
    for (int j = 0; j < KVR; j++) {
      const int step = step4 + j;
      const uint64_t kb = kb0 + (uint64_t)(j * (GRP_BYTES >> 4));
      float S[64]; uint32_t PA[16], PB[16];
#pragma unroll
      for (int i = 0; i < 64; i++) S[i] = 0.f;
      mbar_wait(sbase + OFF_BAR + (BAR_KV + j) * 8, (step / KVR) & 1);
      fence_regs(S);
      wg_fence();
      wgmma_rs_n128<0>(S, q[0], q[1], q[2], q[3], kb + (uint64_t)((PLANE >> 4) << 16));
      wgmma_rs_n128<1>(S, q[4], q[5], q[6], q[7], kb + (uint64_t)(2 * PLANE >> 4));
      wg_commit();
      const uint32_t old = kv_release_begin(sbase, (j + KVR - 1) & (KVR - 1), elected && step > step0 && step - 1 + KVR < NSTEP);
      wg_wait<0>();
      fence_regs(S);
      softmax_half<0>(S, PA, one2);
      fence_regs(PA); fence_regs(O);
      wg_fence();
      issue_pv(O, PA, kb + VOFF);
      wg_commit();
      softmax_half<1>(S, PB, one2);
      fence_regs(PB);
      wg_fence();
      issue_pv(O, PB, kb + VOFF + 4 * (768 >> 4));
      wg_commit();
      if (old == 3u) kv_load(sbase, step - 1 + KVR);
      wg_wait<0>();
      fence_regs(PA); fence_regs(PB); fence_regs(O);
    }
  }
  kv_release(sbase, step0 + nsteps - 1, elected);
}
template <int H>
__device__ __forceinline__ void slow_step(const uint32_t (&q)[8], float (&O)[12], uint64_t kb, float& m0, float& m1) {
  float S[32]; uint32_t P[16];
#pragma unroll
  for (int i = 0; i < 32; i++) S[i] = 0.f;
  fence_regs(S);
  wg_fence();
  issue_qk(S, q, kb + 64 * H);
  wg_commit();
  wg_wait<0>();
  fence_regs(S);
  softmax_slow<8 * H>(S, P, O, m0, m1);
  fence_regs(P); fence_regs(O);
  wg_fence();
  issue_pv(O, P, kb + VOFF + H * 4 * (768 >> 4));
  wg_commit();
  wg_wait<0>();
  fence_regs(O); fence_regs(P);
}
__device__ __forceinline__ void attn_slow(const uint32_t (&q)[8], float (&O)[12], uint32_t sbase, int step0, int nsteps, bool elected, float& m0, float& m1) {
#pragma unroll 1
  for (int step = step0; step < step0 + nsteps; step++) {
    kv_wait(sbase, step);
    const uint64_t kb = mkd(((sbase & 0x3FFFFu) >> 4) + (step & (KVR - 1)) * (GRP_BYTES >> 4), DHI_KV);
    slow_step<0>(q, O, kb, m0, m1);
    slow_step<1>(q, O, kb, m0, m1);
    kv_release(sbase, step, elected);
  }
}

__device__ __forceinline__ void softmax8(float (&sc)[8], float scale) {
  float mx = sc[0];
#pragma unroll
  for (int w = 1; w < 8; w++) mx = fmaxf(mx, sc[w]);
  float l = 0.f;
#pragma unroll
  for (int w = 0; w < 8; w++) { sc[w] = ex2(sc[w] - mx); l += sc[w]; }
  const float r = __fdividef(scale, l);
#pragma unroll
  for (int w = 0; w < 8; w++) sc[w] *= r;
}
#define LEV(wg) 1
constexpr int LBOX = 30 * 320;
__device__ __forceinline__ uint2 lds64(uint32_t a) {
  uint2 v; asm volatile("ld.shared.v2.u32 {%0, %1}, [%2];" : "=r"(v.x), "=r"(v.y) : "r"(a)); return v;
}
__device__ __forceinline__ void local_attn(uint32_t stage, int t0, int i, int lane) {
  constexpr float SC = 0.22360679774997896f * 1.4426950408889634f, NEG = -1e9f * 1.4426950408889634f;
  const uint32_t base = stage + (lane >> 3) * LBOX + (lane & 7) * 40 + (i + 14) * 320;
  const int t = t0 + i;
  float sc[8];
#pragma unroll
  for (int w = 0; w < 8; w++) sc[w] = 0.f;
#pragma unroll 1
  for (int c = 0; c < 5; c++) {
    const uint2 qv = lds64(base + c * 8);
    const float q0 = bf_lo(qv.x), q1 = bf_hi(qv.x), q2 = bf_lo(qv.y), q3 = bf_hi(qv.y);
#pragma unroll
    for (int w = 0; w < 8; w++) {
      const uint2 k = lds64(base + c * 8 + 4 * LBOX - w * 640);
      sc[w] = fmaf(q0, bf_lo(k.x), sc[w]); sc[w] = fmaf(q1, bf_hi(k.x), sc[w]);
      sc[w] = fmaf(q2, bf_lo(k.y), sc[w]); sc[w] = fmaf(q3, bf_hi(k.y), sc[w]);
    }
  }
#pragma unroll
  for (int w = 0; w < 8; w++) sc[w] = t - 2 * w >= 0 ? sc[w] * SC : NEG;
  softmax8(sc, 1.f - g_gate[t]);
  uint2* dst = reinterpret_cast<uint2*>(g_a2 + (size_t)t * (2 * D_MODEL) + D_MODEL + lane * DH);
#pragma unroll 1
  for (int c = 0; c < 5; c++) {
    float o0 = 0.f, o1 = 0.f, o2 = 0.f, o3 = 0.f;
#pragma unroll
    for (int w = 0; w < 8; w++) {
      const uint2 v = lds64(base + c * 8 + 8 * LBOX - w * 640);
      o0 = fmaf(sc[w], bf_lo(v.x), o0); o1 = fmaf(sc[w], bf_hi(v.x), o1);
      o2 = fmaf(sc[w], bf_lo(v.y), o2); o3 = fmaf(sc[w], bf_hi(v.y), o3);
    }
    dst[c] = make_uint2(pack_bf16(o0, o1), pack_bf16(o2, o3));
  }
}
__device__ __forceinline__ uint32_t ta_slot(int i) { return i < 4 ? OFF_X + i * 16384 : (i - 4) * 16384; }

__global__ void __launch_bounds__(640, 1)
attn_kernel(const __grid_constant__ CUtensorMap tmA2, const __grid_constant__ CUtensorMap tmL, __nv_bfloat16* __restrict__ out, uint32_t one2) {
  extern __shared__ uint8_t smem_raw[];
  uint8_t* smem = reinterpret_cast<uint8_t*>((reinterpret_cast<uintptr_t>(smem_raw) + 1023) & ~(uintptr_t)1023);
  const uint32_t sbase = smem_u32(smem);
  const uint32_t dbase = sbase & 0x3FFFFu;
  const uint32_t bars = sbase + OFF_BAR;
  const int tid = threadIdx.x, wg = tid >> 7, warp = (tid >> 5) & 3, lane = tid & 31, g = lane >> 2, t = lane & 3;
  const int mb = blockIdx.x >> 3, nb = blockIdx.x & 7;
  const bool elected = (tid & 127) == 0;
  if (tid == 512) { prefetch_tmap(&tmL); prefetch_tmap(&tmA2); }
  if (tid == 0) {
    for (int i = 0; i < BAR_TE; i++) mbar_init(bars + i * 8, 1);
    for (int i = BAR_TE; i < BAR_TE + TSL; i++) mbar_init(bars + i * 8, 8);
    mbar_init(bars + BAR_OWN * 8, 4);
    mbar_init(bars + BAR_L * 8, 1);
    for (int i = 0; i < 10; i++) { mbar_init(bars + (BAR_WA + i) * 8, 1); mbar_init(bars + (BAR_WF + i) * 8, 8); }
    for (int i = 0; i < 4; i++) *reinterpret_cast<uint32_t*>(smem + OFF_BAR + CNT_KV * 8 + i * 4) = 0u;
    *reinterpret_cast<uint32_t*>(smem + OFF_BAR + CNT_TK * 8) = 0u;
    fence_mbar_init();
  }
  __syncthreads();
  auto tail_load = [&](int i) {
    const uint32_t fb = bars + (BAR_TA + i % TSL) * 8;
    mbar_expect_tx(fb, 16384);
    tma_2d(sbase + ta_slot(i % TSL), &tmA2, i < 10 ? D_MODEL + i * 64 : (i - 10) * 64, mb * 128, fb);
  };
  if (wg == 4) {
    asm volatile("setmaxnreg.dec.sync.aligned.u32 32;");
    pdl_wait();
    if (tid == 512) {
      for (int j = 0; j < KVR; j++) kv_load(sbase, j);
      mbar_expect_tx(bars + BAR_L * 8, 12 * LBOX);
      for (int i = 0; i < 12; i++) tma_2d(sbase + OFF_W + i * LBOX, &tmL, i * 160, blockIdx.x * 16 - 14, bars + BAR_L * 8);
    }
    __syncwarp();
    mbar_wait(bars + BAR_L * 8, 0);
#pragma unroll 1
    for (int i = 0; i < 4; i++) local_attn(sbase + OFF_W, blockIdx.x * 16, warp * 4 + i, lane);
    signal_done(&g_doneL[blockIdx.x], wg, tid);
    if (tid == 512) {
      PROF2(0, 2);
      fence_proxy_async();
      mbar_expect_tx(bars + BAR_W * 8, 10 * 10240);
      for (int i = 0; i < 5; i++) bulk_g2s(sbase + OFF_W + i * 20480, g_wimg + ((8 + nb) * 10) * 10240 + i * 20480, 20480, bars + BAR_W * 8);
      wait_flags8(&g_doneL[mb * 8], 1u);
      for (int i = 0; i < 4; i++) tail_load(i);
      mbar_wait(bars + BAR_OWN * 8, 0);
      for (int i = 4; i < 20; i++) {
        if (i >= TSL) mbar_wait(bars + (BAR_TE + i % TSL) * 8, (i / TSL - 1) & 1);
        if (i == 10) { wait_flags8(&g_done[mb * 8], 1u); PROF2(2, 0); }
        tail_load(i);
      }
    } else if (tid == 576) {
      mbar_wait(bars + BAR_OWN * 8, 0);
      asm volatile("red.release.gpu.global.add.u32 [%0], 1;" :: "l"(&g_done[blockIdx.x]) : "memory");
    } else if (tid == 544) {
      for (int kt = 0; kt < 10; kt++) {
        mbar_wait(bars + (BAR_WF + kt) * 8, 0);
        mbar_expect_tx(bars + (BAR_WA + kt) * 8, 10240);
        bulk_g2s(sbase + OFF_W + kt * 10240, g_wimg + (nb * 10 + kt) * 10240, 10240, bars + (BAR_WA + kt) * 8);
      }
    }
    return;
  }
  asm volatile("setmaxnreg.inc.sync.aligned.u32 112;");
  pdl_wait();
  PROF(1, 1);
  uint32_t q[8], q2[6];
  const int rowA = (blockIdx.x * 8 + wg) * 64 + warp * 16 + g;
  {
    const uint32_t* r0 = reinterpret_cast<const uint32_t*>(g_q + (size_t)rowA * DH);
    const uint32_t* r1 = r0 + 8 * (DH / 2);
    const uint32_t* s0 = r0 + 256 * (DH / 2);
    const uint32_t* s1 = s0 + 8 * (DH / 2);
    q[0] = r0[t]; q[1] = r1[t]; q[2] = r0[t + 4]; q[3] = r1[t + 4];
    q[4] = t < 2 ? r0[8 + t] : 0u;
    q[5] = t < 2 ? r1[8 + t] : 0u;
    q2[0] = s0[t]; q2[1] = s1[t]; q2[2] = s0[t + 4]; q2[3] = s1[t + 4];
    q2[4] = t < 2 ? s0[8 + t] : 0u;
    q2[5] = t < 2 ? s1[8 + t] : 0u;
  }
  float kmax2 = 0.f, vmax = 0.f;
#pragma unroll
  for (int i = 0; i < 2; i++) {
    const float a = g_kmax2[lane + 32 * i];
    kmax2 = (a > kmax2 || a != a) ? a : kmax2;
    vmax = fmaxf(vmax, g_vmax[lane + 32 * i]);
  }
#pragma unroll
  for (int o = 1; o < 32; o <<= 1) {
    const float a = __shfl_xor_sync(0xffffffffu, kmax2, o);
    kmax2 = (a > kmax2 || a != a) ? a : kmax2;
    vmax = fmaxf(vmax, __shfl_xor_sync(0xffffffffu, vmax, o));
  }
  const float qlim = (vmax >= 0.00390625f && vmax <= 256.f) ? 9025.f / kmax2 : -1.f;
  PROF(1, 2);
#pragma unroll 1
  for (int it = 0; it < 2; it++) {
    const int row0 = rowA + it * 256;
    if (it == 1) {
#pragma unroll
      for (int i = 0; i < 6; i++) q[i] = q2[i];
    }
    float n0 = bf_lo(q[0]) * bf_lo(q[0]) + bf_hi(q[0]) * bf_hi(q[0]) + bf_lo(q[2]) * bf_lo(q[2]) + bf_hi(q[2]) * bf_hi(q[2]) +
               bf_lo(q[4]) * bf_lo(q[4]) + bf_hi(q[4]) * bf_hi(q[4]);
    float n1 = bf_lo(q[1]) * bf_lo(q[1]) + bf_hi(q[1]) * bf_hi(q[1]) + bf_lo(q[3]) * bf_lo(q[3]) + bf_hi(q[3]) * bf_hi(q[3]) +
               bf_lo(q[5]) * bf_lo(q[5]) + bf_hi(q[5]) * bf_hi(q[5]);
    n0 += __shfl_xor_sync(0xffffffffu, n0, 1); n0 += __shfl_xor_sync(0xffffffffu, n0, 2);
    n1 += __shfl_xor_sync(0xffffffffu, n1, 1); n1 += __shfl_xor_sync(0xffffffffu, n1, 2);
    const bool safe = (n0 <= qlim) && (n1 <= qlim);
    uint32_t unsafe_any;
    asm volatile("{\n.reg .pred p, r;\nsetp.eq.u32 p, %1, 0;\nbarrier.cta.red.or.pred r, %2, 128, p;\nselp.u32 %0, 1, 0, r;\n}\n"
                 : "=r"(unsafe_any) : "r"((uint32_t)safe), "r"(wg + 1) : "memory");
    float O[12];
#pragma unroll
    for (int i = 0; i < 12; i++) O[i] = 0.f;
    if (!unsafe_any && t >= 2) { q[4] = q[5] = (t == 2) ? 0x3F804100u : 0x00003B80u; }
    q[6] = q[4]; q[7] = q[5];
    fence_regs(q);
    float m0 = -INFINITY, m1 = -INFINITY;
    if (!unsafe_any) attn_fast(q, O, sbase, it * NGRP, NGRP, elected, one2);
    else attn_slow(q, O, sbase, it * NGRP, NGRP, elected, m0, m1);
    const float l0 = __shfl_sync(0xffffffffu, O[8], (lane & ~3) | 2);
    const float l1 = __shfl_sync(0xffffffffu, O[10], (lane & ~3) | 2);
    const int tok = row0 >> 5;
    const float gt = g_gate[tok];
    const float i0 = gt / l0, i1 = gt / l1;
    uint32_t* o0 = reinterpret_cast<uint32_t*>(g_a2 + (size_t)tok * (2 * D_MODEL) + (row0 & 31) * DH);
    uint32_t* o1 = o0 + 8 * (DH / 2);
    o0[t] = pack_bf16(O[0] * i0, O[1] * i0); o1[t] = pack_bf16(O[2] * i1, O[3] * i1);
    o0[t + 4] = pack_bf16(O[4] * i0, O[5] * i0); o1[t + 4] = pack_bf16(O[6] * i1, O[7] * i1);
    if (t < 2) { o0[t + 8] = pack_bf16(O[8] * i0, O[9] * i0); o1[t + 8] = pack_bf16(O[10] * i1, O[11] * i1); }
  }
  uint32_t* ticket = reinterpret_cast<uint32_t*>(smem + OFF_BAR + CNT_TK * 8);
  if (elected) ticket[1 + wg] = atomicAdd(ticket, 1u);
  asm volatile("bar.sync %0, 128;" :: "r"(wg + 1) : "memory");
  if (elected) mbar_arrive(bars + BAR_OWN * 8);
  const int mt = ticket[1 + wg];
  PROF(1, 3);
  if (mt < 2) {
    float acc[40];
#pragma unroll
    for (int i = 0; i < 40; i++) acc[i] = 0.f;
    mbar_wait(bars + BAR_W * 8, 0);
    int sl = 0, ph = 0;
#pragma unroll 1
    for (int i = 0; i < 20; i++) {
      mbar_wait(bars + (BAR_TA + sl) * 8, ph);
      if (i >= 10) mbar_wait(bars + (BAR_WA + i - 10) * 8, 0);
      const uint32_t alo = ((dbase + ta_slot(sl) + mt * 8192) >> 4) | (1u << 16);
      const uint32_t blo = ((dbase + OFF_W + (i >= 10 ? i - 10 : i) * 10240) >> 4) | ((128u >> 4) << 16);
      fence_regs(acc);
      wg_fence();
#pragma unroll
      for (int k = 0; k < 4; k++) wgmma_ss_n80_tb(acc, mkd(alo + k * 2, DHI_SW128_K), mkd(blo + k * 16, 1024u >> 4));
      wg_commit();
      if (i > 0) {
        wg_wait<1>();
        if (lane == 0) mbar_arrive(bars + (BAR_TE + (sl == 0 ? TSL - 1 : sl - 1)) * 8);
        if (lane == 1 && i <= 10) mbar_arrive(bars + (BAR_WF + i - 1) * 8);
      }
      if (++sl == TSL) { sl = 0; ph ^= 1; }
    }
    wg_wait<0>();
    fence_regs(acc);
    asm volatile("bar.sync %0, 128;" :: "r"(wg + 1) : "memory");
    const uint32_t so = ta_slot(warp) + mt * 8192;
    const int row0 = mb * 128 + mt * 64 + warp * 16;
    store_tile_bf16<80>(acc, 1.0f, sbase + so, smem + so, out + (size_t)row0 * D_MODEL + nb * 80, D_MODEL, lane);
  }
}

typedef CUresult (*EncodeFn)(CUtensorMap*, CUtensorMapDataType, cuuint32_t, void*, const cuuint64_t*, const cuuint64_t*,
                             const cuuint32_t*, const cuuint32_t*, CUtensorMapInterleave, CUtensorMapSwizzle,
                             CUtensorMapL2promotion, CUtensorMapFloatOOBfill);

void make_map(EncodeFn fn, CUtensorMap* tm, const void* ptr, int rank, const cuuint64_t* dims, const cuuint64_t* strides,
              const cuuint32_t* box, CUtensorMapSwizzle sw) {
  const cuuint32_t es[3] = {1, 1, 1};
  fn(tm, CU_TENSOR_MAP_DATA_TYPE_BFLOAT16, rank, const_cast<void*>(ptr), dims, strides, box, es, CU_TENSOR_MAP_INTERLEAVE_NONE, sw,
     CU_TENSOR_MAP_L2_PROMOTION_L2_256B, CU_TENSOR_MAP_FLOAT_OOB_FILL_NONE);
}
void map_a(EncodeFn fn, CUtensorMap* tm, const void* p, int rows, int cols, int box_rows) {
  const cuuint64_t dims[2] = {(cuuint64_t)cols, (cuuint64_t)rows};
  const cuuint64_t str[1] = {(cuuint64_t)cols * 2};
  const cuuint32_t box[2] = {64, (cuuint32_t)box_rows};
  make_map(fn, tm, p, 2, dims, str, box, CU_TENSOR_MAP_SWIZZLE_128B);
}
void map_w(EncodeFn fn, CUtensorMap* tm, const void* p, int K, int N, int atom, CUtensorMapSwizzle sw) {
  const cuuint64_t dims[3] = {(cuuint64_t)atom, (cuuint64_t)K, (cuuint64_t)(N / atom)};
  const cuuint64_t str[2] = {(cuuint64_t)N * 2, (cuuint64_t)atom * 2};
  const cuuint32_t box[3] = {(cuuint32_t)atom, 64, 5};
  make_map(fn, tm, p, 3, dims, str, box, sw);
}

template <typename... KArgs, typename... Args>
void launch(void (*kern)(KArgs...), int grid, int block, int smem, bool pdl, Args... args) {
  cudaLaunchConfig_t cfg = {};
  cfg.gridDim = dim3(grid); cfg.blockDim = dim3(block); cfg.dynamicSmemBytes = smem; cfg.stream = cudaStreamPerThread;
  cudaLaunchAttribute at[1];
  at[0].id = cudaLaunchAttributeProgrammaticStreamSerialization;
  at[0].val.programmaticStreamSerializationAllowed = 1;
  cfg.attrs = at; cfg.numAttrs = pdl ? 1 : 0;
  cudaLaunchKernelEx(&cfg, kern, KArgs(args)...);
}

}

extern "C" void kernel_launch(void* const* d_in, const int* in_sizes, int n_in, void* d_out, int out_size) {
  (void)in_sizes; (void)n_in; (void)out_size;
  const __nv_bfloat16* x = (const __nv_bfloat16*)d_in[0];
  const __nv_bfloat16* wq = (const __nv_bfloat16*)d_in[1];
  const __nv_bfloat16* wk = (const __nv_bfloat16*)d_in[2];
  const __nv_bfloat16* wv = (const __nv_bfloat16*)d_in[3];
  const __nv_bfloat16* woA = (const __nv_bfloat16*)d_in[4];
  const __nv_bfloat16* wqkv = (const __nv_bfloat16*)d_in[6];
  const __nv_bfloat16* woB = (const __nv_bfloat16*)d_in[7];
  const __nv_bfloat16* gate_w = (const __nv_bfloat16*)d_in[8];

  static EncodeFn enc = nullptr;
  static void* a2_ptr = nullptr;
  static void* qkv_ptr = nullptr;
  if (!enc) {
    void* fp = nullptr;
    cudaDriverEntryPointQueryResult qr;
    cudaGetDriverEntryPoint("cuTensorMapEncodeTiled", &fp, cudaEnableDefault, &qr);
    enc = (EncodeFn)fp;
    cudaGetSymbolAddress(&a2_ptr, g_a2);
    cudaGetSymbolAddress(&qkv_ptr, g_qkv);
    cudaFuncSetAttribute(proj_kernel, cudaFuncAttributeMaxDynamicSharedMemorySize, K1_SMEM);
    cudaFuncSetAttribute(attn_kernel, cudaFuncAttributeMaxDynamicSharedMemorySize, K2_SMEM);
  }
  CUtensorMap tmX, tmWq, tmWqkv, tmA2, tmL;
  {
    const cuuint64_t dims[2] = {3 * D_MODEL, S_LEN};
    const cuuint64_t str[1] = {3 * D_MODEL * 2};
    const cuuint32_t box[2] = {160, 30};
    make_map(enc, &tmL, qkv_ptr, 2, dims, str, box, CU_TENSOR_MAP_SWIZZLE_NONE);
  }
  map_a(enc, &tmX, x, S_LEN, D_MODEL, 256);
  map_w(enc, &tmWq, wq, D_MODEL, D_MODEL, 32, CU_TENSOR_MAP_SWIZZLE_64B);
  map_w(enc, &tmWqkv, wqkv, D_MODEL, 3 * D_MODEL, 32, CU_TENSOR_MAP_SWIZZLE_64B);
  map_a(enc, &tmA2, a2_ptr, S_LEN, 2 * D_MODEL, 128);

  launch(proj_kernel, 132, 512, K1_SMEM, false, tmX, tmWq, tmWqkv, wk, wv, gate_w, woA, woB);
  launch(attn_kernel, 128, 640, K2_SMEM, true, tmA2, tmL, (__nv_bfloat16*)d_out, 0x3F803F80u);
}
```

```cpp
#include <cuda_runtime.h>
#include <cuda_bf16.h>
#include <cuda.h>
#include <stdint.h>

namespace {

constexpr int S_LEN = 2048, D_MODEL = 640, DH = 20;

constexpr int GRP = 128;
constexpr int PLANE = GRP * 16;
constexpr int GRP_BYTES = GRP * 16 * 6;
constexpr int NGRP = S_LEN / GRP;
#define TMASKV 0x6DB6u
constexpr uint32_t TMASK = TMASKV;

__device__ __align__(1024) __nv_bfloat16 g_q[S_LEN * D_MODEL];
__device__ __align__(1024) __nv_bfloat16 g_qkv[S_LEN * 3 * D_MODEL];
__device__ __align__(1024) __nv_bfloat16 g_a2[S_LEN * 2 * D_MODEL];
__device__ __align__(1024) uint8_t g_kvimg[NGRP * GRP_BYTES];
__device__ __align__(1024) uint8_t g_wimg[2 * 8 * 10 * 10240];
__device__ float g_gate[S_LEN];
__device__ float g_kmax2[64];
__device__ float g_vmax[64];
__device__ __align__(32) unsigned int g_doneL[128];
__device__ __align__(32) unsigned int g_done[128];

#define PROF(k, slot)
#define PROF2(k, slot)
__device__ __forceinline__ uint32_t smem_u32(const void* p) { return (uint32_t)__cvta_generic_to_shared(p); }
__device__ __forceinline__ uint64_t mkd(uint32_t lo, uint32_t hi) {
  uint64_t d; asm("mov.b64 %0, {%1, %2};" : "=l"(d) : "r"(lo), "r"(hi)); return d;
}
__device__ __forceinline__ void wg_fence() { asm volatile("wgmma.fence.sync.aligned;" ::: "memory"); }
__device__ __forceinline__ void wg_commit() { asm volatile("wgmma.commit_group.sync.aligned;" ::: "memory"); }
template <int N> __device__ __forceinline__ void wg_wait() { asm volatile("wgmma.wait_group.sync.aligned %0;" :: "n"(N) : "memory"); }
template <int N> __device__ __forceinline__ void fence_regs(float (&d)[N]) {
#pragma unroll
  for (int i = 0; i < N; i++) asm volatile("" : "+f"(d[i]) :: "memory");
}
template <int N> __device__ __forceinline__ void fence_regs(uint32_t (&d)[N]) {
#pragma unroll
  for (int i = 0; i < N; i++) asm volatile("" : "+r"(d[i]) :: "memory");
}
__device__ __forceinline__ void mbar_init(uint32_t bar, uint32_t cnt) { asm volatile("mbarrier.init.shared::cta.b64 [%0], %1;" :: "r"(bar), "r"(cnt)); }
__device__ __forceinline__ void mbar_expect_tx(uint32_t bar, uint32_t bytes) {
  asm volatile("mbarrier.arrive.expect_tx.shared::cta.b64 _, [%0], %1;" :: "r"(bar), "r"(bytes) : "memory");
}
__device__ __forceinline__ void mbar_arrive(uint32_t bar) { asm volatile("mbarrier.arrive.shared::cta.b64 _, [%0];" :: "r"(bar) : "memory"); }
#define WAIT_HINT 20000u
__device__ __forceinline__ void mbar_wait(uint32_t bar, uint32_t parity) {
  asm volatile("{\n.reg .pred p;\nWAIT_%=:\nmbarrier.try_wait.parity.shared::cta.b64 p, [%0], %1, %2;\n@p bra DONE_%=;\nbra WAIT_%=;\nDONE_%=:\n}\n"
               :: "r"(bar), "r"(parity), "r"(WAIT_HINT) : "memory");
}
__device__ __forceinline__ void fence_mbar_init() { asm volatile("fence.mbarrier_init.release.cluster;" ::: "memory"); }
__device__ __forceinline__ void fence_proxy_async() { asm volatile("fence.proxy.async.shared::cta;" ::: "memory"); }
__device__ __forceinline__ void bulk_g2s(uint32_t dst, const void* src, uint32_t bytes, uint32_t bar) {
  asm volatile("cp.async.bulk.shared::cluster.global.mbarrier::complete_tx::bytes [%0], [%1], %2, [%3];"
               :: "r"(dst), "l"(src), "r"(bytes), "r"(bar) : "memory");
}
__device__ __forceinline__ void tma_2d(uint32_t dst, const CUtensorMap* tm, int c0, int c1, uint32_t bar) {
  asm volatile("cp.async.bulk.tensor.2d.shared::cluster.global.mbarrier::complete_tx::bytes [%0], [%1, {%3, %4}], [%2];"
               :: "r"(dst), "l"((uint64_t)tm), "r"(bar), "r"(c0), "r"(c1) : "memory");
}
__device__ __forceinline__ void tma_3d(uint32_t dst, const CUtensorMap* tm, int c0, int c1, int c2, uint32_t bar) {
  asm volatile("cp.async.bulk.tensor.3d.shared::cluster.global.mbarrier::complete_tx::bytes [%0], [%1, {%3, %4, %5}], [%2];"
               :: "r"(dst), "l"((uint64_t)tm), "r"(bar), "r"(c0), "r"(c1), "r"(c2) : "memory");
}
__device__ __forceinline__ void prefetch_tmap(const CUtensorMap* tm) { asm volatile("prefetch.tensormap [%0];" :: "l"((uint64_t)tm) : "memory"); }
__device__ __forceinline__ void pdl_wait() { asm volatile("griddepcontrol.wait;" ::: "memory"); }
__device__ __forceinline__ void pdl_launch() { asm volatile("griddepcontrol.launch_dependents;" ::: "memory"); }
__device__ __forceinline__ float ex2(float x) { float y; asm("ex2.approx.ftz.f32 %0, %1;" : "=f"(y) : "f"(x)); return y; }
__device__ __forceinline__ uint32_t pack_bf16(float lo, float hi) {
  uint32_t r; asm("cvt.rn.bf16x2.f32 %0, %1, %2;" : "=r"(r) : "f"(hi), "f"(lo)); return r;
}
__device__ __forceinline__ float bf_lo(uint32_t x) { return __uint_as_float(x << 16); }
__device__ __forceinline__ float bf_hi(uint32_t x) { return __uint_as_float(x & 0xffff0000u); }
__device__ __forceinline__ void stsm4(uint32_t addr, uint32_t r0, uint32_t r1, uint32_t r2, uint32_t r3) {
  asm volatile("stmatrix.sync.aligned.m8n8.x4.shared.b16 [%0], {%1, %2, %3, %4};" :: "r"(addr), "r"(r0), "r"(r1), "r"(r2), "r"(r3) : "memory");
}

__device__ __forceinline__ void wgmma_ss_n160_tb(float (&d)[80], uint64_t descA, uint64_t descB) {
  asm volatile("wgmma.mma_async.sync.aligned.m64n160k16.f32.bf16.bf16 {%0, %1, %2, %3, %4, %5, %6, %7, %8, %9, %10, %11, %12, %13, %14, %15, %16, %17, %18, %19, %20, %21, %22, %23, %24, %25, %26, %27, %28, %29, %30, %31, %32, %33, %34, %35, %36, %37, %38, %39, %40, %41, %42, %43, %44, %45, %46, %47, %48, %49, %50, %51, %52, %53, %54, %55, %56, %57, %58, %59, %60, %61, %62, %63, %64, %65, %66, %67, %68, %69, %70, %71, %72, %73, %74, %75, %76, %77, %78, %79}, %80, %81, 1, 1, 1, 0, 1;\n"
    : "+f"(d[0]), "+f"(d[1]), "+f"(d[2]), "+f"(d[3]), "+f"(d[4]), "+f"(d[5]), "+f"(d[6]), "+f"(d[7]), "+f"(d[8]), "+f"(d[9]), "+f"(d[10]), "+f"(d[11]), "+f"(d[12]), "+f"(d[13]), "+f"(d[14]), "+f"(d[15]), "+f"(d[16]), "+f"(d[17]), "+f"(d[18]), "+f"(d[19]), "+f"(d[20]), "+f"(d[21]), "+f"(d[22]), "+f"(d[23]), "+f"(d[24]), "+f"(d[25]), "+f"(d[26]), "+f"(d[27]), "+f"(d[28]), "+f"(d[29]), "+f"(d[30]), "+f"(d[31]), "+f"(d[32]), "+f"(d[33]), "+f"(d[34]), "+f"(d[35]), "+f"(d[36]), "+f"(d[37]), "+f"(d[38]), "+f"(d[39]), "+f"(d[40]), "+f"(d[41]), "+f"(d[42]), "+f"(d[43]), "+f"(d[44]), "+f"(d[45]), "+f"(d[46]), "+f"(d[47]), "+f"(d[48]), "+f"(d[49]), "+f"(d[50]), "+f"(d[51]), "+f"(d[52]), "+f"(d[53]), "+f"(d[54]), "+f"(d[55]), "+f"(d[56]), "+f"(d[57]), "+f"(d[58]), "+f"(d[59]), "+f"(d[60]), "+f"(d[61]), "+f"(d[62]), "+f"(d[63]), "+f"(d[64]), "+f"(d[65]), "+f"(d[66]), "+f"(d[67]), "+f"(d[68]), "+f"(d[69]), "+f"(d[70]), "+f"(d[71]), "+f"(d[72]), "+f"(d[73]), "+f"(d[74]), "+f"(d[75]), "+f"(d[76]), "+f"(d[77]), "+f"(d[78]), "+f"(d[79])
    : "l"(descA), "l"(descB));
}
__device__ __forceinline__ void wgmma_ss_n96_tb(float (&d)[48], uint64_t descA, uint64_t descB) {
  asm volatile("wgmma.mma_async.sync.aligned.m64n96k16.f32.bf16.bf16 {%0, %1, %2, %3, %4, %5, %6, %7, %8, %9, %10, %11, %12, %13, %14, %15, %16, %17, %18, %19, %20, %21, %22, %23, %24, %25, %26, %27, %28, %29, %30, %31, %32, %33, %34, %35, %36, %37, %38, %39, %40, %41, %42, %43, %44, %45, %46, %47}, %48, %49, 1, 1, 1, 0, 1;\n"
    : "+f"(d[0]), "+f"(d[1]), "+f"(d[2]), "+f"(d[3]), "+f"(d[4]), "+f"(d[5]), "+f"(d[6]), "+f"(d[7]), "+f"(d[8]), "+f"(d[9]), "+f"(d[10]), "+f"(d[11]), "+f"(d[12]), "+f"(d[13]), "+f"(d[14]), "+f"(d[15]), "+f"(d[16]), "+f"(d[17]), "+f"(d[18]), "+f"(d[19]), "+f"(d[20]), "+f"(d[21]), "+f"(d[22]), "+f"(d[23]), "+f"(d[24]), "+f"(d[25]), "+f"(d[26]), "+f"(d[27]), "+f"(d[28]), "+f"(d[29]), "+f"(d[30]), "+f"(d[31]), "+f"(d[32]), "+f"(d[33]), "+f"(d[34]), "+f"(d[35]), "+f"(d[36]), "+f"(d[37]), "+f"(d[38]), "+f"(d[39]), "+f"(d[40]), "+f"(d[41]), "+f"(d[42]), "+f"(d[43]), "+f"(d[44]), "+f"(d[45]), "+f"(d[46]), "+f"(d[47])
    : "l"(descA), "l"(descB));
}
__device__ __forceinline__ void wgmma_ss_n64_tb(float (&d)[32], uint64_t descA, uint64_t descB) {
  asm volatile("wgmma.mma_async.sync.aligned.m64n64k16.f32.bf16.bf16 {%0, %1, %2, %3, %4, %5, %6, %7, %8, %9, %10, %11, %12, %13, %14, %15, %16, %17, %18, %19, %20, %21, %22, %23, %24, %25, %26, %27, %28, %29, %30, %31}, %32, %33, 1, 1, 1, 0, 1;\n"
    : "+f"(d[0]), "+f"(d[1]), "+f"(d[2]), "+f"(d[3]), "+f"(d[4]), "+f"(d[5]), "+f"(d[6]), "+f"(d[7]), "+f"(d[8]), "+f"(d[9]), "+f"(d[10]), "+f"(d[11]), "+f"(d[12]), "+f"(d[13]), "+f"(d[14]), "+f"(d[15]), "+f"(d[16]), "+f"(d[17]), "+f"(d[18]), "+f"(d[19]), "+f"(d[20]), "+f"(d[21]), "+f"(d[22]), "+f"(d[23]), "+f"(d[24]), "+f"(d[25]), "+f"(d[26]), "+f"(d[27]), "+f"(d[28]), "+f"(d[29]), "+f"(d[30]), "+f"(d[31])
    : "l"(descA), "l"(descB));
}
__device__ __forceinline__ void wgmma_ss_n48_tb(float (&d)[24], uint64_t descA, uint64_t descB) {
  asm volatile("wgmma.mma_async.sync.aligned.m64n48k16.f32.bf16.bf16 {%0, %1, %2, %3, %4, %5, %6, %7, %8, %9, %10, %11, %12, %13, %14, %15, %16, %17, %18, %19, %20, %21, %22, %23}, %24, %25, 1, 1, 1, 0, 1;\n"
    : "+f"(d[0]), "+f"(d[1]), "+f"(d[2]), "+f"(d[3]), "+f"(d[4]), "+f"(d[5]), "+f"(d[6]), "+f"(d[7]), "+f"(d[8]), "+f"(d[9]), "+f"(d[10]), "+f"(d[11]), "+f"(d[12]), "+f"(d[13]), "+f"(d[14]), "+f"(d[15]), "+f"(d[16]), "+f"(d[17]), "+f"(d[18]), "+f"(d[19]), "+f"(d[20]), "+f"(d[21]), "+f"(d[22]), "+f"(d[23])
    : "l"(descA), "l"(descB));
}
__device__ __forceinline__ void wgmma_ss_n80_tb(float (&d)[40], uint64_t descA, uint64_t descB) {
  asm volatile("wgmma.mma_async.sync.aligned.m64n80k16.f32.bf16.bf16 {%0, %1, %2, %3, %4, %5, %6, %7, %8, %9, %10, %11, %12, %13, %14, %15, %16, %17, %18, %19, %20, %21, %22, %23, %24, %25, %26, %27, %28, %29, %30, %31, %32, %33, %34, %35, %36, %37, %38, %39}, %40, %41, 1, 1, 1, 0, 1;\n"
    : "+f"(d[0]), "+f"(d[1]), "+f"(d[2]), "+f"(d[3]), "+f"(d[4]), "+f"(d[5]), "+f"(d[6]), "+f"(d[7]), "+f"(d[8]), "+f"(d[9]), "+f"(d[10]), "+f"(d[11]), "+f"(d[12]), "+f"(d[13]), "+f"(d[14]), "+f"(d[15]), "+f"(d[16]), "+f"(d[17]), "+f"(d[18]), "+f"(d[19]), "+f"(d[20]), "+f"(d[21]), "+f"(d[22]), "+f"(d[23]), "+f"(d[24]), "+f"(d[25]), "+f"(d[26]), "+f"(d[27]), "+f"(d[28]), "+f"(d[29]), "+f"(d[30]), "+f"(d[31]), "+f"(d[32]), "+f"(d[33]), "+f"(d[34]), "+f"(d[35]), "+f"(d[36]), "+f"(d[37]), "+f"(d[38]), "+f"(d[39])
    : "l"(descA), "l"(descB));
}
template <int SCALE_D>
__device__ __forceinline__ void wgmma_rs_n64(float (&d)[32], uint32_t a0, uint32_t a1, uint32_t a2, uint32_t a3, uint64_t descB) {
  asm volatile("wgmma.mma_async.sync.aligned.m64n64k16.f32.bf16.bf16 {%0, %1, %2, %3, %4, %5, %6, %7, %8, %9, %10, %11, %12, %13, %14, %15, %16, %17, %18, %19, %20, %21, %22, %23, %24, %25, %26, %27, %28, %29, %30, %31}, {%32, %33, %34, %35}, %36, %37, 1, 1, 0;\n"
    : "+f"(d[0]), "+f"(d[1]), "+f"(d[2]), "+f"(d[3]), "+f"(d[4]), "+f"(d[5]), "+f"(d[6]), "+f"(d[7]), "+f"(d[8]), "+f"(d[9]), "+f"(d[10]), "+f"(d[11]), "+f"(d[12]), "+f"(d[13]), "+f"(d[14]), "+f"(d[15]), "+f"(d[16]), "+f"(d[17]), "+f"(d[18]), "+f"(d[19]), "+f"(d[20]), "+f"(d[21]), "+f"(d[22]), "+f"(d[23]), "+f"(d[24]), "+f"(d[25]), "+f"(d[26]), "+f"(d[27]), "+f"(d[28]), "+f"(d[29]), "+f"(d[30]), "+f"(d[31])
    : "r"(a0), "r"(a1), "r"(a2), "r"(a3), "l"(descB), "n"(SCALE_D));
}
template <int SCALE_D>
__device__ __forceinline__ void wgmma_rs_n128(float (&d)[64], uint32_t a0, uint32_t a1, uint32_t a2, uint32_t a3, uint64_t descB) {
  asm volatile("wgmma.mma_async.sync.aligned.m64n128k16.f32.bf16.bf16 {%0, %1, %2, %3, %4, %5, %6, %7, %8, %9, %10, %11, %12, %13, %14, %15, %16, %17, %18, %19, %20, %21, %22, %23, %24, %25, %26, %27, %28, %29, %30, %31, %32, %33, %34, %35, %36, %37, %38, %39, %40, %41, %42, %43, %44, %45, %46, %47, %48, %49, %50, %51, %52, %53, %54, %55, %56, %57, %58, %59, %60, %61, %62, %63}, {%64, %65, %66, %67}, %68, %69, 1, 1, 0;\n"
    : "+f"(d[0]), "+f"(d[1]), "+f"(d[2]), "+f"(d[3]), "+f"(d[4]), "+f"(d[5]), "+f"(d[6]), "+f"(d[7]), "+f"(d[8]), "+f"(d[9]), "+f"(d[10]), "+f"(d[11]), "+f"(d[12]), "+f"(d[13]), "+f"(d[14]), "+f"(d[15]), "+f"(d[16]), "+f"(d[17]), "+f"(d[18]), "+f"(d[19]), "+f"(d[20]), "+f"(d[21]), "+f"(d[22]), "+f"(d[23]), "+f"(d[24]), "+f"(d[25]), "+f"(d[26]), "+f"(d[27]), "+f"(d[28]), "+f"(d[29]), "+f"(d[30]), "+f"(d[31]), "+f"(d[32]), "+f"(d[33]), "+f"(d[34]), "+f"(d[35]), "+f"(d[36]), "+f"(d[37]), "+f"(d[38]), "+f"(d[39]), "+f"(d[40]), "+f"(d[41]), "+f"(d[42]), "+f"(d[43]), "+f"(d[44]), "+f"(d[45]), "+f"(d[46]), "+f"(d[47]), "+f"(d[48]), "+f"(d[49]), "+f"(d[50]), "+f"(d[51]), "+f"(d[52]), "+f"(d[53]), "+f"(d[54]), "+f"(d[55]), "+f"(d[56]), "+f"(d[57]), "+f"(d[58]), "+f"(d[59]), "+f"(d[60]), "+f"(d[61]), "+f"(d[62]), "+f"(d[63])
    : "r"(a0), "r"(a1), "r"(a2), "r"(a3), "l"(descB), "n"(SCALE_D));
}
template <int SCALE_D>
__device__ __forceinline__ void wgmma_rs_n24_tb(float (&d)[12], uint32_t a0, uint32_t a1, uint32_t a2, uint32_t a3, uint64_t descB) {
  asm volatile("wgmma.mma_async.sync.aligned.m64n24k16.f32.bf16.bf16 {%0, %1, %2, %3, %4, %5, %6, %7, %8, %9, %10, %11}, {%12, %13, %14, %15}, %16, %17, 1, 1, 1;\n"
    : "+f"(d[0]), "+f"(d[1]), "+f"(d[2]), "+f"(d[3]), "+f"(d[4]), "+f"(d[5]), "+f"(d[6]), "+f"(d[7]), "+f"(d[8]), "+f"(d[9]), "+f"(d[10]), "+f"(d[11])
    : "r"(a0), "r"(a1), "r"(a2), "r"(a3), "l"(descB), "n"(SCALE_D));
}

constexpr uint32_t DHI_SW128_K = (1024 >> 4) | (1u << 30);
constexpr uint32_t DHI_SW64_MN = (512 >> 4) | (2u << 30);

template <int NC>
__device__ __forceinline__ void store_tile_bf16(const float (&acc)[NC / 2], float scale, uint32_t stage, uint8_t* stage_ptr,
                                                __nv_bfloat16* gdst, int gpitch, int lane) {
  constexpr int PITCH = NC * 2 + 16;
  const uint32_t waddr = stage + ((lane & 7) + ((lane >> 3) & 1) * 8) * PITCH + (lane >> 4) * 16;
#pragma unroll
  for (int j = 0; j < NC / 16; j++) {
    stsm4(waddr + j * 32, pack_bf16(acc[8 * j] * scale, acc[8 * j + 1] * scale), pack_bf16(acc[8 * j + 2] * scale, acc[8 * j + 3] * scale),
          pack_bf16(acc[8 * j + 4] * scale, acc[8 * j + 5] * scale), pack_bf16(acc[8 * j + 6] * scale, acc[8 * j + 7] * scale));
  }
  __syncwarp();
  constexpr int CPR = NC / 8;
#pragma unroll
  for (int i = 0; i < CPR / 2; i++) {
    const int c = i * 32 + lane, r = c / CPR, cc = c % CPR;
    const uint4 v = *reinterpret_cast<const uint4*>(stage_ptr + r * PITCH + cc * 16);
    *reinterpret_cast<uint4*>(gdst + (size_t)r * gpitch + cc * 8) = v;
  }
}

__device__ __forceinline__ void signal_done(unsigned int* flag, int wg, int tid) {
  asm volatile("bar.sync %0, 128;" :: "r"(wg + 1) : "memory");
  if ((tid & 127) == 0) asm volatile("red.release.gpu.global.add.u32 [%0], 1;" :: "l"(flag) : "memory");
}
__device__ __forceinline__ void wait_flags8(const unsigned int* f, unsigned int target) {
  for (int spin = 0; spin < (1 << 26); spin++) {
    unsigned int a, b, c, d, e, g, h, i;
    asm volatile("ld.volatile.global.v4.u32 {%0, %1, %2, %3}, [%4];" : "=r"(a), "=r"(b), "=r"(c), "=r"(d) : "l"(f) : "memory");
    asm volatile("ld.volatile.global.v4.u32 {%0, %1, %2, %3}, [%4];" : "=r"(e), "=r"(g), "=r"(h), "=r"(i) : "l"(f + 4) : "memory");
    if (min(min(min(a, b), min(c, d)), min(min(e, g), min(h, i))) >= target) break;
    __nanosleep(32);
  }
  asm volatile("fence.acq_rel.gpu;" ::: "memory");
  asm volatile("fence.proxy.async;" ::: "memory");
}

#define RP_LD 2
#define RP_ST 6
constexpr int K1_STAGES = 4;
constexpr int K1_A_BYTES = 256 * 128;
constexpr int K1_B_BYTES = 64 * 160 * 2;
constexpr int K1_STAGE = K1_A_BYTES + K1_B_BYTES;
constexpr int K1_SMEM = 5 * K1_A_BYTES + 61440 + 1024;
constexpr int KV_STAGES = 5;
constexpr int KVW_OFF = KV_STAGES * K1_A_BYTES;

__global__ void __launch_bounds__(512, 1)
proj_kernel(const __grid_constant__ CUtensorMap tmX, const __grid_constant__ CUtensorMap tmWq, const __grid_constant__ CUtensorMap tmWqkv,
            const __nv_bfloat16* __restrict__ wk, const __nv_bfloat16* __restrict__ wv, const __nv_bfloat16* __restrict__ gate_w,
            const __nv_bfloat16* __restrict__ woA, const __nv_bfloat16* __restrict__ woB) {
  extern __shared__ uint8_t smem_raw[];
  __shared__ __align__(8) uint64_t bar_full[KV_STAGES], bar_empty[KV_STAGES];
  uint8_t* smem = reinterpret_cast<uint8_t*>((reinterpret_cast<uintptr_t>(smem_raw) + 1023) & ~(uintptr_t)1023);
  const uint32_t sbase = smem_u32(smem);
  const uint32_t dbase = sbase & 0x3FFFFu;
  const int tid = threadIdx.x, warp = tid >> 5, lane = tid & 31;
  const bool is_kv = blockIdx.x >= 128;
  PROF(0, 0);
  if (tid == 32) { prefetch_tmap(&tmX); prefetch_tmap((blockIdx.x & 15) < 4 ? &tmWq : &tmWqkv); }
  if (tid == 0) {
    for (int i = 0; i < KV_STAGES; i++) { mbar_init(smem_u32(&bar_full[i]), 1); mbar_init(smem_u32(&bar_empty[i]), is_kv ? 8 : 16); }
    fence_mbar_init();
  }
  uint2 wa[2][5], wb[2][5]; uint32_t gw[2];
  if (is_kv && tid < 320) {
#pragma unroll
    for (int r = 0; r < 2; r++) {
      const int k = tid + r * 320;
      const uint2* pk = reinterpret_cast<const uint2*>(wk + k * 20);
      const uint2* pv = reinterpret_cast<const uint2*>(wv + k * 20);
#pragma unroll
      for (int i = 0; i < 5; i++) { wa[r][i] = __ldg(pk + i); wb[r][i] = __ldg(pv + i); }
      gw[r] = (uint32_t)__bfloat16_as_ushort(gate_w[k]);
    }
  }
  __syncthreads();
  if (tid == 480) {
    if (!is_kv) { g_done[blockIdx.x] = 0u; g_doneL[blockIdx.x] = 0u; }
    asm volatile("fence.acq_rel.gpu;" ::: "memory");
    pdl_launch();
  }
  __syncwarp();

  if (!is_kv) {
    const int mb = blockIdx.x >> 4, nb = blockIdx.x & 15;
    const CUtensorMap* tw = nb < 4 ? &tmWq : &tmWqkv;
    const int j0 = (nb < 4 ? nb : nb - 4) * 5;
    auto load = [&](int kt) {
      const int s = kt % K1_STAGES;
      const uint32_t fb = smem_u32(&bar_full[s]);
      mbar_expect_tx(fb, K1_STAGE);
      tma_2d(sbase + s * K1_STAGE, &tmX, kt * 64, mb * 256, fb);
      tma_3d(sbase + s * K1_STAGE + K1_A_BYTES, tw, 0, kt * 64, j0, fb);
    };
    if (tid == 0) for (int kt = 0; kt < K1_STAGES; kt++) load(kt);
    __syncwarp();
    uint4 wv2[2];
    const int rq = blockIdx.x * 400 + tid - 112;
    const int rhalf = rq >= 25600, rr = rq - rhalf * 25600, rk = 2 * (rr / 80), rch = rr % 80;
    {
      const int wg = warp >> 2;
      float acc[80];
      float (&acc0)[48] = *reinterpret_cast<float (*)[48]>(&acc[0]);
      float (&acc1)[32] = *reinterpret_cast<float (*)[32]>(&acc[48]);
#pragma unroll
      for (int i = 0; i < 80; i++) acc[i] = 0.f;
      auto descs = [&](int kt, uint32_t& alo, uint32_t& blo) {
        const int s = kt % K1_STAGES;
        alo = ((dbase + s * K1_STAGE + wg * 8192) >> 4) | (1u << 16);
        blo = ((dbase + s * K1_STAGE + K1_A_BYTES) >> 4) | ((4096u >> 4) << 16);
      };
      for (int kt = 0; kt < 7; kt++) {
        mbar_wait(smem_u32(&bar_full[kt % K1_STAGES]), (kt / K1_STAGES) & 1);
        uint32_t alo, blo;
        descs(kt, alo, blo);
        fence_regs(acc0); fence_regs(acc1);
        wg_fence();
#pragma unroll
        for (int k = 0; k < 4; k++) wgmma_ss_n160_tb(acc, mkd(alo + k * 2, DHI_SW128_K), mkd(blo + k * 64, DHI_SW64_MN));
        wg_commit();
        if (kt == RP_LD && tid >= 112) {
          const uint4* src = reinterpret_cast<const uint4*>((rhalf ? woB : woA) + rk * D_MODEL + rch * 8);
          wv2[0] = __ldg(src); wv2[1] = __ldg(src + D_MODEL / 8);
        }
        if (kt == RP_ST && tid >= 112) {
          uint4* dst = reinterpret_cast<uint4*>(g_wimg + ((rhalf * 8 + rch / 10) * 10 + (rk >> 6)) * 10240 + (rch % 10) * 1024 + (rk & 63) * 16);
          dst[0] = wv2[0]; dst[1] = wv2[1];
        }
        __syncwarp();
        if (kt > 0) {
          wg_wait<1>();
          const uint32_t eb = smem_u32(&bar_empty[(kt - 1) % K1_STAGES]);
          if (lane == 0) mbar_arrive(eb);
          if (tid == 0) { mbar_wait(eb, ((kt - 1) / K1_STAGES) & 1); load(kt - 1 + K1_STAGES); }
          __syncwarp();
        }
      }
      wg_wait<0>();
      fence_regs(acc0); fence_regs(acc1);
#pragma unroll
      for (int kt = 7; kt < 10; kt++) {
        mbar_wait(smem_u32(&bar_full[kt % K1_STAGES]), (kt / K1_STAGES) & 1);
        uint32_t alo, blo;
        descs(kt, alo, blo);
        wg_fence();
#pragma unroll
        for (int k = 0; k < 4; k++) wgmma_ss_n96_tb(acc0, mkd(alo + k * 2, DHI_SW128_K), mkd(blo + k * 64, DHI_SW64_MN));
      }
      wg_commit();
#pragma unroll
      for (int kt = 7; kt < 10; kt++) {
        uint32_t alo, blo;
        descs(kt, alo, blo);
#pragma unroll
        for (int k = 0; k < 4; k++) wgmma_ss_n64_tb(acc1, mkd(alo + k * 2, DHI_SW128_K), mkd(blo + 768 + k * 64, DHI_SW64_MN));
      }
      wg_commit();
      wg_wait<1>();
      fence_regs(acc0);
      {
        const uint32_t eb = smem_u32(&bar_empty[6 % K1_STAGES]);
        if (lane == 0) mbar_arrive(eb);
        mbar_wait(eb, (6 / K1_STAGES) & 1);
      }
      const int w4 = warp & 3;
      const int row0 = mb * 256 + wg * 64 + w4 * 16;
      const float scale = nb < 4 ? 0.22360679774997896f * 1.4426950408889634f : 1.0f;
      __nv_bfloat16* gdst = nb < 4 ? g_q + (size_t)row0 * D_MODEL + nb * 160 : g_qkv + (size_t)row0 * (3 * D_MODEL) + (nb - 4) * 160;
      const int gpitch = nb < 4 ? D_MODEL : 3 * D_MODEL;
      {
        const uint32_t off = (6 % K1_STAGES) * K1_STAGE + warp * (16 * (96 * 2 + 16));
        store_tile_bf16<96>(acc0, scale, sbase + off, smem + off, gdst, gpitch, lane);
        wg_wait<0>();
        fence_regs(acc1);
        PROF(0, 1);
        __syncwarp();
        store_tile_bf16<64>(acc1, scale, sbase + off, smem + off, gdst + 96, gpitch, lane);
      }
    }
  } else {
    const int cb = blockIdx.x - 128;
    if (warp == 8 && lane == 0) {
      for (int it = 0; it < KV_STAGES; it++) {
        const uint32_t fb = smem_u32(&bar_full[it]);
        mbar_expect_tx(fb, K1_A_BYTES);
        tma_2d(sbase + it * K1_A_BYTES, &tmX, it * 64, cb * 512, fb);
      }
    }
    __syncwarp();
    if (tid < 320) {
#pragma unroll
      for (int r = 0; r < 2; r++) {
        uint4* dst = reinterpret_cast<uint4*>(smem + KVW_OFF + (tid + r * 320) * 16);
        dst[0] = make_uint4(wa[r][0].x, wa[r][0].y, wa[r][1].x, wa[r][1].y);
        dst[640] = make_uint4(wa[r][2].x, wa[r][2].y, wa[r][3].x, wa[r][3].y);
        dst[1280] = make_uint4(wa[r][4].x, wa[r][4].y, 0u, 0u);
        dst[1920] = make_uint4(wb[r][0].x, wb[r][0].y, wb[r][1].x, wb[r][1].y);
        dst[2560] = make_uint4(wb[r][2].x, wb[r][2].y, wb[r][3].x, wb[r][3].y);
        dst[3200] = make_uint4(wb[r][4].x, wb[r][4].y, gw[r], 0u);
      }
    }
    fence_proxy_async();
    asm volatile("bar.sync 1, 512;" ::: "memory");
    PROF(0, 1);
    auto produce = [&](int it0, int it1) {
      for (int it = it0; it < it1; it++) {
        const int s = it % KV_STAGES;
        mbar_wait(smem_u32(&bar_empty[s]), (it / KV_STAGES - 1) & 1);
        const uint32_t fb = smem_u32(&bar_full[s]);
        mbar_expect_tx(fb, K1_A_BYTES);
        tma_2d(sbase + s * K1_A_BYTES, &tmX, (it >= 10 ? it - 10 : it) * 64, cb * 512 + (it >= 10 ? 256 : 0), fb);
      }
    };
    if (tid == 256) produce(KV_STAGES, 15);
    __syncwarp();
    {
      const int pass = warp >> 3, wg = (warp >> 2) & 1, w4 = warp & 3, g = lane >> 2, t = lane & 3;
      if (pass == 1) asm volatile("bar.sync 2, 512;" ::: "memory");
      {
        float acc[2][24];
#pragma unroll
        for (int i = 0; i < 24; i++) { acc[0][i] = 0.f; acc[1][i] = 0.f; }
        for (int kt = 0; kt < 10; kt++) {
          const int it = pass * 10 + kt, s = it % KV_STAGES;
          mbar_wait(smem_u32(&bar_full[s]), (it / KV_STAGES) & 1);
          const uint32_t alo = ((dbase + s * K1_A_BYTES + wg * 16384) >> 4) | (1u << 16);
          const uint32_t blo = ((dbase + KVW_OFF + kt * 1024) >> 4) | ((128u >> 4) << 16);
          fence_regs(acc[0]); fence_regs(acc[1]);
          wg_fence();
#pragma unroll
          for (int k = 0; k < 4; k++) {
            wgmma_ss_n48_tb(acc[0], mkd(alo + k * 2, DHI_SW128_K), mkd(blo + k * 16, 10240u >> 4));
            wgmma_ss_n48_tb(acc[1], mkd(alo + 512 + k * 2, DHI_SW128_K), mkd(blo + k * 16, 10240u >> 4));
          }
          wg_commit();
          if (kt > 0) {
            wg_wait<1>();
            if (lane == 0) mbar_arrive(smem_u32(&bar_empty[(it - 1) % KV_STAGES]));
          }
        }
        wg_wait<0>();
        fence_regs(acc[0]); fence_regs(acc[1]);
        if (lane == 0) mbar_arrive(smem_u32(&bar_empty[(pass * 10 + 9) % KV_STAGES]));
        if (pass == 0) asm volatile("bar.arrive 2, 512;" ::: "memory");
        PROF(0, 2);
        if (tid == 0) produce(15, 20);
        __syncwarp();
        float kmax2 = 0.f, vmax = 0.f;
#pragma unroll
        for (int hh = 0; hh < 4; hh++) {
          const int h = hh & 1;
          const float (&a)[24] = acc[hh >> 1];
          const int key = cb * 512 + pass * 256 + wg * 128 + (hh >> 1) * 64 + w4 * 16 + g + h * 8;
          const int grp = key >> 7, kk = key & 127;
          const bool poly = (TMASK >> (kk >> 3)) & 1;
          uint8_t* gp = g_kvimg + grp * GRP_BYTES;
          const uint32_t k0 = pack_bf16(a[2 * h], a[2 * h + 1]);
          const uint32_t k1 = pack_bf16(a[4 + 2 * h], a[5 + 2 * h]);
          uint32_t k2 = pack_bf16(a[8 + 2 * h], a[9 + 2 * h]);
          float n2 = bf_lo(k0) * bf_lo(k0) + bf_hi(k0) * bf_hi(k0) + bf_lo(k1) * bf_lo(k1) + bf_hi(k1) * bf_hi(k1);
          if (t < 2) {
            n2 += bf_lo(k2) * bf_lo(k2) + bf_hi(k2) * bf_hi(k2);
            k2 = pack_bf16(bf_lo(k2) * 0.5f, bf_hi(k2) * 0.5f);
          } else if (t == 2) k2 = poly ? pack_bf16(24.f, 2.5f) : pack_bf16(0.5f, 0.f);
          else k2 = poly ? pack_bf16(0.5f, 0.f) : 0u;
          *reinterpret_cast<uint32_t*>(gp + kk * 16 + t * 4) = k0;
          *reinterpret_cast<uint32_t*>(gp + PLANE + kk * 16 + t * 4) = k1;
          *reinterpret_cast<uint32_t*>(gp + 2 * PLANE + kk * 16 + t * 4) = k2;
          n2 += __shfl_xor_sync(0xffffffffu, n2, 1);
          n2 += __shfl_xor_sync(0xffffffffu, n2, 2);
          kmax2 = (n2 > kmax2 || n2 != n2) ? n2 : kmax2;
          uint32_t v0 = pack_bf16(a[12 + 2 * h], a[13 + 2 * h]);
          uint32_t v1 = pack_bf16(a[16 + 2 * h], a[17 + 2 * h]);
          uint32_t v2 = pack_bf16(a[20 + 2 * h], a[21 + 2 * h]);
          float vm = fmaxf(fmaxf(fabsf(bf_lo(v0)), fabsf(bf_hi(v0))), fmaxf(fabsf(bf_lo(v1)), fabsf(bf_hi(v1))));
          if (t < 2) vm = fmaxf(vm, fmaxf(fabsf(bf_lo(v2)), fabsf(bf_hi(v2))));
          else if (t == 2) {
            const float z = a[20 + 2 * h];
            g_gate[key] = 1.f / (1.f + __expf(-z));
            v2 = 0x00003F80u;
          } else v2 = 0u;
          vmax = fmaxf(vmax, vm);
          if (poly) { v0 ^= 0x80008000u; v1 ^= 0x80008000u; v2 ^= 0x80008000u; }
          uint8_t* vp = gp + 3 * PLANE + (kk >> 3) * 384 + (kk & 7) * 16 + t * 4;
          *reinterpret_cast<uint32_t*>(vp) = v0;
          *reinterpret_cast<uint32_t*>(vp + 128) = v1;
          *reinterpret_cast<uint32_t*>(vp + 256) = v2;
        }
#pragma unroll
        for (int o = 1; o < 32; o <<= 1) {
          const float a = __shfl_xor_sync(0xffffffffu, kmax2, o);
          kmax2 = (a > kmax2 || a != a) ? a : kmax2;
          vmax = fmaxf(vmax, __shfl_xor_sync(0xffffffffu, vmax, o));
        }
        if (lane == 0) { g_kmax2[cb * 16 + warp] = kmax2; g_vmax[cb * 16 + warp] = vmax; }
      }
    }
  }
}

__device__ __forceinline__ uint32_t ex2_pair_poly(float u0, float u1, uint32_t one2) {
  const uint32_t W = __byte_perm(__float_as_uint(u0), __float_as_uint(u1), 0x6521);
  uint32_t v; asm("lop3.b32 %0, %1, 0x007F007F, %2, 0xEA;" : "=r"(v) : "r"(W), "r"(one2));
  uint32_t L, p;
  asm("fma.rn.bf16x2 %0, %1, %2, %3;" : "=r"(L) : "r"(v), "r"(0x1f961f96u), "r"(0x9fe39fe3u));
  asm("fma.rn.bf16x2 %0, %1, %1, %2;" : "=r"(p) : "r"(L), "r"(0x00f500f5u));
  return W + p;
}
template <int JOFF>
__device__ __forceinline__ void softmax_slow(const float (&S)[32], uint32_t (&P)[16], float (&O)[12], float& m0, float& m1) {
  float a0 = m0, a1 = m1;
#pragma unroll
  for (int j = 0; j < 8; j++) {
    a0 = fmaxf(a0, fmaxf(S[4 * j], S[4 * j + 1]));
    a1 = fmaxf(a1, fmaxf(S[4 * j + 2], S[4 * j + 3]));
  }
  a0 = fmaxf(a0, __shfl_xor_sync(0xffffffffu, a0, 1)); a0 = fmaxf(a0, __shfl_xor_sync(0xffffffffu, a0, 2));
  a1 = fmaxf(a1, __shfl_xor_sync(0xffffffffu, a1, 1)); a1 = fmaxf(a1, __shfl_xor_sync(0xffffffffu, a1, 2));
  const float c0 = ex2(m0 - a0), c1 = ex2(m1 - a1);
  m0 = a0; m1 = a1;
#pragma unroll
  for (int j = 0; j < 3; j++) { O[4 * j] *= c0; O[4 * j + 1] *= c0; O[4 * j + 2] *= c1; O[4 * j + 3] *= c1; }
#pragma unroll
  for (int i = 0; i < 16; i++) {
    const float m = (i & 1) ? a1 : a0;
    const uint32_t p = pack_bf16(ex2(S[2 * i] - m), ex2(S[2 * i + 1] - m));
    P[i] = ((TMASK >> (JOFF + i / 2)) & 1) ? (p ^ 0x80008000u) : p;
  }
}
constexpr uint32_t DHI_KV = 128 >> 4;
__device__ __forceinline__ void issue_qk(float (&S)[32], const uint32_t (&q)[8], uint64_t base) {
  wgmma_rs_n64<0>(S, q[0], q[1], q[2], q[3], base + (uint64_t)((PLANE >> 4) << 16));
  wgmma_rs_n64<1>(S, q[4], q[5], q[6], q[7], base + (uint64_t)(2 * PLANE >> 4));
}
__device__ __forceinline__ void issue_pv(float (&O)[12], const uint32_t (&P)[16], uint64_t vbase) {
#pragma unroll
  for (int kk = 0; kk < 4; kk++)
    wgmma_rs_n24_tb<1>(O, P[4 * kk], P[4 * kk + 1], P[4 * kk + 2], P[4 * kk + 3], vbase + (uint64_t)(kk * (768 >> 4)));
}

constexpr uint32_t VOFF = ((3 * PLANE) >> 4) + ((384u >> 4) << 16);
constexpr int KVR = 4;
constexpr int OFF_W = KVR * GRP_BYTES;
constexpr int OFF_X = OFF_W + 10 * 10240;
constexpr int OFF_BAR = OFF_X + 4 * 16384;
constexpr int K2_SMEM = OFF_BAR + 512 + 1024;
constexpr int TSL = 7;
constexpr int BAR_KV = 0, BAR_W = 4, BAR_TA = 5, BAR_TE = 12, BAR_OWN = 19, BAR_L = 20, CNT_KV = 21, BAR_WA = 23, BAR_WF = 33, CNT_TK = 43;
constexpr int NSTEP = 2 * NGRP;

__device__ __forceinline__ void kv_load(uint32_t sbase, int step) {
  const uint32_t bar = sbase + OFF_BAR + (BAR_KV + (step & (KVR - 1))) * 8;
  mbar_expect_tx(bar, GRP_BYTES);
  bulk_g2s(sbase + (step & (KVR - 1)) * GRP_BYTES, g_kvimg + (step & (NGRP - 1)) * GRP_BYTES, GRP_BYTES, bar);
}
__device__ __forceinline__ void kv_release(uint32_t sbase, int step, bool elected) {
  if (elected && step + KVR < NSTEP) {
    uint32_t old;
    asm volatile("atom.acq_rel.cta.shared::cta.inc.u32 %0, [%1], 3;" : "=r"(old) : "r"(sbase + OFF_BAR + CNT_KV * 8 + (step & (KVR - 1)) * 4) : "memory");
    if (old == 3u) kv_load(sbase, step + KVR);
  }
  __syncwarp();
}
__device__ __forceinline__ void kv_wait(uint32_t sbase, int step) {
  mbar_wait(sbase + OFF_BAR + (BAR_KV + (step & (KVR - 1))) * 8, (step / KVR) & 1);
}

__device__ __forceinline__ uint32_t kv_release_begin(uint32_t sbase, int slot, bool doit) {
  uint32_t old = 0;
  asm volatile("{\n.reg .pred p;\nsetp.ne.u32 p, %2, 0;\n@p atom.relaxed.cta.shared::cta.inc.u32 %0, [%1], 3;\n}\n"
               : "+r"(old) : "r"(sbase + OFF_BAR + CNT_KV * 8 + slot * 4), "r"((uint32_t)doit) : "memory");
  return old;
}
template <int H>
__device__ __forceinline__ void softmax_half(const float (&S)[64], uint32_t (&P)[16], uint32_t one2) {
#pragma unroll
  for (int i = 0; i < 16; i++) {
    if ((TMASK >> (8 * H + i / 2)) & 1) P[i] = ex2_pair_poly(S[32 * H + 2 * i], S[32 * H + 2 * i + 1], one2);
    else P[i] = pack_bf16(ex2(S[32 * H + 2 * i]), ex2(S[32 * H + 2 * i + 1]));
  }
}
__device__ __forceinline__ void attn_fast(const uint32_t (&q)[8], float (&O)[12], uint32_t sbase, int step0, int nsteps, bool elected, uint32_t one2) {
  uint64_t kb0 = mkd((sbase & 0x3FFFFu) >> 4, DHI_KV);
  asm volatile("" : "+l"(kb0));
#pragma unroll 1
  for (int step4 = step0; step4 < step0 + nsteps; step4 += KVR) {
#pragma unroll
    for (int j = 0; j < KVR; j++) {
      const int step = step4 + j;
      const uint64_t kb = kb0 + (uint64_t)(j * (GRP_BYTES >> 4));
      float S[64]; uint32_t PA[16], PB[16];
#pragma unroll
      for (int i = 0; i < 64; i++) S[i] = 0.f;
      mbar_wait(sbase + OFF_BAR + (BAR_KV + j) * 8, (step / KVR) & 1);
      fence_regs(S);
      wg_fence();
      wgmma_rs_n128<0>(S, q[0], q[1], q[2], q[3], kb + (uint64_t)((PLANE >> 4) << 16));
      wgmma_rs_n128<1>(S, q[4], q[5], q[6], q[7], kb + (uint64_t)(2 * PLANE >> 4));
      wg_commit();
      const uint32_t old = kv_release_begin(sbase, (j + KVR - 1) & (KVR - 1), elected && step > step0 && step - 1 + KVR < NSTEP);
      wg_wait<0>();
      fence_regs(S);
      softmax_half<0>(S, PA, one2);
      fence_regs(PA); fence_regs(O);
      wg_fence();
      issue_pv(O, PA, kb + VOFF);
      wg_commit();
      softmax_half<1>(S, PB, one2);
      fence_regs(PB);
      wg_fence();
      issue_pv(O, PB, kb + VOFF + 4 * (768 >> 4));
      wg_commit();
      if (old == 3u) kv_load(sbase, step - 1 + KVR);
      wg_wait<0>();
      fence_regs(PA); fence_regs(PB); fence_regs(O);
    }
  }
  kv_release(sbase, step0 + nsteps - 1, elected);
}
template <int H>
__device__ __forceinline__ void slow_step(const uint32_t (&q)[8], float (&O)[12], uint64_t kb, float& m0, float& m1) {
  float S[32]; uint32_t P[16];
#pragma unroll
  for (int i = 0; i < 32; i++) S[i] = 0.f;
  fence_regs(S);
  wg_fence();
  issue_qk(S, q, kb + 64 * H);
  wg_commit();
  wg_wait<0>();
  fence_regs(S);
  softmax_slow<8 * H>(S, P, O, m0, m1);
  fence_regs(P); fence_regs(O);
  wg_fence();
  issue_pv(O, P, kb + VOFF + H * 4 * (768 >> 4));
  wg_commit();
  wg_wait<0>();
  fence_regs(O); fence_regs(P);
}
__device__ __forceinline__ void attn_slow(const uint32_t (&q)[8], float (&O)[12], uint32_t sbase, int step0, int nsteps, bool elected, float& m0, float& m1) {
#pragma unroll 1
  for (int step = step0; step < step0 + nsteps; step++) {
    kv_wait(sbase, step);
    const uint64_t kb = mkd(((sbase & 0x3FFFFu) >> 4) + (step & (KVR - 1)) * (GRP_BYTES >> 4), DHI_KV);
    slow_step<0>(q, O, kb, m0, m1);
    slow_step<1>(q, O, kb, m0, m1);
    kv_release(sbase, step, elected);
  }
}

__device__ __forceinline__ void softmax8(float (&sc)[8], float scale) {
  float mx = sc[0];
#pragma unroll
  for (int w = 1; w < 8; w++) mx = fmaxf(mx, sc[w]);
  float l = 0.f;
#pragma unroll
  for (int w = 0; w < 8; w++) { sc[w] = ex2(sc[w] - mx); l += sc[w]; }
  const float r = __fdividef(scale, l);
#pragma unroll
  for (int w = 0; w < 8; w++) sc[w] *= r;
}
#define LEV(wg) 1
constexpr int LBOX = 30 * 320;
__device__ __forceinline__ uint2 lds64(uint32_t a) {
  uint2 v; asm volatile("ld.shared.v2.u32 {%0, %1}, [%2];" : "=r"(v.x), "=r"(v.y) : "r"(a)); return v;
}
__device__ __forceinline__ void local_attn(uint32_t stage, int t0, int i, int lane) {
  constexpr float SC = 0.22360679774997896f * 1.4426950408889634f, NEG = -1e9f * 1.4426950408889634f;
  const uint32_t base = stage + (lane >> 3) * LBOX + (lane & 7) * 40 + (i + 14) * 320;
  const int t = t0 + i;
  float sc[8];
#pragma unroll
  for (int w = 0; w < 8; w++) sc[w] = 0.f;
#pragma unroll 1
  for (int c = 0; c < 5; c++) {
    const uint2 qv = lds64(base + c * 8);
    const float q0 = bf_lo(qv.x), q1 = bf_hi(qv.x), q2 = bf_lo(qv.y), q3 = bf_hi(qv.y);
#pragma unroll
    for (int w = 0; w < 8; w++) {
      const uint2 k = lds64(base + c * 8 + 4 * LBOX - w * 640);
      sc[w] = fmaf(q0, bf_lo(k.x), sc[w]); sc[w] = fmaf(q1, bf_hi(k.x), sc[w]);
      sc[w] = fmaf(q2, bf_lo(k.y), sc[w]); sc[w] = fmaf(q3, bf_hi(k.y), sc[w]);
    }
  }
#pragma unroll
  for (int w = 0; w < 8; w++) sc[w] = t - 2 * w >= 0 ? sc[w] * SC : NEG;
  softmax8(sc, 1.f - g_gate[t]);
  uint2* dst = reinterpret_cast<uint2*>(g_a2 + (size_t)t * (2 * D_MODEL) + D_MODEL + lane * DH);
#pragma unroll 1
  for (int c = 0; c < 5; c++) {
    float o0 = 0.f, o1 = 0.f, o2 = 0.f, o3 = 0.f;
#pragma unroll
    for (int w = 0; w < 8; w++) {
      const uint2 v = lds64(base + c * 8 + 8 * LBOX - w * 640);
      o0 = fmaf(sc[w], bf_lo(v.x), o0); o1 = fmaf(sc[w], bf_hi(v.x), o1);
      o2 = fmaf(sc[w], bf_lo(v.y), o2); o3 = fmaf(sc[w], bf_hi(v.y), o3);
    }
    dst[c] = make_uint2(pack_bf16(o0, o1), pack_bf16(o2, o3));
  }
}
__device__ __forceinline__ uint32_t ta_slot(int i) { return i < 4 ? OFF_X + i * 16384 : (i - 4) * 16384; }

__global__ void __launch_bounds__(640, 1)
attn_kernel(const __grid_constant__ CUtensorMap tmA2, const __grid_constant__ CUtensorMap tmL, __nv_bfloat16* __restrict__ out, uint32_t one2) {
  extern __shared__ uint8_t smem_raw[];
  uint8_t* smem = reinterpret_cast<uint8_t*>((reinterpret_cast<uintptr_t>(smem_raw) + 1023) & ~(uintptr_t)1023);
  const uint32_t sbase = smem_u32(smem);
  const uint32_t dbase = sbase & 0x3FFFFu;
  const uint32_t bars = sbase + OFF_BAR;
  const int tid = threadIdx.x, wg = tid >> 7, warp = (tid >> 5) & 3, lane = tid & 31, g = lane >> 2, t = lane & 3;
  const int mb = blockIdx.x >> 3, nb = blockIdx.x & 7;
  const bool elected = (tid & 127) == 0;
  if (tid == 512) { prefetch_tmap(&tmL); prefetch_tmap(&tmA2); }
  if (tid == 0) {
    for (int i = 0; i < BAR_TE; i++) mbar_init(bars + i * 8, 1);
    for (int i = BAR_TE; i < BAR_TE + TSL; i++) mbar_init(bars + i * 8, 8);
    mbar_init(bars + BAR_OWN * 8, 4);
    mbar_init(bars + BAR_L * 8, 1);
    for (int i = 0; i < 10; i++) { mbar_init(bars + (BAR_WA + i) * 8, 1); mbar_init(bars + (BAR_WF + i) * 8, 8); }
    for (int i = 0; i < 4; i++) *reinterpret_cast<uint32_t*>(smem + OFF_BAR + CNT_KV * 8 + i * 4) = 0u;
    *reinterpret_cast<uint32_t*>(smem + OFF_BAR + CNT_TK * 8) = 0u;
    fence_mbar_init();
  }
  __syncthreads();
  auto tail_load = [&](int i) {
    const uint32_t fb = bars + (BAR_TA + i % TSL) * 8;
    mbar_expect_tx(fb, 16384);
    tma_2d(sbase + ta_slot(i % TSL), &tmA2, i < 10 ? D_MODEL + i * 64 : (i - 10) * 64, mb * 128, fb);
  };
  if (wg == 4) {
    asm volatile("setmaxnreg.dec.sync.aligned.u32 32;");
    pdl_wait();
    if (tid == 512) {
      for (int j = 0; j < KVR; j++) kv_load(sbase, j);
      mbar_expect_tx(bars + BAR_L * 8, 12 * LBOX);
      for (int i = 0; i < 12; i++) tma_2d(sbase + OFF_W + i * LBOX, &tmL, i * 160, blockIdx.x * 16 - 14, bars + BAR_L * 8);
    }
    __syncwarp();
    mbar_wait(bars + BAR_L * 8, 0);
#pragma unroll 1
    for (int i = 0; i < 4; i++) local_attn(sbase + OFF_W, blockIdx.x * 16, warp * 4 + i, lane);
    signal_done(&g_doneL[blockIdx.x], wg, tid);
    if (tid == 512) {
      PROF2(0, 2);
      fence_proxy_async();
      mbar_expect_tx(bars + BAR_W * 8, 10 * 10240);
      for (int i = 0; i < 5; i++) bulk_g2s(sbase + OFF_W + i * 20480, g_wimg + ((8 + nb) * 10) * 10240 + i * 20480, 20480, bars + BAR_W * 8);
      wait_flags8(&g_doneL[mb * 8], 1u);
      for (int i = 0; i < 4; i++) tail_load(i);
      mbar_wait(bars + BAR_OWN * 8, 0);
      for (int i = 4; i < 20; i++) {
        if (i >= TSL) mbar_wait(bars + (BAR_TE + i % TSL) * 8, (i / TSL - 1) & 1);
        if (i == 10) { wait_flags8(&g_done[mb * 8], 1u); PROF2(2, 0); }
        tail_load(i);
      }
    } else if (tid == 576) {
      mbar_wait(bars + BAR_OWN * 8, 0);
      asm volatile("red.release.gpu.global.add.u32 [%0], 1;" :: "l"(&g_done[blockIdx.x]) : "memory");
    } else if (tid == 544) {
      for (int kt = 0; kt < 10; kt++) {
        mbar_wait(bars + (BAR_WF + kt) * 8, 0);
        mbar_expect_tx(bars + (BAR_WA + kt) * 8, 10240);
        bulk_g2s(sbase + OFF_W + kt * 10240, g_wimg + (nb * 10 + kt) * 10240, 10240, bars + (BAR_WA + kt) * 8);
      }
    }
    return;
  }
  asm volatile("setmaxnreg.inc.sync.aligned.u32 112;");
  pdl_wait();
  PROF(1, 1);
  uint32_t q[8], q2[6];
  const int rowA = (blockIdx.x * 8 + wg) * 64 + warp * 16 + g;
  {
    const uint32_t* r0 = reinterpret_cast<const uint32_t*>(g_q + (size_t)rowA * DH);
    const uint32_t* r1 = r0 + 8 * (DH / 2);
    const uint32_t* s0 = r0 + 256 * (DH / 2);
    const uint32_t* s1 = s0 + 8 * (DH / 2);
    q[0] = r0[t]; q[1] = r1[t]; q[2] = r0[t + 4]; q[3] = r1[t + 4];
    q[4] = t < 2 ? r0[8 + t] : 0u;
    q[5] = t < 2 ? r1[8 + t] : 0u;
    q2[0] = s0[t]; q2[1] = s1[t]; q2[2] = s0[t + 4]; q2[3] = s1[t + 4];
    q2[4] = t < 2 ? s0[8 + t] : 0u;
    q2[5] = t < 2 ? s1[8 + t] : 0u;
  }
  float kmax2 = 0.f, vmax = 0.f;
#pragma unroll
  for (int i = 0; i < 2; i++) {
    const float a = g_kmax2[lane + 32 * i];
    kmax2 = (a > kmax2 || a != a) ? a : kmax2;
    vmax = fmaxf(vmax, g_vmax[lane + 32 * i]);
  }
#pragma unroll
  for (int o = 1; o < 32; o <<= 1) {
    const float a = __shfl_xor_sync(0xffffffffu, kmax2, o);
    kmax2 = (a > kmax2 || a != a) ? a : kmax2;
    vmax = fmaxf(vmax, __shfl_xor_sync(0xffffffffu, vmax, o));
  }
  const float qlim = (vmax >= 0.00390625f && vmax <= 256.f) ? 9025.f / kmax2 : -1.f;
  PROF(1, 2);
#pragma unroll 1
  for (int it = 0; it < 2; it++) {
    const int row0 = rowA + it * 256;
    if (it == 1) {
#pragma unroll
      for (int i = 0; i < 6; i++) q[i] = q2[i];
    }
    float n0 = bf_lo(q[0]) * bf_lo(q[0]) + bf_hi(q[0]) * bf_hi(q[0]) + bf_lo(q[2]) * bf_lo(q[2]) + bf_hi(q[2]) * bf_hi(q[2]) +
               bf_lo(q[4]) * bf_lo(q[4]) + bf_hi(q[4]) * bf_hi(q[4]);
    float n1 = bf_lo(q[1]) * bf_lo(q[1]) + bf_hi(q[1]) * bf_hi(q[1]) + bf_lo(q[3]) * bf_lo(q[3]) + bf_hi(q[3]) * bf_hi(q[3]) +
               bf_lo(q[5]) * bf_lo(q[5]) + bf_hi(q[5]) * bf_hi(q[5]);
    n0 += __shfl_xor_sync(0xffffffffu, n0, 1); n0 += __shfl_xor_sync(0xffffffffu, n0, 2);
    n1 += __shfl_xor_sync(0xffffffffu, n1, 1); n1 += __shfl_xor_sync(0xffffffffu, n1, 2);
    const bool safe = (n0 <= qlim) && (n1 <= qlim);
    uint32_t unsafe_any;
    asm volatile("{\n.reg .pred p, r;\nsetp.eq.u32 p, %1, 0;\nbarrier.cta.red.or.pred r, %2, 128, p;\nselp.u32 %0, 1, 0, r;\n}\n"
                 : "=r"(unsafe_any) : "r"((uint32_t)safe), "r"(wg + 1) : "memory");
    float O[12];
#pragma unroll
    for (int i = 0; i < 12; i++) O[i] = 0.f;
    if (!unsafe_any && t >= 2) { q[4] = q[5] = (t == 2) ? 0x3F804100u : 0x00003B80u; }
    q[6] = q[4]; q[7] = q[5];
    fence_regs(q);
    float m0 = -INFINITY, m1 = -INFINITY;
    if (!unsafe_any) attn_fast(q, O, sbase, it * NGRP, NGRP, elected, one2);
    else attn_slow(q, O, sbase, it * NGRP, NGRP, elected, m0, m1);
    const float l0 = __shfl_sync(0xffffffffu, O[8], (lane & ~3) | 2);
    const float l1 = __shfl_sync(0xffffffffu, O[10], (lane & ~3) | 2);
    const int tok = row0 >> 5;
    const float gt = g_gate[tok];
    const float i0 = gt / l0, i1 = gt / l1;
    uint32_t* o0 = reinterpret_cast<uint32_t*>(g_a2 + (size_t)tok * (2 * D_MODEL) + (row0 & 31) * DH);
    uint32_t* o1 = o0 + 8 * (DH / 2);
    o0[t] = pack_bf16(O[0] * i0, O[1] * i0); o1[t] = pack_bf16(O[2] * i1, O[3] * i1);
    o0[t + 4] = pack_bf16(O[4] * i0, O[5] * i0); o1[t + 4] = pack_bf16(O[6] * i1, O[7] * i1);
    if (t < 2) { o0[t + 8] = pack_bf16(O[8] * i0, O[9] * i0); o1[t + 8] = pack_bf16(O[10] * i1, O[11] * i1); }
  }
  uint32_t* ticket = reinterpret_cast<uint32_t*>(smem + OFF_BAR + CNT_TK * 8);
  if (elected) ticket[1 + wg] = atomicAdd(ticket, 1u);
  asm volatile("bar.sync %0, 128;" :: "r"(wg + 1) : "memory");
  if (elected) mbar_arrive(bars + BAR_OWN * 8);
  const int mt = ticket[1 + wg];
  PROF(1, 3);
  if (mt < 2) {
    float acc[40];
#pragma unroll
    for (int i = 0; i < 40; i++) acc[i] = 0.f;
    mbar_wait(bars + BAR_W * 8, 0);
    int sl = 0, ph = 0;
#pragma unroll 1
    for (int i = 0; i < 20; i++) {
      mbar_wait(bars + (BAR_TA + sl) * 8, ph);
      if (i >= 10) mbar_wait(bars + (BAR_WA + i - 10) * 8, 0);
      const uint32_t alo = ((dbase + ta_slot(sl) + mt * 8192) >> 4) | (1u << 16);
      const uint32_t blo = ((dbase + OFF_W + (i >= 10 ? i - 10 : i) * 10240) >> 4) | ((128u >> 4) << 16);
      fence_regs(acc);
      wg_fence();
#pragma unroll
      for (int k = 0; k < 4; k++) wgmma_ss_n80_tb(acc, mkd(alo + k * 2, DHI_SW128_K), mkd(blo + k * 16, 1024u >> 4));
      wg_commit();
      if (i > 0) {
        wg_wait<1>();
        if (lane == 0) mbar_arrive(bars + (BAR_TE + (sl == 0 ? TSL - 1 : sl - 1)) * 8);
        if (lane == 1 && i <= 10) mbar_arrive(bars + (BAR_WF + i - 1) * 8);
      }
      if (++sl == TSL) { sl = 0; ph ^= 1; }
    }
    wg_wait<0>();
    fence_regs(acc);
    asm volatile("bar.sync %0, 128;" :: "r"(wg + 1) : "memory");
    const uint32_t so = ta_slot(warp) + mt * 8192;
    const int row0 = mb * 128 + mt * 64 + warp * 16;
    store_tile_bf16<80>(acc, 1.0f, sbase + so, smem + so, out + (size_t)row0 * D_MODEL + nb * 80, D_MODEL, lane);
  }
}

typedef CUresult (*EncodeFn)(CUtensorMap*, CUtensorMapDataType, cuuint32_t, void*, const cuuint64_t*, const cuuint64_t*,
                             const cuuint32_t*, const cuuint32_t*, CUtensorMapInterleave, CUtensorMapSwizzle,
                             CUtensorMapL2promotion, CUtensorMapFloatOOBfill);

void make_map(EncodeFn fn, CUtensorMap* tm, const void* ptr, int rank, const cuuint64_t* dims, const cuuint64_t* strides,
              const cuuint32_t* box, CUtensorMapSwizzle sw) {
  const cuuint32_t es[3] = {1, 1, 1};
  fn(tm, CU_TENSOR_MAP_DATA_TYPE_BFLOAT16, rank, const_cast<void*>(ptr), dims, strides, box, es, CU_TENSOR_MAP_INTERLEAVE_NONE, sw,
     CU_TENSOR_MAP_L2_PROMOTION_L2_256B, CU_TENSOR_MAP_FLOAT_OOB_FILL_NONE);
}
void map_a(EncodeFn fn, CUtensorMap* tm, const void* p, int rows, int cols, int box_rows) {
  const cuuint64_t dims[2] = {(cuuint64_t)cols, (cuuint64_t)rows};
  const cuuint64_t str[1] = {(cuuint64_t)cols * 2};
  const cuuint32_t box[2] = {64, (cuuint32_t)box_rows};
  make_map(fn, tm, p, 2, dims, str, box, CU_TENSOR_MAP_SWIZZLE_128B);
}
void map_w(EncodeFn fn, CUtensorMap* tm, const void* p, int K, int N, int atom, CUtensorMapSwizzle sw) {
  const cuuint64_t dims[3] = {(cuuint64_t)atom, (cuuint64_t)K, (cuuint64_t)(N / atom)};
  const cuuint64_t str[2] = {(cuuint64_t)N * 2, (cuuint64_t)atom * 2};
  const cuuint32_t box[3] = {(cuuint32_t)atom, 64, 5};
  make_map(fn, tm, p, 3, dims, str, box, sw);
}

template <typename... KArgs, typename... Args>
void launch(void (*kern)(KArgs...), int grid, int block, int smem, bool pdl, Args... args) {
  cudaLaunchConfig_t cfg = {};
  cfg.gridDim = dim3(grid); cfg.blockDim = dim3(block); cfg.dynamicSmemBytes = smem; cfg.stream = cudaStreamPerThread;
  cudaLaunchAttribute at[1];
  at[0].id = cudaLaunchAttributeProgrammaticStreamSerialization;
  at[0].val.programmaticStreamSerializationAllowed = 1;
  cfg.attrs = at; cfg.numAttrs = pdl ? 1 : 0;
  cudaLaunchKernelEx(&cfg, kern, KArgs(args)...);
}

}

extern "C" void kernel_launch(void* const* d_in, const int* in_sizes, int n_in, void* d_out, int out_size) {
  (void)in_sizes; (void)n_in; (void)out_size;
  const __nv_bfloat16* x = (const __nv_bfloat16*)d_in[0];
  const __nv_bfloat16* wq = (const __nv_bfloat16*)d_in[1];
  const __nv_bfloat16* wk = (const __nv_bfloat16*)d_in[2];
  const __nv_bfloat16* wv = (const __nv_bfloat16*)d_in[3];
  const __nv_bfloat16* woA = (const __nv_bfloat16*)d_in[4];
  const __nv_bfloat16* wqkv = (const __nv_bfloat16*)d_in[6];
  const __nv_bfloat16* woB = (const __nv_bfloat16*)d_in[7];
  const __nv_bfloat16* gate_w = (const __nv_bfloat16*)d_in[8];

  static EncodeFn enc = nullptr;
  static void* a2_ptr = nullptr;
  static void* qkv_ptr = nullptr;
  if (!enc) {
    void* fp = nullptr;
    cudaDriverEntryPointQueryResult qr;
    cudaGetDriverEntryPoint("cuTensorMapEncodeTiled", &fp, cudaEnableDefault, &qr);
    enc = (EncodeFn)fp;
    cudaGetSymbolAddress(&a2_ptr, g_a2);
    cudaGetSymbolAddress(&qkv_ptr, g_qkv);
    cudaFuncSetAttribute(proj_kernel, cudaFuncAttributeMaxDynamicSharedMemorySize, K1_SMEM);
    cudaFuncSetAttribute(attn_kernel, cudaFuncAttributeMaxDynamicSharedMemorySize, K2_SMEM);
  }
  CUtensorMap tmX, tmWq, tmWqkv, tmA2, tmL;
  {
    const cuuint64_t dims[2] = {3 * D_MODEL, S_LEN};
    const cuuint64_t str[1] = {3 * D_MODEL * 2};
    const cuuint32_t box[2] = {160, 30};
    make_map(enc, &tmL, qkv_ptr, 2, dims, str, box, CU_TENSOR_MAP_SWIZZLE_NONE);
  }
  map_a(enc, &tmX, x, S_LEN, D_MODEL, 256);
  map_w(enc, &tmWq, wq, D_MODEL, D_MODEL, 32, CU_TENSOR_MAP_SWIZZLE_64B);
  map_w(enc, &tmWqkv, wqkv, D_MODEL, 3 * D_MODEL, 32, CU_TENSOR_MAP_SWIZZLE_64B);
  map_a(enc, &tmA2, a2_ptr, S_LEN, 2 * D_MODEL, 128);

  launch(proj_kernel, 132, 512, K1_SMEM, false, tmX, tmWq, tmWqkv, wk, wv, gate_w, woA, woB);
  launch(attn_kernel, 128, 640, K2_SMEM, true, tmA2, tmL, (__nv_bfloat16*)d_out, 0x3F803F80u);
}
```

```cpp
#include <cuda_runtime.h>
#include <cuda_bf16.h>
#include <cuda.h>
#include <stdint.h>

namespace {

constexpr int S_LEN = 2048, D_MODEL = 640, DH = 20;

constexpr int GRP = 128;
constexpr int PLANE = GRP * 16;
constexpr int GRP_BYTES = GRP * 16 * 6;
constexpr int NGRP = S_LEN / GRP;
constexpr uint32_t TMASK = 0x6DB6u;

__device__ __align__(1024) __nv_bfloat16 g_q[S_LEN * D_MODEL];
__device__ __align__(1024) __nv_bfloat16 g_qkv[S_LEN * 3 * D_MODEL];
__device__ __align__(1024) __nv_bfloat16 g_a2[S_LEN * 2 * D_MODEL];
__device__ __align__(1024) uint8_t g_kvimg[NGRP * GRP_BYTES];
__device__ __align__(1024) uint8_t g_wimg[2 * 8 * 10 * 10240];
__device__ float g_gate[S_LEN];
__device__ float g_kmax2[64];
__device__ float g_vmax[64];
__device__ __align__(32) unsigned int g_doneL[128];
__device__ __align__(32) unsigned int g_done[128];

__device__ __forceinline__ uint32_t smem_u32(const void* p) { return (uint32_t)__cvta_generic_to_shared(p); }
__device__ __forceinline__ uint64_t mkd(uint32_t lo, uint32_t hi) {
  uint64_t d; asm("mov.b64 %0, {%1, %2};" : "=l"(d) : "r"(lo), "r"(hi)); return d;
}
__device__ __forceinline__ void wg_fence() { asm volatile("wgmma.fence.sync.aligned;" ::: "memory"); }
__device__ __forceinline__ void wg_commit() { asm volatile("wgmma.commit_group.sync.aligned;" ::: "memory"); }
template <int N> __device__ __forceinline__ void wg_wait() { asm volatile("wgmma.wait_group.sync.aligned %0;" :: "n"(N) : "memory"); }
template <int N> __device__ __forceinline__ void fence_regs(float (&d)[N]) {
#pragma unroll
  for (int i = 0; i < N; i++) asm volatile("" : "+f"(d[i]) :: "memory");
}
template <int N> __device__ __forceinline__ void fence_regs(uint32_t (&d)[N]) {
#pragma unroll
  for (int i = 0; i < N; i++) asm volatile("" : "+r"(d[i]) :: "memory");
}
__device__ __forceinline__ void mbar_init(uint32_t bar, uint32_t cnt) { asm volatile("mbarrier.init.shared::cta.b64 [%0], %1;" :: "r"(bar), "r"(cnt)); }
__device__ __forceinline__ void mbar_expect_tx(uint32_t bar, uint32_t bytes) {
  asm volatile("mbarrier.arrive.expect_tx.shared::cta.b64 _, [%0], %1;" :: "r"(bar), "r"(bytes) : "memory");
}
__device__ __forceinline__ void mbar_arrive(uint32_t bar) { asm volatile("mbarrier.arrive.shared::cta.b64 _, [%0];" :: "r"(bar) : "memory"); }
constexpr uint32_t WAIT_HINT = 20000u;
__device__ __forceinline__ void mbar_wait(uint32_t bar, uint32_t parity) {
  asm volatile("{\n.reg .pred p;\nWAIT_%=:\nmbarrier.try_wait.parity.shared::cta.b64 p, [%0], %1, %2;\n@p bra DONE_%=;\nbra WAIT_%=;\nDONE_%=:\n}\n"
               :: "r"(bar), "r"(parity), "r"(WAIT_HINT) : "memory");
}
__device__ __forceinline__ void fence_mbar_init() { asm volatile("fence.mbarrier_init.release.cluster;" ::: "memory"); }
__device__ __forceinline__ void fence_proxy_async() { asm volatile("fence.proxy.async.shared::cta;" ::: "memory"); }
__device__ __forceinline__ void bulk_g2s(uint32_t dst, const void* src, uint32_t bytes, uint32_t bar) {
  asm volatile("cp.async.bulk.shared::cluster.global.mbarrier::complete_tx::bytes [%0], [%1], %2, [%3];"
               :: "r"(dst), "l"(src), "r"(bytes), "r"(bar) : "memory");
}
__device__ __forceinline__ void tma_2d(uint32_t dst, const CUtensorMap* tm, int c0, int c1, uint32_t bar) {
  asm volatile("cp.async.bulk.tensor.2d.shared::cluster.global.mbarrier::complete_tx::bytes [%0], [%1, {%3, %4}], [%2];"
               :: "r"(dst), "l"((uint64_t)tm), "r"(bar), "r"(c0), "r"(c1) : "memory");
}
__device__ __forceinline__ void tma_3d(uint32_t dst, const CUtensorMap* tm, int c0, int c1, int c2, uint32_t bar) {
  asm volatile("cp.async.bulk.tensor.3d.shared::cluster.global.mbarrier::complete_tx::bytes [%0], [%1, {%3, %4, %5}], [%2];"
               :: "r"(dst), "l"((uint64_t)tm), "r"(bar), "r"(c0), "r"(c1), "r"(c2) : "memory");
}
__device__ __forceinline__ void prefetch_tmap(const CUtensorMap* tm) { asm volatile("prefetch.tensormap [%0];" :: "l"((uint64_t)tm) : "memory"); }
__device__ __forceinline__ void pdl_wait() { asm volatile("griddepcontrol.wait;" ::: "memory"); }
__device__ __forceinline__ void pdl_launch() { asm volatile("griddepcontrol.launch_dependents;" ::: "memory"); }
__device__ __forceinline__ float ex2(float x) { float y; asm("ex2.approx.ftz.f32 %0, %1;" : "=f"(y) : "f"(x)); return y; }
__device__ __forceinline__ uint32_t pack_bf16(float lo, float hi) {
  uint32_t r; asm("cvt.rn.bf16x2.f32 %0, %1, %2;" : "=r"(r) : "f"(hi), "f"(lo)); return r;
}
__device__ __forceinline__ float bf_lo(uint32_t x) { return __uint_as_float(x << 16); }
__device__ __forceinline__ float bf_hi(uint32_t x) { return __uint_as_float(x & 0xffff0000u); }
__device__ __forceinline__ void stsm4(uint32_t addr, uint32_t r0, uint32_t r1, uint32_t r2, uint32_t r3) {
  asm volatile("stmatrix.sync.aligned.m8n8.x4.shared.b16 [%0], {%1, %2, %3, %4};" :: "r"(addr), "r"(r0), "r"(r1), "r"(r2), "r"(r3) : "memory");
}

__device__ __forceinline__ void wgmma_ss_n160_tb(float (&d)[80], uint64_t descA, uint64_t descB) {
  asm volatile("wgmma.mma_async.sync.aligned.m64n160k16.f32.bf16.bf16 {%0, %1, %2, %3, %4, %5, %6, %7, %8, %9, %10, %11, %12, %13, %14, %15, %16, %17, %18, %19, %20, %21, %22, %23, %24, %25, %26, %27, %28, %29, %30, %31, %32, %33, %34, %35, %36, %37, %38, %39, %40, %41, %42, %43, %44, %45, %46, %47, %48, %49, %50, %51, %52, %53, %54, %55, %56, %57, %58, %59, %60, %61, %62, %63, %64, %65, %66, %67, %68, %69, %70, %71, %72, %73, %74, %75, %76, %77, %78, %79}, %80, %81, 1, 1, 1, 0, 1;\n"
    : "+f"(d[0]), "+f"(d[1]), "+f"(d[2]), "+f"(d[3]), "+f"(d[4]), "+f"(d[5]), "+f"(d[6]), "+f"(d[7]), "+f"(d[8]), "+f"(d[9]), "+f"(d[10]), "+f"(d[11]), "+f"(d[12]), "+f"(d[13]), "+f"(d[14]), "+f"(d[15]), "+f"(d[16]), "+f"(d[17]), "+f"(d[18]), "+f"(d[19]), "+f"(d[20]), "+f"(d[21]), "+f"(d[22]), "+f"(d[23]), "+f"(d[24]), "+f"(d[25]), "+f"(d[26]), "+f"(d[27]), "+f"(d[28]), "+f"(d[29]), "+f"(d[30]), "+f"(d[31]), "+f"(d[32]), "+f"(d[33]), "+f"(d[34]), "+f"(d[35]), "+f"(d[36]), "+f"(d[37]), "+f"(d[38]), "+f"(d[39]), "+f"(d[40]), "+f"(d[41]), "+f"(d[42]), "+f"(d[43]), "+f"(d[44]), "+f"(d[45]), "+f"(d[46]), "+f"(d[47]), "+f"(d[48]), "+f"(d[49]), "+f"(d[50]), "+f"(d[51]), "+f"(d[52]), "+f"(d[53]), "+f"(d[54]), "+f"(d[55]), "+f"(d[56]), "+f"(d[57]), "+f"(d[58]), "+f"(d[59]), "+f"(d[60]), "+f"(d[61]), "+f"(d[62]), "+f"(d[63]), "+f"(d[64]), "+f"(d[65]), "+f"(d[66]), "+f"(d[67]), "+f"(d[68]), "+f"(d[69]), "+f"(d[70]), "+f"(d[71]), "+f"(d[72]), "+f"(d[73]), "+f"(d[74]), "+f"(d[75]), "+f"(d[76]), "+f"(d[77]), "+f"(d[78]), "+f"(d[79])
    : "l"(descA), "l"(descB));
}
__device__ __forceinline__ void wgmma_ss_n48_tb(float (&d)[24], uint64_t descA, uint64_t descB) {
  asm volatile("wgmma.mma_async.sync.aligned.m64n48k16.f32.bf16.bf16 {%0, %1, %2, %3, %4, %5, %6, %7, %8, %9, %10, %11, %12, %13, %14, %15, %16, %17, %18, %19, %20, %21, %22, %23}, %24, %25, 1, 1, 1, 0, 1;\n"
    : "+f"(d[0]), "+f"(d[1]), "+f"(d[2]), "+f"(d[3]), "+f"(d[4]), "+f"(d[5]), "+f"(d[6]), "+f"(d[7]), "+f"(d[8]), "+f"(d[9]), "+f"(d[10]), "+f"(d[11]), "+f"(d[12]), "+f"(d[13]), "+f"(d[14]), "+f"(d[15]), "+f"(d[16]), "+f"(d[17]), "+f"(d[18]), "+f"(d[19]), "+f"(d[20]), "+f"(d[21]), "+f"(d[22]), "+f"(d[23])
    : "l"(descA), "l"(descB));
}
__device__ __forceinline__ void wgmma_ss_n80_tb(float (&d)[40], uint64_t descA, uint64_t descB) {
  asm volatile("wgmma.mma_async.sync.aligned.m64n80k16.f32.bf16.bf16 {%0, %1, %2, %3, %4, %5, %6, %7, %8, %9, %10, %11, %12, %13, %14, %15, %16, %17, %18, %19, %20, %21, %22, %23, %24, %25, %26, %27, %28, %29, %30, %31, %32, %33, %34, %35, %36, %37, %38, %39}, %40, %41, 1, 1, 1, 0, 1;\n"
    : "+f"(d[0]), "+f"(d[1]), "+f"(d[2]), "+f"(d[3]), "+f"(d[4]), "+f"(d[5]), "+f"(d[6]), "+f"(d[7]), "+f"(d[8]), "+f"(d[9]), "+f"(d[10]), "+f"(d[11]), "+f"(d[12]), "+f"(d[13]), "+f"(d[14]), "+f"(d[15]), "+f"(d[16]), "+f"(d[17]), "+f"(d[18]), "+f"(d[19]), "+f"(d[20]), "+f"(d[21]), "+f"(d[22]), "+f"(d[23]), "+f"(d[24]), "+f"(d[25]), "+f"(d[26]), "+f"(d[27]), "+f"(d[28]), "+f"(d[29]), "+f"(d[30]), "+f"(d[31]), "+f"(d[32]), "+f"(d[33]), "+f"(d[34]), "+f"(d[35]), "+f"(d[36]), "+f"(d[37]), "+f"(d[38]), "+f"(d[39])
    : "l"(descA), "l"(descB));
}
template <int SCALE_D>
__device__ __forceinline__ void wgmma_rs_n64(float (&d)[32], uint32_t a0, uint32_t a1, uint32_t a2, uint32_t a3, uint64_t descB) {
  asm volatile("wgmma.mma_async.sync.aligned.m64n64k16.f32.bf16.bf16 {%0, %1, %2, %3, %4, %5, %6, %7, %8, %9, %10, %11, %12, %13, %14, %15, %16, %17, %18, %19, %20, %21, %22, %23, %24, %25, %26, %27, %28, %29, %30, %31}, {%32, %33, %34, %35}, %36, %37, 1, 1, 0;\n"
    : "+f"(d[0]), "+f"(d[1]), "+f"(d[2]), "+f"(d[3]), "+f"(d[4]), "+f"(d[5]), "+f"(d[6]), "+f"(d[7]), "+f"(d[8]), "+f"(d[9]), "+f"(d[10]), "+f"(d[11]), "+f"(d[12]), "+f"(d[13]), "+f"(d[14]), "+f"(d[15]), "+f"(d[16]), "+f"(d[17]), "+f"(d[18]), "+f"(d[19]), "+f"(d[20]), "+f"(d[21]), "+f"(d[22]), "+f"(d[23]), "+f"(d[24]), "+f"(d[25]), "+f"(d[26]), "+f"(d[27]), "+f"(d[28]), "+f"(d[29]), "+f"(d[30]), "+f"(d[31])
    : "r"(a0), "r"(a1), "r"(a2), "r"(a3), "l"(descB), "n"(SCALE_D));
}
template <int SCALE_D>
__device__ __forceinline__ void wgmma_rs_n128(float (&d)[64], uint32_t a0, uint32_t a1, uint32_t a2, uint32_t a3, uint64_t descB) {
  asm volatile("wgmma.mma_async.sync.aligned.m64n128k16.f32.bf16.bf16 {%0, %1, %2, %3, %4, %5, %6, %7, %8, %9, %10, %11, %12, %13, %14, %15, %16, %17, %18, %19, %20, %21, %22, %23, %24, %25, %26, %27, %28, %29, %30, %31, %32, %33, %34, %35, %36, %37, %38, %39, %40, %41, %42, %43, %44, %45, %46, %47, %48, %49, %50, %51, %52, %53, %54, %55, %56, %57, %58, %59, %60, %61, %62, %63}, {%64, %65, %66, %67}, %68, %69, 1, 1, 0;\n"
    : "+f"(d[0]), "+f"(d[1]), "+f"(d[2]), "+f"(d[3]), "+f"(d[4]), "+f"(d[5]), "+f"(d[6]), "+f"(d[7]), "+f"(d[8]), "+f"(d[9]), "+f"(d[10]), "+f"(d[11]), "+f"(d[12]), "+f"(d[13]), "+f"(d[14]), "+f"(d[15]), "+f"(d[16]), "+f"(d[17]), "+f"(d[18]), "+f"(d[19]), "+f"(d[20]), "+f"(d[21]), "+f"(d[22]), "+f"(d[23]), "+f"(d[24]), "+f"(d[25]), "+f"(d[26]), "+f"(d[27]), "+f"(d[28]), "+f"(d[29]), "+f"(d[30]), "+f"(d[31]), "+f"(d[32]), "+f"(d[33]), "+f"(d[34]), "+f"(d[35]), "+f"(d[36]), "+f"(d[37]), "+f"(d[38]), "+f"(d[39]), "+f"(d[40]), "+f"(d[41]), "+f"(d[42]), "+f"(d[43]), "+f"(d[44]), "+f"(d[45]), "+f"(d[46]), "+f"(d[47]), "+f"(d[48]), "+f"(d[49]), "+f"(d[50]), "+f"(d[51]), "+f"(d[52]), "+f"(d[53]), "+f"(d[54]), "+f"(d[55]), "+f"(d[56]), "+f"(d[57]), "+f"(d[58]), "+f"(d[59]), "+f"(d[60]), "+f"(d[61]), "+f"(d[62]), "+f"(d[63])
    : "r"(a0), "r"(a1), "r"(a2), "r"(a3), "l"(descB), "n"(SCALE_D));
}
template <int SCALE_D>
__device__ __forceinline__ void wgmma_rs_n24_tb(float (&d)[12], uint32_t a0, uint32_t a1, uint32_t a2, uint32_t a3, uint64_t descB) {
  asm volatile("wgmma.mma_async.sync.aligned.m64n24k16.f32.bf16.bf16 {%0, %1, %2, %3, %4, %5, %6, %7, %8, %9, %10, %11}, {%12, %13, %14, %15}, %16, %17, 1, 1, 1;\n"
    : "+f"(d[0]), "+f"(d[1]), "+f"(d[2]), "+f"(d[3]), "+f"(d[4]), "+f"(d[5]), "+f"(d[6]), "+f"(d[7]), "+f"(d[8]), "+f"(d[9]), "+f"(d[10]), "+f"(d[11])
    : "r"(a0), "r"(a1), "r"(a2), "r"(a3), "l"(descB), "n"(SCALE_D));
}

constexpr uint32_t DHI_SW128_K = (1024 >> 4) | (1u << 30);
constexpr uint32_t DHI_SW64_MN = (512 >> 4) | (2u << 30);

template <int NC>
__device__ __forceinline__ void store_tile_bf16(const float (&acc)[NC / 2], float scale, uint32_t stage, uint8_t* stage_ptr,
                                                __nv_bfloat16* gdst, int gpitch, int lane) {
  constexpr int PITCH = NC * 2 + 16;
  const uint32_t waddr = stage + ((lane & 7) + ((lane >> 3) & 1) * 8) * PITCH + (lane >> 4) * 16;
#pragma unroll
  for (int j = 0; j < NC / 16; j++) {
    stsm4(waddr + j * 32, pack_bf16(acc[8 * j] * scale, acc[8 * j + 1] * scale), pack_bf16(acc[8 * j + 2] * scale, acc[8 * j + 3] * scale),
          pack_bf16(acc[8 * j + 4] * scale, acc[8 * j + 5] * scale), pack_bf16(acc[8 * j + 6] * scale, acc[8 * j + 7] * scale));
  }
  __syncwarp();
  constexpr int CPR = NC / 8;
#pragma unroll
  for (int i = 0; i < CPR / 2; i++) {
    const int c = i * 32 + lane, r = c / CPR, cc = c % CPR;
    const uint4 v = *reinterpret_cast<const uint4*>(stage_ptr + r * PITCH + cc * 16);
    *reinterpret_cast<uint4*>(gdst + (size_t)r * gpitch + cc * 8) = v;
  }
}

__device__ __forceinline__ void signal_done(unsigned int* flag, int wg, int tid) {
  asm volatile("bar.sync %0, 128;" :: "r"(wg + 1) : "memory");
  if ((tid & 127) == 0) asm volatile("red.release.gpu.global.add.u32 [%0], 1;" :: "l"(flag) : "memory");
}
__device__ __forceinline__ void wait_flags8(const unsigned int* f, unsigned int target) {
  for (int spin = 0; spin < (1 << 26); spin++) {
    unsigned int a, b, c, d, e, g, h, i;
    asm volatile("ld.volatile.global.v4.u32 {%0, %1, %2, %3}, [%4];" : "=r"(a), "=r"(b), "=r"(c), "=r"(d) : "l"(f) : "memory");
    asm volatile("ld.volatile.global.v4.u32 {%0, %1, %2, %3}, [%4];" : "=r"(e), "=r"(g), "=r"(h), "=r"(i) : "l"(f + 4) : "memory");
    if (min(min(min(a, b), min(c, d)), min(min(e, g), min(h, i))) >= target) break;
    __nanosleep(32);
  }
  asm volatile("fence.acq_rel.gpu;" ::: "memory");
  asm volatile("fence.proxy.async;" ::: "memory");
}

constexpr int RP_LD = 3, RP_ST = 7;
constexpr int K1_STAGES = 4;
constexpr int K1_A_BYTES = 256 * 128;
constexpr int K1_B_BYTES = 64 * 160 * 2;
constexpr int K1_STAGE = K1_A_BYTES + K1_B_BYTES;
constexpr int K1_SMEM = 5 * K1_A_BYTES + 61440 + 1024;
constexpr int KV_STAGES = 5;
constexpr int KVW_OFF = KV_STAGES * K1_A_BYTES;

__global__ void __launch_bounds__(512, 1)
proj_kernel(const __grid_constant__ CUtensorMap tmX, const __grid_constant__ CUtensorMap tmWq, const __grid_constant__ CUtensorMap tmWqkv,
            const __nv_bfloat16* __restrict__ wk, const __nv_bfloat16* __restrict__ wv, const __nv_bfloat16* __restrict__ gate_w,
            const __nv_bfloat16* __restrict__ woA, const __nv_bfloat16* __restrict__ woB) {
  extern __shared__ uint8_t smem_raw[];
  __shared__ __align__(8) uint64_t bar_full[KV_STAGES], bar_empty[KV_STAGES];
  uint8_t* smem = reinterpret_cast<uint8_t*>((reinterpret_cast<uintptr_t>(smem_raw) + 1023) & ~(uintptr_t)1023);
  const uint32_t sbase = smem_u32(smem);
  const uint32_t dbase = sbase & 0x3FFFFu;
  const int tid = threadIdx.x, warp = tid >> 5, lane = tid & 31;
  const bool is_kv = blockIdx.x >= 128;
  if (tid == 32) { prefetch_tmap(&tmX); prefetch_tmap((blockIdx.x & 15) < 4 ? &tmWq : &tmWqkv); }
  if (tid == 0) {
    for (int i = 0; i < KV_STAGES; i++) { mbar_init(smem_u32(&bar_full[i]), 1); mbar_init(smem_u32(&bar_empty[i]), is_kv ? 8 : 16); }
    fence_mbar_init();
  }
  uint2 wa[2][5], wb[2][5]; uint32_t gw[2];
  if (is_kv && tid < 320) {
#pragma unroll
    for (int r = 0; r < 2; r++) {
      const int k = tid + r * 320;
      const uint2* pk = reinterpret_cast<const uint2*>(wk + k * 20);
      const uint2* pv = reinterpret_cast<const uint2*>(wv + k * 20);
#pragma unroll
      for (int i = 0; i < 5; i++) { wa[r][i] = __ldg(pk + i); wb[r][i] = __ldg(pv + i); }
      gw[r] = (uint32_t)__bfloat16_as_ushort(gate_w[k]);
    }
  }
  __syncthreads();
  if (tid == 480 && !is_kv) { g_done[blockIdx.x] = 0u; g_doneL[blockIdx.x] = 0u; }
  pdl_launch();

  if (!is_kv) {
    const int mb = blockIdx.x >> 4, nb = blockIdx.x & 15;
    const CUtensorMap* tw = nb < 4 ? &tmWq : &tmWqkv;
    const int j0 = (nb < 4 ? nb : nb - 4) * 5;
    auto load = [&](int kt) {
      const int s = kt % K1_STAGES;
      const uint32_t fb = smem_u32(&bar_full[s]);
      mbar_expect_tx(fb, K1_STAGE);
      tma_2d(sbase + s * K1_STAGE, &tmX, kt * 64, mb * 256, fb);
      tma_3d(sbase + s * K1_STAGE + K1_A_BYTES, tw, 0, kt * 64, j0, fb);
    };
    if (tid == 0) for (int kt = 0; kt < K1_STAGES; kt++) load(kt);
    __syncwarp();
    uint4 wv2[2];
    const int rq = blockIdx.x * 400 + tid - 112;
    const int rhalf = rq >= 25600, rr = rq - rhalf * 25600, rk = 2 * (rr / 80), rch = rr % 80;
    {
      const int wg = warp >> 2;
      float acc[80];
#pragma unroll
      for (int i = 0; i < 80; i++) acc[i] = 0.f;
      for (int kt = 0; kt < 10; kt++) {
        const int s = kt % K1_STAGES;
        mbar_wait(smem_u32(&bar_full[s]), (kt / K1_STAGES) & 1);
        const uint32_t alo = ((dbase + s * K1_STAGE + wg * 8192) >> 4) | (1u << 16);
        const uint32_t blo = ((dbase + s * K1_STAGE + K1_A_BYTES) >> 4) | ((4096u >> 4) << 16);
        fence_regs(acc);
        wg_fence();
#pragma unroll
        for (int k = 0; k < 4; k++) wgmma_ss_n160_tb(acc, mkd(alo + k * 2, DHI_SW128_K), mkd(blo + k * 64, DHI_SW64_MN));
        wg_commit();
        if (kt == RP_LD && tid >= 112) {
          const uint4* src = reinterpret_cast<const uint4*>((rhalf ? woB : woA) + rk * D_MODEL + rch * 8);
          wv2[0] = __ldg(src); wv2[1] = __ldg(src + D_MODEL / 8);
        }
        if (kt == RP_ST && tid >= 112) {
          uint4* dst = reinterpret_cast<uint4*>(g_wimg + ((rhalf * 8 + rch / 10) * 10 + (rk >> 6)) * 10240 + (rch % 10) * 1024 + (rk & 63) * 16);
          dst[0] = wv2[0]; dst[1] = wv2[1];
        }
        __syncwarp();
        if (kt > 0 && kt - 1 + K1_STAGES < 10) {
          wg_wait<1>();
          const uint32_t eb = smem_u32(&bar_empty[(kt - 1) % K1_STAGES]);
          if (lane == 0) mbar_arrive(eb);
          if (tid == 0) { mbar_wait(eb, ((kt - 1) / K1_STAGES) & 1); load(kt - 1 + K1_STAGES); }
          __syncwarp();
        }
      }
      wg_wait<0>();
      fence_regs(acc);
      asm volatile("bar.sync %0, 128;" :: "r"(wg + 1) : "memory");
      const int w4 = warp & 3;
      const uint32_t off = w4 * K1_STAGE + wg * 8192;
      const int row0 = mb * 256 + wg * 64 + w4 * 16;
      if (nb < 4) {
        store_tile_bf16<160>(acc, 0.22360679774997896f * 1.4426950408889634f, sbase + off, smem + off,
                             g_q + (size_t)row0 * D_MODEL + nb * 160, D_MODEL, lane);
      } else {
        store_tile_bf16<160>(acc, 1.0f, sbase + off, smem + off, g_qkv + (size_t)row0 * (3 * D_MODEL) + (nb - 4) * 160, 3 * D_MODEL, lane);
      }
    }
  } else {
    const int cb = blockIdx.x - 128;
    if (warp == 8 && lane == 0) {
      for (int it = 0; it < KV_STAGES; it++) {
        const uint32_t fb = smem_u32(&bar_full[it]);
        mbar_expect_tx(fb, K1_A_BYTES);
        tma_2d(sbase + it * K1_A_BYTES, &tmX, it * 64, cb * 512, fb);
      }
    }
    __syncwarp();
    if (tid < 320) {
#pragma unroll
      for (int r = 0; r < 2; r++) {
        uint4* dst = reinterpret_cast<uint4*>(smem + KVW_OFF + (tid + r * 320) * 16);
        dst[0] = make_uint4(wa[r][0].x, wa[r][0].y, wa[r][1].x, wa[r][1].y);
        dst[640] = make_uint4(wa[r][2].x, wa[r][2].y, wa[r][3].x, wa[r][3].y);
        dst[1280] = make_uint4(wa[r][4].x, wa[r][4].y, 0u, 0u);
        dst[1920] = make_uint4(wb[r][0].x, wb[r][0].y, wb[r][1].x, wb[r][1].y);
        dst[2560] = make_uint4(wb[r][2].x, wb[r][2].y, wb[r][3].x, wb[r][3].y);
        dst[3200] = make_uint4(wb[r][4].x, wb[r][4].y, gw[r], 0u);
      }
    }
    fence_proxy_async();
    asm volatile("bar.sync 1, 512;" ::: "memory");
    auto produce = [&](int it0, int it1) {
      for (int it = it0; it < it1; it++) {
        const int s = it % KV_STAGES;
        mbar_wait(smem_u32(&bar_empty[s]), (it / KV_STAGES - 1) & 1);
        const uint32_t fb = smem_u32(&bar_full[s]);
        mbar_expect_tx(fb, K1_A_BYTES);
        tma_2d(sbase + s * K1_A_BYTES, &tmX, (it >= 10 ? it - 10 : it) * 64, cb * 512 + (it >= 10 ? 256 : 0), fb);
      }
    };
    if (tid == 256) produce(KV_STAGES, 15);
    __syncwarp();
    {
      const int pass = warp >> 3, wg = (warp >> 2) & 1, w4 = warp & 3, g = lane >> 2, t = lane & 3;
      if (pass == 1) asm volatile("bar.sync 2, 512;" ::: "memory");
      {
        float acc[2][24];
#pragma unroll
        for (int i = 0; i < 24; i++) { acc[0][i] = 0.f; acc[1][i] = 0.f; }
        for (int kt = 0; kt < 10; kt++) {
          const int it = pass * 10 + kt, s = it % KV_STAGES;
          mbar_wait(smem_u32(&bar_full[s]), (it / KV_STAGES) & 1);
          const uint32_t alo = ((dbase + s * K1_A_BYTES + wg * 16384) >> 4) | (1u << 16);
          const uint32_t blo = ((dbase + KVW_OFF + kt * 1024) >> 4) | ((128u >> 4) << 16);
          fence_regs(acc[0]); fence_regs(acc[1]);
          wg_fence();
#pragma unroll
          for (int k = 0; k < 4; k++) {
            wgmma_ss_n48_tb(acc[0], mkd(alo + k * 2, DHI_SW128_K), mkd(blo + k * 16, 10240u >> 4));
            wgmma_ss_n48_tb(acc[1], mkd(alo + 512 + k * 2, DHI_SW128_K), mkd(blo + k * 16, 10240u >> 4));
          }
          wg_commit();
          if (kt > 0) {
            wg_wait<1>();
            if (lane == 0) mbar_arrive(smem_u32(&bar_empty[(it - 1) % KV_STAGES]));
          }
        }
        wg_wait<0>();
        fence_regs(acc[0]); fence_regs(acc[1]);
        if (lane == 0) mbar_arrive(smem_u32(&bar_empty[(pass * 10 + 9) % KV_STAGES]));
        if (pass == 0) asm volatile("bar.arrive 2, 512;" ::: "memory");
        if (tid == 0) produce(15, 20);
        __syncwarp();
        float kmax2 = 0.f, vmax = 0.f;
#pragma unroll
        for (int hh = 0; hh < 4; hh++) {
          const int h = hh & 1;
          const float (&a)[24] = acc[hh >> 1];
          const int key = cb * 512 + pass * 256 + wg * 128 + (hh >> 1) * 64 + w4 * 16 + g + h * 8;
          const int grp = key >> 7, kk = key & 127;
          const bool poly = (TMASK >> (kk >> 3)) & 1;
          uint8_t* gp = g_kvimg + grp * GRP_BYTES;
          const uint32_t k0 = pack_bf16(a[2 * h], a[2 * h + 1]);
          const uint32_t k1 = pack_bf16(a[4 + 2 * h], a[5 + 2 * h]);
          uint32_t k2 = pack_bf16(a[8 + 2 * h], a[9 + 2 * h]);
          float n2 = bf_lo(k0) * bf_lo(k0) + bf_hi(k0) * bf_hi(k0) + bf_lo(k1) * bf_lo(k1) + bf_hi(k1) * bf_hi(k1);
          if (t < 2) {
            n2 += bf_lo(k2) * bf_lo(k2) + bf_hi(k2) * bf_hi(k2);
            k2 = pack_bf16(bf_lo(k2) * 0.5f, bf_hi(k2) * 0.5f);
          } else if (t == 2) k2 = poly ? pack_bf16(24.f, 2.5f) : pack_bf16(0.5f, 0.f);
          else k2 = poly ? pack_bf16(0.5f, 0.f) : 0u;
          *reinterpret_cast<uint32_t*>(gp + kk * 16 + t * 4) = k0;
          *reinterpret_cast<uint32_t*>(gp + PLANE + kk * 16 + t * 4) = k1;
          *reinterpret_cast<uint32_t*>(gp + 2 * PLANE + kk * 16 + t * 4) = k2;
          n2 += __shfl_xor_sync(0xffffffffu, n2, 1);
          n2 += __shfl_xor_sync(0xffffffffu, n2, 2);
          kmax2 = (n2 > kmax2 || n2 != n2) ? n2 : kmax2;
          uint32_t v0 = pack_bf16(a[12 + 2 * h], a[13 + 2 * h]);
          uint32_t v1 = pack_bf16(a[16 + 2 * h], a[17 + 2 * h]);
          uint32_t v2 = pack_bf16(a[20 + 2 * h], a[21 + 2 * h]);
          float vm = fmaxf(fmaxf(fabsf(bf_lo(v0)), fabsf(bf_hi(v0))), fmaxf(fabsf(bf_lo(v1)), fabsf(bf_hi(v1))));
          if (t < 2) vm = fmaxf(vm, fmaxf(fabsf(bf_lo(v2)), fabsf(bf_hi(v2))));
          else if (t == 2) {
            const float z = a[20 + 2 * h];
            g_gate[key] = 1.f / (1.f + __expf(-z));
            v2 = 0x00003F80u;
          } else v2 = 0u;
          vmax = fmaxf(vmax, vm);
          if (poly) { v0 ^= 0x80008000u; v1 ^= 0x80008000u; v2 ^= 0x80008000u; }
          uint8_t* vp = gp + 3 * PLANE + (kk >> 3) * 384 + (kk & 7) * 16 + t * 4;
          *reinterpret_cast<uint32_t*>(vp) = v0;
          *reinterpret_cast<uint32_t*>(vp + 128) = v1;
          *reinterpret_cast<uint32_t*>(vp + 256) = v2;
        }
#pragma unroll
        for (int o = 1; o < 32; o <<= 1) {
          const float a = __shfl_xor_sync(0xffffffffu, kmax2, o);
          kmax2 = (a > kmax2 || a != a) ? a : kmax2;
          vmax = fmaxf(vmax, __shfl_xor_sync(0xffffffffu, vmax, o));
        }
        if (lane == 0) { g_kmax2[cb * 16 + warp] = kmax2; g_vmax[cb * 16 + warp] = vmax; }
      }
    }
  }
}

__device__ __forceinline__ uint32_t ex2_pair_poly(float u0, float u1, uint32_t one2) {
  const uint32_t W = __byte_perm(__float_as_uint(u0), __float_as_uint(u1), 0x6521);
  uint32_t v; asm("lop3.b32 %0, %1, 0x007F007F, %2, 0xEA;" : "=r"(v) : "r"(W), "r"(one2));
  uint32_t L, p;
  asm("fma.rn.bf16x2 %0, %1, %2, %3;" : "=r"(L) : "r"(v), "r"(0x1f961f96u), "r"(0x9fe39fe3u));
  asm("fma.rn.bf16x2 %0, %1, %1, %2;" : "=r"(p) : "r"(L), "r"(0x00f500f5u));
  return W + p;
}
template <int JOFF>
__device__ __forceinline__ void softmax_slow(const float (&S)[32], uint32_t (&P)[16], float (&O)[12], float& m0, float& m1) {
  float a0 = m0, a1 = m1;
#pragma unroll
  for (int j = 0; j < 8; j++) {
    a0 = fmaxf(a0, fmaxf(S[4 * j], S[4 * j + 1]));
    a1 = fmaxf(a1, fmaxf(S[4 * j + 2], S[4 * j + 3]));
  }
  a0 = fmaxf(a0, __shfl_xor_sync(0xffffffffu, a0, 1)); a0 = fmaxf(a0, __shfl_xor_sync(0xffffffffu, a0, 2));
  a1 = fmaxf(a1, __shfl_xor_sync(0xffffffffu, a1, 1)); a1 = fmaxf(a1, __shfl_xor_sync(0xffffffffu, a1, 2));
  const float c0 = ex2(m0 - a0), c1 = ex2(m1 - a1);
  m0 = a0; m1 = a1;
#pragma unroll
  for (int j = 0; j < 3; j++) { O[4 * j] *= c0; O[4 * j + 1] *= c0; O[4 * j + 2] *= c1; O[4 * j + 3] *= c1; }
#pragma unroll
  for (int i = 0; i < 16; i++) {
    const float m = (i & 1) ? a1 : a0;
    const uint32_t p = pack_bf16(ex2(S[2 * i] - m), ex2(S[2 * i + 1] - m));
    P[i] = ((TMASK >> (JOFF + i / 2)) & 1) ? (p ^ 0x80008000u) : p;
  }
}
constexpr uint32_t DHI_KV = 128 >> 4;
__device__ __forceinline__ void issue_qk(float (&S)[32], const uint32_t (&q)[8], uint64_t base) {
  wgmma_rs_n64<0>(S, q[0], q[1], q[2], q[3], base + (uint64_t)((PLANE >> 4) << 16));
  wgmma_rs_n64<1>(S, q[4], q[5], q[6], q[7], base + (uint64_t)(2 * PLANE >> 4));
}
__device__ __forceinline__ void issue_pv(float (&O)[12], const uint32_t (&P)[16], uint64_t vbase) {
#pragma unroll
  for (int kk = 0; kk < 4; kk++)
    wgmma_rs_n24_tb<1>(O, P[4 * kk], P[4 * kk + 1], P[4 * kk + 2], P[4 * kk + 3], vbase + (uint64_t)(kk * (768 >> 4)));
}

constexpr uint32_t VOFF = ((3 * PLANE) >> 4) + ((384u >> 4) << 16);
constexpr int KVR = 4;
constexpr int OFF_W = KVR * GRP_BYTES;
constexpr int OFF_X = OFF_W + 10 * 10240;
constexpr int OFF_BAR = OFF_X + 4 * 16384;
constexpr int K2_SMEM = OFF_BAR + 512 + 1024;
constexpr int TSL = 7;
constexpr int BAR_KV = 0, BAR_W = 4, BAR_TA = 5, BAR_TE = 12, BAR_OWN = 19, BAR_L = 20, CNT_KV = 21, BAR_WA = 23, BAR_WF = 33, CNT_TK = 43;
constexpr int NSTEP = 2 * NGRP;

__device__ __forceinline__ void kv_load(uint32_t sbase, int step) {
  const uint32_t bar = sbase + OFF_BAR + (BAR_KV + (step & (KVR - 1))) * 8;
  mbar_expect_tx(bar, GRP_BYTES);
  bulk_g2s(sbase + (step & (KVR - 1)) * GRP_BYTES, g_kvimg + (step & (NGRP - 1)) * GRP_BYTES, GRP_BYTES, bar);
}
__device__ __forceinline__ void kv_release(uint32_t sbase, int step, bool elected) {
  if (elected && step + KVR < NSTEP) {
    uint32_t old;
    asm volatile("atom.acq_rel.cta.shared::cta.inc.u32 %0, [%1], 3;" : "=r"(old) : "r"(sbase + OFF_BAR + CNT_KV * 8 + (step & (KVR - 1)) * 4) : "memory");
    if (old == 3u) kv_load(sbase, step + KVR);
  }
  __syncwarp();
}
__device__ __forceinline__ void kv_wait(uint32_t sbase, int step) {
  mbar_wait(sbase + OFF_BAR + (BAR_KV + (step & (KVR - 1))) * 8, (step / KVR) & 1);
}

__device__ __forceinline__ uint32_t kv_release_begin(uint32_t sbase, int slot, bool doit) {
  uint32_t old = 0;
  asm volatile("{\n.reg .pred p;\nsetp.ne.u32 p, %2, 0;\n@p atom.relaxed.cta.shared::cta.inc.u32 %0, [%1], 3;\n}\n"
               : "+r"(old) : "r"(sbase + OFF_BAR + CNT_KV * 8 + slot * 4), "r"((uint32_t)doit) : "memory");
  return old;
}
template <int H>
__device__ __forceinline__ void softmax_half(const float (&S)[64], uint32_t (&P)[16], uint32_t one2) {
#pragma unroll
  for (int i = 0; i < 16; i++) {
    if ((TMASK >> (8 * H + i / 2)) & 1) P[i] = ex2_pair_poly(S[32 * H + 2 * i], S[32 * H + 2 * i + 1], one2);
    else P[i] = pack_bf16(ex2(S[32 * H + 2 * i]), ex2(S[32 * H + 2 * i + 1]));
  }
}
__device__ __forceinline__ void attn_fast(const uint32_t (&q)[8], float (&O)[12], uint32_t sbase, int step0, int nsteps, bool elected, uint32_t one2) {
  uint64_t kb0 = mkd((sbase & 0x3FFFFu) >> 4, DHI_KV);
  asm volatile("" : "+l"(kb0));
#pragma unroll 1
  for (int step4 = step0; step4 < step0 + nsteps; step4 += KVR) {
#pragma unroll
    for (int j = 0; j < KVR; j++) {
      const int step = step4 + j;
      const uint64_t kb = kb0 + (uint64_t)(j * (GRP_BYTES >> 4));
      float S[64]; uint32_t PA[16], PB[16];
#pragma unroll
      for (int i = 0; i < 64; i++) S[i] = 0.f;
      mbar_wait(sbase + OFF_BAR + (BAR_KV + j) * 8, (step / KVR) & 1);
      fence_regs(S);
      wg_fence();
      wgmma_rs_n128<0>(S, q[0], q[1], q[2], q[3], kb + (uint64_t)((PLANE >> 4) << 16));
      wgmma_rs_n128<1>(S, q[4], q[5], q[6], q[7], kb + (uint64_t)(2 * PLANE >> 4));
      wg_commit();
      const uint32_t old = kv_release_begin(sbase, (j + KVR - 1) & (KVR - 1), elected && step > step0 && step - 1 + KVR < NSTEP);
      wg_wait<0>();
      fence_regs(S);
      softmax_half<0>(S, PA, one2);
      fence_regs(PA); fence_regs(O);
      wg_fence();
      issue_pv(O, PA, kb + VOFF);
      wg_commit();
      softmax_half<1>(S, PB, one2);
      fence_regs(PB);
      wg_fence();
      issue_pv(O, PB, kb + VOFF + 4 * (768 >> 4));
      wg_commit();
      if (old == 3u) kv_load(sbase, step - 1 + KVR);
      wg_wait<0>();
      fence_regs(PA); fence_regs(PB); fence_regs(O);
    }
  }
  kv_release(sbase, step0 + nsteps - 1, elected);
}
template <int H>
__device__ __forceinline__ void slow_step(const uint32_t (&q)[8], float (&O)[12], uint64_t kb, float& m0, float& m1) {
  float S[32]; uint32_t P[16];
#pragma unroll
  for (int i = 0; i < 32; i++) S[i] = 0.f;
  fence_regs(S);
  wg_fence();
  issue_qk(S, q, kb + 64 * H);
  wg_commit();
  wg_wait<0>();
  fence_regs(S);
  softmax_slow<8 * H>(S, P, O, m0, m1);
  fence_regs(P); fence_regs(O);
  wg_fence();
  issue_pv(O, P, kb + VOFF + H * 4 * (768 >> 4));
  wg_commit();
  wg_wait<0>();
  fence_regs(O); fence_regs(P);
}
__device__ __forceinline__ void attn_slow(const uint32_t (&q)[8], float (&O)[12], uint32_t sbase, int step0, int nsteps, bool elected, float& m0, float& m1) {
#pragma unroll 1
  for (int step = step0; step < step0 + nsteps; step++) {
    kv_wait(sbase, step);
    const uint64_t kb = mkd(((sbase & 0x3FFFFu) >> 4) + (step & (KVR - 1)) * (GRP_BYTES >> 4), DHI_KV);
    slow_step<0>(q, O, kb, m0, m1);
    slow_step<1>(q, O, kb, m0, m1);
    kv_release(sbase, step, elected);
  }
}

__device__ __forceinline__ void softmax8(float (&sc)[8], float scale) {
  float mx = sc[0];
#pragma unroll
  for (int w = 1; w < 8; w++) mx = fmaxf(mx, sc[w]);
  float l = 0.f;
#pragma unroll
  for (int w = 0; w < 8; w++) { sc[w] = ex2(sc[w] - mx); l += sc[w]; }
  const float r = __fdividef(scale, l);
#pragma unroll
  for (int w = 0; w < 8; w++) sc[w] *= r;
}
constexpr int LBOX = 30 * 320;
__device__ __forceinline__ uint2 lds64(uint32_t a) {
  uint2 v; asm volatile("ld.shared.v2.u32 {%0, %1}, [%2];" : "=r"(v.x), "=r"(v.y) : "r"(a)); return v;
}
__device__ __forceinline__ void local_attn(uint32_t stage, int t0, int i, int lane) {
  constexpr float SC = 0.22360679774997896f * 1.4426950408889634f, NEG = -1e9f * 1.4426950408889634f;
  const uint32_t base = stage + (lane >> 3) * LBOX + (lane & 7) * 40 + (i + 14) * 320;
  const int t = t0 + i;
  float sc[8];
#pragma unroll
  for (int w = 0; w < 8; w++) sc[w] = 0.f;
#pragma unroll 1
  for (int c = 0; c < 5; c++) {
    const uint2 qv = lds64(base + c * 8);
    const float q0 = bf_lo(qv.x), q1 = bf_hi(qv.x), q2 = bf_lo(qv.y), q3 = bf_hi(qv.y);
#pragma unroll
    for (int w = 0; w < 8; w++) {
      const uint2 k = lds64(base + c * 8 + 4 * LBOX - w * 640);
      sc[w] = fmaf(q0, bf_lo(k.x), sc[w]); sc[w] = fmaf(q1, bf_hi(k.x), sc[w]);
      sc[w] = fmaf(q2, bf_lo(k.y), sc[w]); sc[w] = fmaf(q3, bf_hi(k.y), sc[w]);
    }
  }
#pragma unroll
  for (int w = 0; w < 8; w++) sc[w] = t - 2 * w >= 0 ? sc[w] * SC : NEG;
  softmax8(sc, 1.f - g_gate[t]);
  uint2* dst = reinterpret_cast<uint2*>(g_a2 + (size_t)t * (2 * D_MODEL) + D_MODEL + lane * DH);
#pragma unroll 1
  for (int c = 0; c < 5; c++) {
    float o0 = 0.f, o1 = 0.f, o2 = 0.f, o3 = 0.f;
#pragma unroll
    for (int w = 0; w < 8; w++) {
      const uint2 v = lds64(base + c * 8 + 8 * LBOX - w * 640);
      o0 = fmaf(sc[w], bf_lo(v.x), o0); o1 = fmaf(sc[w], bf_hi(v.x), o1);
      o2 = fmaf(sc[w], bf_lo(v.y), o2); o3 = fmaf(sc[w], bf_hi(v.y), o3);
    }
    dst[c] = make_uint2(pack_bf16(o0, o1), pack_bf16(o2, o3));
  }
}
__device__ __forceinline__ uint32_t ta_slot(int i) { return i < 4 ? OFF_X + i * 16384 : (i - 4) * 16384; }

__global__ void __launch_bounds__(640, 1)
attn_kernel(const __grid_constant__ CUtensorMap tmA2, const __grid_constant__ CUtensorMap tmL, __nv_bfloat16* __restrict__ out, uint32_t one2) {
  extern __shared__ uint8_t smem_raw[];
  uint8_t* smem = reinterpret_cast<uint8_t*>((reinterpret_cast<uintptr_t>(smem_raw) + 1023) & ~(uintptr_t)1023);
  const uint32_t sbase = smem_u32(smem);
  const uint32_t dbase = sbase & 0x3FFFFu;
  const uint32_t bars = sbase + OFF_BAR;
  const int tid = threadIdx.x, wg = tid >> 7, warp = (tid >> 5) & 3, lane = tid & 31, g = lane >> 2, t = lane & 3;
  const int mb = blockIdx.x >> 3, nb = blockIdx.x & 7;
  const bool elected = (tid & 127) == 0;
  if (tid == 512) { prefetch_tmap(&tmL); prefetch_tmap(&tmA2); }
  if (tid == 0) {
    for (int i = 0; i < BAR_TE; i++) mbar_init(bars + i * 8, 1);
    for (int i = BAR_TE; i < BAR_TE + TSL; i++) mbar_init(bars + i * 8, 8);
    mbar_init(bars + BAR_OWN * 8, 4);
    mbar_init(bars + BAR_L * 8, 1);
    for (int i = 0; i < 10; i++) { mbar_init(bars + (BAR_WA + i) * 8, 1); mbar_init(bars + (BAR_WF + i) * 8, 8); }
    for (int i = 0; i < 4; i++) *reinterpret_cast<uint32_t*>(smem + OFF_BAR + CNT_KV * 8 + i * 4) = 0u;
    *reinterpret_cast<uint32_t*>(smem + OFF_BAR + CNT_TK * 8) = 0u;
    fence_mbar_init();
  }
  __syncthreads();
  auto tail_load = [&](int i) {
    const uint32_t fb = bars + (BAR_TA + i % TSL) * 8;
    mbar_expect_tx(fb, 16384);
    tma_2d(sbase + ta_slot(i % TSL), &tmA2, i < 10 ? D_MODEL + i * 64 : (i - 10) * 64, mb * 128, fb);
  };
  if (wg == 4) {
    asm volatile("setmaxnreg.dec.sync.aligned.u32 32;");
    pdl_wait();
    if (tid == 512) {
      for (int j = 0; j < KVR; j++) kv_load(sbase, j);
      mbar_expect_tx(bars + BAR_L * 8, 12 * LBOX);
      for (int i = 0; i < 12; i++) tma_2d(sbase + OFF_W + i * LBOX, &tmL, i * 160, blockIdx.x * 16 - 14, bars + BAR_L * 8);
    }
    __syncwarp();
    mbar_wait(bars + BAR_L * 8, 0);
#pragma unroll 1
    for (int i = 0; i < 4; i++) local_attn(sbase + OFF_W, blockIdx.x * 16, warp * 4 + i, lane);
    signal_done(&g_doneL[blockIdx.x], wg, tid);
    if (tid == 512) {
      fence_proxy_async();
      mbar_expect_tx(bars + BAR_W * 8, 10 * 10240);
      for (int i = 0; i < 5; i++) bulk_g2s(sbase + OFF_W + i * 20480, g_wimg + ((8 + nb) * 10) * 10240 + i * 20480, 20480, bars + BAR_W * 8);
      wait_flags8(&g_doneL[mb * 8], 1u);
      for (int i = 0; i < 4; i++) tail_load(i);
      mbar_wait(bars + BAR_OWN * 8, 0);
      for (int i = 4; i < 20; i++) {
        if (i >= TSL) mbar_wait(bars + (BAR_TE + i % TSL) * 8, (i / TSL - 1) & 1);
        if (i == 10) { wait_flags8(&g_done[mb * 8], 1u); }
        tail_load(i);
      }
    } else if (tid == 576) {
      mbar_wait(bars + BAR_OWN * 8, 0);
      asm volatile("red.release.gpu.global.add.u32 [%0], 1;" :: "l"(&g_done[blockIdx.x]) : "memory");
    } else if (tid == 544) {
      for (int kt = 0; kt < 10; kt++) {
        mbar_wait(bars + (BAR_WF + kt) * 8, 0);
        mbar_expect_tx(bars + (BAR_WA + kt) * 8, 10240);
        bulk_g2s(sbase + OFF_W + kt * 10240, g_wimg + (nb * 10 + kt) * 10240, 10240, bars + (BAR_WA + kt) * 8);
      }
    }
    return;
  }
  asm volatile("setmaxnreg.inc.sync.aligned.u32 112;");
  pdl_wait();
  uint32_t q[8], q2[6];
  const int rowA = (blockIdx.x * 8 + wg) * 64 + warp * 16 + g;
  {
    const uint32_t* r0 = reinterpret_cast<const uint32_t*>(g_q + (size_t)rowA * DH);
    const uint32_t* r1 = r0 + 8 * (DH / 2);
    const uint32_t* s0 = r0 + 256 * (DH / 2);
    const uint32_t* s1 = s0 + 8 * (DH / 2);
    q[0] = r0[t]; q[1] = r1[t]; q[2] = r0[t + 4]; q[3] = r1[t + 4];
    q[4] = t < 2 ? r0[8 + t] : 0u;
    q[5] = t < 2 ? r1[8 + t] : 0u;
    q2[0] = s0[t]; q2[1] = s1[t]; q2[2] = s0[t + 4]; q2[3] = s1[t + 4];
    q2[4] = t < 2 ? s0[8 + t] : 0u;
    q2[5] = t < 2 ? s1[8 + t] : 0u;
  }
  float kmax2 = 0.f, vmax = 0.f;
#pragma unroll
  for (int i = 0; i < 2; i++) {
    const float a = g_kmax2[lane + 32 * i];
    kmax2 = (a > kmax2 || a != a) ? a : kmax2;
    vmax = fmaxf(vmax, g_vmax[lane + 32 * i]);
  }
#pragma unroll
  for (int o = 1; o < 32; o <<= 1) {
    const float a = __shfl_xor_sync(0xffffffffu, kmax2, o);
    kmax2 = (a > kmax2 || a != a) ? a : kmax2;
    vmax = fmaxf(vmax, __shfl_xor_sync(0xffffffffu, vmax, o));
  }
  const float qlim = (vmax >= 0.00390625f && vmax <= 256.f) ? 9025.f / kmax2 : -1.f;
#pragma unroll 1
  for (int it = 0; it < 2; it++) {
    const int row0 = rowA + it * 256;
    if (it == 1) {
#pragma unroll
      for (int i = 0; i < 6; i++) q[i] = q2[i];
    }
    float n0 = bf_lo(q[0]) * bf_lo(q[0]) + bf_hi(q[0]) * bf_hi(q[0]) + bf_lo(q[2]) * bf_lo(q[2]) + bf_hi(q[2]) * bf_hi(q[2]) +
               bf_lo(q[4]) * bf_lo(q[4]) + bf_hi(q[4]) * bf_hi(q[4]);
    float n1 = bf_lo(q[1]) * bf_lo(q[1]) + bf_hi(q[1]) * bf_hi(q[1]) + bf_lo(q[3]) * bf_lo(q[3]) + bf_hi(q[3]) * bf_hi(q[3]) +
               bf_lo(q[5]) * bf_lo(q[5]) + bf_hi(q[5]) * bf_hi(q[5]);
    n0 += __shfl_xor_sync(0xffffffffu, n0, 1); n0 += __shfl_xor_sync(0xffffffffu, n0, 2);
    n1 += __shfl_xor_sync(0xffffffffu, n1, 1); n1 += __shfl_xor_sync(0xffffffffu, n1, 2);
    const bool safe = (n0 <= qlim) && (n1 <= qlim);
    uint32_t unsafe_any;
    asm volatile("{\n.reg .pred p, r;\nsetp.eq.u32 p, %1, 0;\nbarrier.cta.red.or.pred r, %2, 128, p;\nselp.u32 %0, 1, 0, r;\n}\n"
                 : "=r"(unsafe_any) : "r"((uint32_t)safe), "r"(wg + 1) : "memory");
    float O[12];
#pragma unroll
    for (int i = 0; i < 12; i++) O[i] = 0.f;
    if (!unsafe_any && t >= 2) { q[4] = q[5] = (t == 2) ? 0x3F804100u : 0x00003B80u; }
    q[6] = q[4]; q[7] = q[5];
    fence_regs(q);
    float m0 = -INFINITY, m1 = -INFINITY;
    if (!unsafe_any) attn_fast(q, O, sbase, it * NGRP, NGRP, elected, one2);
    else attn_slow(q, O, sbase, it * NGRP, NGRP, elected, m0, m1);
    const float l0 = __shfl_sync(0xffffffffu, O[8], (lane & ~3) | 2);
    const float l1 = __shfl_sync(0xffffffffu, O[10], (lane & ~3) | 2);
    const int tok = row0 >> 5;
    const float gt = g_gate[tok];
    const float i0 = gt / l0, i1 = gt / l1;
    uint32_t* o0 = reinterpret_cast<uint32_t*>(g_a2 + (size_t)tok * (2 * D_MODEL) + (row0 & 31) * DH);
    uint32_t* o1 = o0 + 8 * (DH / 2);
    o0[t] = pack_bf16(O[0] * i0, O[1] * i0); o1[t] = pack_bf16(O[2] * i1, O[3] * i1);
    o0[t + 4] = pack_bf16(O[4] * i0, O[5] * i0); o1[t + 4] = pack_bf16(O[6] * i1, O[7] * i1);
    if (t < 2) { o0[t + 8] = pack_bf16(O[8] * i0, O[9] * i0); o1[t + 8] = pack_bf16(O[10] * i1, O[11] * i1); }
  }
  uint32_t* ticket = reinterpret_cast<uint32_t*>(smem + OFF_BAR + CNT_TK * 8);
  if (elected) ticket[1 + wg] = atomicAdd(ticket, 1u);
  asm volatile("bar.sync %0, 128;" :: "r"(wg + 1) : "memory");
  if (elected) mbar_arrive(bars + BAR_OWN * 8);
  const int mt = ticket[1 + wg];
  if (mt < 2) {
    float acc[40];
#pragma unroll
    for (int i = 0; i < 40; i++) acc[i] = 0.f;
    mbar_wait(bars + BAR_W * 8, 0);
    int sl = 0, ph = 0;
#pragma unroll 1
    for (int i = 0; i < 20; i++) {
      mbar_wait(bars + (BAR_TA + sl) * 8, ph);
      if (i >= 10) mbar_wait(bars + (BAR_WA + i - 10) * 8, 0);
      const uint32_t alo = ((dbase + ta_slot(sl) + mt * 8192) >> 4) | (1u << 16);
      const uint32_t blo = ((dbase + OFF_W + (i >= 10 ? i - 10 : i) * 10240) >> 4) | ((128u >> 4) << 16);
      fence_regs(acc);
      wg_fence();
#pragma unroll
      for (int k = 0; k < 4; k++) wgmma_ss_n80_tb(acc, mkd(alo + k * 2, DHI_SW128_K), mkd(blo + k * 16, 1024u >> 4));
      wg_commit();
      if (i > 0) {
        wg_wait<1>();
        if (lane == 0) mbar_arrive(bars + (BAR_TE + (sl == 0 ? TSL - 1 : sl - 1)) * 8);
        if (lane == 1 && i <= 10) mbar_arrive(bars + (BAR_WF + i - 1) * 8);
      }
      if (++sl == TSL) { sl = 0; ph ^= 1; }
    }
    wg_wait<0>();
    fence_regs(acc);
    asm volatile("bar.sync %0, 128;" :: "r"(wg + 1) : "memory");
    const uint32_t so = ta_slot(warp) + mt * 8192;
    const int row0 = mb * 128 + mt * 64 + warp * 16;
    store_tile_bf16<80>(acc, 1.0f, sbase + so, smem + so, out + (size_t)row0 * D_MODEL + nb * 80, D_MODEL, lane);
  }
}

typedef CUresult (*EncodeFn)(CUtensorMap*, CUtensorMapDataType, cuuint32_t, void*, const cuuint64_t*, const cuuint64_t*,
                             const cuuint32_t*, const cuuint32_t*, CUtensorMapInterleave, CUtensorMapSwizzle,
                             CUtensorMapL2promotion, CUtensorMapFloatOOBfill);

void make_map(EncodeFn fn, CUtensorMap* tm, const void* ptr, int rank, const cuuint64_t* dims, const cuuint64_t* strides,
              const cuuint32_t* box, CUtensorMapSwizzle sw) {
  const cuuint32_t es[3] = {1, 1, 1};
  fn(tm, CU_TENSOR_MAP_DATA_TYPE_BFLOAT16, rank, const_cast<void*>(ptr), dims, strides, box, es, CU_TENSOR_MAP_INTERLEAVE_NONE, sw,
     CU_TENSOR_MAP_L2_PROMOTION_L2_256B, CU_TENSOR_MAP_FLOAT_OOB_FILL_NONE);
}
void map_a(EncodeFn fn, CUtensorMap* tm, const void* p, int rows, int cols, int box_rows) {
  const cuuint64_t dims[2] = {(cuuint64_t)cols, (cuuint64_t)rows};
  const cuuint64_t str[1] = {(cuuint64_t)cols * 2};
  const cuuint32_t box[2] = {64, (cuuint32_t)box_rows};
  make_map(fn, tm, p, 2, dims, str, box, CU_TENSOR_MAP_SWIZZLE_128B);
}
void map_w(EncodeFn fn, CUtensorMap* tm, const void* p, int K, int N, int atom, CUtensorMapSwizzle sw) {
  const cuuint64_t dims[3] = {(cuuint64_t)atom, (cuuint64_t)K, (cuuint64_t)(N / atom)};
  const cuuint64_t str[2] = {(cuuint64_t)N * 2, (cuuint64_t)atom * 2};
  const cuuint32_t box[3] = {(cuuint32_t)atom, 64, 5};
  make_map(fn, tm, p, 3, dims, str, box, sw);
}

template <typename... KArgs, typename... Args>
void launch(void (*kern)(KArgs...), int grid, int block, int smem, bool pdl, Args... args) {
  cudaLaunchConfig_t cfg = {};
  cfg.gridDim = dim3(grid); cfg.blockDim = dim3(block); cfg.dynamicSmemBytes = smem; cfg.stream = cudaStreamPerThread;
  cudaLaunchAttribute at[1];
  at[0].id = cudaLaunchAttributeProgrammaticStreamSerialization;
  at[0].val.programmaticStreamSerializationAllowed = 1;
  cfg.attrs = at; cfg.numAttrs = pdl ? 1 : 0;
  cudaLaunchKernelEx(&cfg, kern, KArgs(args)...);
}

}

extern "C" void kernel_launch(void* const* d_in, const int* in_sizes, int n_in, void* d_out, int out_size) {
  (void)in_sizes; (void)n_in; (void)out_size;
  const __nv_bfloat16* x = (const __nv_bfloat16*)d_in[0];
  const __nv_bfloat16* wq = (const __nv_bfloat16*)d_in[1];
  const __nv_bfloat16* wk = (const __nv_bfloat16*)d_in[2];
  const __nv_bfloat16* wv = (const __nv_bfloat16*)d_in[3];
  const __nv_bfloat16* woA = (const __nv_bfloat16*)d_in[4];
  const __nv_bfloat16* wqkv = (const __nv_bfloat16*)d_in[6];
  const __nv_bfloat16* woB = (const __nv_bfloat16*)d_in[7];
  const __nv_bfloat16* gate_w = (const __nv_bfloat16*)d_in[8];

  static EncodeFn enc = nullptr;
  static void* a2_ptr = nullptr;
  static void* qkv_ptr = nullptr;
  if (!enc) {
    void* fp = nullptr;
    cudaDriverEntryPointQueryResult qr;
    cudaGetDriverEntryPoint("cuTensorMapEncodeTiled", &fp, cudaEnableDefault, &qr);
    enc = (EncodeFn)fp;
    cudaGetSymbolAddress(&a2_ptr, g_a2);
    cudaGetSymbolAddress(&qkv_ptr, g_qkv);
    cudaFuncSetAttribute(proj_kernel, cudaFuncAttributeMaxDynamicSharedMemorySize, K1_SMEM);
    cudaFuncSetAttribute(attn_kernel, cudaFuncAttributeMaxDynamicSharedMemorySize, K2_SMEM);
  }
  CUtensorMap tmX, tmWq, tmWqkv, tmA2, tmL;
  {
    const cuuint64_t dims[2] = {3 * D_MODEL, S_LEN};
    const cuuint64_t str[1] = {3 * D_MODEL * 2};
    const cuuint32_t box[2] = {160, 30};
    make_map(enc, &tmL, qkv_ptr, 2, dims, str, box, CU_TENSOR_MAP_SWIZZLE_NONE);
  }
  map_a(enc, &tmX, x, S_LEN, D_MODEL, 256);
  map_w(enc, &tmWq, wq, D_MODEL, D_MODEL, 32, CU_TENSOR_MAP_SWIZZLE_64B);
  map_w(enc, &tmWqkv, wqkv, D_MODEL, 3 * D_MODEL, 32, CU_TENSOR_MAP_SWIZZLE_64B);
  map_a(enc, &tmA2, a2_ptr, S_LEN, 2 * D_MODEL, 128);

  launch(proj_kernel, 132, 512, K1_SMEM, false, tmX, tmWq, tmWqkv, wk, wv, gate_w, woA, woB);
  launch(attn_kernel, 128, 640, K2_SMEM, true, tmA2, tmL, (__nv_bfloat16*)d_out, 0x3F803F80u);
}
```

```cpp
#include <cuda_runtime.h>
#include <cuda_bf16.h>
#include <cuda.h>
#include <stdint.h>

namespace {

constexpr int S_LEN = 2048, D_MODEL = 640, DH = 20;

constexpr int GRP = 128;
constexpr int PLANE = GRP * 16;
constexpr int GRP_BYTES = GRP * 16 * 6;
constexpr int NGRP = S_LEN / GRP;
#define TMASKV 0x6DB6u
constexpr uint32_t TMASK = TMASKV;

__device__ __align__(1024) __nv_bfloat16 g_q[S_LEN * D_MODEL];
__device__ __align__(1024) __nv_bfloat16 g_qkv[S_LEN * 3 * D_MODEL];
__device__ __align__(1024) __nv_bfloat16 g_a2[S_LEN * 2 * D_MODEL];
__device__ __align__(1024) uint8_t g_kvimg[NGRP * GRP_BYTES];
__device__ __align__(1024) uint8_t g_wimg[2 * 8 * 10 * 10240];
__device__ float g_gate[S_LEN];
__device__ float g_kmax2[64];
__device__ float g_vmax[64];
__device__ __align__(32) unsigned int g_doneL[128];
__device__ __align__(32) unsigned int g_done[128];

#define PROF(k, slot)
#define PROF2(k, slot)
__device__ __forceinline__ uint32_t smem_u32(const void* p) { return (uint32_t)__cvta_generic_to_shared(p); }
__device__ __forceinline__ uint64_t mkd(uint32_t lo, uint32_t hi) {
  uint64_t d; asm("mov.b64 %0, {%1, %2};" : "=l"(d) : "r"(lo), "r"(hi)); return d;
}
__device__ __forceinline__ void wg_fence() { asm volatile("wgmma.fence.sync.aligned;" ::: "memory"); }
__device__ __forceinline__ void wg_commit() { asm volatile("wgmma.commit_group.sync.aligned;" ::: "memory"); }
template <int N> __device__ __forceinline__ void wg_wait() { asm volatile("wgmma.wait_group.sync.aligned %0;" :: "n"(N) : "memory"); }
template <int N> __device__ __forceinline__ void fence_regs(float (&d)[N]) {
#pragma unroll
  for (int i = 0; i < N; i++) asm volatile("" : "+f"(d[i]) :: "memory");
}
template <int N> __device__ __forceinline__ void fence_regs(uint32_t (&d)[N]) {
#pragma unroll
  for (int i = 0; i < N; i++) asm volatile("" : "+r"(d[i]) :: "memory");
}
__device__ __forceinline__ void mbar_init(uint32_t bar, uint32_t cnt) { asm volatile("mbarrier.init.shared::cta.b64 [%0], %1;" :: "r"(bar), "r"(cnt)); }
__device__ __forceinline__ void mbar_expect_tx(uint32_t bar, uint32_t bytes) {
  asm volatile("mbarrier.arrive.expect_tx.shared::cta.b64 _, [%0], %1;" :: "r"(bar), "r"(bytes) : "memory");
}
__device__ __forceinline__ void mbar_arrive(uint32_t bar) { asm volatile("mbarrier.arrive.shared::cta.b64 _, [%0];" :: "r"(bar) : "memory"); }
#define WAIT_HINT 20000u
__device__ __forceinline__ void mbar_wait(uint32_t bar, uint32_t parity) {
  asm volatile("{\n.reg .pred p;\nWAIT_%=:\nmbarrier.try_wait.parity.shared::cta.b64 p, [%0], %1, %2;\n@p bra DONE_%=;\nbra WAIT_%=;\nDONE_%=:\n}\n"
               :: "r"(bar), "r"(parity), "r"(WAIT_HINT) : "memory");
}
__device__ __forceinline__ void fence_mbar_init() { asm volatile("fence.mbarrier_init.release.cluster;" ::: "memory"); }
__device__ __forceinline__ void fence_proxy_async() { asm volatile("fence.proxy.async.shared::cta;" ::: "memory"); }
__device__ __forceinline__ void bulk_g2s(uint32_t dst, const void* src, uint32_t bytes, uint32_t bar) {
  asm volatile("cp.async.bulk.shared::cluster.global.mbarrier::complete_tx::bytes [%0], [%1], %2, [%3];"
               :: "r"(dst), "l"(src), "r"(bytes), "r"(bar) : "memory");
}
__device__ __forceinline__ void tma_2d(uint32_t dst, const CUtensorMap* tm, int c0, int c1, uint32_t bar) {
  asm volatile("cp.async.bulk.tensor.2d.shared::cluster.global.mbarrier::complete_tx::bytes [%0], [%1, {%3, %4}], [%2];"
               :: "r"(dst), "l"((uint64_t)tm), "r"(bar), "r"(c0), "r"(c1) : "memory");
}
__device__ __forceinline__ void tma_3d(uint32_t dst, const CUtensorMap* tm, int c0, int c1, int c2, uint32_t bar) {
  asm volatile("cp.async.bulk.tensor.3d.shared::cluster.global.mbarrier::complete_tx::bytes [%0], [%1, {%3, %4, %5}], [%2];"
               :: "r"(dst), "l"((uint64_t)tm), "r"(bar), "r"(c0), "r"(c1), "r"(c2) : "memory");
}
__device__ __forceinline__ void prefetch_tmap(const CUtensorMap* tm) { asm volatile("prefetch.tensormap [%0];" :: "l"((uint64_t)tm) : "memory"); }
__device__ __forceinline__ void pdl_wait() { asm volatile("griddepcontrol.wait;" ::: "memory"); }
__device__ __forceinline__ void pdl_launch() { asm volatile("griddepcontrol.launch_dependents;" ::: "memory"); }
__device__ __forceinline__ float ex2(float x) { float y; asm("ex2.approx.ftz.f32 %0, %1;" : "=f"(y) : "f"(x)); return y; }
__device__ __forceinline__ uint32_t pack_bf16(float lo, float hi) {
  uint32_t r; asm("cvt.rn.bf16x2.f32 %0, %1, %2;" : "=r"(r) : "f"(hi), "f"(lo)); return r;
}
__device__ __forceinline__ float bf_lo(uint32_t x) { return __uint_as_float(x << 16); }
__device__ __forceinline__ float bf_hi(uint32_t x) { return __uint_as_float(x & 0xffff0000u); }
__device__ __forceinline__ void stsm4(uint32_t addr, uint32_t r0, uint32_t r1, uint32_t r2, uint32_t r3) {
  asm volatile("stmatrix.sync.aligned.m8n8.x4.shared.b16 [%0], {%1, %2, %3, %4};" :: "r"(addr), "r"(r0), "r"(r1), "r"(r2), "r"(r3) : "memory");
}

__device__ __forceinline__ void wgmma_ss_n160_tb(float (&d)[80], uint64_t descA, uint64_t descB) {
  asm volatile("wgmma.mma_async.sync.aligned.m64n160k16.f32.bf16.bf16 {%0, %1, %2, %3, %4, %5, %6, %7, %8, %9, %10, %11, %12, %13, %14, %15, %16, %17, %18, %19, %20, %21, %22, %23, %24, %25, %26, %27, %28, %29, %30, %31, %32, %33, %34, %35, %36, %37, %38, %39, %40, %41, %42, %43, %44, %45, %46, %47, %48, %49, %50, %51, %52, %53, %54, %55, %56, %57, %58, %59, %60, %61, %62, %63, %64, %65, %66, %67, %68, %69, %70, %71, %72, %73, %74, %75, %76, %77, %78, %79}, %80, %81, 1, 1, 1, 0, 1;\n"
    : "+f"(d[0]), "+f"(d[1]), "+f"(d[2]), "+f"(d[3]), "+f"(d[4]), "+f"(d[5]), "+f"(d[6]), "+f"(d[7]), "+f"(d[8]), "+f"(d[9]), "+f"(d[10]), "+f"(d[11]), "+f"(d[12]), "+f"(d[13]), "+f"(d[14]), "+f"(d[15]), "+f"(d[16]), "+f"(d[17]), "+f"(d[18]), "+f"(d[19]), "+f"(d[20]), "+f"(d[21]), "+f"(d[22]), "+f"(d[23]), "+f"(d[24]), "+f"(d[25]), "+f"(d[26]), "+f"(d[27]), "+f"(d[28]), "+f"(d[29]), "+f"(d[30]), "+f"(d[31]), "+f"(d[32]), "+f"(d[33]), "+f"(d[34]), "+f"(d[35]), "+f"(d[36]), "+f"(d[37]), "+f"(d[38]), "+f"(d[39]), "+f"(d[40]), "+f"(d[41]), "+f"(d[42]), "+f"(d[43]), "+f"(d[44]), "+f"(d[45]), "+f"(d[46]), "+f"(d[47]), "+f"(d[48]), "+f"(d[49]), "+f"(d[50]), "+f"(d[51]), "+f"(d[52]), "+f"(d[53]), "+f"(d[54]), "+f"(d[55]), "+f"(d[56]), "+f"(d[57]), "+f"(d[58]), "+f"(d[59]), "+f"(d[60]), "+f"(d[61]), "+f"(d[62]), "+f"(d[63]), "+f"(d[64]), "+f"(d[65]), "+f"(d[66]), "+f"(d[67]), "+f"(d[68]), "+f"(d[69]), "+f"(d[70]), "+f"(d[71]), "+f"(d[72]), "+f"(d[73]), "+f"(d[74]), "+f"(d[75]), "+f"(d[76]), "+f"(d[77]), "+f"(d[78]), "+f"(d[79])
    : "l"(descA), "l"(descB));
}
__device__ __forceinline__ void wgmma_ss_n48_tb(float (&d)[24], uint64_t descA, uint64_t descB) {
  asm volatile("wgmma.mma_async.sync.aligned.m64n48k16.f32.bf16.bf16 {%0, %1, %2, %3, %4, %5, %6, %7, %8, %9, %10, %11, %12, %13, %14, %15, %16, %17, %18, %19, %20, %21, %22, %23}, %24, %25, 1, 1, 1, 0, 1;\n"
    : "+f"(d[0]), "+f"(d[1]), "+f"(d[2]), "+f"(d[3]), "+f"(d[4]), "+f"(d[5]), "+f"(d[6]), "+f"(d[7]), "+f"(d[8]), "+f"(d[9]), "+f"(d[10]), "+f"(d[11]), "+f"(d[12]), "+f"(d[13]), "+f"(d[14]), "+f"(d[15]), "+f"(d[16]), "+f"(d[17]), "+f"(d[18]), "+f"(d[19]), "+f"(d[20]), "+f"(d[21]), "+f"(d[22]), "+f"(d[23])
    : "l"(descA), "l"(descB));
}
__device__ __forceinline__ void wgmma_ss_n80_tb(float (&d)[40], uint64_t descA, uint64_t descB) {
  asm volatile("wgmma.mma_async.sync.aligned.m64n80k16.f32.bf16.bf16 {%0, %1, %2, %3, %4, %5, %6, %7, %8, %9, %10, %11, %12, %13, %14, %15, %16, %17, %18, %19, %20, %21, %22, %23, %24, %25, %26, %27, %28, %29, %30, %31, %32, %33, %34, %35, %36, %37, %38, %39}, %40, %41, 1, 1, 1, 0, 1;\n"
    : "+f"(d[0]), "+f"(d[1]), "+f"(d[2]), "+f"(d[3]), "+f"(d[4]), "+f"(d[5]), "+f"(d[6]), "+f"(d[7]), "+f"(d[8]), "+f"(d[9]), "+f"(d[10]), "+f"(d[11]), "+f"(d[12]), "+f"(d[13]), "+f"(d[14]), "+f"(d[15]), "+f"(d[16]), "+f"(d[17]), "+f"(d[18]), "+f"(d[19]), "+f"(d[20]), "+f"(d[21]), "+f"(d[22]), "+f"(d[23]), "+f"(d[24]), "+f"(d[25]), "+f"(d[26]), "+f"(d[27]), "+f"(d[28]), "+f"(d[29]), "+f"(d[30]), "+f"(d[31]), "+f"(d[32]), "+f"(d[33]), "+f"(d[34]), "+f"(d[35]), "+f"(d[36]), "+f"(d[37]), "+f"(d[38]), "+f"(d[39])
    : "l"(descA), "l"(descB));
}
template <int SCALE_D>
__device__ __forceinline__ void wgmma_rs_n64(float (&d)[32], uint32_t a0, uint32_t a1, uint32_t a2, uint32_t a3, uint64_t descB) {
  asm volatile("wgmma.mma_async.sync.aligned.m64n64k16.f32.bf16.bf16 {%0, %1, %2, %3, %4, %5, %6, %7, %8, %9, %10, %11, %12, %13, %14, %15, %16, %17, %18, %19, %20, %21, %22, %23, %24, %25, %26, %27, %28, %29, %30, %31}, {%32, %33, %34, %35}, %36, %37, 1, 1, 0;\n"
    : "+f"(d[0]), "+f"(d[1]), "+f"(d[2]), "+f"(d[3]), "+f"(d[4]), "+f"(d[5]), "+f"(d[6]), "+f"(d[7]), "+f"(d[8]), "+f"(d[9]), "+f"(d[10]), "+f"(d[11]), "+f"(d[12]), "+f"(d[13]), "+f"(d[14]), "+f"(d[15]), "+f"(d[16]), "+f"(d[17]), "+f"(d[18]), "+f"(d[19]), "+f"(d[20]), "+f"(d[21]), "+f"(d[22]), "+f"(d[23]), "+f"(d[24]), "+f"(d[25]), "+f"(d[26]), "+f"(d[27]), "+f"(d[28]), "+f"(d[29]), "+f"(d[30]), "+f"(d[31])
    : "r"(a0), "r"(a1), "r"(a2), "r"(a3), "l"(descB), "n"(SCALE_D));
}
template <int SCALE_D>
__device__ __forceinline__ void wgmma_rs_n128(float (&d)[64], uint32_t a0, uint32_t a1, uint32_t a2, uint32_t a3, uint64_t descB) {
  asm volatile("wgmma.mma_async.sync.aligned.m64n128k16.f32.bf16.bf16 {%0, %1, %2, %3, %4, %5, %6, %7, %8, %9, %10, %11, %12, %13, %14, %15, %16, %17, %18, %19, %20, %21, %22, %23, %24, %25, %26, %27, %28, %29, %30, %31, %32, %33, %34, %35, %36, %37, %38, %39, %40, %41, %42, %43, %44, %45, %46, %47, %48, %49, %50, %51, %52, %53, %54, %55, %56, %57, %58, %59, %60, %61, %62, %63}, {%64, %65, %66, %67}, %68, %69, 1, 1, 0;\n"
    : "+f"(d[0]), "+f"(d[1]), "+f"(d[2]), "+f"(d[3]), "+f"(d[4]), "+f"(d[5]), "+f"(d[6]), "+f"(d[7]), "+f"(d[8]), "+f"(d[9]), "+f"(d[10]), "+f"(d[11]), "+f"(d[12]), "+f"(d[13]), "+f"(d[14]), "+f"(d[15]), "+f"(d[16]), "+f"(d[17]), "+f"(d[18]), "+f"(d[19]), "+f"(d[20]), "+f"(d[21]), "+f"(d[22]), "+f"(d[23]), "+f"(d[24]), "+f"(d[25]), "+f"(d[26]), "+f"(d[27]), "+f"(d[28]), "+f"(d[29]), "+f"(d[30]), "+f"(d[31]), "+f"(d[32]), "+f"(d[33]), "+f"(d[34]), "+f"(d[35]), "+f"(d[36]), "+f"(d[37]), "+f"(d[38]), "+f"(d[39]), "+f"(d[40]), "+f"(d[41]), "+f"(d[42]), "+f"(d[43]), "+f"(d[44]), "+f"(d[45]), "+f"(d[46]), "+f"(d[47]), "+f"(d[48]), "+f"(d[49]), "+f"(d[50]), "+f"(d[51]), "+f"(d[52]), "+f"(d[53]), "+f"(d[54]), "+f"(d[55]), "+f"(d[56]), "+f"(d[57]), "+f"(d[58]), "+f"(d[59]), "+f"(d[60]), "+f"(d[61]), "+f"(d[62]), "+f"(d[63])
    : "r"(a0), "r"(a1), "r"(a2), "r"(a3), "l"(descB), "n"(SCALE_D));
}
template <int SCALE_D>
__device__ __forceinline__ void wgmma_rs_n24_tb(float (&d)[12], uint32_t a0, uint32_t a1, uint32_t a2, uint32_t a3, uint64_t descB) {
  asm volatile("wgmma.mma_async.sync.aligned.m64n24k16.f32.bf16.bf16 {%0, %1, %2, %3, %4, %5, %6, %7, %8, %9, %10, %11}, {%12, %13, %14, %15}, %16, %17, 1, 1, 1;\n"
    : "+f"(d[0]), "+f"(d[1]), "+f"(d[2]), "+f"(d[3]), "+f"(d[4]), "+f"(d[5]), "+f"(d[6]), "+f"(d[7]), "+f"(d[8]), "+f"(d[9]), "+f"(d[10]), "+f"(d[11])
    : "r"(a0), "r"(a1), "r"(a2), "r"(a3), "l"(descB), "n"(SCALE_D));
}

constexpr uint32_t DHI_SW128_K = (1024 >> 4) | (1u << 30);
constexpr uint32_t DHI_SW64_MN = (512 >> 4) | (2u << 30);

template <int NC>
__device__ __forceinline__ void store_tile_bf16(const float (&acc)[NC / 2], float scale, uint32_t stage, uint8_t* stage_ptr,
                                                __nv_bfloat16* gdst, int gpitch, int lane) {
  constexpr int PITCH = NC * 2 + 16;
  const uint32_t waddr = stage + ((lane & 7) + ((lane >> 3) & 1) * 8) * PITCH + (lane >> 4) * 16;
#pragma unroll
  for (int j = 0; j < NC / 16; j++) {
    stsm4(waddr + j * 32, pack_bf16(acc[8 * j] * scale, acc[8 * j + 1] * scale), pack_bf16(acc[8 * j + 2] * scale, acc[8 * j + 3] * scale),
          pack_bf16(acc[8 * j + 4] * scale, acc[8 * j + 5] * scale), pack_bf16(acc[8 * j + 6] * scale, acc[8 * j + 7] * scale));
  }
  __syncwarp();
  constexpr int CPR = NC / 8;
#pragma unroll
  for (int i = 0; i < CPR / 2; i++) {
    const int c = i * 32 + lane, r = c / CPR, cc = c % CPR;
    const uint4 v = *reinterpret_cast<const uint4*>(stage_ptr + r * PITCH + cc * 16);
    *reinterpret_cast<uint4*>(gdst + (size_t)r * gpitch + cc * 8) = v;
  }
}

__device__ __forceinline__ void signal_done(unsigned int* flag, int wg, int tid) {
  asm volatile("bar.sync %0, 128;" :: "r"(wg + 1) : "memory");
  if ((tid & 127) == 0) asm volatile("red.release.gpu.global.add.u32 [%0], 1;" :: "l"(flag) : "memory");
}
__device__ __forceinline__ void wait_flags8(const unsigned int* f, unsigned int target) {
  for (int spin = 0; spin < (1 << 26); spin++) {
    unsigned int a, b, c, d, e, g, h, i;
    asm volatile("ld.volatile.global.v4.u32 {%0, %1, %2, %3}, [%4];" : "=r"(a), "=r"(b), "=r"(c), "=r"(d) : "l"(f) : "memory");
    asm volatile("ld.volatile.global.v4.u32 {%0, %1, %2, %3}, [%4];" : "=r"(e), "=r"(g), "=r"(h), "=r"(i) : "l"(f + 4) : "memory");
    if (min(min(min(a, b), min(c, d)), min(min(e, g), min(h, i))) >= target) break;
    __nanosleep(32);
  }
  asm volatile("fence.acq_rel.gpu;" ::: "memory");
  asm volatile("fence.proxy.async;" ::: "memory");
}

#define RP_LD 3
#define RP_ST 7
constexpr int K1_STAGES = 4;
constexpr int K1_A_BYTES = 256 * 128;
constexpr int K1_B_BYTES = 64 * 160 * 2;
constexpr int K1_STAGE = K1_A_BYTES + K1_B_BYTES;
constexpr int K1_SMEM = 5 * K1_A_BYTES + 61440 + 1024;
constexpr int KV_STAGES = 5;
constexpr int KVW_OFF = KV_STAGES * K1_A_BYTES;

__global__ void __launch_bounds__(512, 1)
proj_kernel(const __grid_constant__ CUtensorMap tmX, const __grid_constant__ CUtensorMap tmWq, const __grid_constant__ CUtensorMap tmWqkv,
            const __nv_bfloat16* __restrict__ wk, const __nv_bfloat16* __restrict__ wv, const __nv_bfloat16* __restrict__ gate_w,
            const __nv_bfloat16* __restrict__ woA, const __nv_bfloat16* __restrict__ woB) {
  extern __shared__ uint8_t smem_raw[];
  __shared__ __align__(8) uint64_t bar_full[KV_STAGES], bar_empty[KV_STAGES];
  uint8_t* smem = reinterpret_cast<uint8_t*>((reinterpret_cast<uintptr_t>(smem_raw) + 1023) & ~(uintptr_t)1023);
  const uint32_t sbase = smem_u32(smem);
  const uint32_t dbase = sbase & 0x3FFFFu;
  const int tid = threadIdx.x, warp = tid >> 5, lane = tid & 31;
  const bool is_kv = blockIdx.x >= 128;
  PROF(0, 0);
  if (tid == 32) { prefetch_tmap(&tmX); prefetch_tmap((blockIdx.x & 15) < 4 ? &tmWq : &tmWqkv); }
  if (tid == 0) {
    for (int i = 0; i < KV_STAGES; i++) { mbar_init(smem_u32(&bar_full[i]), 1); mbar_init(smem_u32(&bar_empty[i]), is_kv ? 8 : 16); }
    fence_mbar_init();
  }
  uint2 wa[2][5], wb[2][5]; uint32_t gw[2];
  if (is_kv && tid < 320) {
#pragma unroll
    for (int r = 0; r < 2; r++) {
      const int k = tid + r * 320;
      const uint2* pk = reinterpret_cast<const uint2*>(wk + k * 20);
      const uint2* pv = reinterpret_cast<const uint2*>(wv + k * 20);
#pragma unroll
      for (int i = 0; i < 5; i++) { wa[r][i] = __ldg(pk + i); wb[r][i] = __ldg(pv + i); }
      gw[r] = (uint32_t)__bfloat16_as_ushort(gate_w[k]);
    }
  }
  __syncthreads();
  if (tid == 480 && !is_kv) { g_done[blockIdx.x] = 0u; g_doneL[blockIdx.x] = 0u; }
  pdl_launch();

  if (!is_kv) {
    const int mb = blockIdx.x >> 4, nb = blockIdx.x & 15;
    const CUtensorMap* tw = nb < 4 ? &tmWq : &tmWqkv;
    const int j0 = (nb < 4 ? nb : nb - 4) * 5;
    auto load = [&](int kt) {
      const int s = kt % K1_STAGES;
      const uint32_t fb = smem_u32(&bar_full[s]);
      mbar_expect_tx(fb, K1_STAGE);
      tma_2d(sbase + s * K1_STAGE, &tmX, kt * 64, mb * 256, fb);
      tma_3d(sbase + s * K1_STAGE + K1_A_BYTES, tw, 0, kt * 64, j0, fb);
    };
    if (tid == 0) for (int kt = 0; kt < K1_STAGES; kt++) load(kt);
    __syncwarp();
    uint4 wv2[2];
    const int rq = blockIdx.x * 400 + tid - 112;
    const int rhalf = rq >= 25600, rr = rq - rhalf * 25600, rk = 2 * (rr / 80), rch = rr % 80;
    {
      const int wg = warp >> 2;
      float acc[80];
#pragma unroll
      for (int i = 0; i < 80; i++) acc[i] = 0.f;
      for (int kt = 0; kt < 10; kt++) {
        const int s = kt % K1_STAGES;
        mbar_wait(smem_u32(&bar_full[s]), (kt / K1_STAGES) & 1);
        const uint32_t alo = ((dbase + s * K1_STAGE + wg * 8192) >> 4) | (1u << 16);
        const uint32_t blo = ((dbase + s * K1_STAGE + K1_A_BYTES) >> 4) | ((4096u >> 4) << 16);
        fence_regs(acc);
        wg_fence();
#pragma unroll
        for (int k = 0; k < 4; k++) wgmma_ss_n160_tb(acc, mkd(alo + k * 2, DHI_SW128_K), mkd(blo + k * 64, DHI_SW64_MN));
        wg_commit();
        if (kt == RP_LD && tid >= 112) {
          const uint4* src = reinterpret_cast<const uint4*>((rhalf ? woB : woA) + rk * D_MODEL + rch * 8);
          wv2[0] = __ldg(src); wv2[1] = __ldg(src + D_MODEL / 8);
        }
        if (kt == RP_ST && tid >= 112) {
          uint4* dst = reinterpret_cast<uint4*>(g_wimg + ((rhalf * 8 + rch / 10) * 10 + (rk >> 6)) * 10240 + (rch % 10) * 1024 + (rk & 63) * 16);
          dst[0] = wv2[0]; dst[1] = wv2[1];
        }
        __syncwarp();
        if (kt > 0 && kt - 1 + K1_STAGES < 10) {
          wg_wait<1>();
          const uint32_t eb = smem_u32(&bar_empty[(kt - 1) % K1_STAGES]);
          if (lane == 0) mbar_arrive(eb);
          if (tid == 0) { mbar_wait(eb, ((kt - 1) / K1_STAGES) & 1); load(kt - 1 + K1_STAGES); }
          __syncwarp();
        }
      }
      wg_wait<0>();
      fence_regs(acc);
      PROF(0, 1);
      asm volatile("bar.sync %0, 128;" :: "r"(wg + 1) : "memory");
      const int w4 = warp & 3;
      const uint32_t off = w4 * K1_STAGE + wg * 8192;
      const int row0 = mb * 256 + wg * 64 + w4 * 16;
      if (nb < 4) {
        store_tile_bf16<160>(acc, 0.22360679774997896f * 1.4426950408889634f, sbase + off, smem + off,
                             g_q + (size_t)row0 * D_MODEL + nb * 160, D_MODEL, lane);
      } else {
        store_tile_bf16<160>(acc, 1.0f, sbase + off, smem + off, g_qkv + (size_t)row0 * (3 * D_MODEL) + (nb - 4) * 160, 3 * D_MODEL, lane);
      }
    }
  } else {
    const int cb = blockIdx.x - 128;
    if (warp == 8 && lane == 0) {
      for (int it = 0; it < KV_STAGES; it++) {
        const uint32_t fb = smem_u32(&bar_full[it]);
        mbar_expect_tx(fb, K1_A_BYTES);
        tma_2d(sbase + it * K1_A_BYTES, &tmX, it * 64, cb * 512, fb);
      }
    }
    __syncwarp();
    if (tid < 320) {
#pragma unroll
      for (int r = 0; r < 2; r++) {
        uint4* dst = reinterpret_cast<uint4*>(smem + KVW_OFF + (tid + r * 320) * 16);
        dst[0] = make_uint4(wa[r][0].x, wa[r][0].y, wa[r][1].x, wa[r][1].y);
        dst[640] = make_uint4(wa[r][2].x, wa[r][2].y, wa[r][3].x, wa[r][3].y);
        dst[1280] = make_uint4(wa[r][4].x, wa[r][4].y, 0u, 0u);
        dst[1920] = make_uint4(wb[r][0].x, wb[r][0].y, wb[r][1].x, wb[r][1].y);
        dst[2560] = make_uint4(wb[r][2].x, wb[r][2].y, wb[r][3].x, wb[r][3].y);
        dst[3200] = make_uint4(wb[r][4].x, wb[r][4].y, gw[r], 0u);
      }
    }
    fence_proxy_async();
    asm volatile("bar.sync 1, 512;" ::: "memory");
    PROF(0, 1);
    auto produce = [&](int it0, int it1) {
      for (int it = it0; it < it1; it++) {
        const int s = it % KV_STAGES;
        mbar_wait(smem_u32(&bar_empty[s]), (it / KV_STAGES - 1) & 1);
        const uint32_t fb = smem_u32(&bar_full[s]);
        mbar_expect_tx(fb, K1_A_BYTES);
        tma_2d(sbase + s * K1_A_BYTES, &tmX, (it >= 10 ? it - 10 : it) * 64, cb * 512 + (it >= 10 ? 256 : 0), fb);
      }
    };
    if (tid == 256) produce(KV_STAGES, 15);
    __syncwarp();
    {
      const int pass = warp >> 3, wg = (warp >> 2) & 1, w4 = warp & 3, g = lane >> 2, t = lane & 3;
      if (pass == 1) asm volatile("bar.sync 2, 512;" ::: "memory");
      {
        float acc[2][24];
#pragma unroll
        for (int i = 0; i < 24; i++) { acc[0][i] = 0.f; acc[1][i] = 0.f; }
        for (int kt = 0; kt < 10; kt++) {
          const int it = pass * 10 + kt, s = it % KV_STAGES;
          mbar_wait(smem_u32(&bar_full[s]), (it / KV_STAGES) & 1);
          const uint32_t alo = ((dbase + s * K1_A_BYTES + wg * 16384) >> 4) | (1u << 16);
          const uint32_t blo = ((dbase + KVW_OFF + kt * 1024) >> 4) | ((128u >> 4) << 16);
          fence_regs(acc[0]); fence_regs(acc[1]);
          wg_fence();
#pragma unroll
          for (int k = 0; k < 4; k++) {
            wgmma_ss_n48_tb(acc[0], mkd(alo + k * 2, DHI_SW128_K), mkd(blo + k * 16, 10240u >> 4));
            wgmma_ss_n48_tb(acc[1], mkd(alo + 512 + k * 2, DHI_SW128_K), mkd(blo + k * 16, 10240u >> 4));
          }
          wg_commit();
          if (kt > 0) {
            wg_wait<1>();
            if (lane == 0) mbar_arrive(smem_u32(&bar_empty[(it - 1) % KV_STAGES]));
          }
        }
        wg_wait<0>();
        fence_regs(acc[0]); fence_regs(acc[1]);
        if (lane == 0) mbar_arrive(smem_u32(&bar_empty[(pass * 10 + 9) % KV_STAGES]));
        if (pass == 0) asm volatile("bar.arrive 2, 512;" ::: "memory");
        PROF(0, 2);
        if (tid == 0) produce(15, 20);
        __syncwarp();
        float kmax2 = 0.f, vmax = 0.f;
#pragma unroll
        for (int hh = 0; hh < 4; hh++) {
          const int h = hh & 1;
          const float (&a)[24] = acc[hh >> 1];
          const int key = cb * 512 + pass * 256 + wg * 128 + (hh >> 1) * 64 + w4 * 16 + g + h * 8;
          const int grp = key >> 7, kk = key & 127;
          const bool poly = (TMASK >> (kk >> 3)) & 1;
          uint8_t* gp = g_kvimg + grp * GRP_BYTES;
          const uint32_t k0 = pack_bf16(a[2 * h], a[2 * h + 1]);
          const uint32_t k1 = pack_bf16(a[4 + 2 * h], a[5 + 2 * h]);
          uint32_t k2 = pack_bf16(a[8 + 2 * h], a[9 + 2 * h]);
          float n2 = bf_lo(k0) * bf_lo(k0) + bf_hi(k0) * bf_hi(k0) + bf_lo(k1) * bf_lo(k1) + bf_hi(k1) * bf_hi(k1);
          if (t < 2) {
            n2 += bf_lo(k2) * bf_lo(k2) + bf_hi(k2) * bf_hi(k2);
            k2 = pack_bf16(bf_lo(k2) * 0.5f, bf_hi(k2) * 0.5f);
          } else if (t == 2) k2 = poly ? pack_bf16(24.f, 2.5f) : pack_bf16(0.5f, 0.f);
          else k2 = poly ? pack_bf16(0.5f, 0.f) : 0u;
          *reinterpret_cast<uint32_t*>(gp + kk * 16 + t * 4) = k0;
          *reinterpret_cast<uint32_t*>(gp + PLANE + kk * 16 + t * 4) = k1;
          *reinterpret_cast<uint32_t*>(gp + 2 * PLANE + kk * 16 + t * 4) = k2;
          n2 += __shfl_xor_sync(0xffffffffu, n2, 1);
          n2 += __shfl_xor_sync(0xffffffffu, n2, 2);
          kmax2 = (n2 > kmax2 || n2 != n2) ? n2 : kmax2;
          uint32_t v0 = pack_bf16(a[12 + 2 * h], a[13 + 2 * h]);
          uint32_t v1 = pack_bf16(a[16 + 2 * h], a[17 + 2 * h]);
          uint32_t v2 = pack_bf16(a[20 + 2 * h], a[21 + 2 * h]);
          float vm = fmaxf(fmaxf(fabsf(bf_lo(v0)), fabsf(bf_hi(v0))), fmaxf(fabsf(bf_lo(v1)), fabsf(bf_hi(v1))));
          if (t < 2) vm = fmaxf(vm, fmaxf(fabsf(bf_lo(v2)), fabsf(bf_hi(v2))));
          else if (t == 2) {
            const float z = a[20 + 2 * h];
            g_gate[key] = 1.f / (1.f + __expf(-z));
            v2 = 0x00003F80u;
          } else v2 = 0u;
          vmax = fmaxf(vmax, vm);
          if (poly) { v0 ^= 0x80008000u; v1 ^= 0x80008000u; v2 ^= 0x80008000u; }
          uint8_t* vp = gp + 3 * PLANE + (kk >> 3) * 384 + (kk & 7) * 16 + t * 4;
          *reinterpret_cast<uint32_t*>(vp) = v0;
          *reinterpret_cast<uint32_t*>(vp + 128) = v1;
          *reinterpret_cast<uint32_t*>(vp + 256) = v2;
        }
#pragma unroll
        for (int o = 1; o < 32; o <<= 1) {
          const float a = __shfl_xor_sync(0xffffffffu, kmax2, o);
          kmax2 = (a > kmax2 || a != a) ? a : kmax2;
          vmax = fmaxf(vmax, __shfl_xor_sync(0xffffffffu, vmax, o));
        }
        if (lane == 0) { g_kmax2[cb * 16 + warp] = kmax2; g_vmax[cb * 16 + warp] = vmax; }
      }
    }
  }
}

__device__ __forceinline__ uint32_t ex2_pair_poly(float u0, float u1, uint32_t one2) {
  const uint32_t W = __byte_perm(__float_as_uint(u0), __float_as_uint(u1), 0x6521);
  uint32_t v; asm("lop3.b32 %0, %1, 0x007F007F, %2, 0xEA;" : "=r"(v) : "r"(W), "r"(one2));
  uint32_t L, p;
  asm("fma.rn.bf16x2 %0, %1, %2, %3;" : "=r"(L) : "r"(v), "r"(0x1f961f96u), "r"(0x9fe39fe3u));
  asm("fma.rn.bf16x2 %0, %1, %1, %2;" : "=r"(p) : "r"(L), "r"(0x00f500f5u));
  return W + p;
}
template <int JOFF>
__device__ __forceinline__ void softmax_slow(const float (&S)[32], uint32_t (&P)[16], float (&O)[12], float& m0, float& m1) {
  float a0 = m0, a1 = m1;
#pragma unroll
  for (int j = 0; j < 8; j++) {
    a0 = fmaxf(a0, fmaxf(S[4 * j], S[4 * j + 1]));
    a1 = fmaxf(a1, fmaxf(S[4 * j + 2], S[4 * j + 3]));
  }
  a0 = fmaxf(a0, __shfl_xor_sync(0xffffffffu, a0, 1)); a0 = fmaxf(a0, __shfl_xor_sync(0xffffffffu, a0, 2));
  a1 = fmaxf(a1, __shfl_xor_sync(0xffffffffu, a1, 1)); a1 = fmaxf(a1, __shfl_xor_sync(0xffffffffu, a1, 2));
  const float c0 = ex2(m0 - a0), c1 = ex2(m1 - a1);
  m0 = a0; m1 = a1;
#pragma unroll
  for (int j = 0; j < 3; j++) { O[4 * j] *= c0; O[4 * j + 1] *= c0; O[4 * j + 2] *= c1; O[4 * j + 3] *= c1; }
#pragma unroll
  for (int i = 0; i < 16; i++) {
    const float m = (i & 1) ? a1 : a0;
    const uint32_t p = pack_bf16(ex2(S[2 * i] - m), ex2(S[2 * i + 1] - m));
    P[i] = ((TMASK >> (JOFF + i / 2)) & 1) ? (p ^ 0x80008000u) : p;
  }
}
constexpr uint32_t DHI_KV = 128 >> 4;
__device__ __forceinline__ void issue_qk(float (&S)[32], const uint32_t (&q)[8], uint64_t base) {
  wgmma_rs_n64<0>(S, q[0], q[1], q[2], q[3], base + (uint64_t)((PLANE >> 4) << 16));
  wgmma_rs_n64<1>(S, q[4], q[5], q[6], q[7], base + (uint64_t)(2 * PLANE >> 4));
}
__device__ __forceinline__ void issue_pv(float (&O)[12], const uint32_t (&P)[16], uint64_t vbase) {
#pragma unroll
  for (int kk = 0; kk < 4; kk++)
    wgmma_rs_n24_tb<1>(O, P[4 * kk], P[4 * kk + 1], P[4 * kk + 2], P[4 * kk + 3], vbase + (uint64_t)(kk * (768 >> 4)));
}

constexpr uint32_t VOFF = ((3 * PLANE) >> 4) + ((384u >> 4) << 16);
constexpr int KVR = 4;
constexpr int OFF_W = KVR * GRP_BYTES;
constexpr int OFF_X = OFF_W + 10 * 10240;
constexpr int OFF_BAR = OFF_X + 4 * 16384;
constexpr int K2_SMEM = OFF_BAR + 512 + 1024;
constexpr int TSL = 7;
constexpr int BAR_KV = 0, BAR_W = 4, BAR_TA = 5, BAR_TE = 12, BAR_OWN = 19, BAR_L = 20, CNT_KV = 21, BAR_WA = 23, BAR_WF = 33, CNT_TK = 43;
constexpr int NSTEP = 2 * NGRP;

__device__ __forceinline__ void kv_load(uint32_t sbase, int step) {
  const uint32_t bar = sbase + OFF_BAR + (BAR_KV + (step & (KVR - 1))) * 8;
  mbar_expect_tx(bar, GRP_BYTES);
  bulk_g2s(sbase + (step & (KVR - 1)) * GRP_BYTES, g_kvimg + (step & (NGRP - 1)) * GRP_BYTES, GRP_BYTES, bar);
}
__device__ __forceinline__ void kv_release(uint32_t sbase, int step, bool elected) {
  if (elected && step + KVR < NSTEP) {
    uint32_t old;
    asm volatile("atom.acq_rel.cta.shared::cta.inc.u32 %0, [%1], 3;" : "=r"(old) : "r"(sbase + OFF_BAR + CNT_KV * 8 + (step & (KVR - 1)) * 4) : "memory");
    if (old == 3u) kv_load(sbase, step + KVR);
  }
  __syncwarp();
}
__device__ __forceinline__ void kv_wait(uint32_t sbase, int step) {
  mbar_wait(sbase + OFF_BAR + (BAR_KV + (step & (KVR - 1))) * 8, (step / KVR) & 1);
}

__device__ __forceinline__ uint32_t kv_release_begin(uint32_t sbase, int slot, bool doit) {
  uint32_t old = 0;
  asm volatile("{\n.reg .pred p;\nsetp.ne.u32 p, %2, 0;\n@p atom.relaxed.cta.shared::cta.inc.u32 %0, [%1], 3;\n}\n"
               : "+r"(old) : "r"(sbase + OFF_BAR + CNT_KV * 8 + slot * 4), "r"((uint32_t)doit) : "memory");
  return old;
}
template <int H>
__device__ __forceinline__ void softmax_half(const float (&S)[64], uint32_t (&P)[16], uint32_t one2) {
#pragma unroll
  for (int i = 0; i < 16; i++) {
    if ((TMASK >> (8 * H + i / 2)) & 1) P[i] = ex2_pair_poly(S[32 * H + 2 * i], S[32 * H + 2 * i + 1], one2);
    else P[i] = pack_bf16(ex2(S[32 * H + 2 * i]), ex2(S[32 * H + 2 * i + 1]));
  }
}
__device__ __forceinline__ void attn_fast(const uint32_t (&q)[8], float (&O)[12], uint32_t sbase, int step0, int nsteps, bool elected, uint32_t one2) {
  uint64_t kb0 = mkd((sbase & 0x3FFFFu) >> 4, DHI_KV);
  asm volatile("" : "+l"(kb0));
#pragma unroll 1
  for (int step4 = step0; step4 < step0 + nsteps; step4 += KVR) {
#pragma unroll
    for (int j = 0; j < KVR; j++) {
      const int step = step4 + j;
      const uint64_t kb = kb0 + (uint64_t)(j * (GRP_BYTES >> 4));
      float S[64]; uint32_t PA[16], PB[16];
#pragma unroll
      for (int i = 0; i < 64; i++) S[i] = 0.f;
      mbar_wait(sbase + OFF_BAR + (BAR_KV + j) * 8, (step / KVR) & 1);
      fence_regs(S);
      wg_fence();
      wgmma_rs_n128<0>(S, q[0], q[1], q[2], q[3], kb + (uint64_t)((PLANE >> 4) << 16));
      wgmma_rs_n128<1>(S, q[4], q[5], q[6], q[7], kb + (uint64_t)(2 * PLANE >> 4));
      wg_commit();
      const uint32_t old = kv_release_begin(sbase, (j + KVR - 1) & (KVR - 1), elected && step > step0 && step - 1 + KVR < NSTEP);
      wg_wait<0>();
      fence_regs(S);
      softmax_half<0>(S, PA, one2);
      fence_regs(PA); fence_regs(O);
      wg_fence();
      issue_pv(O, PA, kb + VOFF);
      wg_commit();
      softmax_half<1>(S, PB, one2);
      fence_regs(PB);
      wg_fence();
      issue_pv(O, PB, kb + VOFF + 4 * (768 >> 4));
      wg_commit();
      if (old == 3u) kv_load(sbase, step - 1 + KVR);
      wg_wait<0>();
      fence_regs(PA); fence_regs(PB); fence_regs(O);
    }
  }
  kv_release(sbase, step0 + nsteps - 1, elected);
}
template <int H>
__device__ __forceinline__ void slow_step(const uint32_t (&q)[8], float (&O)[12], uint64_t kb, float& m0, float& m1) {
  float S[32]; uint32_t P[16];
#pragma unroll
  for (int i = 0; i < 32; i++) S[i] = 0.f;
  fence_regs(S);
  wg_fence();
  issue_qk(S, q, kb + 64 * H);
  wg_commit();
  wg_wait<0>();
  fence_regs(S);
  softmax_slow<8 * H>(S, P, O, m0, m1);
  fence_regs(P); fence_regs(O);
  wg_fence();
  issue_pv(O, P, kb + VOFF + H * 4 * (768 >> 4));
  wg_commit();
  wg_wait<0>();
  fence_regs(O); fence_regs(P);
}
__device__ __forceinline__ void attn_slow(const uint32_t (&q)[8], float (&O)[12], uint32_t sbase, int step0, int nsteps, bool elected, float& m0, float& m1) {
#pragma unroll 1
  for (int step = step0; step < step0 + nsteps; step++) {
    kv_wait(sbase, step);
    const uint64_t kb = mkd(((sbase & 0x3FFFFu) >> 4) + (step & (KVR - 1)) * (GRP_BYTES >> 4), DHI_KV);
    slow_step<0>(q, O, kb, m0, m1);
    slow_step<1>(q, O, kb, m0, m1);
    kv_release(sbase, step, elected);
  }
}

__device__ __forceinline__ void softmax8(float (&sc)[8], float scale) {
  float mx = sc[0];
#pragma unroll
  for (int w = 1; w < 8; w++) mx = fmaxf(mx, sc[w]);
  float l = 0.f;
#pragma unroll
  for (int w = 0; w < 8; w++) { sc[w] = ex2(sc[w] - mx); l += sc[w]; }
  const float r = __fdividef(scale, l);
#pragma unroll
  for (int w = 0; w < 8; w++) sc[w] *= r;
}
#define LEV(wg) 1
constexpr int LBOX = 32 * 320;
__device__ __forceinline__ uint2 lds64(uint32_t a) {
  uint2 v; asm volatile("ld.shared.v2.u32 {%0, %1}, [%2];" : "=r"(v.x), "=r"(v.y) : "r"(a)); return v;
}
__device__ __forceinline__ void local_attn(uint32_t stage, int t0, int i, int lane) {
  constexpr float SC = 0.22360679774997896f * 1.4426950408889634f, NEG = -1e9f * 1.4426950408889634f;
  const uint32_t base = stage + (lane >> 3) * LBOX + (lane & 7) * 40 + (i + 14 + ((lane >> 3) & 1)) * 320;
  const int t = t0 + i;
  float sc[8];
#pragma unroll
  for (int w = 0; w < 8; w++) sc[w] = 0.f;
#pragma unroll 1
  for (int c = 0; c < 5; c++) {
    const uint2 qv = lds64(base + c * 8);
    const float q0 = bf_lo(qv.x), q1 = bf_hi(qv.x), q2 = bf_lo(qv.y), q3 = bf_hi(qv.y);
#pragma unroll
    for (int w = 0; w < 8; w++) {
      const uint2 k = lds64(base + c * 8 + 4 * LBOX - w * 640);
      sc[w] = fmaf(q0, bf_lo(k.x), sc[w]); sc[w] = fmaf(q1, bf_hi(k.x), sc[w]);
      sc[w] = fmaf(q2, bf_lo(k.y), sc[w]); sc[w] = fmaf(q3, bf_hi(k.y), sc[w]);
    }
  }
#pragma unroll
  for (int w = 0; w < 8; w++) sc[w] = t - 2 * w >= 0 ? sc[w] * SC : NEG;
  softmax8(sc, 1.f - g_gate[t]);
  uint2* dst = reinterpret_cast<uint2*>(g_a2 + (size_t)t * (2 * D_MODEL) + D_MODEL + lane * DH);
#pragma unroll 1
  for (int c = 0; c < 5; c++) {
    float o0 = 0.f, o1 = 0.f, o2 = 0.f, o3 = 0.f;
#pragma unroll
    for (int w = 0; w < 8; w++) {
      const uint2 v = lds64(base + c * 8 + 8 * LBOX - w * 640);
      o0 = fmaf(sc[w], bf_lo(v.x), o0); o1 = fmaf(sc[w], bf_hi(v.x), o1);
      o2 = fmaf(sc[w], bf_lo(v.y), o2); o3 = fmaf(sc[w], bf_hi(v.y), o3);
    }
    dst[c] = make_uint2(pack_bf16(o0, o1), pack_bf16(o2, o3));
  }
}
__device__ __forceinline__ uint32_t ta_slot(int i) { return i < 4 ? OFF_X + i * 16384 : (i - 4) * 16384; }

__global__ void __launch_bounds__(640, 1)
attn_kernel(const __grid_constant__ CUtensorMap tmA2, const __grid_constant__ CUtensorMap tmL, __nv_bfloat16* __restrict__ out, uint32_t one2) {
  extern __shared__ uint8_t smem_raw[];
  uint8_t* smem = reinterpret_cast<uint8_t*>((reinterpret_cast<uintptr_t>(smem_raw) + 1023) & ~(uintptr_t)1023);
  const uint32_t sbase = smem_u32(smem);
  const uint32_t dbase = sbase & 0x3FFFFu;
  const uint32_t bars = sbase + OFF_BAR;
  const int tid = threadIdx.x, wg = tid >> 7, warp = (tid >> 5) & 3, lane = tid & 31, g = lane >> 2, t = lane & 3;
  const int mb = blockIdx.x >> 3, nb = blockIdx.x & 7;
  const bool elected = (tid & 127) == 0;
  if (tid == 512) { prefetch_tmap(&tmL); prefetch_tmap(&tmA2); }
  if (tid == 0) {
    for (int i = 0; i < BAR_TE; i++) mbar_init(bars + i * 8, 1);
    for (int i = BAR_TE; i < BAR_TE + TSL; i++) mbar_init(bars + i * 8, 8);
    mbar_init(bars + BAR_OWN * 8, 4);
    mbar_init(bars + BAR_L * 8, 1);
    for (int i = 0; i < 10; i++) { mbar_init(bars + (BAR_WA + i) * 8, 1); mbar_init(bars + (BAR_WF + i) * 8, 8); }
    for (int i = 0; i < 4; i++) *reinterpret_cast<uint32_t*>(smem + OFF_BAR + CNT_KV * 8 + i * 4) = 0u;
    *reinterpret_cast<uint32_t*>(smem + OFF_BAR + CNT_TK * 8) = 0u;
    fence_mbar_init();
  }
  __syncthreads();
  auto tail_load = [&](int i) {
    const uint32_t fb = bars + (BAR_TA + i % TSL) * 8;
    mbar_expect_tx(fb, 16384);
    tma_2d(sbase + ta_slot(i % TSL), &tmA2, i < 10 ? D_MODEL + i * 64 : (i - 10) * 64, mb * 128, fb);
  };
  if (wg == 4) {
    asm volatile("setmaxnreg.dec.sync.aligned.u32 32;");
    pdl_wait();
    if (tid == 512) {
      for (int j = 0; j < KVR; j++) kv_load(sbase, j);
      mbar_expect_tx(bars + BAR_L * 8, 12 * LBOX);
      for (int i = 0; i < 12; i++) tma_2d(sbase + OFF_W + i * LBOX, &tmL, i * 160, blockIdx.x * 16 - 14 - (i & 1), bars + BAR_L * 8);
    }
    __syncwarp();
    mbar_wait(bars + BAR_L * 8, 0);
#pragma unroll 1
    for (int i = 0; i < 4; i++) local_attn(sbase + OFF_W, blockIdx.x * 16, warp * 4 + i, lane);
    signal_done(&g_doneL[blockIdx.x], wg, tid);
    if (tid == 512) {
      PROF2(0, 2);
      fence_proxy_async();
      mbar_expect_tx(bars + BAR_W * 8, 10 * 10240);
      for (int i = 0; i < 5; i++) bulk_g2s(sbase + OFF_W + i * 20480, g_wimg + ((8 + nb) * 10) * 10240 + i * 20480, 20480, bars + BAR_W * 8);
      wait_flags8(&g_doneL[mb * 8], 1u);
      for (int i = 0; i < 4; i++) tail_load(i);
      mbar_wait(bars + BAR_OWN * 8, 0);
      for (int i = 4; i < 20; i++) {
        if (i >= TSL) mbar_wait(bars + (BAR_TE + i % TSL) * 8, (i / TSL - 1) & 1);
        if (i == 10) { wait_flags8(&g_done[mb * 8], 1u); PROF2(2, 0); }
        tail_load(i);
      }
    } else if (tid == 576) {
      mbar_wait(bars + BAR_OWN * 8, 0);
      asm volatile("red.release.gpu.global.add.u32 [%0], 1;" :: "l"(&g_done[blockIdx.x]) : "memory");
    } else if (tid == 544) {
      for (int kt = 0; kt < 10; kt++) {
        mbar_wait(bars + (BAR_WF + kt) * 8, 0);
        mbar_expect_tx(bars + (BAR_WA + kt) * 8, 10240);
        bulk_g2s(sbase + OFF_W + kt * 10240, g_wimg + (nb * 10 + kt) * 10240, 10240, bars + (BAR_WA + kt) * 8);
      }
    }
    return;
  }
  asm volatile("setmaxnreg.inc.sync.aligned.u32 112;");
  pdl_wait();
  PROF(1, 1);
  uint32_t q[8], q2[6];
  const int rowA = (blockIdx.x * 8 + wg) * 64 + warp * 16 + g;
  {
    const uint32_t* r0 = reinterpret_cast<const uint32_t*>(g_q + (size_t)rowA * DH);
    const uint32_t* r1 = r0 + 8 * (DH / 2);
    const uint32_t* s0 = r0 + 256 * (DH / 2);
    const uint32_t* s1 = s0 + 8 * (DH / 2);
    q[0] = r0[t]; q[1] = r1[t]; q[2] = r0[t + 4]; q[3] = r1[t + 4];
    q[4] = t < 2 ? r0[8 + t] : 0u;
    q[5] = t < 2 ? r1[8 + t] : 0u;
    q2[0] = s0[t]; q2[1] = s1[t]; q2[2] = s0[t + 4]; q2[3] = s1[t + 4];
    q2[4] = t < 2 ? s0[8 + t] : 0u;
    q2[5] = t < 2 ? s1[8 + t] : 0u;
  }
  float kmax2 = 0.f, vmax = 0.f;
#pragma unroll
  for (int i = 0; i < 2; i++) {
    const float a = g_kmax2[lane + 32 * i];
    kmax2 = (a > kmax2 || a != a) ? a : kmax2;
    vmax = fmaxf(vmax, g_vmax[lane + 32 * i]);
  }
#pragma unroll
  for (int o = 1; o < 32; o <<= 1) {
    const float a = __shfl_xor_sync(0xffffffffu, kmax2, o);
    kmax2 = (a > kmax2 || a != a) ? a : kmax2;
    vmax = fmaxf(vmax, __shfl_xor_sync(0xffffffffu, vmax, o));
  }
  const float qlim = (vmax >= 0.00390625f && vmax <= 256.f) ? 9025.f / kmax2 : -1.f;
  PROF(1, 2);
#pragma unroll 1
  for (int it = 0; it < 2; it++) {
    const int row0 = rowA + it * 256;
    if (it == 1) {
#pragma unroll
      for (int i = 0; i < 6; i++) q[i] = q2[i];
    }
    float n0 = bf_lo(q[0]) * bf_lo(q[0]) + bf_hi(q[0]) * bf_hi(q[0]) + bf_lo(q[2]) * bf_lo(q[2]) + bf_hi(q[2]) * bf_hi(q[2]) +
               bf_lo(q[4]) * bf_lo(q[4]) + bf_hi(q[4]) * bf_hi(q[4]);
    float n1 = bf_lo(q[1]) * bf_lo(q[1]) + bf_hi(q[1]) * bf_hi(q[1]) + bf_lo(q[3]) * bf_lo(q[3]) + bf_hi(q[3]) * bf_hi(q[3]) +
               bf_lo(q[5]) * bf_lo(q[5]) + bf_hi(q[5]) * bf_hi(q[5]);
    n0 += __shfl_xor_sync(0xffffffffu, n0, 1); n0 += __shfl_xor_sync(0xffffffffu, n0, 2);
    n1 += __shfl_xor_sync(0xffffffffu, n1, 1); n1 += __shfl_xor_sync(0xffffffffu, n1, 2);
    const bool safe = (n0 <= qlim) && (n1 <= qlim);
    uint32_t unsafe_any;
    asm volatile("{\n.reg .pred p, r;\nsetp.eq.u32 p, %1, 0;\nbarrier.cta.red.or.pred r, %2, 128, p;\nselp.u32 %0, 1, 0, r;\n}\n"
                 : "=r"(unsafe_any) : "r"((uint32_t)safe), "r"(wg + 1) : "memory");
    float O[12];
#pragma unroll
    for (int i = 0; i < 12; i++) O[i] = 0.f;
    if (!unsafe_any && t >= 2) { q[4] = q[5] = (t == 2) ? 0x3F804100u : 0x00003B80u; }
    q[6] = q[4]; q[7] = q[5];
    fence_regs(q);
    float m0 = -INFINITY, m1 = -INFINITY;
    if (!unsafe_any) attn_fast(q, O, sbase, it * NGRP, NGRP, elected, one2);
    else attn_slow(q, O, sbase, it * NGRP, NGRP, elected, m0, m1);
    const float l0 = __shfl_sync(0xffffffffu, O[8], (lane & ~3) | 2);
    const float l1 = __shfl_sync(0xffffffffu, O[10], (lane & ~3) | 2);
    const int tok = row0 >> 5;
    const float gt = g_gate[tok];
    const float i0 = gt / l0, i1 = gt / l1;
    uint32_t* o0 = reinterpret_cast<uint32_t*>(g_a2 + (size_t)tok * (2 * D_MODEL) + (row0 & 31) * DH);
    uint32_t* o1 = o0 + 8 * (DH / 2);
    o0[t] = pack_bf16(O[0] * i0, O[1] * i0); o1[t] = pack_bf16(O[2] * i1, O[3] * i1);
    o0[t + 4] = pack_bf16(O[4] * i0, O[5] * i0); o1[t + 4] = pack_bf16(O[6] * i1, O[7] * i1);
    if (t < 2) { o0[t + 8] = pack_bf16(O[8] * i0, O[9] * i0); o1[t + 8] = pack_bf16(O[10] * i1, O[11] * i1); }
  }
  uint32_t* ticket = reinterpret_cast<uint32_t*>(smem + OFF_BAR + CNT_TK * 8);
  if (elected) ticket[1 + wg] = atomicAdd(ticket, 1u);
  asm volatile("bar.sync %0, 128;" :: "r"(wg + 1) : "memory");
  if (elected) mbar_arrive(bars + BAR_OWN * 8);
  const int mt = ticket[1 + wg];
  PROF(1, 3);
  if (mt < 2) {
    float acc[40];
#pragma unroll
    for (int i = 0; i < 40; i++) acc[i] = 0.f;
    mbar_wait(bars + BAR_W * 8, 0);
    int sl = 0, ph = 0;
#pragma unroll 1
    for (int i = 0; i < 20; i++) {
      mbar_wait(bars + (BAR_TA + sl) * 8, ph);
      if (i >= 10) mbar_wait(bars + (BAR_WA + i - 10) * 8, 0);
      const uint32_t alo = ((dbase + ta_slot(sl) + mt * 8192) >> 4) | (1u << 16);
      const uint32_t blo = ((dbase + OFF_W + (i >= 10 ? i - 10 : i) * 10240) >> 4) | ((128u >> 4) << 16);
      fence_regs(acc);
      wg_fence();
#pragma unroll
      for (int k = 0; k < 4; k++) wgmma_ss_n80_tb(acc, mkd(alo + k * 2, DHI_SW128_K), mkd(blo + k * 16, 1024u >> 4));
      wg_commit();
      if (i > 0) {
        wg_wait<1>();
        if (lane == 0) mbar_arrive(bars + (BAR_TE + (sl == 0 ? TSL - 1 : sl - 1)) * 8);
        if (lane == 1 && i <= 10) mbar_arrive(bars + (BAR_WF + i - 1) * 8);
      }
      if (++sl == TSL) { sl = 0; ph ^= 1; }
    }
    wg_wait<0>();
    fence_regs(acc);
    asm volatile("bar.sync %0, 128;" :: "r"(wg + 1) : "memory");
    const uint32_t so = ta_slot(warp) + mt * 8192;
    const int row0 = mb * 128 + mt * 64 + warp * 16;
    store_tile_bf16<80>(acc, 1.0f, sbase + so, smem + so, out + (size_t)row0 * D_MODEL + nb * 80, D_MODEL, lane);
  }
}

typedef CUresult (*EncodeFn)(CUtensorMap*, CUtensorMapDataType, cuuint32_t, void*, const cuuint64_t*, const cuuint64_t*,
                             const cuuint32_t*, const cuuint32_t*, CUtensorMapInterleave, CUtensorMapSwizzle,
                             CUtensorMapL2promotion, CUtensorMapFloatOOBfill);

void make_map(EncodeFn fn, CUtensorMap* tm, const void* ptr, int rank, const cuuint64_t* dims, const cuuint64_t* strides,
              const cuuint32_t* box, CUtensorMapSwizzle sw) {
  const cuuint32_t es[3] = {1, 1, 1};
  fn(tm, CU_TENSOR_MAP_DATA_TYPE_BFLOAT16, rank, const_cast<void*>(ptr), dims, strides, box, es, CU_TENSOR_MAP_INTERLEAVE_NONE, sw,
     CU_TENSOR_MAP_L2_PROMOTION_L2_256B, CU_TENSOR_MAP_FLOAT_OOB_FILL_NONE);
}
void map_a(EncodeFn fn, CUtensorMap* tm, const void* p, int rows, int cols, int box_rows) {
  const cuuint64_t dims[2] = {(cuuint64_t)cols, (cuuint64_t)rows};
  const cuuint64_t str[1] = {(cuuint64_t)cols * 2};
  const cuuint32_t box[2] = {64, (cuuint32_t)box_rows};
  make_map(fn, tm, p, 2, dims, str, box, CU_TENSOR_MAP_SWIZZLE_128B);
}
void map_w(EncodeFn fn, CUtensorMap* tm, const void* p, int K, int N, int atom, CUtensorMapSwizzle sw) {
  const cuuint64_t dims[3] = {(cuuint64_t)atom, (cuuint64_t)K, (cuuint64_t)(N / atom)};
  const cuuint64_t str[2] = {(cuuint64_t)N * 2, (cuuint64_t)atom * 2};
  const cuuint32_t box[3] = {(cuuint32_t)atom, 64, 5};
  make_map(fn, tm, p, 3, dims, str, box, sw);
}

template <typename... KArgs, typename... Args>
void launch(void (*kern)(KArgs...), int grid, int block, int smem, bool pdl, Args... args) {
  cudaLaunchConfig_t cfg = {};
  cfg.gridDim = dim3(grid); cfg.blockDim = dim3(block); cfg.dynamicSmemBytes = smem; cfg.stream = cudaStreamPerThread;
  cudaLaunchAttribute at[1];
  at[0].id = cudaLaunchAttributeProgrammaticStreamSerialization;
  at[0].val.programmaticStreamSerializationAllowed = 1;
  cfg.attrs = at; cfg.numAttrs = pdl ? 1 : 0;
  cudaLaunchKernelEx(&cfg, kern, KArgs(args)...);
}

}

extern "C" void kernel_launch(void* const* d_in, const int* in_sizes, int n_in, void* d_out, int out_size) {
  (void)in_sizes; (void)n_in; (void)out_size;
  const __nv_bfloat16* x = (const __nv_bfloat16*)d_in[0];
  const __nv_bfloat16* wq = (const __nv_bfloat16*)d_in[1];
  const __nv_bfloat16* wk = (const __nv_bfloat16*)d_in[2];
  const __nv_bfloat16* wv = (const __nv_bfloat16*)d_in[3];
  const __nv_bfloat16* woA = (const __nv_bfloat16*)d_in[4];
  const __nv_bfloat16* wqkv = (const __nv_bfloat16*)d_in[6];
  const __nv_bfloat16* woB = (const __nv_bfloat16*)d_in[7];
  const __nv_bfloat16* gate_w = (const __nv_bfloat16*)d_in[8];

  static EncodeFn enc = nullptr;
  static void* a2_ptr = nullptr;
  static void* qkv_ptr = nullptr;
  if (!enc) {
    void* fp = nullptr;
    cudaDriverEntryPointQueryResult qr;
    cudaGetDriverEntryPoint("cuTensorMapEncodeTiled", &fp, cudaEnableDefault, &qr);
    enc = (EncodeFn)fp;
    cudaGetSymbolAddress(&a2_ptr, g_a2);
    cudaGetSymbolAddress(&qkv_ptr, g_qkv);
    cudaFuncSetAttribute(proj_kernel, cudaFuncAttributeMaxDynamicSharedMemorySize, K1_SMEM);
    cudaFuncSetAttribute(attn_kernel, cudaFuncAttributeMaxDynamicSharedMemorySize, K2_SMEM);
  }
  CUtensorMap tmX, tmWq, tmWqkv, tmA2, tmL;
  {
    const cuuint64_t dims[2] = {3 * D_MODEL, S_LEN};
    const cuuint64_t str[1] = {3 * D_MODEL * 2};
    const cuuint32_t box[2] = {160, 32};
    make_map(enc, &tmL, qkv_ptr, 2, dims, str, box, CU_TENSOR_MAP_SWIZZLE_NONE);
  }
  map_a(enc, &tmX, x, S_LEN, D_MODEL, 256);
  map_w(enc, &tmWq, wq, D_MODEL, D_MODEL, 32, CU_TENSOR_MAP_SWIZZLE_64B);
  map_w(enc, &tmWqkv, wqkv, D_MODEL, 3 * D_MODEL, 32, CU_TENSOR_MAP_SWIZZLE_64B);
  map_a(enc, &tmA2, a2_ptr, S_LEN, 2 * D_MODEL, 128);

  launch(proj_kernel, 132, 512, K1_SMEM, false, tmX, tmWq, tmWqkv, wk, wv, gate_w, woA, woB);
  launch(attn_kernel, 128, 640, K2_SMEM, true, tmA2, tmL, (__nv_bfloat16*)d_out, 0x3F803F80u);
}
```

```cpp
#include <cuda_runtime.h>
#include <cuda_bf16.h>
#include <cuda.h>
#include <stdint.h>

namespace {

constexpr int S_LEN = 2048, D_MODEL = 640, DH = 20;

constexpr int GRP = 128;
constexpr int PLANE = GRP * 16;
constexpr int GRP_BYTES = GRP * 16 * 6;
constexpr int NGRP = S_LEN / GRP;
#define TMASKV 0x6DB6u
constexpr uint32_t TMASK = TMASKV;

__device__ __align__(1024) __nv_bfloat16 g_q[S_LEN * D_MODEL];
__device__ __align__(1024) __nv_bfloat16 g_qkv[S_LEN * 3 * D_MODEL];
__device__ __align__(1024) __nv_bfloat16 g_a2[S_LEN * 2 * D_MODEL];
__device__ __align__(1024) uint8_t g_kvimg[NGRP * GRP_BYTES];
__device__ __align__(1024) uint8_t g_wimg[2 * 8 * 10 * 10240];
__device__ float g_gate[S_LEN];
__device__ float g_kmax2[64];
__device__ float g_vmax[64];
__device__ __align__(32) unsigned int g_doneL[128];
__device__ __align__(32) unsigned int g_done[128];

#define PROF(k, slot)
#define PROF2(k, slot)
__device__ __forceinline__ uint32_t smem_u32(const void* p) { return (uint32_t)__cvta_generic_to_shared(p); }
__device__ __forceinline__ uint64_t mkd(uint32_t lo, uint32_t hi) {
  uint64_t d; asm("mov.b64 %0, {%1, %2};" : "=l"(d) : "r"(lo), "r"(hi)); return d;
}
__device__ __forceinline__ void wg_fence() { asm volatile("wgmma.fence.sync.aligned;" ::: "memory"); }
__device__ __forceinline__ void wg_commit() { asm volatile("wgmma.commit_group.sync.aligned;" ::: "memory"); }
template <int N> __device__ __forceinline__ void wg_wait() { asm volatile("wgmma.wait_group.sync.aligned %0;" :: "n"(N) : "memory"); }
template <int N> __device__ __forceinline__ void fence_regs(float (&d)[N]) {
#pragma unroll
  for (int i = 0; i < N; i++) asm volatile("" : "+f"(d[i]) :: "memory");
}
template <int N> __device__ __forceinline__ void fence_regs(uint32_t (&d)[N]) {
#pragma unroll
  for (int i = 0; i < N; i++) asm volatile("" : "+r"(d[i]) :: "memory");
}
__device__ __forceinline__ void mbar_init(uint32_t bar, uint32_t cnt) { asm volatile("mbarrier.init.shared::cta.b64 [%0], %1;" :: "r"(bar), "r"(cnt)); }
__device__ __forceinline__ void mbar_expect_tx(uint32_t bar, uint32_t bytes) {
  asm volatile("mbarrier.arrive.expect_tx.shared::cta.b64 _, [%0], %1;" :: "r"(bar), "r"(bytes) : "memory");
}
__device__ __forceinline__ void mbar_arrive(uint32_t bar) { asm volatile("mbarrier.arrive.shared::cta.b64 _, [%0];" :: "r"(bar) : "memory"); }
#define WAIT_HINT 20000u
__device__ __forceinline__ void mbar_wait(uint32_t bar, uint32_t parity) {
  asm volatile("{\n.reg .pred p;\nWAIT_%=:\nmbarrier.try_wait.parity.shared::cta.b64 p, [%0], %1, %2;\n@p bra DONE_%=;\nbra WAIT_%=;\nDONE_%=:\n}\n"
               :: "r"(bar), "r"(parity), "r"(WAIT_HINT) : "memory");
}
__device__ __forceinline__ void fence_mbar_init() { asm volatile("fence.mbarrier_init.release.cluster;" ::: "memory"); }
__device__ __forceinline__ void fence_proxy_async() { asm volatile("fence.proxy.async.shared::cta;" ::: "memory"); }
__device__ __forceinline__ void bulk_g2s(uint32_t dst, const void* src, uint32_t bytes, uint32_t bar) {
  asm volatile("cp.async.bulk.shared::cluster.global.mbarrier::complete_tx::bytes [%0], [%1], %2, [%3];"
               :: "r"(dst), "l"(src), "r"(bytes), "r"(bar) : "memory");
}
__device__ __forceinline__ void tma_2d(uint32_t dst, const CUtensorMap* tm, int c0, int c1, uint32_t bar) {
  asm volatile("cp.async.bulk.tensor.2d.shared::cluster.global.mbarrier::complete_tx::bytes [%0], [%1, {%3, %4}], [%2];"
               :: "r"(dst), "l"((uint64_t)tm), "r"(bar), "r"(c0), "r"(c1) : "memory");
}
__device__ __forceinline__ void tma_3d(uint32_t dst, const CUtensorMap* tm, int c0, int c1, int c2, uint32_t bar) {
  asm volatile("cp.async.bulk.tensor.3d.shared::cluster.global.mbarrier::complete_tx::bytes [%0], [%1, {%3, %4, %5}], [%2];"
               :: "r"(dst), "l"((uint64_t)tm), "r"(bar), "r"(c0), "r"(c1), "r"(c2) : "memory");
}
__device__ __forceinline__ void prefetch_tmap(const CUtensorMap* tm) { asm volatile("prefetch.tensormap [%0];" :: "l"((uint64_t)tm) : "memory"); }
__device__ __forceinline__ void pdl_wait() { asm volatile("griddepcontrol.wait;" ::: "memory"); }
__device__ __forceinline__ void pdl_launch() { asm volatile("griddepcontrol.launch_dependents;" ::: "memory"); }
__device__ __forceinline__ float ex2(float x) { float y; asm("ex2.approx.ftz.f32 %0, %1;" : "=f"(y) : "f"(x)); return y; }
__device__ __forceinline__ uint32_t pack_bf16(float lo, float hi) {
  uint32_t r; asm("cvt.rn.bf16x2.f32 %0, %1, %2;" : "=r"(r) : "f"(hi), "f"(lo)); return r;
}
__device__ __forceinline__ float bf_lo(uint32_t x) { return __uint_as_float(x << 16); }
__device__ __forceinline__ float bf_hi(uint32_t x) { return __uint_as_float(x & 0xffff0000u); }
__device__ __forceinline__ void stsm4(uint32_t addr, uint32_t r0, uint32_t r1, uint32_t r2, uint32_t r3) {
  asm volatile("stmatrix.sync.aligned.m8n8.x4.shared.b16 [%0], {%1, %2, %3, %4};" :: "r"(addr), "r"(r0), "r"(r1), "r"(r2), "r"(r3) : "memory");
}

__device__ __forceinline__ void wgmma_ss_n160_tb(float (&d)[80], uint64_t descA, uint64_t descB) {
  asm volatile("wgmma.mma_async.sync.aligned.m64n160k16.f32.bf16.bf16 {%0, %1, %2, %3, %4, %5, %6, %7, %8, %9, %10, %11, %12, %13, %14, %15, %16, %17, %18, %19, %20, %21, %22, %23, %24, %25, %26, %27, %28, %29, %30, %31, %32, %33, %34, %35, %36, %37, %38, %39, %40, %41, %42, %43, %44, %45, %46, %47, %48, %49, %50, %51, %52, %53, %54, %55, %56, %57, %58, %59, %60, %61, %62, %63, %64, %65, %66, %67, %68, %69, %70, %71, %72, %73, %74, %75, %76, %77, %78, %79}, %80, %81, 1, 1, 1, 0, 1;\n"
    : "+f"(d[0]), "+f"(d[1]), "+f"(d[2]), "+f"(d[3]), "+f"(d[4]), "+f"(d[5]), "+f"(d[6]), "+f"(d[7]), "+f"(d[8]), "+f"(d[9]), "+f"(d[10]), "+f"(d[11]), "+f"(d[12]), "+f"(d[13]), "+f"(d[14]), "+f"(d[15]), "+f"(d[16]), "+f"(d[17]), "+f"(d[18]), "+f"(d[19]), "+f"(d[20]), "+f"(d[21]), "+f"(d[22]), "+f"(d[23]), "+f"(d[24]), "+f"(d[25]), "+f"(d[26]), "+f"(d[27]), "+f"(d[28]), "+f"(d[29]), "+f"(d[30]), "+f"(d[31]), "+f"(d[32]), "+f"(d[33]), "+f"(d[34]), "+f"(d[35]), "+f"(d[36]), "+f"(d[37]), "+f"(d[38]), "+f"(d[39]), "+f"(d[40]), "+f"(d[41]), "+f"(d[42]), "+f"(d[43]), "+f"(d[44]), "+f"(d[45]), "+f"(d[46]), "+f"(d[47]), "+f"(d[48]), "+f"(d[49]), "+f"(d[50]), "+f"(d[51]), "+f"(d[52]), "+f"(d[53]), "+f"(d[54]), "+f"(d[55]), "+f"(d[56]), "+f"(d[57]), "+f"(d[58]), "+f"(d[59]), "+f"(d[60]), "+f"(d[61]), "+f"(d[62]), "+f"(d[63]), "+f"(d[64]), "+f"(d[65]), "+f"(d[66]), "+f"(d[67]), "+f"(d[68]), "+f"(d[69]), "+f"(d[70]), "+f"(d[71]), "+f"(d[72]), "+f"(d[73]), "+f"(d[74]), "+f"(d[75]), "+f"(d[76]), "+f"(d[77]), "+f"(d[78]), "+f"(d[79])
    : "l"(descA), "l"(descB));
}
__device__ __forceinline__ void wgmma_ss_n48_tb(float (&d)[24], uint64_t descA, uint64_t descB) {
  asm volatile("wgmma.mma_async.sync.aligned.m64n48k16.f32.bf16.bf16 {%0, %1, %2, %3, %4, %5, %6, %7, %8, %9, %10, %11, %12, %13, %14, %15, %16, %17, %18, %19, %20, %21, %22, %23}, %24, %25, 1, 1, 1, 0, 1;\n"
    : "+f"(d[0]), "+f"(d[1]), "+f"(d[2]), "+f"(d[3]), "+f"(d[4]), "+f"(d[5]), "+f"(d[6]), "+f"(d[7]), "+f"(d[8]), "+f"(d[9]), "+f"(d[10]), "+f"(d[11]), "+f"(d[12]), "+f"(d[13]), "+f"(d[14]), "+f"(d[15]), "+f"(d[16]), "+f"(d[17]), "+f"(d[18]), "+f"(d[19]), "+f"(d[20]), "+f"(d[21]), "+f"(d[22]), "+f"(d[23])
    : "l"(descA), "l"(descB));
}
__device__ __forceinline__ void wgmma_ss_n80_tb(float (&d)[40], uint64_t descA, uint64_t descB) {
  asm volatile("wgmma.mma_async.sync.aligned.m64n80k16.f32.bf16.bf16 {%0, %1, %2, %3, %4, %5, %6, %7, %8, %9, %10, %11, %12, %13, %14, %15, %16, %17, %18, %19, %20, %21, %22, %23, %24, %25, %26, %27, %28, %29, %30, %31, %32, %33, %34, %35, %36, %37, %38, %39}, %40, %41, 1, 1, 1, 0, 1;\n"
    : "+f"(d[0]), "+f"(d[1]), "+f"(d[2]), "+f"(d[3]), "+f"(d[4]), "+f"(d[5]), "+f"(d[6]), "+f"(d[7]), "+f"(d[8]), "+f"(d[9]), "+f"(d[10]), "+f"(d[11]), "+f"(d[12]), "+f"(d[13]), "+f"(d[14]), "+f"(d[15]), "+f"(d[16]), "+f"(d[17]), "+f"(d[18]), "+f"(d[19]), "+f"(d[20]), "+f"(d[21]), "+f"(d[22]), "+f"(d[23]), "+f"(d[24]), "+f"(d[25]), "+f"(d[26]), "+f"(d[27]), "+f"(d[28]), "+f"(d[29]), "+f"(d[30]), "+f"(d[31]), "+f"(d[32]), "+f"(d[33]), "+f"(d[34]), "+f"(d[35]), "+f"(d[36]), "+f"(d[37]), "+f"(d[38]), "+f"(d[39])
    : "l"(descA), "l"(descB));
}
template <int SCALE_D>
__device__ __forceinline__ void wgmma_rs_n64(float (&d)[32], uint32_t a0, uint32_t a1, uint32_t a2, uint32_t a3, uint64_t descB) {
  asm volatile("wgmma.mma_async.sync.aligned.m64n64k16.f32.bf16.bf16 {%0, %1, %2, %3, %4, %5, %6, %7, %8, %9, %10, %11, %12, %13, %14, %15, %16, %17, %18, %19, %20, %21, %22, %23, %24, %25, %26, %27, %28, %29, %30, %31}, {%32, %33, %34, %35}, %36, %37, 1, 1, 0;\n"
    : "+f"(d[0]), "+f"(d[1]), "+f"(d[2]), "+f"(d[3]), "+f"(d[4]), "+f"(d[5]), "+f"(d[6]), "+f"(d[7]), "+f"(d[8]), "+f"(d[9]), "+f"(d[10]), "+f"(d[11]), "+f"(d[12]), "+f"(d[13]), "+f"(d[14]), "+f"(d[15]), "+f"(d[16]), "+f"(d[17]), "+f"(d[18]), "+f"(d[19]), "+f"(d[20]), "+f"(d[21]), "+f"(d[22]), "+f"(d[23]), "+f"(d[24]), "+f"(d[25]), "+f"(d[26]), "+f"(d[27]), "+f"(d[28]), "+f"(d[29]), "+f"(d[30]), "+f"(d[31])
    : "r"(a0), "r"(a1), "r"(a2), "r"(a3), "l"(descB), "n"(SCALE_D));
}
template <int SCALE_D>
__device__ __forceinline__ void wgmma_rs_n128(float (&d)[64], uint32_t a0, uint32_t a1, uint32_t a2, uint32_t a3, uint64_t descB) {
  asm volatile("wgmma.mma_async.sync.aligned.m64n128k16.f32.bf16.bf16 {%0, %1, %2, %3, %4, %5, %6, %7, %8, %9, %10, %11, %12, %13, %14, %15, %16, %17, %18, %19, %20, %21, %22, %23, %24, %25, %26, %27, %28, %29, %30, %31, %32, %33, %34, %35, %36, %37, %38, %39, %40, %41, %42, %43, %44, %45, %46, %47, %48, %49, %50, %51, %52, %53, %54, %55, %56, %57, %58, %59, %60, %61, %62, %63}, {%64, %65, %66, %67}, %68, %69, 1, 1, 0;\n"
    : "+f"(d[0]), "+f"(d[1]), "+f"(d[2]), "+f"(d[3]), "+f"(d[4]), "+f"(d[5]), "+f"(d[6]), "+f"(d[7]), "+f"(d[8]), "+f"(d[9]), "+f"(d[10]), "+f"(d[11]), "+f"(d[12]), "+f"(d[13]), "+f"(d[14]), "+f"(d[15]), "+f"(d[16]), "+f"(d[17]), "+f"(d[18]), "+f"(d[19]), "+f"(d[20]), "+f"(d[21]), "+f"(d[22]), "+f"(d[23]), "+f"(d[24]), "+f"(d[25]), "+f"(d[26]), "+f"(d[27]), "+f"(d[28]), "+f"(d[29]), "+f"(d[30]), "+f"(d[31]), "+f"(d[32]), "+f"(d[33]), "+f"(d[34]), "+f"(d[35]), "+f"(d[36]), "+f"(d[37]), "+f"(d[38]), "+f"(d[39]), "+f"(d[40]), "+f"(d[41]), "+f"(d[42]), "+f"(d[43]), "+f"(d[44]), "+f"(d[45]), "+f"(d[46]), "+f"(d[47]), "+f"(d[48]), "+f"(d[49]), "+f"(d[50]), "+f"(d[51]), "+f"(d[52]), "+f"(d[53]), "+f"(d[54]), "+f"(d[55]), "+f"(d[56]), "+f"(d[57]), "+f"(d[58]), "+f"(d[59]), "+f"(d[60]), "+f"(d[61]), "+f"(d[62]), "+f"(d[63])
    : "r"(a0), "r"(a1), "r"(a2), "r"(a3), "l"(descB), "n"(SCALE_D));
}
template <int SCALE_D>
__device__ __forceinline__ void wgmma_rs_n24_tb(float (&d)[12], uint32_t a0, uint32_t a1, uint32_t a2, uint32_t a3, uint64_t descB) {
  asm volatile("wgmma.mma_async.sync.aligned.m64n24k16.f32.bf16.bf16 {%0, %1, %2, %3, %4, %5, %6, %7, %8, %9, %10, %11}, {%12, %13, %14, %15}, %16, %17, 1, 1, 1;\n"
    : "+f"(d[0]), "+f"(d[1]), "+f"(d[2]), "+f"(d[3]), "+f"(d[4]), "+f"(d[5]), "+f"(d[6]), "+f"(d[7]), "+f"(d[8]), "+f"(d[9]), "+f"(d[10]), "+f"(d[11])
    : "r"(a0), "r"(a1), "r"(a2), "r"(a3), "l"(descB), "n"(SCALE_D));
}

constexpr uint32_t DHI_SW128_K = (1024 >> 4) | (1u << 30);
constexpr uint32_t DHI_SW64_MN = (512 >> 4) | (2u << 30);

template <int NC>
__device__ __forceinline__ void store_tile_bf16(const float (&acc)[NC / 2], float scale, uint32_t stage, uint8_t* stage_ptr,
                                                __nv_bfloat16* gdst, int gpitch, int lane) {
  constexpr int PITCH = NC * 2 + 16;
  const uint32_t waddr = stage + ((lane & 7) + ((lane >> 3) & 1) * 8) * PITCH + (lane >> 4) * 16;
#pragma unroll
  for (int j = 0; j < NC / 16; j++) {
    stsm4(waddr + j * 32, pack_bf16(acc[8 * j] * scale, acc[8 * j + 1] * scale), pack_bf16(acc[8 * j + 2] * scale, acc[8 * j + 3] * scale),
          pack_bf16(acc[8 * j + 4] * scale, acc[8 * j + 5] * scale), pack_bf16(acc[8 * j + 6] * scale, acc[8 * j + 7] * scale));
  }
  __syncwarp();
  constexpr int CPR = NC / 8;
#pragma unroll
  for (int i = 0; i < CPR / 2; i++) {
    const int c = i * 32 + lane, r = c / CPR, cc = c % CPR;
    const uint4 v = *reinterpret_cast<const uint4*>(stage_ptr + r * PITCH + cc * 16);
    *reinterpret_cast<uint4*>(gdst + (size_t)r * gpitch + cc * 8) = v;
  }
}

__device__ __forceinline__ void signal_done(unsigned int* flag, int wg, int tid) {
  asm volatile("bar.sync %0, 128;" :: "r"(wg + 1) : "memory");
  if ((tid & 127) == 0) asm volatile("red.release.gpu.global.add.u32 [%0], 1;" :: "l"(flag) : "memory");
}
__device__ __forceinline__ void wait_flags8(const unsigned int* f, unsigned int target) {
  for (int spin = 0; spin < (1 << 26); spin++) {
    unsigned int a, b, c, d, e, g, h, i;
    asm volatile("ld.volatile.global.v4.u32 {%0, %1, %2, %3}, [%4];" : "=r"(a), "=r"(b), "=r"(c), "=r"(d) : "l"(f) : "memory");
    asm volatile("ld.volatile.global.v4.u32 {%0, %1, %2, %3}, [%4];" : "=r"(e), "=r"(g), "=r"(h), "=r"(i) : "l"(f + 4) : "memory");
    if (min(min(min(a, b), min(c, d)), min(min(e, g), min(h, i))) >= target) break;
    __nanosleep(32);
  }
  asm volatile("fence.acq_rel.gpu;" ::: "memory");
  asm volatile("fence.proxy.async;" ::: "memory");
}

#define RP_LD 3
#define RP_ST 7
constexpr int K1_STAGES = 4;
constexpr int K1_A_BYTES = 256 * 128;
constexpr int K1_B_BYTES = 64 * 160 * 2;
constexpr int K1_STAGE = K1_A_BYTES + K1_B_BYTES;
constexpr int K1_SMEM = 5 * K1_A_BYTES + 61440 + 1024;
constexpr int KV_STAGES = 5;
constexpr int KVW_OFF = KV_STAGES * K1_A_BYTES;

__global__ void __launch_bounds__(512, 1)
proj_kernel(const __grid_constant__ CUtensorMap tmX, const __grid_constant__ CUtensorMap tmWq, const __grid_constant__ CUtensorMap tmWqkv,
            const __nv_bfloat16* __restrict__ wk, const __nv_bfloat16* __restrict__ wv, const __nv_bfloat16* __restrict__ gate_w,
            const __nv_bfloat16* __restrict__ woA, const __nv_bfloat16* __restrict__ woB) {
  extern __shared__ uint8_t smem_raw[];
  __shared__ __align__(8) uint64_t bar_full[KV_STAGES], bar_empty[KV_STAGES];
  uint8_t* smem = reinterpret_cast<uint8_t*>((reinterpret_cast<uintptr_t>(smem_raw) + 1023) & ~(uintptr_t)1023);
  const uint32_t sbase = smem_u32(smem);
  const uint32_t dbase = sbase & 0x3FFFFu;
  const int tid = threadIdx.x, warp = tid >> 5, lane = tid & 31;
  const bool is_kv = blockIdx.x >= 128;
  PROF(0, 0);
  if (tid == 32) { prefetch_tmap(&tmX); prefetch_tmap((blockIdx.x & 15) < 4 ? &tmWq : &tmWqkv); }
  if (tid == 0) {
    for (int i = 0; i < KV_STAGES; i++) { mbar_init(smem_u32(&bar_full[i]), 1); mbar_init(smem_u32(&bar_empty[i]), is_kv ? 8 : 16); }
    fence_mbar_init();
  }
  uint2 wa[2][5], wb[2][5]; uint32_t gw[2];
  if (is_kv && tid < 320) {
#pragma unroll
    for (int r = 0; r < 2; r++) {
      const int k = tid + r * 320;
      const uint2* pk = reinterpret_cast<const uint2*>(wk + k * 20);
      const uint2* pv = reinterpret_cast<const uint2*>(wv + k * 20);
#pragma unroll
      for (int i = 0; i < 5; i++) { wa[r][i] = __ldg(pk + i); wb[r][i] = __ldg(pv + i); }
      gw[r] = (uint32_t)__bfloat16_as_ushort(gate_w[k]);
    }
  }
  __syncthreads();
  if (tid == 480 && !is_kv) { g_done[blockIdx.x] = 0u; g_doneL[blockIdx.x] = 0u; }
  pdl_launch();

  if (!is_kv) {
    const int mb = blockIdx.x >> 4, nb = blockIdx.x & 15;
    const CUtensorMap* tw = nb < 4 ? &tmWq : &tmWqkv;
    const int j0 = (nb < 4 ? nb : nb - 4) * 5;
    auto load = [&](int kt) {
      const int s = kt % K1_STAGES;
      const uint32_t fb = smem_u32(&bar_full[s]);
      mbar_expect_tx(fb, K1_STAGE);
      tma_2d(sbase + s * K1_STAGE, &tmX, kt * 64, mb * 256, fb);
      tma_3d(sbase + s * K1_STAGE + K1_A_BYTES, tw, 0, kt * 64, j0, fb);
    };
    if (tid == 0) for (int kt = 0; kt < K1_STAGES; kt++) load(kt);
    __syncwarp();
    uint4 wv2[2];
    const int rq = blockIdx.x * 400 + tid - 112;
    const int rhalf = rq >= 25600, rr = rq - rhalf * 25600, rk = 2 * (rr / 80), rch = rr % 80;
    {
      const int wg = warp >> 2;
      float acc[80];
#pragma unroll
      for (int i = 0; i < 80; i++) acc[i] = 0.f;
      for (int kt = 0; kt < 10; kt++) {
        const int s = kt % K1_STAGES;
        mbar_wait(smem_u32(&bar_full[s]), (kt / K1_STAGES) & 1);
        const uint32_t alo = ((dbase + s * K1_STAGE + wg * 8192) >> 4) | (1u << 16);
        const uint32_t blo = ((dbase + s * K1_STAGE + K1_A_BYTES) >> 4) | ((4096u >> 4) << 16);
        fence_regs(acc);
        wg_fence();
#pragma unroll
        for (int k = 0; k < 4; k++) wgmma_ss_n160_tb(acc, mkd(alo + k * 2, DHI_SW128_K), mkd(blo + k * 64, DHI_SW64_MN));
        wg_commit();
        if (kt == RP_LD && tid >= 112) {
          const uint4* src = reinterpret_cast<const uint4*>((rhalf ? woB : woA) + rk * D_MODEL + rch * 8);
          wv2[0] = __ldg(src); wv2[1] = __ldg(src + D_MODEL / 8);
        }
        if (kt == RP_ST && tid >= 112) {
          uint4* dst = reinterpret_cast<uint4*>(g_wimg + ((rhalf * 8 + rch / 10) * 10 + (rk >> 6)) * 10240 + (rch % 10) * 1024 + (rk & 63) * 16);
          dst[0] = wv2[0]; dst[1] = wv2[1];
        }
        __syncwarp();
        if (kt > 0 && kt - 1 + K1_STAGES < 10) {
          wg_wait<1>();
          const uint32_t eb = smem_u32(&bar_empty[(kt - 1) % K1_STAGES]);
          if (lane == 0) mbar_arrive(eb);
          if (tid == 0) { mbar_wait(eb, ((kt - 1) / K1_STAGES) & 1); load(kt - 1 + K1_STAGES); }
          __syncwarp();
        }
      }
      wg_wait<0>();
      fence_regs(acc);
      PROF(0, 1);
      asm volatile("bar.sync %0, 128;" :: "r"(wg + 1) : "memory");
      const int w4 = warp & 3;
      const uint32_t off = w4 * K1_STAGE + wg * 8192;
      const int row0 = mb * 256 + wg * 64 + w4 * 16;
      if (nb < 4) {
        store_tile_bf16<160>(acc, 0.22360679774997896f * 1.4426950408889634f, sbase + off, smem + off,
                             g_q + (size_t)row0 * D_MODEL + nb * 160, D_MODEL, lane);
      } else {
        store_tile_bf16<160>(acc, 1.0f, sbase + off, smem + off, g_qkv + (size_t)row0 * (3 * D_MODEL) + (nb - 4) * 160, 3 * D_MODEL, lane);
      }
    }
  } else {
    const int cb = blockIdx.x - 128;
    if (warp == 8 && lane == 0) {
      for (int it = 0; it < KV_STAGES; it++) {
        const uint32_t fb = smem_u32(&bar_full[it]);
        mbar_expect_tx(fb, K1_A_BYTES);
        tma_2d(sbase + it * K1_A_BYTES, &tmX, it * 64, cb * 512, fb);
      }
    }
    __syncwarp();
    if (tid < 320) {
#pragma unroll
      for (int r = 0; r < 2; r++) {
        uint4* dst = reinterpret_cast<uint4*>(smem + KVW_OFF + (tid + r * 320) * 16);
        dst[0] = make_uint4(wa[r][0].x, wa[r][0].y, wa[r][1].x, wa[r][1].y);
        dst[640] = make_uint4(wa[r][2].x, wa[r][2].y, wa[r][3].x, wa[r][3].y);
        dst[1280] = make_uint4(wa[r][4].x, wa[r][4].y, 0u, 0u);
        dst[1920] = make_uint4(wb[r][0].x, wb[r][0].y, wb[r][1].x, wb[r][1].y);
        dst[2560] = make_uint4(wb[r][2].x, wb[r][2].y, wb[r][3].x, wb[r][3].y);
        dst[3200] = make_uint4(wb[r][4].x, wb[r][4].y, gw[r], 0u);
      }
    }
    fence_proxy_async();
    asm volatile("bar.sync 1, 512;" ::: "memory");
    PROF(0, 1);
    auto produce = [&](int it0, int it1) {
      for (int it = it0; it < it1; it++) {
        const int s = it % KV_STAGES;
        mbar_wait(smem_u32(&bar_empty[s]), (it / KV_STAGES - 1) & 1);
        const uint32_t fb = smem_u32(&bar_full[s]);
        mbar_expect_tx(fb, K1_A_BYTES);
        tma_2d(sbase + s * K1_A_BYTES, &tmX, (it >= 10 ? it - 10 : it) * 64, cb * 512 + (it >= 10 ? 256 : 0), fb);
      }
    };
    if (tid == 256) produce(KV_STAGES, 15);
    __syncwarp();
    {
      const int pass = warp >> 3, wg = (warp >> 2) & 1, w4 = warp & 3, g = lane >> 2, t = lane & 3;
      if (pass == 1) asm volatile("bar.sync 2, 512;" ::: "memory");
      {
        float acc[2][24];
#pragma unroll
        for (int i = 0; i < 24; i++) { acc[0][i] = 0.f; acc[1][i] = 0.f; }
        for (int kt = 0; kt < 10; kt++) {
          const int it = pass * 10 + kt, s = it % KV_STAGES;
          mbar_wait(smem_u32(&bar_full[s]), (it / KV_STAGES) & 1);
          const uint32_t alo = ((dbase + s * K1_A_BYTES + wg * 16384) >> 4) | (1u << 16);
          const uint32_t blo = ((dbase + KVW_OFF + kt * 1024) >> 4) | ((128u >> 4) << 16);
          fence_regs(acc[0]); fence_regs(acc[1]);
          wg_fence();
#pragma unroll
          for (int k = 0; k < 4; k++) {
            wgmma_ss_n48_tb(acc[0], mkd(alo + k * 2, DHI_SW128_K), mkd(blo + k * 16, 10240u >> 4));
            wgmma_ss_n48_tb(acc[1], mkd(alo + 512 + k * 2, DHI_SW128_K), mkd(blo + k * 16, 10240u >> 4));
          }
          wg_commit();
          if (kt > 0) {
            wg_wait<1>();
            if (lane == 0) mbar_arrive(smem_u32(&bar_empty[(it - 1) % KV_STAGES]));
          }
        }
        wg_wait<0>();
        fence_regs(acc[0]); fence_regs(acc[1]);
        if (lane == 0) mbar_arrive(smem_u32(&bar_empty[(pass * 10 + 9) % KV_STAGES]));
        if (pass == 0) asm volatile("bar.arrive 2, 512;" ::: "memory");
        PROF(0, 2);
        if (tid == 0) produce(15, 20);
        __syncwarp();
        float kmax2 = 0.f, vmax = 0.f;
#pragma unroll
        for (int hh = 0; hh < 4; hh++) {
          const int h = hh & 1;
          const float (&a)[24] = acc[hh >> 1];
          const int key = cb * 512 + pass * 256 + wg * 128 + (hh >> 1) * 64 + w4 * 16 + g + h * 8;
          const int grp = key >> 7, kk = key & 127;
          const bool poly = (TMASK >> (kk >> 3)) & 1;
          uint8_t* gp = g_kvimg + grp * GRP_BYTES;
          const uint32_t k0 = pack_bf16(a[2 * h], a[2 * h + 1]);
          const uint32_t k1 = pack_bf16(a[4 + 2 * h], a[5 + 2 * h]);
          uint32_t k2 = pack_bf16(a[8 + 2 * h], a[9 + 2 * h]);
          float n2 = bf_lo(k0) * bf_lo(k0) + bf_hi(k0) * bf_hi(k0) + bf_lo(k1) * bf_lo(k1) + bf_hi(k1) * bf_hi(k1);
          if (t < 2) {
            n2 += bf_lo(k2) * bf_lo(k2) + bf_hi(k2) * bf_hi(k2);
            k2 = pack_bf16(bf_lo(k2) * 0.5f, bf_hi(k2) * 0.5f);
          } else if (t == 2) k2 = poly ? pack_bf16(24.f, 2.5f) : pack_bf16(0.5f, 0.f);
          else k2 = poly ? pack_bf16(0.5f, 0.f) : 0u;
          *reinterpret_cast<uint32_t*>(gp + kk * 16 + t * 4) = k0;
          *reinterpret_cast<uint32_t*>(gp + PLANE + kk * 16 + t * 4) = k1;
          *reinterpret_cast<uint32_t*>(gp + 2 * PLANE + kk * 16 + t * 4) = k2;
          n2 += __shfl_xor_sync(0xffffffffu, n2, 1);
          n2 += __shfl_xor_sync(0xffffffffu, n2, 2);
          kmax2 = (n2 > kmax2 || n2 != n2) ? n2 : kmax2;
          uint32_t v0 = pack_bf16(a[12 + 2 * h], a[13 + 2 * h]);
          uint32_t v1 = pack_bf16(a[16 + 2 * h], a[17 + 2 * h]);
          uint32_t v2 = pack_bf16(a[20 + 2 * h], a[21 + 2 * h]);
          float vm = fmaxf(fmaxf(fabsf(bf_lo(v0)), fabsf(bf_hi(v0))), fmaxf(fabsf(bf_lo(v1)), fabsf(bf_hi(v1))));
          if (t < 2) vm = fmaxf(vm, fmaxf(fabsf(bf_lo(v2)), fabsf(bf_hi(v2))));
          else if (t == 2) {
            const float z = a[20 + 2 * h];
            g_gate[key] = 1.f / (1.f + __expf(-z));
            v2 = 0x00003F80u;
          } else v2 = 0u;
          vmax = fmaxf(vmax, vm);
          if (poly) { v0 ^= 0x80008000u; v1 ^= 0x80008000u; v2 ^= 0x80008000u; }
          uint8_t* vp = gp + 3 * PLANE + (kk >> 3) * 384 + (kk & 7) * 16 + t * 4;
          *reinterpret_cast<uint32_t*>(vp) = v0;
          *reinterpret_cast<uint32_t*>(vp + 128) = v1;
          *reinterpret_cast<uint32_t*>(vp + 256) = v2;
        }
#pragma unroll
        for (int o = 1; o < 32; o <<= 1) {
          const float a = __shfl_xor_sync(0xffffffffu, kmax2, o);
          kmax2 = (a > kmax2 || a != a) ? a : kmax2;
          vmax = fmaxf(vmax, __shfl_xor_sync(0xffffffffu, vmax, o));
        }
        if (lane == 0) { g_kmax2[cb * 16 + warp] = kmax2; g_vmax[cb * 16 + warp] = vmax; }
      }
    }
  }
}

__device__ __forceinline__ uint32_t ex2_pair_poly(float u0, float u1, uint32_t one2) {
  const uint32_t W = __byte_perm(__float_as_uint(u0), __float_as_uint(u1), 0x6521);
  uint32_t v; asm("lop3.b32 %0, %1, 0x007F007F, %2, 0xEA;" : "=r"(v) : "r"(W), "r"(one2));
  uint32_t L, p;
  asm("fma.rn.bf16x2 %0, %1, %2, %3;" : "=r"(L) : "r"(v), "r"(0x1f961f96u), "r"(0x9fe39fe3u));
  asm("fma.rn.bf16x2 %0, %1, %1, %2;" : "=r"(p) : "r"(L), "r"(0x00f500f5u));
  return W + p;
}
template <int JOFF>
__device__ __forceinline__ void softmax_slow(const float (&S)[32], uint32_t (&P)[16], float (&O)[12], float& m0, float& m1) {
  float a0 = m0, a1 = m1;
#pragma unroll
  for (int j = 0; j < 8; j++) {
    a0 = fmaxf(a0, fmaxf(S[4 * j], S[4 * j + 1]));
    a1 = fmaxf(a1, fmaxf(S[4 * j + 2], S[4 * j + 3]));
  }
  a0 = fmaxf(a0, __shfl_xor_sync(0xffffffffu, a0, 1)); a0 = fmaxf(a0, __shfl_xor_sync(0xffffffffu, a0, 2));
  a1 = fmaxf(a1, __shfl_xor_sync(0xffffffffu, a1, 1)); a1 = fmaxf(a1, __shfl_xor_sync(0xffffffffu, a1, 2));
  const float c0 = ex2(m0 - a0), c1 = ex2(m1 - a1);
  m0 = a0; m1 = a1;
#pragma unroll
  for (int j = 0; j < 3; j++) { O[4 * j] *= c0; O[4 * j + 1] *= c0; O[4 * j + 2] *= c1; O[4 * j + 3] *= c1; }
#pragma unroll
  for (int i = 0; i < 16; i++) {
    const float m = (i & 1) ? a1 : a0;
    const uint32_t p = pack_bf16(ex2(S[2 * i] - m), ex2(S[2 * i + 1] - m));
    P[i] = ((TMASK >> (JOFF + i / 2)) & 1) ? (p ^ 0x80008000u) : p;
  }
}
constexpr uint32_t DHI_KV = 128 >> 4;
__device__ __forceinline__ void issue_qk(float (&S)[32], const uint32_t (&q)[8], uint64_t base) {
  wgmma_rs_n64<0>(S, q[0], q[1], q[2], q[3], base + (uint64_t)((PLANE >> 4) << 16));
  wgmma_rs_n64<1>(S, q[4], q[5], q[6], q[7], base + (uint64_t)(2 * PLANE >> 4));
}
__device__ __forceinline__ void issue_pv(float (&O)[12], const uint32_t (&P)[16], uint64_t vbase) {
#pragma unroll
  for (int kk = 0; kk < 4; kk++)
    wgmma_rs_n24_tb<1>(O, P[4 * kk], P[4 * kk + 1], P[4 * kk + 2], P[4 * kk + 3], vbase + (uint64_t)(kk * (768 >> 4)));
}

constexpr uint32_t VOFF = ((3 * PLANE) >> 4) + ((384u >> 4) << 16);
constexpr int KVR = 4;
constexpr int OFF_W = KVR * GRP_BYTES;
constexpr int OFF_X = OFF_W + 10 * 10240;
constexpr int OFF_BAR = OFF_X + 4 * 16384;
constexpr int K2_SMEM = OFF_BAR + 512 + 1024;
constexpr int TSL = 3;
constexpr int BAR_KV = 0, BAR_W = 4, BAR_TA = 5, BAR_TE = 12, BAR_OWN = 19, BAR_L = 20, CNT_KV = 21, BAR_WA = 23, BAR_WF = 33, CNT_TK = 43;
constexpr int NSTEP = 2 * NGRP;

__device__ __forceinline__ void kv_load(uint32_t sbase, int step) {
  const uint32_t bar = sbase + OFF_BAR + (BAR_KV + (step & (KVR - 1))) * 8;
  mbar_expect_tx(bar, GRP_BYTES);
  bulk_g2s(sbase + (step & (KVR - 1)) * GRP_BYTES, g_kvimg + (step & (NGRP - 1)) * GRP_BYTES, GRP_BYTES, bar);
}
__device__ __forceinline__ void kv_release(uint32_t sbase, int step, bool elected) {
  if (elected && step + KVR < NSTEP) {
    uint32_t old;
    asm volatile("atom.acq_rel.cta.shared::cta.inc.u32 %0, [%1], 3;" : "=r"(old) : "r"(sbase + OFF_BAR + CNT_KV * 8 + (step & (KVR - 1)) * 4) : "memory");
    if (old == 3u) kv_load(sbase, step + KVR);
  }
  __syncwarp();
}
__device__ __forceinline__ void kv_wait(uint32_t sbase, int step) {
  mbar_wait(sbase + OFF_BAR + (BAR_KV + (step & (KVR - 1))) * 8, (step / KVR) & 1);
}

__device__ __forceinline__ uint32_t kv_release_begin(uint32_t sbase, int slot, bool doit) {
  uint32_t old = 0;
  asm volatile("{\n.reg .pred p;\nsetp.ne.u32 p, %2, 0;\n@p atom.relaxed.cta.shared::cta.inc.u32 %0, [%1], 3;\n}\n"
               : "+r"(old) : "r"(sbase + OFF_BAR + CNT_KV * 8 + slot * 4), "r"((uint32_t)doit) : "memory");
  return old;
}
template <int H>
__device__ __forceinline__ void softmax_half(const float (&S)[64], uint32_t (&P)[16], uint32_t one2) {
#pragma unroll
  for (int i = 0; i < 16; i++) {
    if ((TMASK >> (8 * H + i / 2)) & 1) P[i] = ex2_pair_poly(S[32 * H + 2 * i], S[32 * H + 2 * i + 1], one2);
    else P[i] = pack_bf16(ex2(S[32 * H + 2 * i]), ex2(S[32 * H + 2 * i + 1]));
  }
}
__device__ __forceinline__ void attn_fast(const uint32_t (&q)[8], float (&O)[12], uint32_t sbase, int step0, int nsteps, bool elected, uint32_t one2) {
  uint64_t kb0 = mkd((sbase & 0x3FFFFu) >> 4, DHI_KV);
  asm volatile("" : "+l"(kb0));
#pragma unroll 1
  for (int step4 = step0; step4 < step0 + nsteps; step4 += KVR) {
#pragma unroll
    for (int j = 0; j < KVR; j++) {
      const int step = step4 + j;
      const uint64_t kb = kb0 + (uint64_t)(j * (GRP_BYTES >> 4));
      float S[64]; uint32_t PA[16], PB[16];
#pragma unroll
      for (int i = 0; i < 64; i++) S[i] = 0.f;
      mbar_wait(sbase + OFF_BAR + (BAR_KV + j) * 8, (step / KVR) & 1);
      fence_regs(S);
      wg_fence();
      wgmma_rs_n128<0>(S, q[0], q[1], q[2], q[3], kb + (uint64_t)((PLANE >> 4) << 16));
      wgmma_rs_n128<1>(S, q[4], q[5], q[6], q[7], kb + (uint64_t)(2 * PLANE >> 4));
      wg_commit();
      const uint32_t old = kv_release_begin(sbase, (j + KVR - 1) & (KVR - 1), elected && step > step0 && step - 1 + KVR < NSTEP);
      wg_wait<0>();
      fence_regs(S);
      softmax_half<0>(S, PA, one2);
      fence_regs(PA); fence_regs(O);
      wg_fence();
      issue_pv(O, PA, kb + VOFF);
      wg_commit();
      softmax_half<1>(S, PB, one2);
      fence_regs(PB);
      wg_fence();
      issue_pv(O, PB, kb + VOFF + 4 * (768 >> 4));
      wg_commit();
      if (old == 3u) kv_load(sbase, step - 1 + KVR);
      wg_wait<0>();
      fence_regs(PA); fence_regs(PB); fence_regs(O);
    }
  }
  kv_release(sbase, step0 + nsteps - 1, elected);
}
template <int H>
__device__ __forceinline__ void slow_step(const uint32_t (&q)[8], float (&O)[12], uint64_t kb, float& m0, float& m1) {
  float S[32]; uint32_t P[16];
#pragma unroll
  for (int i = 0; i < 32; i++) S[i] = 0.f;
  fence_regs(S);
  wg_fence();
  issue_qk(S, q, kb + 64 * H);
  wg_commit();
  wg_wait<0>();
  fence_regs(S);
  softmax_slow<8 * H>(S, P, O, m0, m1);
  fence_regs(P); fence_regs(O);
  wg_fence();
  issue_pv(O, P, kb + VOFF + H * 4 * (768 >> 4));
  wg_commit();
  wg_wait<0>();
  fence_regs(O); fence_regs(P);
}
__device__ __forceinline__ void attn_slow(const uint32_t (&q)[8], float (&O)[12], uint32_t sbase, int step0, int nsteps, bool elected, float& m0, float& m1) {
#pragma unroll 1
  for (int step = step0; step < step0 + nsteps; step++) {
    kv_wait(sbase, step);
    const uint64_t kb = mkd(((sbase & 0x3FFFFu) >> 4) + (step & (KVR - 1)) * (GRP_BYTES >> 4), DHI_KV);
    slow_step<0>(q, O, kb, m0, m1);
    slow_step<1>(q, O, kb, m0, m1);
    kv_release(sbase, step, elected);
  }
}

__device__ __forceinline__ void softmax8(float (&sc)[8], float scale) {
  float mx = sc[0];
#pragma unroll
  for (int w = 1; w < 8; w++) mx = fmaxf(mx, sc[w]);
  float l = 0.f;
#pragma unroll
  for (int w = 0; w < 8; w++) { sc[w] = ex2(sc[w] - mx); l += sc[w]; }
  const float r = __fdividef(scale, l);
#pragma unroll
  for (int w = 0; w < 8; w++) sc[w] *= r;
}
#define LEV(wg) 1
constexpr int LBOX = 32 * 320;
__device__ __forceinline__ uint2 lds64(uint32_t a) {
  uint2 v; asm volatile("ld.shared.v2.u32 {%0, %1}, [%2];" : "=r"(v.x), "=r"(v.y) : "r"(a)); return v;
}
__device__ __forceinline__ void local_attn(uint32_t stage, int t0, int i, int lane) {
  constexpr float SC = 0.22360679774997896f * 1.4426950408889634f, NEG = -1e9f * 1.4426950408889634f;
  const uint32_t base = stage + (lane >> 3) * LBOX + (lane & 7) * 40 + (i + 14 + ((lane >> 3) & 1)) * 320;
  const int t = t0 + i;
  float sc[8];
#pragma unroll
  for (int w = 0; w < 8; w++) sc[w] = 0.f;
#pragma unroll 1
  for (int c = 0; c < 5; c++) {
    const uint2 qv = lds64(base + c * 8);
    const float q0 = bf_lo(qv.x), q1 = bf_hi(qv.x), q2 = bf_lo(qv.y), q3 = bf_hi(qv.y);
#pragma unroll
    for (int w = 0; w < 8; w++) {
      const uint2 k = lds64(base + c * 8 + 4 * LBOX - w * 640);
      sc[w] = fmaf(q0, bf_lo(k.x), sc[w]); sc[w] = fmaf(q1, bf_hi(k.x), sc[w]);
      sc[w] = fmaf(q2, bf_lo(k.y), sc[w]); sc[w] = fmaf(q3, bf_hi(k.y), sc[w]);
    }
  }
#pragma unroll
  for (int w = 0; w < 8; w++) sc[w] = t - 2 * w >= 0 ? sc[w] * SC : NEG;
  softmax8(sc, 1.f - g_gate[t]);
  uint2* dst = reinterpret_cast<uint2*>(g_a2 + (size_t)t * (2 * D_MODEL) + D_MODEL + lane * DH);
#pragma unroll 1
  for (int c = 0; c < 5; c++) {
    float o0 = 0.f, o1 = 0.f, o2 = 0.f, o3 = 0.f;
#pragma unroll
    for (int w = 0; w < 8; w++) {
      const uint2 v = lds64(base + c * 8 + 8 * LBOX - w * 640);
      o0 = fmaf(sc[w], bf_lo(v.x), o0); o1 = fmaf(sc[w], bf_hi(v.x), o1);
      o2 = fmaf(sc[w], bf_lo(v.y), o2); o3 = fmaf(sc[w], bf_hi(v.y), o3);
    }
    dst[c] = make_uint2(pack_bf16(o0, o1), pack_bf16(o2, o3));
  }
}
__device__ __forceinline__ uint32_t ta_slot(int i) { return i < 2 ? OFF_X + i * 32768 : 0; }

__global__ void __launch_bounds__(640, 1)
attn_kernel(const __grid_constant__ CUtensorMap tmA2, const __grid_constant__ CUtensorMap tmL, __nv_bfloat16* __restrict__ out, uint32_t one2) {
  extern __shared__ uint8_t smem_raw[];
  uint8_t* smem = reinterpret_cast<uint8_t*>((reinterpret_cast<uintptr_t>(smem_raw) + 1023) & ~(uintptr_t)1023);
  const uint32_t sbase = smem_u32(smem);
  const uint32_t dbase = sbase & 0x3FFFFu;
  const uint32_t bars = sbase + OFF_BAR;
  const int tid = threadIdx.x, wg = tid >> 7, warp = (tid >> 5) & 3, lane = tid & 31, g = lane >> 2, t = lane & 3;
  const int mb = blockIdx.x >> 3, nb = blockIdx.x & 7;
  const bool elected = (tid & 127) == 0;
  if (tid == 512) { prefetch_tmap(&tmL); prefetch_tmap(&tmA2); }
  if (tid == 0) {
    for (int i = 0; i < BAR_TE; i++) mbar_init(bars + i * 8, 1);
    for (int i = BAR_TE; i < BAR_TE + TSL; i++) mbar_init(bars + i * 8, 8);
    mbar_init(bars + BAR_OWN * 8, 4);
    mbar_init(bars + BAR_L * 8, 1);
    for (int i = 0; i < 10; i++) { mbar_init(bars + (BAR_WA + i) * 8, 1); mbar_init(bars + (BAR_WF + i) * 8, 8); }
    for (int i = 0; i < 4; i++) *reinterpret_cast<uint32_t*>(smem + OFF_BAR + CNT_KV * 8 + i * 4) = 0u;
    *reinterpret_cast<uint32_t*>(smem + OFF_BAR + CNT_TK * 8) = 0u;
    fence_mbar_init();
  }
  __syncthreads();
  auto tail_load = [&](int i) {
    const uint32_t fb = bars + (BAR_TA + i % TSL) * 8;
    mbar_expect_tx(fb, 32768);
    tma_3d(sbase + ta_slot(i % TSL), &tmA2, 0, mb * 128, i < 5 ? 10 + 2 * i : 2 * (i - 5), fb);
  };
  if (wg == 4) {
    asm volatile("setmaxnreg.dec.sync.aligned.u32 32;");
    pdl_wait();
    if (tid == 512) {
      for (int j = 0; j < KVR; j++) kv_load(sbase, j);
      mbar_expect_tx(bars + BAR_L * 8, 12 * LBOX);
      for (int i = 0; i < 12; i++) tma_2d(sbase + OFF_W + i * LBOX, &tmL, i * 160, blockIdx.x * 16 - 14 - (i & 1), bars + BAR_L * 8);
    }
    __syncwarp();
    mbar_wait(bars + BAR_L * 8, 0);
#pragma unroll 1
    for (int i = 0; i < 4; i++) local_attn(sbase + OFF_W, blockIdx.x * 16, warp * 4 + i, lane);
    signal_done(&g_doneL[blockIdx.x], wg, tid);
    if (tid == 512) {
      PROF2(0, 2);
      fence_proxy_async();
      mbar_expect_tx(bars + BAR_W * 8, 10 * 10240);
      for (int i = 0; i < 5; i++) bulk_g2s(sbase + OFF_W + i * 20480, g_wimg + ((8 + nb) * 10) * 10240 + i * 20480, 20480, bars + BAR_W * 8);
      wait_flags8(&g_doneL[mb * 8], 1u);
      tail_load(0); tail_load(1);
      mbar_wait(bars + BAR_OWN * 8, 0);
      for (int i = 2; i < 10; i++) {
        if (i >= TSL) mbar_wait(bars + (BAR_TE + i % TSL) * 8, (i / TSL - 1) & 1);
        if (i == 5) { wait_flags8(&g_done[mb * 8], 1u); PROF2(2, 0); }
        tail_load(i);
      }
    } else if (tid == 576) {
      mbar_wait(bars + BAR_OWN * 8, 0);
      asm volatile("red.release.gpu.global.add.u32 [%0], 1;" :: "l"(&g_done[blockIdx.x]) : "memory");
    } else if (tid == 544) {
      for (int i = 0; i < 5; i++) {
        mbar_wait(bars + (BAR_WF + i) * 8, 0);
        mbar_expect_tx(bars + (BAR_WA + i) * 8, 20480);
        bulk_g2s(sbase + OFF_W + i * 20480, g_wimg + nb * 102400 + i * 20480, 20480, bars + (BAR_WA + i) * 8);
      }
    }
    return;
  }
  asm volatile("setmaxnreg.inc.sync.aligned.u32 112;");
  pdl_wait();
  PROF(1, 1);
  uint32_t q[8], q2[6];
  const int rowA = (blockIdx.x * 8 + wg) * 64 + warp * 16 + g;
  {
    const uint32_t* r0 = reinterpret_cast<const uint32_t*>(g_q + (size_t)rowA * DH);
    const uint32_t* r1 = r0 + 8 * (DH / 2);
    const uint32_t* s0 = r0 + 256 * (DH / 2);
    const uint32_t* s1 = s0 + 8 * (DH / 2);
    q[0] = r0[t]; q[1] = r1[t]; q[2] = r0[t + 4]; q[3] = r1[t + 4];
    q[4] = t < 2 ? r0[8 + t] : 0u;
    q[5] = t < 2 ? r1[8 + t] : 0u;
    q2[0] = s0[t]; q2[1] = s1[t]; q2[2] = s0[t + 4]; q2[3] = s1[t + 4];
    q2[4] = t < 2 ? s0[8 + t] : 0u;
    q2[5] = t < 2 ? s1[8 + t] : 0u;
  }
  float kmax2 = 0.f, vmax = 0.f;
#pragma unroll
  for (int i = 0; i < 2; i++) {
    const float a = g_kmax2[lane + 32 * i];
    kmax2 = (a > kmax2 || a != a) ? a : kmax2;
    vmax = fmaxf(vmax, g_vmax[lane + 32 * i]);
  }
#pragma unroll
  for (int o = 1; o < 32; o <<= 1) {
    const float a = __shfl_xor_sync(0xffffffffu, kmax2, o);
    kmax2 = (a > kmax2 || a != a) ? a : kmax2;
    vmax = fmaxf(vmax, __shfl_xor_sync(0xffffffffu, vmax, o));
  }
  const float qlim = (vmax >= 0.00390625f && vmax <= 256.f) ? 9025.f / kmax2 : -1.f;
  PROF(1, 2);
#pragma unroll 1
  for (int it = 0; it < 2; it++) {
    const int row0 = rowA + it * 256;
    if (it == 1) {
#pragma unroll
      for (int i = 0; i < 6; i++) q[i] = q2[i];
    }
    float n0 = bf_lo(q[0]) * bf_lo(q[0]) + bf_hi(q[0]) * bf_hi(q[0]) + bf_lo(q[2]) * bf_lo(q[2]) + bf_hi(q[2]) * bf_hi(q[2]) +
               bf_lo(q[4]) * bf_lo(q[4]) + bf_hi(q[4]) * bf_hi(q[4]);
    float n1 = bf_lo(q[1]) * bf_lo(q[1]) + bf_hi(q[1]) * bf_hi(q[1]) + bf_lo(q[3]) * bf_lo(q[3]) + bf_hi(q[3]) * bf_hi(q[3]) +
               bf_lo(q[5]) * bf_lo(q[5]) + bf_hi(q[5]) * bf_hi(q[5]);
    n0 += __shfl_xor_sync(0xffffffffu, n0, 1); n0 += __shfl_xor_sync(0xffffffffu, n0, 2);
    n1 += __shfl_xor_sync(0xffffffffu, n1, 1); n1 += __shfl_xor_sync(0xffffffffu, n1, 2);
    const bool safe = (n0 <= qlim) && (n1 <= qlim);
    uint32_t unsafe_any;
    asm volatile("{\n.reg .pred p, r;\nsetp.eq.u32 p, %1, 0;\nbarrier.cta.red.or.pred r, %2, 128, p;\nselp.u32 %0, 1, 0, r;\n}\n"
                 : "=r"(unsafe_any) : "r"((uint32_t)safe), "r"(wg + 1) : "memory");
    float O[12];
#pragma unroll
    for (int i = 0; i < 12; i++) O[i] = 0.f;
    if (!unsafe_any && t >= 2) { q[4] = q[5] = (t == 2) ? 0x3F804100u : 0x00003B80u; }
    q[6] = q[4]; q[7] = q[5];
    fence_regs(q);
    float m0 = -INFINITY, m1 = -INFINITY;
    if (!unsafe_any) attn_fast(q, O, sbase, it * NGRP, NGRP, elected, one2);
    else attn_slow(q, O, sbase, it * NGRP, NGRP, elected, m0, m1);
    const float l0 = __shfl_sync(0xffffffffu, O[8], (lane & ~3) | 2);
    const float l1 = __shfl_sync(0xffffffffu, O[10], (lane & ~3) | 2);
    const int tok = row0 >> 5;
    const float gt = g_gate[tok];
    const float i0 = gt / l0, i1 = gt / l1;
    uint32_t* o0 = reinterpret_cast<uint32_t*>(g_a2 + (size_t)tok * (2 * D_MODEL) + (row0 & 31) * DH);
    uint32_t* o1 = o0 + 8 * (DH / 2);
    o0[t] = pack_bf16(O[0] * i0, O[1] * i0); o1[t] = pack_bf16(O[2] * i1, O[3] * i1);
    o0[t + 4] = pack_bf16(O[4] * i0, O[5] * i0); o1[t + 4] = pack_bf16(O[6] * i1, O[7] * i1);
    if (t < 2) { o0[t + 8] = pack_bf16(O[8] * i0, O[9] * i0); o1[t + 8] = pack_bf16(O[10] * i1, O[11] * i1); }
  }
  uint32_t* ticket = reinterpret_cast<uint32_t*>(smem + OFF_BAR + CNT_TK * 8);
  if (elected) ticket[1 + wg] = atomicAdd(ticket, 1u);
  asm volatile("bar.sync %0, 128;" :: "r"(wg + 1) : "memory");
  if (elected) mbar_arrive(bars + BAR_OWN * 8);
  const int mt = ticket[1 + wg];
  PROF(1, 3);
  if (mt < 2) {
    float acc[40];
#pragma unroll
    for (int i = 0; i < 40; i++) acc[i] = 0.f;
    mbar_wait(bars + BAR_W * 8, 0);
    int sl = 0, ph = 0;
#pragma unroll 1
    for (int i = 0; i < 10; i++) {
      mbar_wait(bars + (BAR_TA + sl) * 8, ph);
      if (i >= 5) mbar_wait(bars + (BAR_WA + i - 5) * 8, 0);
      const uint32_t alo = ((dbase + ta_slot(sl) + mt * 8192) >> 4) | (1u << 16);
      const uint32_t blo = ((dbase + OFF_W + (i >= 5 ? i - 5 : i) * 20480) >> 4) | ((128u >> 4) << 16);
      fence_regs(acc);
      wg_fence();
#pragma unroll
      for (int k = 0; k < 8; k++)
        wgmma_ss_n80_tb(acc, mkd(alo + (k >> 2) * 1024 + (k & 3) * 2, DHI_SW128_K), mkd(blo + (k >> 2) * 640 + (k & 3) * 16, 1024u >> 4));
      wg_commit();
      wg_wait<0>();
      if (lane == 0) mbar_arrive(bars + (BAR_TE + sl) * 8);
      if (lane == 1 && i < 5) mbar_arrive(bars + (BAR_WF + i) * 8);
      if (++sl == TSL) { sl = 0; ph ^= 1; }
    }
    wg_wait<0>();
    fence_regs(acc);
    asm volatile("bar.sync %0, 128;" :: "r"(wg + 1) : "memory");
    const uint32_t so = OFF_X + warp * 16384 + mt * 8192;
    const int row0 = mb * 128 + mt * 64 + warp * 16;
    store_tile_bf16<80>(acc, 1.0f, sbase + so, smem + so, out + (size_t)row0 * D_MODEL + nb * 80, D_MODEL, lane);
  }
}

typedef CUresult (*EncodeFn)(CUtensorMap*, CUtensorMapDataType, cuuint32_t, void*, const cuuint64_t*, const cuuint64_t*,
                             const cuuint32_t*, const cuuint32_t*, CUtensorMapInterleave, CUtensorMapSwizzle,
                             CUtensorMapL2promotion, CUtensorMapFloatOOBfill);

void make_map(EncodeFn fn, CUtensorMap* tm, const void* ptr, int rank, const cuuint64_t* dims, const cuuint64_t* strides,
              const cuuint32_t* box, CUtensorMapSwizzle sw) {
  const cuuint32_t es[3] = {1, 1, 1};
  fn(tm, CU_TENSOR_MAP_DATA_TYPE_BFLOAT16, rank, const_cast<void*>(ptr), dims, strides, box, es, CU_TENSOR_MAP_INTERLEAVE_NONE, sw,
     CU_TENSOR_MAP_L2_PROMOTION_L2_256B, CU_TENSOR_MAP_FLOAT_OOB_FILL_NONE);
}
void map_a(EncodeFn fn, CUtensorMap* tm, const void* p, int rows, int cols, int box_rows) {
  const cuuint64_t dims[2] = {(cuuint64_t)cols, (cuuint64_t)rows};
  const cuuint64_t str[1] = {(cuuint64_t)cols * 2};
  const cuuint32_t box[2] = {64, (cuuint32_t)box_rows};
  make_map(fn, tm, p, 2, dims, str, box, CU_TENSOR_MAP_SWIZZLE_128B);
}
void map_w(EncodeFn fn, CUtensorMap* tm, const void* p, int K, int N, int atom, CUtensorMapSwizzle sw) {
  const cuuint64_t dims[3] = {(cuuint64_t)atom, (cuuint64_t)K, (cuuint64_t)(N / atom)};
  const cuuint64_t str[2] = {(cuuint64_t)N * 2, (cuuint64_t)atom * 2};
  const cuuint32_t box[3] = {(cuuint32_t)atom, 64, 5};
  make_map(fn, tm, p, 3, dims, str, box, sw);
}

template <typename... KArgs, typename... Args>
void launch(void (*kern)(KArgs...), int grid, int block, int smem, bool pdl, Args... args) {
  cudaLaunchConfig_t cfg = {};
  cfg.gridDim = dim3(grid); cfg.blockDim = dim3(block); cfg.dynamicSmemBytes = smem; cfg.stream = cudaStreamPerThread;
  cudaLaunchAttribute at[1];
  at[0].id = cudaLaunchAttributeProgrammaticStreamSerialization;
  at[0].val.programmaticStreamSerializationAllowed = 1;
  cfg.attrs = at; cfg.numAttrs = pdl ? 1 : 0;
  cudaLaunchKernelEx(&cfg, kern, KArgs(args)...);
}

}

extern "C" void kernel_launch(void* const* d_in, const int* in_sizes, int n_in, void* d_out, int out_size) {
  (void)in_sizes; (void)n_in; (void)out_size;
  const __nv_bfloat16* x = (const __nv_bfloat16*)d_in[0];
  const __nv_bfloat16* wq = (const __nv_bfloat16*)d_in[1];
  const __nv_bfloat16* wk = (const __nv_bfloat16*)d_in[2];
  const __nv_bfloat16* wv = (const __nv_bfloat16*)d_in[3];
  const __nv_bfloat16* woA = (const __nv_bfloat16*)d_in[4];
  const __nv_bfloat16* wqkv = (const __nv_bfloat16*)d_in[6];
  const __nv_bfloat16* woB = (const __nv_bfloat16*)d_in[7];
  const __nv_bfloat16* gate_w = (const __nv_bfloat16*)d_in[8];

  static EncodeFn enc = nullptr;
  static void* a2_ptr = nullptr;
  static void* qkv_ptr = nullptr;
  if (!enc) {
    void* fp = nullptr;
    cudaDriverEntryPointQueryResult qr;
    cudaGetDriverEntryPoint("cuTensorMapEncodeTiled", &fp, cudaEnableDefault, &qr);
    enc = (EncodeFn)fp;
    cudaGetSymbolAddress(&a2_ptr, g_a2);
    cudaGetSymbolAddress(&qkv_ptr, g_qkv);
    cudaFuncSetAttribute(proj_kernel, cudaFuncAttributeMaxDynamicSharedMemorySize, K1_SMEM);
    cudaFuncSetAttribute(attn_kernel, cudaFuncAttributeMaxDynamicSharedMemorySize, K2_SMEM);
  }
  CUtensorMap tmX, tmWq, tmWqkv, tmA2, tmL;
  {
    const cuuint64_t dims[2] = {3 * D_MODEL, S_LEN};
    const cuuint64_t str[1] = {3 * D_MODEL * 2};
    const cuuint32_t box[2] = {160, 32};
    make_map(enc, &tmL, qkv_ptr, 2, dims, str, box, CU_TENSOR_MAP_SWIZZLE_NONE);
  }
  map_a(enc, &tmX, x, S_LEN, D_MODEL, 256);
  map_w(enc, &tmWq, wq, D_MODEL, D_MODEL, 32, CU_TENSOR_MAP_SWIZZLE_64B);
  map_w(enc, &tmWqkv, wqkv, D_MODEL, 3 * D_MODEL, 32, CU_TENSOR_MAP_SWIZZLE_64B);
  {
    const cuuint64_t dims[3] = {64, S_LEN, 2 * D_MODEL / 64};
    const cuuint64_t str[2] = {2 * D_MODEL * 2, 128};
    const cuuint32_t box[3] = {64, 128, 2};
    make_map(enc, &tmA2, a2_ptr, 3, dims, str, box, CU_TENSOR_MAP_SWIZZLE_128B);
  }

  launch(proj_kernel, 132, 512, K1_SMEM, false, tmX, tmWq, tmWqkv, wk, wv, gate_w, woA, woB);
  launch(attn_kernel, 128, 640, K2_SMEM, true, tmA2, tmL, (__nv_bfloat16*)d_out, 0x3F803F80u);
}
```

```cpp
#include <cuda_runtime.h>
#include <cuda_bf16.h>
#include <cuda.h>
#include <stdint.h>

namespace {

constexpr int S_LEN = 2048, D_MODEL = 640, DH = 20;

constexpr int GRP = 128;
constexpr int PLANE = GRP * 16;
constexpr int GRP_BYTES = GRP * 16 * 6;
constexpr int NGRP = S_LEN / GRP;
#define TMASKV 0x6DB6u
constexpr uint32_t TMASK = TMASKV;

__device__ __align__(1024) __nv_bfloat16 g_q[S_LEN * D_MODEL];
__device__ __align__(1024) __nv_bfloat16 g_qkv[S_LEN * 3 * D_MODEL];
__device__ __align__(1024) __nv_bfloat16 g_a2[S_LEN * 2 * D_MODEL];
__device__ __align__(1024) uint8_t g_kvimg[NGRP * GRP_BYTES];
__device__ __align__(1024) uint8_t g_wimg[2 * 8 * 10 * 10240];
__device__ float g_gate[S_LEN];
__device__ float g_kmax2[64];
__device__ float g_vmax[64];
__device__ __align__(32) unsigned int g_doneL[128];
__device__ __align__(32) unsigned int g_done[128];

#define PROF(k, slot)
#define PROF2(k, slot)
__device__ __forceinline__ uint32_t smem_u32(const void* p) { return (uint32_t)__cvta_generic_to_shared(p); }
__device__ __forceinline__ uint64_t mkd(uint32_t lo, uint32_t hi) {
  uint64_t d; asm("mov.b64 %0, {%1, %2};" : "=l"(d) : "r"(lo), "r"(hi)); return d;
}
__device__ __forceinline__ void wg_fence() { asm volatile("wgmma.fence.sync.aligned;" ::: "memory"); }
__device__ __forceinline__ void wg_commit() { asm volatile("wgmma.commit_group.sync.aligned;" ::: "memory"); }
template <int N> __device__ __forceinline__ void wg_wait() { asm volatile("wgmma.wait_group.sync.aligned %0;" :: "n"(N) : "memory"); }
template <int N> __device__ __forceinline__ void fence_regs(float (&d)[N]) {
#pragma unroll
  for (int i = 0; i < N; i++) asm volatile("" : "+f"(d[i]) :: "memory");
}
template <int N> __device__ __forceinline__ void fence_regs(uint32_t (&d)[N]) {
#pragma unroll
  for (int i = 0; i < N; i++) asm volatile("" : "+r"(d[i]) :: "memory");
}
__device__ __forceinline__ void mbar_init(uint32_t bar, uint32_t cnt) { asm volatile("mbarrier.init.shared::cta.b64 [%0], %1;" :: "r"(bar), "r"(cnt)); }
__device__ __forceinline__ void mbar_expect_tx(uint32_t bar, uint32_t bytes) {
  asm volatile("mbarrier.arrive.expect_tx.shared::cta.b64 _, [%0], %1;" :: "r"(bar), "r"(bytes) : "memory");
}
__device__ __forceinline__ void mbar_arrive(uint32_t bar) { asm volatile("mbarrier.arrive.shared::cta.b64 _, [%0];" :: "r"(bar) : "memory"); }
#define WAIT_HINT 20000u
__device__ __forceinline__ void mbar_wait(uint32_t bar, uint32_t parity) {
  asm volatile("{\n.reg .pred p;\nWAIT_%=:\nmbarrier.try_wait.parity.shared::cta.b64 p, [%0], %1, %2;\n@p bra DONE_%=;\nbra WAIT_%=;\nDONE_%=:\n}\n"
               :: "r"(bar), "r"(parity), "r"(WAIT_HINT) : "memory");
}
__device__ __forceinline__ void fence_mbar_init() { asm volatile("fence.mbarrier_init.release.cluster;" ::: "memory"); }
__device__ __forceinline__ void fence_proxy_async() { asm volatile("fence.proxy.async.shared::cta;" ::: "memory"); }
__device__ __forceinline__ void bulk_g2s(uint32_t dst, const void* src, uint32_t bytes, uint32_t bar) {
  asm volatile("cp.async.bulk.shared::cluster.global.mbarrier::complete_tx::bytes [%0], [%1], %2, [%3];"
               :: "r"(dst), "l"(src), "r"(bytes), "r"(bar) : "memory");
}
__device__ __forceinline__ void tma_2d(uint32_t dst, const CUtensorMap* tm, int c0, int c1, uint32_t bar) {
  asm volatile("cp.async.bulk.tensor.2d.shared::cluster.global.mbarrier::complete_tx::bytes [%0], [%1, {%3, %4}], [%2];"
               :: "r"(dst), "l"((uint64_t)tm), "r"(bar), "r"(c0), "r"(c1) : "memory");
}
__device__ __forceinline__ void tma_3d(uint32_t dst, const CUtensorMap* tm, int c0, int c1, int c2, uint32_t bar) {
  asm volatile("cp.async.bulk.tensor.3d.shared::cluster.global.mbarrier::complete_tx::bytes [%0], [%1, {%3, %4, %5}], [%2];"
               :: "r"(dst), "l"((uint64_t)tm), "r"(bar), "r"(c0), "r"(c1), "r"(c2) : "memory");
}
__device__ __forceinline__ void prefetch_tmap(const CUtensorMap* tm) { asm volatile("prefetch.tensormap [%0];" :: "l"((uint64_t)tm) : "memory"); }
__device__ __forceinline__ void pdl_wait() { asm volatile("griddepcontrol.wait;" ::: "memory"); }
__device__ __forceinline__ void pdl_launch() { asm volatile("griddepcontrol.launch_dependents;" ::: "memory"); }
__device__ __forceinline__ float ex2(float x) { float y; asm("ex2.approx.ftz.f32 %0, %1;" : "=f"(y) : "f"(x)); return y; }
__device__ __forceinline__ uint32_t pack_bf16(float lo, float hi) {
  uint32_t r; asm("cvt.rn.bf16x2.f32 %0, %1, %2;" : "=r"(r) : "f"(hi), "f"(lo)); return r;
}
__device__ __forceinline__ float bf_lo(uint32_t x) { return __uint_as_float(x << 16); }
__device__ __forceinline__ float bf_hi(uint32_t x) { return __uint_as_float(x & 0xffff0000u); }
__device__ __forceinline__ void stsm4(uint32_t addr, uint32_t r0, uint32_t r1, uint32_t r2, uint32_t r3) {
  asm volatile("stmatrix.sync.aligned.m8n8.x4.shared.b16 [%0], {%1, %2, %3, %4};" :: "r"(addr), "r"(r0), "r"(r1), "r"(r2), "r"(r3) : "memory");
}

__device__ __forceinline__ void wgmma_ss_n160_tb(float (&d)[80], uint64_t descA, uint64_t descB) {
  asm volatile("wgmma.mma_async.sync.aligned.m64n160k16.f32.bf16.bf16 {%0, %1, %2, %3, %4, %5, %6, %7, %8, %9, %10, %11, %12, %13, %14, %15, %16, %17, %18, %19, %20, %21, %22, %23, %24, %25, %26, %27, %28, %29, %30, %31, %32, %33, %34, %35, %36, %37, %38, %39, %40, %41, %42, %43, %44, %45, %46, %47, %48, %49, %50, %51, %52, %53, %54, %55, %56, %57, %58, %59, %60, %61, %62, %63, %64, %65, %66, %67, %68, %69, %70, %71, %72, %73, %74, %75, %76, %77, %78, %79}, %80, %81, 1, 1, 1, 0, 1;\n"
    : "+f"(d[0]), "+f"(d[1]), "+f"(d[2]), "+f"(d[3]), "+f"(d[4]), "+f"(d[5]), "+f"(d[6]), "+f"(d[7]), "+f"(d[8]), "+f"(d[9]), "+f"(d[10]), "+f"(d[11]), "+f"(d[12]), "+f"(d[13]), "+f"(d[14]), "+f"(d[15]), "+f"(d[16]), "+f"(d[17]), "+f"(d[18]), "+f"(d[19]), "+f"(d[20]), "+f"(d[21]), "+f"(d[22]), "+f"(d[23]), "+f"(d[24]), "+f"(d[25]), "+f"(d[26]), "+f"(d[27]), "+f"(d[28]), "+f"(d[29]), "+f"(d[30]), "+f"(d[31]), "+f"(d[32]), "+f"(d[33]), "+f"(d[34]), "+f"(d[35]), "+f"(d[36]), "+f"(d[37]), "+f"(d[38]), "+f"(d[39]), "+f"(d[40]), "+f"(d[41]), "+f"(d[42]), "+f"(d[43]), "+f"(d[44]), "+f"(d[45]), "+f"(d[46]), "+f"(d[47]), "+f"(d[48]), "+f"(d[49]), "+f"(d[50]), "+f"(d[51]), "+f"(d[52]), "+f"(d[53]), "+f"(d[54]), "+f"(d[55]), "+f"(d[56]), "+f"(d[57]), "+f"(d[58]), "+f"(d[59]), "+f"(d[60]), "+f"(d[61]), "+f"(d[62]), "+f"(d[63]), "+f"(d[64]), "+f"(d[65]), "+f"(d[66]), "+f"(d[67]), "+f"(d[68]), "+f"(d[69]), "+f"(d[70]), "+f"(d[71]), "+f"(d[72]), "+f"(d[73]), "+f"(d[74]), "+f"(d[75]), "+f"(d[76]), "+f"(d[77]), "+f"(d[78]), "+f"(d[79])
    : "l"(descA), "l"(descB));
}
__device__ __forceinline__ void wgmma_ss_n48_tb(float (&d)[24], uint64_t descA, uint64_t descB) {
  asm volatile("wgmma.mma_async.sync.aligned.m64n48k16.f32.bf16.bf16 {%0, %1, %2, %3, %4, %5, %6, %7, %8, %9, %10, %11, %12, %13, %14, %15, %16, %17, %18, %19, %20, %21, %22, %23}, %24, %25, 1, 1, 1, 0, 1;\n"
    : "+f"(d[0]), "+f"(d[1]), "+f"(d[2]), "+f"(d[3]), "+f"(d[4]), "+f"(d[5]), "+f"(d[6]), "+f"(d[7]), "+f"(d[8]), "+f"(d[9]), "+f"(d[10]), "+f"(d[11]), "+f"(d[12]), "+f"(d[13]), "+f"(d[14]), "+f"(d[15]), "+f"(d[16]), "+f"(d[17]), "+f"(d[18]), "+f"(d[19]), "+f"(d[20]), "+f"(d[21]), "+f"(d[22]), "+f"(d[23])
    : "l"(descA), "l"(descB));
}
__device__ __forceinline__ void wgmma_ss_n80_tb(float (&d)[40], uint64_t descA, uint64_t descB) {
  asm volatile("wgmma.mma_async.sync.aligned.m64n80k16.f32.bf16.bf16 {%0, %1, %2, %3, %4, %5, %6, %7, %8, %9, %10, %11, %12, %13, %14, %15, %16, %17, %18, %19, %20, %21, %22, %23, %24, %25, %26, %27, %28, %29, %30, %31, %32, %33, %34, %35, %36, %37, %38, %39}, %40, %41, 1, 1, 1, 0, 1;\n"
    : "+f"(d[0]), "+f"(d[1]), "+f"(d[2]), "+f"(d[3]), "+f"(d[4]), "+f"(d[5]), "+f"(d[6]), "+f"(d[7]), "+f"(d[8]), "+f"(d[9]), "+f"(d[10]), "+f"(d[11]), "+f"(d[12]), "+f"(d[13]), "+f"(d[14]), "+f"(d[15]), "+f"(d[16]), "+f"(d[17]), "+f"(d[18]), "+f"(d[19]), "+f"(d[20]), "+f"(d[21]), "+f"(d[22]), "+f"(d[23]), "+f"(d[24]), "+f"(d[25]), "+f"(d[26]), "+f"(d[27]), "+f"(d[28]), "+f"(d[29]), "+f"(d[30]), "+f"(d[31]), "+f"(d[32]), "+f"(d[33]), "+f"(d[34]), "+f"(d[35]), "+f"(d[36]), "+f"(d[37]), "+f"(d[38]), "+f"(d[39])
    : "l"(descA), "l"(descB));
}
template <int SCALE_D>
__device__ __forceinline__ void wgmma_rs_n64(float (&d)[32], uint32_t a0, uint32_t a1, uint32_t a2, uint32_t a3, uint64_t descB) {
  asm volatile("wgmma.mma_async.sync.aligned.m64n64k16.f32.bf16.bf16 {%0, %1, %2, %3, %4, %5, %6, %7, %8, %9, %10, %11, %12, %13, %14, %15, %16, %17, %18, %19, %20, %21, %22, %23, %24, %25, %26, %27, %28, %29, %30, %31}, {%32, %33, %34, %35}, %36, %37, 1, 1, 0;\n"
    : "+f"(d[0]), "+f"(d[1]), "+f"(d[2]), "+f"(d[3]), "+f"(d[4]), "+f"(d[5]), "+f"(d[6]), "+f"(d[7]), "+f"(d[8]), "+f"(d[9]), "+f"(d[10]), "+f"(d[11]), "+f"(d[12]), "+f"(d[13]), "+f"(d[14]), "+f"(d[15]), "+f"(d[16]), "+f"(d[17]), "+f"(d[18]), "+f"(d[19]), "+f"(d[20]), "+f"(d[21]), "+f"(d[22]), "+f"(d[23]), "+f"(d[24]), "+f"(d[25]), "+f"(d[26]), "+f"(d[27]), "+f"(d[28]), "+f"(d[29]), "+f"(d[30]), "+f"(d[31])
    : "r"(a0), "r"(a1), "r"(a2), "r"(a3), "l"(descB), "n"(SCALE_D));
}
template <int SCALE_D>
__device__ __forceinline__ void wgmma_rs_n128(float (&d)[64], uint32_t a0, uint32_t a1, uint32_t a2, uint32_t a3, uint64_t descB) {
  asm volatile("wgmma.mma_async.sync.aligned.m64n128k16.f32.bf16.bf16 {%0, %1, %2, %3, %4, %5, %6, %7, %8, %9, %10, %11, %12, %13, %14, %15, %16, %17, %18, %19, %20, %21, %22, %23, %24, %25, %26, %27, %28, %29, %30, %31, %32, %33, %34, %35, %36, %37, %38, %39, %40, %41, %42, %43, %44, %45, %46, %47, %48, %49, %50, %51, %52, %53, %54, %55, %56, %57, %58, %59, %60, %61, %62, %63}, {%64, %65, %66, %67}, %68, %69, 1, 1, 0;\n"
    : "+f"(d[0]), "+f"(d[1]), "+f"(d[2]), "+f"(d[3]), "+f"(d[4]), "+f"(d[5]), "+f"(d[6]), "+f"(d[7]), "+f"(d[8]), "+f"(d[9]), "+f"(d[10]), "+f"(d[11]), "+f"(d[12]), "+f"(d[13]), "+f"(d[14]), "+f"(d[15]), "+f"(d[16]), "+f"(d[17]), "+f"(d[18]), "+f"(d[19]), "+f"(d[20]), "+f"(d[21]), "+f"(d[22]), "+f"(d[23]), "+f"(d[24]), "+f"(d[25]), "+f"(d[26]), "+f"(d[27]), "+f"(d[28]), "+f"(d[29]), "+f"(d[30]), "+f"(d[31]), "+f"(d[32]), "+f"(d[33]), "+f"(d[34]), "+f"(d[35]), "+f"(d[36]), "+f"(d[37]), "+f"(d[38]), "+f"(d[39]), "+f"(d[40]), "+f"(d[41]), "+f"(d[42]), "+f"(d[43]), "+f"(d[44]), "+f"(d[45]), "+f"(d[46]), "+f"(d[47]), "+f"(d[48]), "+f"(d[49]), "+f"(d[50]), "+f"(d[51]), "+f"(d[52]), "+f"(d[53]), "+f"(d[54]), "+f"(d[55]), "+f"(d[56]), "+f"(d[57]), "+f"(d[58]), "+f"(d[59]), "+f"(d[60]), "+f"(d[61]), "+f"(d[62]), "+f"(d[63])
    : "r"(a0), "r"(a1), "r"(a2), "r"(a3), "l"(descB), "n"(SCALE_D));
}
template <int SCALE_D>
__device__ __forceinline__ void wgmma_rs_n24_tb(float (&d)[12], uint32_t a0, uint32_t a1, uint32_t a2, uint32_t a3, uint64_t descB) {
  asm volatile("wgmma.mma_async.sync.aligned.m64n24k16.f32.bf16.bf16 {%0, %1, %2, %3, %4, %5, %6, %7, %8, %9, %10, %11}, {%12, %13, %14, %15}, %16, %17, 1, 1, 1;\n"
    : "+f"(d[0]), "+f"(d[1]), "+f"(d[2]), "+f"(d[3]), "+f"(d[4]), "+f"(d[5]), "+f"(d[6]), "+f"(d[7]), "+f"(d[8]), "+f"(d[9]), "+f"(d[10]), "+f"(d[11])
    : "r"(a0), "r"(a1), "r"(a2), "r"(a3), "l"(descB), "n"(SCALE_D));
}

constexpr uint32_t DHI_SW128_K = (1024 >> 4) | (1u << 30);
constexpr uint32_t DHI_SW64_MN = (512 >> 4) | (2u << 30);

template <int NC>
__device__ __forceinline__ void store_tile_bf16(const float (&acc)[NC / 2], float scale, uint32_t stage, uint8_t* stage_ptr,
                                                __nv_bfloat16* gdst, int gpitch, int lane) {
  constexpr int PITCH = NC * 2 + 16;
  const uint32_t waddr = stage + ((lane & 7) + ((lane >> 3) & 1) * 8) * PITCH + (lane >> 4) * 16;
#pragma unroll
  for (int j = 0; j < NC / 16; j++) {
    stsm4(waddr + j * 32, pack_bf16(acc[8 * j] * scale, acc[8 * j + 1] * scale), pack_bf16(acc[8 * j + 2] * scale, acc[8 * j + 3] * scale),
          pack_bf16(acc[8 * j + 4] * scale, acc[8 * j + 5] * scale), pack_bf16(acc[8 * j + 6] * scale, acc[8 * j + 7] * scale));
  }
  __syncwarp();
  constexpr int CPR = NC / 8;
#pragma unroll
  for (int i = 0; i < CPR / 2; i++) {
    const int c = i * 32 + lane, r = c / CPR, cc = c % CPR;
    const uint4 v = *reinterpret_cast<const uint4*>(stage_ptr + r * PITCH + cc * 16);
    *reinterpret_cast<uint4*>(gdst + (size_t)r * gpitch + cc * 8) = v;
  }
}

__device__ __forceinline__ void signal_done(unsigned int* flag, int wg, int tid) {
  asm volatile("bar.sync %0, 128;" :: "r"(wg + 1) : "memory");
  if ((tid & 127) == 0) asm volatile("red.release.gpu.global.add.u32 [%0], 1;" :: "l"(flag) : "memory");
}
__device__ __forceinline__ void wait_flags8(const unsigned int* f, unsigned int target) {
  for (int spin = 0; spin < (1 << 26); spin++) {
    unsigned int a, b, c, d, e, g, h, i;
    asm volatile("ld.volatile.global.v4.u32 {%0, %1, %2, %3}, [%4];" : "=r"(a), "=r"(b), "=r"(c), "=r"(d) : "l"(f) : "memory");
    asm volatile("ld.volatile.global.v4.u32 {%0, %1, %2, %3}, [%4];" : "=r"(e), "=r"(g), "=r"(h), "=r"(i) : "l"(f + 4) : "memory");
    if (min(min(min(a, b), min(c, d)), min(min(e, g), min(h, i))) >= target) break;
    __nanosleep(32);
  }
  asm volatile("fence.acq_rel.gpu;" ::: "memory");
  asm volatile("fence.proxy.async;" ::: "memory");
}

#define RP_LD 3
#define RP_ST 7
constexpr int K1_STAGES = 4;
constexpr int K1_A_BYTES = 256 * 128;
constexpr int K1_B_BYTES = 64 * 160 * 2;
constexpr int K1_STAGE = K1_A_BYTES + K1_B_BYTES;
constexpr int K1_SMEM = 5 * K1_A_BYTES + 61440 + 1024;
constexpr int KV_STAGES = 5;
constexpr int KVW_OFF = KV_STAGES * K1_A_BYTES;

__global__ void __launch_bounds__(512, 1)
proj_kernel(const __grid_constant__ CUtensorMap tmX, const __grid_constant__ CUtensorMap tmWq, const __grid_constant__ CUtensorMap tmWqkv,
            const __nv_bfloat16* __restrict__ wk, const __nv_bfloat16* __restrict__ wv, const __nv_bfloat16* __restrict__ gate_w,
            const __nv_bfloat16* __restrict__ woA, const __nv_bfloat16* __restrict__ woB) {
  extern __shared__ uint8_t smem_raw[];
  __shared__ __align__(8) uint64_t bar_full[KV_STAGES], bar_empty[KV_STAGES];
  uint8_t* smem = reinterpret_cast<uint8_t*>((reinterpret_cast<uintptr_t>(smem_raw) + 1023) & ~(uintptr_t)1023);
  const uint32_t sbase = smem_u32(smem);
  const uint32_t dbase = sbase & 0x3FFFFu;
  const int tid = threadIdx.x, warp = tid >> 5, lane = tid & 31;
  const bool is_kv = blockIdx.x >= 128;
  PROF(0, 0);
  if (tid == 32) { prefetch_tmap(&tmX); prefetch_tmap((blockIdx.x & 15) < 4 ? &tmWq : &tmWqkv); }
  if (tid == 0) {
    for (int i = 0; i < KV_STAGES; i++) { mbar_init(smem_u32(&bar_full[i]), 1); mbar_init(smem_u32(&bar_empty[i]), is_kv ? 8 : 16); }
    fence_mbar_init();
  }
  uint2 wa[2][5], wb[2][5]; uint32_t gw[2];
  if (is_kv && tid < 320) {
#pragma unroll
    for (int r = 0; r < 2; r++) {
      const int k = tid + r * 320;
      const uint2* pk = reinterpret_cast<const uint2*>(wk + k * 20);
      const uint2* pv = reinterpret_cast<const uint2*>(wv + k * 20);
#pragma unroll
      for (int i = 0; i < 5; i++) { wa[r][i] = __ldg(pk + i); wb[r][i] = __ldg(pv + i); }
      gw[r] = (uint32_t)__bfloat16_as_ushort(gate_w[k]);
    }
  }
  __syncthreads();
  if (tid == 480 && !is_kv) { g_done[blockIdx.x] = 0u; g_doneL[blockIdx.x] = 0u; }
  pdl_launch();

  if (!is_kv) {
    const int mb = blockIdx.x >> 4, nb = blockIdx.x & 15;
    const CUtensorMap* tw = nb < 4 ? &tmWq : &tmWqkv;
    const int j0 = (nb < 4 ? nb : nb - 4) * 5;
    auto load = [&](int kt) {
      const int s = kt % K1_STAGES;
      const uint32_t fb = smem_u32(&bar_full[s]);
      mbar_expect_tx(fb, K1_STAGE);
      tma_2d(sbase + s * K1_STAGE, &tmX, kt * 64, mb * 256, fb);
      tma_3d(sbase + s * K1_STAGE + K1_A_BYTES, tw, 0, kt * 64, j0, fb);
    };
    if (tid == 0) for (int kt = 0; kt < K1_STAGES; kt++) load(kt);
    __syncwarp();
    uint4 wv2[2];
    const int rq = blockIdx.x * 400 + tid - 112;
    const int rhalf = rq >= 25600, rr = rq - rhalf * 25600, rk = 2 * (rr / 80), rch = rr % 80;
    {
      const int wg = warp >> 2;
      float acc[80];
#pragma unroll
      for (int i = 0; i < 80; i++) acc[i] = 0.f;
      for (int kt = 0; kt < 10; kt++) {
        const int s = kt % K1_STAGES;
        mbar_wait(smem_u32(&bar_full[s]), (kt / K1_STAGES) & 1);
        const uint32_t alo = ((dbase + s * K1_STAGE + wg * 8192) >> 4) | (1u << 16);
        const uint32_t blo = ((dbase + s * K1_STAGE + K1_A_BYTES) >> 4) | ((4096u >> 4) << 16);
        fence_regs(acc);
        wg_fence();
#pragma unroll
        for (int k = 0; k < 4; k++) wgmma_ss_n160_tb(acc, mkd(alo + k * 2, DHI_SW128_K), mkd(blo + k * 64, DHI_SW64_MN));
        wg_commit();
        if (kt == RP_LD && tid >= 112) {
          const uint4* src = reinterpret_cast<const uint4*>((rhalf ? woB : woA) + rk * D_MODEL + rch * 8);
          wv2[0] = __ldg(src); wv2[1] = __ldg(src + D_MODEL / 8);
        }
        if (kt == RP_ST && tid >= 112) {
          uint4* dst = reinterpret_cast<uint4*>(g_wimg + ((rhalf * 8 + rch / 10) * 10 + (rk >> 6)) * 10240 + (rch % 10) * 1024 + (rk & 63) * 16);
          dst[0] = wv2[0]; dst[1] = wv2[1];
        }
        __syncwarp();
        if (kt > 0 && kt - 1 + K1_STAGES < 10) {
          wg_wait<1>();
          const uint32_t eb = smem_u32(&bar_empty[(kt - 1) % K1_STAGES]);
          if (lane == 0) mbar_arrive(eb);
          if (tid == 0) { mbar_wait(eb, ((kt - 1) / K1_STAGES) & 1); load(kt - 1 + K1_STAGES); }
          __syncwarp();
        }
      }
      wg_wait<0>();
      fence_regs(acc);
      PROF(0, 1);
      asm volatile("bar.sync %0, 128;" :: "r"(wg + 1) : "memory");
      const int w4 = warp & 3;
      const uint32_t off = w4 * K1_STAGE + wg * 8192;
      const int row0 = mb * 256 + wg * 64 + w4 * 16;
      if (nb < 4) {
        store_tile_bf16<160>(acc, 0.22360679774997896f * 1.4426950408889634f, sbase + off, smem + off,
                             g_q + (size_t)row0 * D_MODEL + nb * 160, D_MODEL, lane);
      } else {
        store_tile_bf16<160>(acc, 1.0f, sbase + off, smem + off, g_qkv + (size_t)row0 * (3 * D_MODEL) + (nb - 4) * 160, 3 * D_MODEL, lane);
      }
    }
  } else {
    const int cb = blockIdx.x - 128;
    if (warp == 8 && lane == 0) {
      for (int it = 0; it < KV_STAGES; it++) {
        const uint32_t fb = smem_u32(&bar_full[it]);
        mbar_expect_tx(fb, K1_A_BYTES);
        tma_2d(sbase + it * K1_A_BYTES, &tmX, it * 64, cb * 512, fb);
      }
    }
    __syncwarp();
    if (tid < 320) {
#pragma unroll
      for (int r = 0; r < 2; r++) {
        uint4* dst = reinterpret_cast<uint4*>(smem + KVW_OFF + (tid + r * 320) * 16);
        dst[0] = make_uint4(wa[r][0].x, wa[r][0].y, wa[r][1].x, wa[r][1].y);
        dst[640] = make_uint4(wa[r][2].x, wa[r][2].y, wa[r][3].x, wa[r][3].y);
        dst[1280] = make_uint4(wa[r][4].x, wa[r][4].y, 0u, 0u);
        dst[1920] = make_uint4(wb[r][0].x, wb[r][0].y, wb[r][1].x, wb[r][1].y);
        dst[2560] = make_uint4(wb[r][2].x, wb[r][2].y, wb[r][3].x, wb[r][3].y);
        dst[3200] = make_uint4(wb[r][4].x, wb[r][4].y, gw[r], 0u);
      }
    }
    fence_proxy_async();
    asm volatile("bar.sync 1, 512;" ::: "memory");
    PROF(0, 1);
    auto produce = [&](int it0, int it1) {
      for (int it = it0; it < it1; it++) {
        const int s = it % KV_STAGES;
        mbar_wait(smem_u32(&bar_empty[s]), (it / KV_STAGES - 1) & 1);
        const uint32_t fb = smem_u32(&bar_full[s]);
        mbar_expect_tx(fb, K1_A_BYTES);
        tma_2d(sbase + s * K1_A_BYTES, &tmX, (it >= 10 ? it - 10 : it) * 64, cb * 512 + (it >= 10 ? 256 : 0), fb);
      }
    };
    if (tid == 256) produce(KV_STAGES, 15);
    __syncwarp();
    {
      const int pass = warp >> 3, wg = (warp >> 2) & 1, w4 = warp & 3, g = lane >> 2, t = lane & 3;
      if (pass == 1) asm volatile("bar.sync 2, 512;" ::: "memory");
      {
        float acc[2][24];
#pragma unroll
        for (int i = 0; i < 24; i++) { acc[0][i] = 0.f; acc[1][i] = 0.f; }
        for (int kt = 0; kt < 10; kt++) {
          const int it = pass * 10 + kt, s = it % KV_STAGES;
          mbar_wait(smem_u32(&bar_full[s]), (it / KV_STAGES) & 1);
          const uint32_t alo = ((dbase + s * K1_A_BYTES + wg * 16384) >> 4) | (1u << 16);
          const uint32_t blo = ((dbase + KVW_OFF + kt * 1024) >> 4) | ((128u >> 4) << 16);
          fence_regs(acc[0]); fence_regs(acc[1]);
          wg_fence();
#pragma unroll
          for (int k = 0; k < 4; k++) {
            wgmma_ss_n48_tb(acc[0], mkd(alo + k * 2, DHI_SW128_K), mkd(blo + k * 16, 10240u >> 4));
            wgmma_ss_n48_tb(acc[1], mkd(alo + 512 + k * 2, DHI_SW128_K), mkd(blo + k * 16, 10240u >> 4));
          }
          wg_commit();
          if (kt > 0) {
            wg_wait<1>();
            if (lane == 0) mbar_arrive(smem_u32(&bar_empty[(it - 1) % KV_STAGES]));
          }
        }
        wg_wait<0>();
        fence_regs(acc[0]); fence_regs(acc[1]);
        if (lane == 0) mbar_arrive(smem_u32(&bar_empty[(pass * 10 + 9) % KV_STAGES]));
        if (pass == 0) asm volatile("bar.arrive 2, 512;" ::: "memory");
        PROF(0, 2);
        if (tid == 0) produce(15, 20);
        __syncwarp();
        float kmax2 = 0.f, vmax = 0.f;
#pragma unroll
        for (int hh = 0; hh < 4; hh++) {
          const int h = hh & 1;
          const float (&a)[24] = acc[hh >> 1];
          const int key = cb * 512 + pass * 256 + wg * 128 + (hh >> 1) * 64 + w4 * 16 + g + h * 8;
          const int grp = key >> 7, kk = key & 127;
          const bool poly = (TMASK >> (kk >> 3)) & 1;
          uint8_t* gp = g_kvimg + grp * GRP_BYTES;
          const uint32_t k0 = pack_bf16(a[2 * h], a[2 * h + 1]);
          const uint32_t k1 = pack_bf16(a[4 + 2 * h], a[5 + 2 * h]);
          uint32_t k2 = pack_bf16(a[8 + 2 * h], a[9 + 2 * h]);
          float n2 = bf_lo(k0) * bf_lo(k0) + bf_hi(k0) * bf_hi(k0) + bf_lo(k1) * bf_lo(k1) + bf_hi(k1) * bf_hi(k1);
          if (t < 2) {
            n2 += bf_lo(k2) * bf_lo(k2) + bf_hi(k2) * bf_hi(k2);
            k2 = pack_bf16(bf_lo(k2) * 0.5f, bf_hi(k2) * 0.5f);
          } else if (t == 2) k2 = poly ? pack_bf16(24.f, 2.5f) : pack_bf16(0.5f, 0.f);
          else k2 = poly ? pack_bf16(0.5f, 0.f) : 0u;
          *reinterpret_cast<uint32_t*>(gp + kk * 16 + t * 4) = k0;
          *reinterpret_cast<uint32_t*>(gp + PLANE + kk * 16 + t * 4) = k1;
          *reinterpret_cast<uint32_t*>(gp + 2 * PLANE + kk * 16 + t * 4) = k2;
          n2 += __shfl_xor_sync(0xffffffffu, n2, 1);
          n2 += __shfl_xor_sync(0xffffffffu, n2, 2);
          kmax2 = (n2 > kmax2 || n2 != n2) ? n2 : kmax2;
          uint32_t v0 = pack_bf16(a[12 + 2 * h], a[13 + 2 * h]);
          uint32_t v1 = pack_bf16(a[16 + 2 * h], a[17 + 2 * h]);
          uint32_t v2 = pack_bf16(a[20 + 2 * h], a[21 + 2 * h]);
          float vm = fmaxf(fmaxf(fabsf(bf_lo(v0)), fabsf(bf_hi(v0))), fmaxf(fabsf(bf_lo(v1)), fabsf(bf_hi(v1))));
          if (t < 2) vm = fmaxf(vm, fmaxf(fabsf(bf_lo(v2)), fabsf(bf_hi(v2))));
          else if (t == 2) {
            const float z = a[20 + 2 * h];
            g_gate[key] = 1.f / (1.f + __expf(-z));
            v2 = 0x00003F80u;
          } else v2 = 0u;
          vmax = fmaxf(vmax, vm);
          if (poly) { v0 ^= 0x80008000u; v1 ^= 0x80008000u; v2 ^= 0x80008000u; }
          uint8_t* vp = gp + 3 * PLANE + (kk >> 3) * 384 + (kk & 7) * 16 + t * 4;
          *reinterpret_cast<uint32_t*>(vp) = v0;
          *reinterpret_cast<uint32_t*>(vp + 128) = v1;
          *reinterpret_cast<uint32_t*>(vp + 256) = v2;
        }
#pragma unroll
        for (int o = 1; o < 32; o <<= 1) {
          const float a = __shfl_xor_sync(0xffffffffu, kmax2, o);
          kmax2 = (a > kmax2 || a != a) ? a : kmax2;
          vmax = fmaxf(vmax, __shfl_xor_sync(0xffffffffu, vmax, o));
        }
        if (lane == 0) { g_kmax2[cb * 16 + warp] = kmax2; g_vmax[cb * 16 + warp] = vmax; }
      }
    }
  }
}

__device__ __forceinline__ uint32_t ex2_pair_poly(float u0, float u1, uint32_t one2) {
  const uint32_t W = __byte_perm(__float_as_uint(u0), __float_as_uint(u1), 0x6521);
  uint32_t v; asm("lop3.b32 %0, %1, 0x007F007F, %2, 0xEA;" : "=r"(v) : "r"(W), "r"(one2));
  uint32_t L, p;
  asm("fma.rn.bf16x2 %0, %1, %2, %3;" : "=r"(L) : "r"(v), "r"(0x1f961f96u), "r"(0x9fe39fe3u));
  asm("fma.rn.bf16x2 %0, %1, %1, %2;" : "=r"(p) : "r"(L), "r"(0x00f500f5u));
  return W + p;
}
template <int JOFF>
__device__ __forceinline__ void softmax_slow(const float (&S)[32], uint32_t (&P)[16], float (&O)[12], float& m0, float& m1) {
  float a0 = m0, a1 = m1;
#pragma unroll
  for (int j = 0; j < 8; j++) {
    a0 = fmaxf(a0, fmaxf(S[4 * j], S[4 * j + 1]));
    a1 = fmaxf(a1, fmaxf(S[4 * j + 2], S[4 * j + 3]));
  }
  a0 = fmaxf(a0, __shfl_xor_sync(0xffffffffu, a0, 1)); a0 = fmaxf(a0, __shfl_xor_sync(0xffffffffu, a0, 2));
  a1 = fmaxf(a1, __shfl_xor_sync(0xffffffffu, a1, 1)); a1 = fmaxf(a1, __shfl_xor_sync(0xffffffffu, a1, 2));
  const float c0 = ex2(m0 - a0), c1 = ex2(m1 - a1);
  m0 = a0; m1 = a1;
#pragma unroll
  for (int j = 0; j < 3; j++) { O[4 * j] *= c0; O[4 * j + 1] *= c0; O[4 * j + 2] *= c1; O[4 * j + 3] *= c1; }
#pragma unroll
  for (int i = 0; i < 16; i++) {
    const float m = (i & 1) ? a1 : a0;
    const uint32_t p = pack_bf16(ex2(S[2 * i] - m), ex2(S[2 * i + 1] - m));
    P[i] = ((TMASK >> (JOFF + i / 2)) & 1) ? (p ^ 0x80008000u) : p;
  }
}
constexpr uint32_t DHI_KV = 128 >> 4;
__device__ __forceinline__ void issue_qk(float (&S)[32], const uint32_t (&q)[8], uint64_t base) {
  wgmma_rs_n64<0>(S, q[0], q[1], q[2], q[3], base + (uint64_t)((PLANE >> 4) << 16));
  wgmma_rs_n64<1>(S, q[4], q[5], q[6], q[7], base + (uint64_t)(2 * PLANE >> 4));
}
__device__ __forceinline__ void issue_pv(float (&O)[12], const uint32_t (&P)[16], uint64_t vbase) {
#pragma unroll
  for (int kk = 0; kk < 4; kk++)
    wgmma_rs_n24_tb<1>(O, P[4 * kk], P[4 * kk + 1], P[4 * kk + 2], P[4 * kk + 3], vbase + (uint64_t)(kk * (768 >> 4)));
}

constexpr uint32_t VOFF = ((3 * PLANE) >> 4) + ((384u >> 4) << 16);
constexpr int KVR = 4;
constexpr int OFF_W = KVR * GRP_BYTES;
constexpr int OFF_X = OFF_W + 10 * 10240;
constexpr int OFF_BAR = OFF_X + 4 * 16384;
constexpr int K2_SMEM = OFF_BAR + 512 + 1024;
constexpr int TSL = 7;
constexpr int BAR_KV = 0, BAR_W = 4, BAR_TA = 5, BAR_TE = 19, BAR_OWN = 33, BAR_L = 34, CNT_KV = 35, BAR_WA = 37, BAR_WF = 47, CNT_TK = 57, BAR_OWN0 = 60;
constexpr int NSTEP = 2 * NGRP;

__device__ __forceinline__ void kv_load(uint32_t sbase, int step) {
  const uint32_t bar = sbase + OFF_BAR + (BAR_KV + (step & (KVR - 1))) * 8;
  mbar_expect_tx(bar, GRP_BYTES);
  bulk_g2s(sbase + (step & (KVR - 1)) * GRP_BYTES, g_kvimg + (step & (NGRP - 1)) * GRP_BYTES, GRP_BYTES, bar);
}
__device__ __forceinline__ void kv_release(uint32_t sbase, int step, bool elected) {
  if (elected && step + KVR < NSTEP) {
    uint32_t old;
    asm volatile("atom.acq_rel.cta.shared::cta.inc.u32 %0, [%1], 3;" : "=r"(old) : "r"(sbase + OFF_BAR + CNT_KV * 8 + (step & (KVR - 1)) * 4) : "memory");
    if (old == 3u) kv_load(sbase, step + KVR);
  }
  __syncwarp();
}
__device__ __forceinline__ void kv_wait(uint32_t sbase, int step) {
  mbar_wait(sbase + OFF_BAR + (BAR_KV + (step & (KVR - 1))) * 8, (step / KVR) & 1);
}

__device__ __forceinline__ uint32_t kv_release_begin(uint32_t sbase, int slot, bool doit) {
  uint32_t old = 0;
  asm volatile("{\n.reg .pred p;\nsetp.ne.u32 p, %2, 0;\n@p atom.relaxed.cta.shared::cta.inc.u32 %0, [%1], 3;\n}\n"
               : "+r"(old) : "r"(sbase + OFF_BAR + CNT_KV * 8 + slot * 4), "r"((uint32_t)doit) : "memory");
  return old;
}
template <int H>
__device__ __forceinline__ void softmax_half(const float (&S)[64], uint32_t (&P)[16], uint32_t one2) {
#pragma unroll
  for (int i = 0; i < 16; i++) {
    if ((TMASK >> (8 * H + i / 2)) & 1) P[i] = ex2_pair_poly(S[32 * H + 2 * i], S[32 * H + 2 * i + 1], one2);
    else P[i] = pack_bf16(ex2(S[32 * H + 2 * i]), ex2(S[32 * H + 2 * i + 1]));
  }
}
__device__ __forceinline__ void attn_fast(const uint32_t (&q)[8], float (&O)[12], uint32_t sbase, int step0, int nsteps, bool elected, uint32_t one2) {
  uint64_t kb0 = mkd((sbase & 0x3FFFFu) >> 4, DHI_KV);
  asm volatile("" : "+l"(kb0));
#pragma unroll 1
  for (int step4 = step0; step4 < step0 + nsteps; step4 += KVR) {
#pragma unroll
    for (int j = 0; j < KVR; j++) {
      const int step = step4 + j;
      const uint64_t kb = kb0 + (uint64_t)(j * (GRP_BYTES >> 4));
      float S[64]; uint32_t PA[16], PB[16];
#pragma unroll
      for (int i = 0; i < 64; i++) S[i] = 0.f;
      mbar_wait(sbase + OFF_BAR + (BAR_KV + j) * 8, (step / KVR) & 1);
      fence_regs(S);
      wg_fence();
      wgmma_rs_n128<0>(S, q[0], q[1], q[2], q[3], kb + (uint64_t)((PLANE >> 4) << 16));
      wgmma_rs_n128<1>(S, q[4], q[5], q[6], q[7], kb + (uint64_t)(2 * PLANE >> 4));
      wg_commit();
      const uint32_t old = kv_release_begin(sbase, (j + KVR - 1) & (KVR - 1), elected && step > step0 && step - 1 + KVR < NSTEP);
      wg_wait<0>();
      fence_regs(S);
      softmax_half<0>(S, PA, one2);
      fence_regs(PA); fence_regs(O);
      wg_fence();
      issue_pv(O, PA, kb + VOFF);
      wg_commit();
      softmax_half<1>(S, PB, one2);
      fence_regs(PB);
      wg_fence();
      issue_pv(O, PB, kb + VOFF + 4 * (768 >> 4));
      wg_commit();
      if (old == 3u) kv_load(sbase, step - 1 + KVR);
      wg_wait<0>();
      fence_regs(PA); fence_regs(PB); fence_regs(O);
    }
  }
  kv_release(sbase, step0 + nsteps - 1, elected);
}
template <int H>
__device__ __forceinline__ void slow_step(const uint32_t (&q)[8], float (&O)[12], uint64_t kb, float& m0, float& m1) {
  float S[32]; uint32_t P[16];
#pragma unroll
  for (int i = 0; i < 32; i++) S[i] = 0.f;
  fence_regs(S);
  wg_fence();
  issue_qk(S, q, kb + 64 * H);
  wg_commit();
  wg_wait<0>();
  fence_regs(S);
  softmax_slow<8 * H>(S, P, O, m0, m1);
  fence_regs(P); fence_regs(O);
  wg_fence();
  issue_pv(O, P, kb + VOFF + H * 4 * (768 >> 4));
  wg_commit();
  wg_wait<0>();
  fence_regs(O); fence_regs(P);
}
__device__ __forceinline__ void attn_slow(const uint32_t (&q)[8], float (&O)[12], uint32_t sbase, int step0, int nsteps, bool elected, float& m0, float& m1) {
#pragma unroll 1
  for (int step = step0; step < step0 + nsteps; step++) {
    kv_wait(sbase, step);
    const uint64_t kb = mkd(((sbase & 0x3FFFFu) >> 4) + (step & (KVR - 1)) * (GRP_BYTES >> 4), DHI_KV);
    slow_step<0>(q, O, kb, m0, m1);
    slow_step<1>(q, O, kb, m0, m1);
    kv_release(sbase, step, elected);
  }
}

__device__ __forceinline__ void softmax8(float (&sc)[8], float scale) {
  float mx = sc[0];
#pragma unroll
  for (int w = 1; w < 8; w++) mx = fmaxf(mx, sc[w]);
  float l = 0.f;
#pragma unroll
  for (int w = 0; w < 8; w++) { sc[w] = ex2(sc[w] - mx); l += sc[w]; }
  const float r = __fdividef(scale, l);
#pragma unroll
  for (int w = 0; w < 8; w++) sc[w] *= r;
}
#define LEV(wg) 1
constexpr int LBOX = 32 * 320;
__device__ __forceinline__ uint2 lds64(uint32_t a) {
  uint2 v; asm volatile("ld.shared.v2.u32 {%0, %1}, [%2];" : "=r"(v.x), "=r"(v.y) : "r"(a)); return v;
}
__device__ __forceinline__ void local_attn(uint32_t stage, int t0, int i, int lane) {
  constexpr float SC = 0.22360679774997896f * 1.4426950408889634f, NEG = -1e9f * 1.4426950408889634f;
  const uint32_t base = stage + (lane >> 3) * LBOX + (lane & 7) * 40 + (i + 14 + ((lane >> 3) & 1)) * 320;
  const int t = t0 + i;
  float sc[8];
#pragma unroll
  for (int w = 0; w < 8; w++) sc[w] = 0.f;
#pragma unroll 1
  for (int c = 0; c < 5; c++) {
    const uint2 qv = lds64(base + c * 8);
    const float q0 = bf_lo(qv.x), q1 = bf_hi(qv.x), q2 = bf_lo(qv.y), q3 = bf_hi(qv.y);
#pragma unroll
    for (int w = 0; w < 8; w++) {
      const uint2 k = lds64(base + c * 8 + 4 * LBOX - w * 640);
      sc[w] = fmaf(q0, bf_lo(k.x), sc[w]); sc[w] = fmaf(q1, bf_hi(k.x), sc[w]);
      sc[w] = fmaf(q2, bf_lo(k.y), sc[w]); sc[w] = fmaf(q3, bf_hi(k.y), sc[w]);
    }
  }
#pragma unroll
  for (int w = 0; w < 8; w++) sc[w] = t - 2 * w >= 0 ? sc[w] * SC : NEG;
  softmax8(sc, 1.f - g_gate[t]);
  uint2* dst = reinterpret_cast<uint2*>(g_a2 + (size_t)t * (2 * D_MODEL) + D_MODEL + lane * DH);
#pragma unroll 1
  for (int c = 0; c < 5; c++) {
    float o0 = 0.f, o1 = 0.f, o2 = 0.f, o3 = 0.f;
#pragma unroll
    for (int w = 0; w < 8; w++) {
      const uint2 v = lds64(base + c * 8 + 8 * LBOX - w * 640);
      o0 = fmaf(sc[w], bf_lo(v.x), o0); o1 = fmaf(sc[w], bf_hi(v.x), o1);
      o2 = fmaf(sc[w], bf_lo(v.y), o2); o3 = fmaf(sc[w], bf_hi(v.y), o3);
    }
    dst[c] = make_uint2(pack_bf16(o0, o1), pack_bf16(o2, o3));
  }
}
__device__ __forceinline__ uint32_t ta_slot(int i) { return i < 4 ? OFF_X + i * 16384 : (i - 4) * 16384; }

__global__ void __launch_bounds__(640, 1)
attn_kernel(const __grid_constant__ CUtensorMap tmA2, const __grid_constant__ CUtensorMap tmL, __nv_bfloat16* __restrict__ out, uint32_t one2) {
  extern __shared__ uint8_t smem_raw[];
  uint8_t* smem = reinterpret_cast<uint8_t*>((reinterpret_cast<uintptr_t>(smem_raw) + 1023) & ~(uintptr_t)1023);
  const uint32_t sbase = smem_u32(smem);
  const uint32_t dbase = sbase & 0x3FFFFu;
  const uint32_t bars = sbase + OFF_BAR;
  const int tid = threadIdx.x, wg = tid >> 7, warp = (tid >> 5) & 3, lane = tid & 31, g = lane >> 2, t = lane & 3;
  const int mb = blockIdx.x >> 3, nb = blockIdx.x & 7;
  const bool elected = (tid & 127) == 0;
  if (tid == 512) { prefetch_tmap(&tmL); prefetch_tmap(&tmA2); }
  if (tid == 0) {
    for (int i = 0; i < BAR_TE; i++) mbar_init(bars + i * 8, 1);
    for (int i = BAR_TE; i < BAR_TE + 2 * TSL; i++) mbar_init(bars + i * 8, 4);
    mbar_init(bars + BAR_OWN * 8, 4);
    mbar_init(bars + BAR_OWN0 * 8, 4);
    mbar_init(bars + BAR_L * 8, 1);
    for (int i = 0; i < 10; i++) { mbar_init(bars + (BAR_WA + i) * 8, 1); mbar_init(bars + (BAR_WF + i) * 8, 8); }
    for (int i = 0; i < 4; i++) *reinterpret_cast<uint32_t*>(smem + OFF_BAR + CNT_KV * 8 + i * 4) = 0u;
    *reinterpret_cast<uint32_t*>(smem + OFF_BAR + CNT_TK * 8) = 0u;
    fence_mbar_init();
  }
  __syncthreads();
  auto tail_load = [&](int m, int i) {
    const uint32_t fb = bars + (BAR_TA + m * TSL + i % TSL) * 8;
    mbar_expect_tx(fb, 8192);
    tma_2d(sbase + ta_slot(i % TSL) + m * 8192, &tmA2, i < 10 ? D_MODEL + i * 64 : (i - 10) * 64, mb * 128 + m * 64, fb);
  };
  if (wg == 4) {
    asm volatile("setmaxnreg.dec.sync.aligned.u32 32;");
    pdl_wait();
    if (tid == 512) {
      for (int j = 0; j < KVR; j++) kv_load(sbase, j);
      mbar_expect_tx(bars + BAR_L * 8, 12 * LBOX);
      for (int i = 0; i < 12; i++) tma_2d(sbase + OFF_W + i * LBOX, &tmL, i * 160, blockIdx.x * 16 - 14 - (i & 1), bars + BAR_L * 8);
    }
    __syncwarp();
    mbar_wait(bars + BAR_L * 8, 0);
#pragma unroll 1
    for (int i = 0; i < 4; i++) local_attn(sbase + OFF_W, blockIdx.x * 16, warp * 4 + i, lane);
    signal_done(&g_doneL[blockIdx.x], wg, tid);
    if (tid == 512) {
      PROF2(0, 2);
      fence_proxy_async();
      mbar_expect_tx(bars + BAR_W * 8, 10 * 10240);
      for (int i = 0; i < 5; i++) bulk_g2s(sbase + OFF_W + i * 20480, g_wimg + ((8 + nb) * 10) * 10240 + i * 20480, 20480, bars + BAR_W * 8);
    }
    if (tid == 512 || tid == 608) {
      const int m = tid == 608;
      wait_flags8(&g_doneL[mb * 8], 1u);
      for (int i = 0; i < 4; i++) tail_load(m, i);
      if (m == 0) wait_flags8(&g_done[mb * 8], 1u);
      mbar_wait(bars + BAR_OWN * 8, 0);
      for (int i = 4; i < 20; i++) {
        if (i >= TSL) mbar_wait(bars + (BAR_TE + m * TSL + i % TSL) * 8, (i / TSL - 1) & 1);
        if (i == 10 && m == 1) { wait_flags8(&g_done[mb * 8], 2u); PROF2(2, 0); }
        tail_load(m, i);
      }
    } else if (tid == 576) {
      for (int ph = 0; ph < 2; ph++) {
        mbar_wait(bars + (ph == 0 ? BAR_OWN0 : BAR_OWN) * 8, 0);
        asm volatile("red.release.gpu.global.add.u32 [%0], 1;" :: "l"(&g_done[blockIdx.x]) : "memory");
      }
    } else if (tid == 544) {
      for (int kt = 0; kt < 10; kt++) {
        mbar_wait(bars + (BAR_WF + kt) * 8, 0);
        mbar_expect_tx(bars + (BAR_WA + kt) * 8, 10240);
        bulk_g2s(sbase + OFF_W + kt * 10240, g_wimg + (nb * 10 + kt) * 10240, 10240, bars + (BAR_WA + kt) * 8);
      }
    }
    return;
  }
  asm volatile("setmaxnreg.inc.sync.aligned.u32 112;");
  pdl_wait();
  PROF(1, 1);
  uint32_t q[8], q2[6];
  const int rowA = (mb * 128 + nb * 8 + wg * 2) * 32 + warp * 16 + g;
  {
    const uint32_t* r0 = reinterpret_cast<const uint32_t*>(g_q + (size_t)rowA * DH);
    const uint32_t* r1 = r0 + 8 * (DH / 2);
    const uint32_t* s0 = r0 + 2048 * (DH / 2);
    const uint32_t* s1 = s0 + 8 * (DH / 2);
    q[0] = r0[t]; q[1] = r1[t]; q[2] = r0[t + 4]; q[3] = r1[t + 4];
    q[4] = t < 2 ? r0[8 + t] : 0u;
    q[5] = t < 2 ? r1[8 + t] : 0u;
    q2[0] = s0[t]; q2[1] = s1[t]; q2[2] = s0[t + 4]; q2[3] = s1[t + 4];
    q2[4] = t < 2 ? s0[8 + t] : 0u;
    q2[5] = t < 2 ? s1[8 + t] : 0u;
  }
  float kmax2 = 0.f, vmax = 0.f;
#pragma unroll
  for (int i = 0; i < 2; i++) {
    const float a = g_kmax2[lane + 32 * i];
    kmax2 = (a > kmax2 || a != a) ? a : kmax2;
    vmax = fmaxf(vmax, g_vmax[lane + 32 * i]);
  }
#pragma unroll
  for (int o = 1; o < 32; o <<= 1) {
    const float a = __shfl_xor_sync(0xffffffffu, kmax2, o);
    kmax2 = (a > kmax2 || a != a) ? a : kmax2;
    vmax = fmaxf(vmax, __shfl_xor_sync(0xffffffffu, vmax, o));
  }
  const float qlim = (vmax >= 0.00390625f && vmax <= 256.f) ? 9025.f / kmax2 : -1.f;
  PROF(1, 2);
#pragma unroll 1
  for (int it = 0; it < 2; it++) {
    const int row0 = rowA + it * 2048;
    if (it == 1) {
#pragma unroll
      for (int i = 0; i < 6; i++) q[i] = q2[i];
    }
    float n0 = bf_lo(q[0]) * bf_lo(q[0]) + bf_hi(q[0]) * bf_hi(q[0]) + bf_lo(q[2]) * bf_lo(q[2]) + bf_hi(q[2]) * bf_hi(q[2]) +
               bf_lo(q[4]) * bf_lo(q[4]) + bf_hi(q[4]) * bf_hi(q[4]);
    float n1 = bf_lo(q[1]) * bf_lo(q[1]) + bf_hi(q[1]) * bf_hi(q[1]) + bf_lo(q[3]) * bf_lo(q[3]) + bf_hi(q[3]) * bf_hi(q[3]) +
               bf_lo(q[5]) * bf_lo(q[5]) + bf_hi(q[5]) * bf_hi(q[5]);
    n0 += __shfl_xor_sync(0xffffffffu, n0, 1); n0 += __shfl_xor_sync(0xffffffffu, n0, 2);
    n1 += __shfl_xor_sync(0xffffffffu, n1, 1); n1 += __shfl_xor_sync(0xffffffffu, n1, 2);
    const bool safe = (n0 <= qlim) && (n1 <= qlim);
    uint32_t unsafe_any;
    asm volatile("{\n.reg .pred p, r;\nsetp.eq.u32 p, %1, 0;\nbarrier.cta.red.or.pred r, %2, 128, p;\nselp.u32 %0, 1, 0, r;\n}\n"
                 : "=r"(unsafe_any) : "r"((uint32_t)safe), "r"(wg + 1) : "memory");
    float O[12];
#pragma unroll
    for (int i = 0; i < 12; i++) O[i] = 0.f;
    if (!unsafe_any && t >= 2) { q[4] = q[5] = (t == 2) ? 0x3F804100u : 0x00003B80u; }
    q[6] = q[4]; q[7] = q[5];
    fence_regs(q);
    float m0 = -INFINITY, m1 = -INFINITY;
    if (!unsafe_any) attn_fast(q, O, sbase, it * NGRP, NGRP, elected, one2);
    else attn_slow(q, O, sbase, it * NGRP, NGRP, elected, m0, m1);
    const float l0 = __shfl_sync(0xffffffffu, O[8], (lane & ~3) | 2);
    const float l1 = __shfl_sync(0xffffffffu, O[10], (lane & ~3) | 2);
    const int tok = row0 >> 5;
    const float gt = g_gate[tok];
    const float i0 = gt / l0, i1 = gt / l1;
    uint32_t* o0 = reinterpret_cast<uint32_t*>(g_a2 + (size_t)tok * (2 * D_MODEL) + (row0 & 31) * DH);
    uint32_t* o1 = o0 + 8 * (DH / 2);
    o0[t] = pack_bf16(O[0] * i0, O[1] * i0); o1[t] = pack_bf16(O[2] * i1, O[3] * i1);
    o0[t + 4] = pack_bf16(O[4] * i0, O[5] * i0); o1[t + 4] = pack_bf16(O[6] * i1, O[7] * i1);
    if (t < 2) { o0[t + 8] = pack_bf16(O[8] * i0, O[9] * i0); o1[t + 8] = pack_bf16(O[10] * i1, O[11] * i1); }
    if (it == 0) {
      asm volatile("bar.sync %0, 128;" :: "r"(wg + 1) : "memory");
      if (elected) mbar_arrive(bars + BAR_OWN0 * 8);
    }
  }
  uint32_t* ticket = reinterpret_cast<uint32_t*>(smem + OFF_BAR + CNT_TK * 8);
  if (elected) ticket[1 + wg] = atomicAdd(ticket, 1u);
  asm volatile("bar.sync %0, 128;" :: "r"(wg + 1) : "memory");
  if (elected) mbar_arrive(bars + BAR_OWN * 8);
  const int mt = ticket[1 + wg];
  PROF(1, 3);
  if (mt < 2) {
    float acc[40];
#pragma unroll
    for (int i = 0; i < 40; i++) acc[i] = 0.f;
    mbar_wait(bars + BAR_W * 8, 0);
    int sl = 0, ph = 0;
#pragma unroll 1
    for (int i = 0; i < 20; i++) {
      mbar_wait(bars + (BAR_TA + mt * TSL + sl) * 8, ph);
      if (i >= 10) mbar_wait(bars + (BAR_WA + i - 10) * 8, 0);
      const uint32_t alo = ((dbase + ta_slot(sl) + mt * 8192) >> 4) | (1u << 16);
      const uint32_t blo = ((dbase + OFF_W + (i >= 10 ? i - 10 : i) * 10240) >> 4) | ((128u >> 4) << 16);
      fence_regs(acc);
      wg_fence();
#pragma unroll
      for (int k = 0; k < 4; k++) wgmma_ss_n80_tb(acc, mkd(alo + k * 2, DHI_SW128_K), mkd(blo + k * 16, 1024u >> 4));
      wg_commit();
      if (i > 0) {
        wg_wait<1>();
        if (lane == 0) mbar_arrive(bars + (BAR_TE + mt * TSL + (sl == 0 ? TSL - 1 : sl - 1)) * 8);
        if (lane == 1 && i <= 10) mbar_arrive(bars + (BAR_WF + i - 1) * 8);
      }
      if (++sl == TSL) { sl = 0; ph ^= 1; }
    }
    wg_wait<0>();
    fence_regs(acc);
    asm volatile("bar.sync %0, 128;" :: "r"(wg + 1) : "memory");
    const uint32_t so = ta_slot(warp) + mt * 8192;
    const int row0 = mb * 128 + mt * 64 + warp * 16;
    store_tile_bf16<80>(acc, 1.0f, sbase + so, smem + so, out + (size_t)row0 * D_MODEL + nb * 80, D_MODEL, lane);
  }
}

typedef CUresult (*EncodeFn)(CUtensorMap*, CUtensorMapDataType, cuuint32_t, void*, const cuuint64_t*, const cuuint64_t*,
                             const cuuint32_t*, const cuuint32_t*, CUtensorMapInterleave, CUtensorMapSwizzle,
                             CUtensorMapL2promotion, CUtensorMapFloatOOBfill);

void make_map(EncodeFn fn, CUtensorMap* tm, const void* ptr, int rank, const cuuint64_t* dims, const cuuint64_t* strides,
              const cuuint32_t* box, CUtensorMapSwizzle sw) {
  const cuuint32_t es[3] = {1, 1, 1};
  fn(tm, CU_TENSOR_MAP_DATA_TYPE_BFLOAT16, rank, const_cast<void*>(ptr), dims, strides, box, es, CU_TENSOR_MAP_INTERLEAVE_NONE, sw,
     CU_TENSOR_MAP_L2_PROMOTION_L2_256B, CU_TENSOR_MAP_FLOAT_OOB_FILL_NONE);
}
void map_a(EncodeFn fn, CUtensorMap* tm, const void* p, int rows, int cols, int box_rows) {
  const cuuint64_t dims[2] = {(cuuint64_t)cols, (cuuint64_t)rows};
  const cuuint64_t str[1] = {(cuuint64_t)cols * 2};
  const cuuint32_t box[2] = {64, (cuuint32_t)box_rows};
  make_map(fn, tm, p, 2, dims, str, box, CU_TENSOR_MAP_SWIZZLE_128B);
}
void map_w(EncodeFn fn, CUtensorMap* tm, const void* p, int K, int N, int atom, CUtensorMapSwizzle sw) {
  const cuuint64_t dims[3] = {(cuuint64_t)atom, (cuuint64_t)K, (cuuint64_t)(N / atom)};
  const cuuint64_t str[2] = {(cuuint64_t)N * 2, (cuuint64_t)atom * 2};
  const cuuint32_t box[3] = {(cuuint32_t)atom, 64, 5};
  make_map(fn, tm, p, 3, dims, str, box, sw);
}

template <typename... KArgs, typename... Args>
void launch(void (*kern)(KArgs...), int grid, int block, int smem, bool pdl, Args... args) {
  cudaLaunchConfig_t cfg = {};
  cfg.gridDim = dim3(grid); cfg.blockDim = dim3(block); cfg.dynamicSmemBytes = smem; cfg.stream = cudaStreamPerThread;
  cudaLaunchAttribute at[1];
  at[0].id = cudaLaunchAttributeProgrammaticStreamSerialization;
  at[0].val.programmaticStreamSerializationAllowed = 1;
  cfg.attrs = at; cfg.numAttrs = pdl ? 1 : 0;
  cudaLaunchKernelEx(&cfg, kern, KArgs(args)...);
}

}

extern "C" void kernel_launch(void* const* d_in, const int* in_sizes, int n_in, void* d_out, int out_size) {
  (void)in_sizes; (void)n_in; (void)out_size;
  const __nv_bfloat16* x = (const __nv_bfloat16*)d_in[0];
  const __nv_bfloat16* wq = (const __nv_bfloat16*)d_in[1];
  const __nv_bfloat16* wk = (const __nv_bfloat16*)d_in[2];
  const __nv_bfloat16* wv = (const __nv_bfloat16*)d_in[3];
  const __nv_bfloat16* woA = (const __nv_bfloat16*)d_in[4];
  const __nv_bfloat16* wqkv = (const __nv_bfloat16*)d_in[6];
  const __nv_bfloat16* woB = (const __nv_bfloat16*)d_in[7];
  const __nv_bfloat16* gate_w = (const __nv_bfloat16*)d_in[8];

  static EncodeFn enc = nullptr;
  static void* a2_ptr = nullptr;
  static void* qkv_ptr = nullptr;
  if (!enc) {
    void* fp = nullptr;
    cudaDriverEntryPointQueryResult qr;
    cudaGetDriverEntryPoint("cuTensorMapEncodeTiled", &fp, cudaEnableDefault, &qr);
    enc = (EncodeFn)fp;
    cudaGetSymbolAddress(&a2_ptr, g_a2);
    cudaGetSymbolAddress(&qkv_ptr, g_qkv);
    cudaFuncSetAttribute(proj_kernel, cudaFuncAttributeMaxDynamicSharedMemorySize, K1_SMEM);
    cudaFuncSetAttribute(attn_kernel, cudaFuncAttributeMaxDynamicSharedMemorySize, K2_SMEM);
  }
  CUtensorMap tmX, tmWq, tmWqkv, tmA2, tmL;
  {
    const cuuint64_t dims[2] = {3 * D_MODEL, S_LEN};
    const cuuint64_t str[1] = {3 * D_MODEL * 2};
    const cuuint32_t box[2] = {160, 32};
    make_map(enc, &tmL, qkv_ptr, 2, dims, str, box, CU_TENSOR_MAP_SWIZZLE_NONE);
  }
  map_a(enc, &tmX, x, S_LEN, D_MODEL, 256);
  map_w(enc, &tmWq, wq, D_MODEL, D_MODEL, 32, CU_TENSOR_MAP_SWIZZLE_64B);
  map_w(enc, &tmWqkv, wqkv, D_MODEL, 3 * D_MODEL, 32, CU_TENSOR_MAP_SWIZZLE_64B);
  map_a(enc, &tmA2, a2_ptr, S_LEN, 2 * D_MODEL, 64);

  launch(proj_kernel, 132, 512, K1_SMEM, false, tmX, tmWq, tmWqkv, wk, wv, gate_w, woA, woB);
  launch(attn_kernel, 128, 640, K2_SMEM, true, tmA2, tmL, (__nv_bfloat16*)d_out, 0x3F803F80u);
}
```

```cpp
#include <cuda_runtime.h>
#include <cuda_bf16.h>
#include <cuda.h>
#include <stdint.h>

namespace {

constexpr int S_LEN = 2048, D_MODEL = 640, DH = 20;

constexpr int GRP = 128;
constexpr int PLANE = GRP * 16;
constexpr int GRP_BYTES = GRP * 16 * 6;
constexpr int NGRP = S_LEN / GRP;
constexpr uint32_t TMASK = 0x6DB6u;

__device__ __align__(1024) __nv_bfloat16 g_q[S_LEN * D_MODEL];
__device__ __align__(1024) __nv_bfloat16 g_qkv[S_LEN * 3 * D_MODEL];
__device__ __align__(1024) __nv_bfloat16 g_a2[S_LEN * 2 * D_MODEL];
__device__ __align__(1024) uint8_t g_kvimg[NGRP * GRP_BYTES];
__device__ __align__(1024) uint8_t g_wimg[2 * 8 * 10 * 10240];
__device__ float g_gate[S_LEN];
__device__ float g_kmax2[64];
__device__ float g_vmax[64];
__device__ __align__(32) unsigned int g_doneL[128];
__device__ __align__(32) unsigned int g_done[128];

__device__ __forceinline__ uint32_t smem_u32(const void* p) { return (uint32_t)__cvta_generic_to_shared(p); }
__device__ __forceinline__ uint64_t mkd(uint32_t lo, uint32_t hi) {
  uint64_t d; asm("mov.b64 %0, {%1, %2};" : "=l"(d) : "r"(lo), "r"(hi)); return d;
}
__device__ __forceinline__ void wg_fence() { asm volatile("wgmma.fence.sync.aligned;" ::: "memory"); }
__device__ __forceinline__ void wg_commit() { asm volatile("wgmma.commit_group.sync.aligned;" ::: "memory"); }
template <int N> __device__ __forceinline__ void wg_wait() { asm volatile("wgmma.wait_group.sync.aligned %0;" :: "n"(N) : "memory"); }
template <int N> __device__ __forceinline__ void fence_regs(float (&d)[N]) {
#pragma unroll
  for (int i = 0; i < N; i++) asm volatile("" : "+f"(d[i]) :: "memory");
}
template <int N> __device__ __forceinline__ void fence_regs(uint32_t (&d)[N]) {
#pragma unroll
  for (int i = 0; i < N; i++) asm volatile("" : "+r"(d[i]) :: "memory");
}
__device__ __forceinline__ void mbar_init(uint32_t bar, uint32_t cnt) { asm volatile("mbarrier.init.shared::cta.b64 [%0], %1;" :: "r"(bar), "r"(cnt)); }
__device__ __forceinline__ void mbar_expect_tx(uint32_t bar, uint32_t bytes) {
  asm volatile("mbarrier.arrive.expect_tx.shared::cta.b64 _, [%0], %1;" :: "r"(bar), "r"(bytes) : "memory");
}
__device__ __forceinline__ void mbar_arrive(uint32_t bar) { asm volatile("mbarrier.arrive.shared::cta.b64 _, [%0];" :: "r"(bar) : "memory"); }
constexpr uint32_t WAIT_HINT = 20000u;
__device__ __forceinline__ void mbar_wait(uint32_t bar, uint32_t parity) {
  asm volatile("{\n.reg .pred p;\nWAIT_%=:\nmbarrier.try_wait.parity.shared::cta.b64 p, [%0], %1, %2;\n@p bra DONE_%=;\nbra WAIT_%=;\nDONE_%=:\n}\n"
               :: "r"(bar), "r"(parity), "r"(WAIT_HINT) : "memory");
}
__device__ __forceinline__ void fence_mbar_init() { asm volatile("fence.mbarrier_init.release.cluster;" ::: "memory"); }
__device__ __forceinline__ void fence_proxy_async() { asm volatile("fence.proxy.async.shared::cta;" ::: "memory"); }
__device__ __forceinline__ void bulk_g2s(uint32_t dst, const void* src, uint32_t bytes, uint32_t bar) {
  asm volatile("cp.async.bulk.shared::cluster.global.mbarrier::complete_tx::bytes [%0], [%1], %2, [%3];"
               :: "r"(dst), "l"(src), "r"(bytes), "r"(bar) : "memory");
}
__device__ __forceinline__ void tma_2d(uint32_t dst, const CUtensorMap* tm, int c0, int c1, uint32_t bar) {
  asm volatile("cp.async.bulk.tensor.2d.shared::cluster.global.mbarrier::complete_tx::bytes [%0], [%1, {%3, %4}], [%2];"
               :: "r"(dst), "l"((uint64_t)tm), "r"(bar), "r"(c0), "r"(c1) : "memory");
}
__device__ __forceinline__ void tma_3d(uint32_t dst, const CUtensorMap* tm, int c0, int c1, int c2, uint32_t bar) {
  asm volatile("cp.async.bulk.tensor.3d.shared::cluster.global.mbarrier::complete_tx::bytes [%0], [%1, {%3, %4, %5}], [%2];"
               :: "r"(dst), "l"((uint64_t)tm), "r"(bar), "r"(c0), "r"(c1), "r"(c2) : "memory");
}
__device__ __forceinline__ void prefetch_tmap(const CUtensorMap* tm) { asm volatile("prefetch.tensormap [%0];" :: "l"((uint64_t)tm) : "memory"); }
__device__ __forceinline__ void pdl_wait() { asm volatile("griddepcontrol.wait;" ::: "memory"); }
__device__ __forceinline__ void pdl_launch() { asm volatile("griddepcontrol.launch_dependents;" ::: "memory"); }
__device__ __forceinline__ float ex2(float x) { float y; asm("ex2.approx.ftz.f32 %0, %1;" : "=f"(y) : "f"(x)); return y; }
__device__ __forceinline__ uint32_t pack_bf16(float lo, float hi) {
  uint32_t r; asm("cvt.rn.bf16x2.f32 %0, %1, %2;" : "=r"(r) : "f"(hi), "f"(lo)); return r;
}
__device__ __forceinline__ float bf_lo(uint32_t x) { return __uint_as_float(x << 16); }
__device__ __forceinline__ float bf_hi(uint32_t x) { return __uint_as_float(x & 0xffff0000u); }
__device__ __forceinline__ void stsm4(uint32_t addr, uint32_t r0, uint32_t r1, uint32_t r2, uint32_t r3) {
  asm volatile("stmatrix.sync.aligned.m8n8.x4.shared.b16 [%0], {%1, %2, %3, %4};" :: "r"(addr), "r"(r0), "r"(r1), "r"(r2), "r"(r3) : "memory");
}

__device__ __forceinline__ void wgmma_ss_n160_tb(float (&d)[80], uint64_t descA, uint64_t descB) {
  asm volatile("wgmma.mma_async.sync.aligned.m64n160k16.f32.bf16.bf16 {%0, %1, %2, %3, %4, %5, %6, %7, %8, %9, %10, %11, %12, %13, %14, %15, %16, %17, %18, %19, %20, %21, %22, %23, %24, %25, %26, %27, %28, %29, %30, %31, %32, %33, %34, %35, %36, %37, %38, %39, %40, %41, %42, %43, %44, %45, %46, %47, %48, %49, %50, %51, %52, %53, %54, %55, %56, %57, %58, %59, %60, %61, %62, %63, %64, %65, %66, %67, %68, %69, %70, %71, %72, %73, %74, %75, %76, %77, %78, %79}, %80, %81, 1, 1, 1, 0, 1;\n"
    : "+f"(d[0]), "+f"(d[1]), "+f"(d[2]), "+f"(d[3]), "+f"(d[4]), "+f"(d[5]), "+f"(d[6]), "+f"(d[7]), "+f"(d[8]), "+f"(d[9]), "+f"(d[10]), "+f"(d[11]), "+f"(d[12]), "+f"(d[13]), "+f"(d[14]), "+f"(d[15]), "+f"(d[16]), "+f"(d[17]), "+f"(d[18]), "+f"(d[19]), "+f"(d[20]), "+f"(d[21]), "+f"(d[22]), "+f"(d[23]), "+f"(d[24]), "+f"(d[25]), "+f"(d[26]), "+f"(d[27]), "+f"(d[28]), "+f"(d[29]), "+f"(d[30]), "+f"(d[31]), "+f"(d[32]), "+f"(d[33]), "+f"(d[34]), "+f"(d[35]), "+f"(d[36]), "+f"(d[37]), "+f"(d[38]), "+f"(d[39]), "+f"(d[40]), "+f"(d[41]), "+f"(d[42]), "+f"(d[43]), "+f"(d[44]), "+f"(d[45]), "+f"(d[46]), "+f"(d[47]), "+f"(d[48]), "+f"(d[49]), "+f"(d[50]), "+f"(d[51]), "+f"(d[52]), "+f"(d[53]), "+f"(d[54]), "+f"(d[55]), "+f"(d[56]), "+f"(d[57]), "+f"(d[58]), "+f"(d[59]), "+f"(d[60]), "+f"(d[61]), "+f"(d[62]), "+f"(d[63]), "+f"(d[64]), "+f"(d[65]), "+f"(d[66]), "+f"(d[67]), "+f"(d[68]), "+f"(d[69]), "+f"(d[70]), "+f"(d[71]), "+f"(d[72]), "+f"(d[73]), "+f"(d[74]), "+f"(d[75]), "+f"(d[76]), "+f"(d[77]), "+f"(d[78]), "+f"(d[79])
    : "l"(descA), "l"(descB));
}
__device__ __forceinline__ void wgmma_ss_n48_tb(float (&d)[24], uint64_t descA, uint64_t descB) {
  asm volatile("wgmma.mma_async.sync.aligned.m64n48k16.f32.bf16.bf16 {%0, %1, %2, %3, %4, %5, %6, %7, %8, %9, %10, %11, %12, %13, %14, %15, %16, %17, %18, %19, %20, %21, %22, %23}, %24, %25, 1, 1, 1, 0, 1;\n"
    : "+f"(d[0]), "+f"(d[1]), "+f"(d[2]), "+f"(d[3]), "+f"(d[4]), "+f"(d[5]), "+f"(d[6]), "+f"(d[7]), "+f"(d[8]), "+f"(d[9]), "+f"(d[10]), "+f"(d[11]), "+f"(d[12]), "+f"(d[13]), "+f"(d[14]), "+f"(d[15]), "+f"(d[16]), "+f"(d[17]), "+f"(d[18]), "+f"(d[19]), "+f"(d[20]), "+f"(d[21]), "+f"(d[22]), "+f"(d[23])
    : "l"(descA), "l"(descB));
}
__device__ __forceinline__ void wgmma_ss_n80_tb(float (&d)[40], uint64_t descA, uint64_t descB) {
  asm volatile("wgmma.mma_async.sync.aligned.m64n80k16.f32.bf16.bf16 {%0, %1, %2, %3, %4, %5, %6, %7, %8, %9, %10, %11, %12, %13, %14, %15, %16, %17, %18, %19, %20, %21, %22, %23, %24, %25, %26, %27, %28, %29, %30, %31, %32, %33, %34, %35, %36, %37, %38, %39}, %40, %41, 1, 1, 1, 0, 1;\n"
    : "+f"(d[0]), "+f"(d[1]), "+f"(d[2]), "+f"(d[3]), "+f"(d[4]), "+f"(d[5]), "+f"(d[6]), "+f"(d[7]), "+f"(d[8]), "+f"(d[9]), "+f"(d[10]), "+f"(d[11]), "+f"(d[12]), "+f"(d[13]), "+f"(d[14]), "+f"(d[15]), "+f"(d[16]), "+f"(d[17]), "+f"(d[18]), "+f"(d[19]), "+f"(d[20]), "+f"(d[21]), "+f"(d[22]), "+f"(d[23]), "+f"(d[24]), "+f"(d[25]), "+f"(d[26]), "+f"(d[27]), "+f"(d[28]), "+f"(d[29]), "+f"(d[30]), "+f"(d[31]), "+f"(d[32]), "+f"(d[33]), "+f"(d[34]), "+f"(d[35]), "+f"(d[36]), "+f"(d[37]), "+f"(d[38]), "+f"(d[39])
    : "l"(descA), "l"(descB));
}
template <int SCALE_D>
__device__ __forceinline__ void wgmma_rs_n64(float (&d)[32], uint32_t a0, uint32_t a1, uint32_t a2, uint32_t a3, uint64_t descB) {
  asm volatile("wgmma.mma_async.sync.aligned.m64n64k16.f32.bf16.bf16 {%0, %1, %2, %3, %4, %5, %6, %7, %8, %9, %10, %11, %12, %13, %14, %15, %16, %17, %18, %19, %20, %21, %22, %23, %24, %25, %26, %27, %28, %29, %30, %31}, {%32, %33, %34, %35}, %36, %37, 1, 1, 0;\n"
    : "+f"(d[0]), "+f"(d[1]), "+f"(d[2]), "+f"(d[3]), "+f"(d[4]), "+f"(d[5]), "+f"(d[6]), "+f"(d[7]), "+f"(d[8]), "+f"(d[9]), "+f"(d[10]), "+f"(d[11]), "+f"(d[12]), "+f"(d[13]), "+f"(d[14]), "+f"(d[15]), "+f"(d[16]), "+f"(d[17]), "+f"(d[18]), "+f"(d[19]), "+f"(d[20]), "+f"(d[21]), "+f"(d[22]), "+f"(d[23]), "+f"(d[24]), "+f"(d[25]), "+f"(d[26]), "+f"(d[27]), "+f"(d[28]), "+f"(d[29]), "+f"(d[30]), "+f"(d[31])
    : "r"(a0), "r"(a1), "r"(a2), "r"(a3), "l"(descB), "n"(SCALE_D));
}
template <int SCALE_D>
__device__ __forceinline__ void wgmma_rs_n128(float (&d)[64], uint32_t a0, uint32_t a1, uint32_t a2, uint32_t a3, uint64_t descB) {
  asm volatile("wgmma.mma_async.sync.aligned.m64n128k16.f32.bf16.bf16 {%0, %1, %2, %3, %4, %5, %6, %7, %8, %9, %10, %11, %12, %13, %14, %15, %16, %17, %18, %19, %20, %21, %22, %23, %24, %25, %26, %27, %28, %29, %30, %31, %32, %33, %34, %35, %36, %37, %38, %39, %40, %41, %42, %43, %44, %45, %46, %47, %48, %49, %50, %51, %52, %53, %54, %55, %56, %57, %58, %59, %60, %61, %62, %63}, {%64, %65, %66, %67}, %68, %69, 1, 1, 0;\n"
    : "+f"(d[0]), "+f"(d[1]), "+f"(d[2]), "+f"(d[3]), "+f"(d[4]), "+f"(d[5]), "+f"(d[6]), "+f"(d[7]), "+f"(d[8]), "+f"(d[9]), "+f"(d[10]), "+f"(d[11]), "+f"(d[12]), "+f"(d[13]), "+f"(d[14]), "+f"(d[15]), "+f"(d[16]), "+f"(d[17]), "+f"(d[18]), "+f"(d[19]), "+f"(d[20]), "+f"(d[21]), "+f"(d[22]), "+f"(d[23]), "+f"(d[24]), "+f"(d[25]), "+f"(d[26]), "+f"(d[27]), "+f"(d[28]), "+f"(d[29]), "+f"(d[30]), "+f"(d[31]), "+f"(d[32]), "+f"(d[33]), "+f"(d[34]), "+f"(d[35]), "+f"(d[36]), "+f"(d[37]), "+f"(d[38]), "+f"(d[39]), "+f"(d[40]), "+f"(d[41]), "+f"(d[42]), "+f"(d[43]), "+f"(d[44]), "+f"(d[45]), "+f"(d[46]), "+f"(d[47]), "+f"(d[48]), "+f"(d[49]), "+f"(d[50]), "+f"(d[51]), "+f"(d[52]), "+f"(d[53]), "+f"(d[54]), "+f"(d[55]), "+f"(d[56]), "+f"(d[57]), "+f"(d[58]), "+f"(d[59]), "+f"(d[60]), "+f"(d[61]), "+f"(d[62]), "+f"(d[63])
    : "r"(a0), "r"(a1), "r"(a2), "r"(a3), "l"(descB), "n"(SCALE_D));
}
template <int SCALE_D>
__device__ __forceinline__ void wgmma_rs_n24_tb(float (&d)[12], uint32_t a0, uint32_t a1, uint32_t a2, uint32_t a3, uint64_t descB) {
  asm volatile("wgmma.mma_async.sync.aligned.m64n24k16.f32.bf16.bf16 {%0, %1, %2, %3, %4, %5, %6, %7, %8, %9, %10, %11}, {%12, %13, %14, %15}, %16, %17, 1, 1, 1;\n"
    : "+f"(d[0]), "+f"(d[1]), "+f"(d[2]), "+f"(d[3]), "+f"(d[4]), "+f"(d[5]), "+f"(d[6]), "+f"(d[7]), "+f"(d[8]), "+f"(d[9]), "+f"(d[10]), "+f"(d[11])
    : "r"(a0), "r"(a1), "r"(a2), "r"(a3), "l"(descB), "n"(SCALE_D));
}

constexpr uint32_t DHI_SW128_K = (1024 >> 4) | (1u << 30);
constexpr uint32_t DHI_SW64_MN = (512 >> 4) | (2u << 30);

template <int NC>
__device__ __forceinline__ void store_tile_bf16(const float (&acc)[NC / 2], float scale, uint32_t stage, uint8_t* stage_ptr,
                                                __nv_bfloat16* gdst, int gpitch, int lane) {
  constexpr int PITCH = NC * 2 + 16;
  const uint32_t waddr = stage + ((lane & 7) + ((lane >> 3) & 1) * 8) * PITCH + (lane >> 4) * 16;
#pragma unroll
  for (int j = 0; j < NC / 16; j++) {
    stsm4(waddr + j * 32, pack_bf16(acc[8 * j] * scale, acc[8 * j + 1] * scale), pack_bf16(acc[8 * j + 2] * scale, acc[8 * j + 3] * scale),
          pack_bf16(acc[8 * j + 4] * scale, acc[8 * j + 5] * scale), pack_bf16(acc[8 * j + 6] * scale, acc[8 * j + 7] * scale));
  }
  __syncwarp();
  constexpr int CPR = NC / 8;
#pragma unroll
  for (int i = 0; i < CPR / 2; i++) {
    const int c = i * 32 + lane, r = c / CPR, cc = c % CPR;
    const uint4 v = *reinterpret_cast<const uint4*>(stage_ptr + r * PITCH + cc * 16);
    *reinterpret_cast<uint4*>(gdst + (size_t)r * gpitch + cc * 8) = v;
  }
}

__device__ __forceinline__ void signal_done(unsigned int* flag, int wg, int tid) {
  asm volatile("bar.sync %0, 128;" :: "r"(wg + 1) : "memory");
  if ((tid & 127) == 0) asm volatile("red.release.gpu.global.add.u32 [%0], 1;" :: "l"(flag) : "memory");
}
__device__ __forceinline__ void wait_flags8(const unsigned int* f, unsigned int target) {
  for (int spin = 0; spin < (1 << 26); spin++) {
    unsigned int a, b, c, d, e, g, h, i;
    asm volatile("ld.volatile.global.v4.u32 {%0, %1, %2, %3}, [%4];" : "=r"(a), "=r"(b), "=r"(c), "=r"(d) : "l"(f) : "memory");
    asm volatile("ld.volatile.global.v4.u32 {%0, %1, %2, %3}, [%4];" : "=r"(e), "=r"(g), "=r"(h), "=r"(i) : "l"(f + 4) : "memory");
    if (min(min(min(a, b), min(c, d)), min(min(e, g), min(h, i))) >= target) break;
    __nanosleep(32);
  }
  asm volatile("fence.acq_rel.gpu;" ::: "memory");
  asm volatile("fence.proxy.async;" ::: "memory");
}

constexpr int RP_LD = 3, RP_ST = 7;
constexpr int K1_STAGES = 4;
constexpr int K1_A_BYTES = 256 * 128;
constexpr int K1_B_BYTES = 64 * 160 * 2;
constexpr int K1_STAGE = K1_A_BYTES + K1_B_BYTES;
constexpr int K1_SMEM = 5 * K1_A_BYTES + 61440 + 1024;
constexpr int KV_STAGES = 5;
constexpr int KVW_OFF = KV_STAGES * K1_A_BYTES;

__global__ void __launch_bounds__(512, 1)
proj_kernel(const __grid_constant__ CUtensorMap tmX, const __grid_constant__ CUtensorMap tmWq, const __grid_constant__ CUtensorMap tmWqkv,
            const __nv_bfloat16* __restrict__ wk, const __nv_bfloat16* __restrict__ wv, const __nv_bfloat16* __restrict__ gate_w,
            const __nv_bfloat16* __restrict__ woA, const __nv_bfloat16* __restrict__ woB) {
  extern __shared__ uint8_t smem_raw[];
  __shared__ __align__(8) uint64_t bar_full[KV_STAGES], bar_empty[KV_STAGES];
  uint8_t* smem = reinterpret_cast<uint8_t*>((reinterpret_cast<uintptr_t>(smem_raw) + 1023) & ~(uintptr_t)1023);
  const uint32_t sbase = smem_u32(smem);
  const uint32_t dbase = sbase & 0x3FFFFu;
  const int tid = threadIdx.x, warp = tid >> 5, lane = tid & 31;
  const bool is_kv = blockIdx.x >= 128;
  if (tid == 32) { prefetch_tmap(&tmX); prefetch_tmap((blockIdx.x & 15) < 4 ? &tmWq : &tmWqkv); }
  if (tid == 0) {
    for (int i = 0; i < KV_STAGES; i++) { mbar_init(smem_u32(&bar_full[i]), 1); mbar_init(smem_u32(&bar_empty[i]), is_kv ? 8 : 16); }
    fence_mbar_init();
  }
  uint2 wa[2][5], wb[2][5]; uint32_t gw[2];
  if (is_kv && tid < 320) {
#pragma unroll
    for (int r = 0; r < 2; r++) {
      const int k = tid + r * 320;
      const uint2* pk = reinterpret_cast<const uint2*>(wk + k * 20);
      const uint2* pv = reinterpret_cast<const uint2*>(wv + k * 20);
#pragma unroll
      for (int i = 0; i < 5; i++) { wa[r][i] = __ldg(pk + i); wb[r][i] = __ldg(pv + i); }
      gw[r] = (uint32_t)__bfloat16_as_ushort(gate_w[k]);
    }
  }
  __syncthreads();
  if (tid == 480 && !is_kv) { g_done[blockIdx.x] = 0u; g_doneL[blockIdx.x] = 0u; }
  pdl_launch();

  if (!is_kv) {
    const int mb = blockIdx.x >> 4, nb = blockIdx.x & 15;
    const CUtensorMap* tw = nb < 4 ? &tmWq : &tmWqkv;
    const int j0 = (nb < 4 ? nb : nb - 4) * 5;
    auto load = [&](int kt) {
      const int s = kt % K1_STAGES;
      const uint32_t fb = smem_u32(&bar_full[s]);
      mbar_expect_tx(fb, K1_STAGE);
      tma_2d(sbase + s * K1_STAGE, &tmX, kt * 64, mb * 256, fb);
      tma_3d(sbase + s * K1_STAGE + K1_A_BYTES, tw, 0, kt * 64, j0, fb);
    };
    if (tid == 0) for (int kt = 0; kt < K1_STAGES; kt++) load(kt);
    __syncwarp();
    uint4 wv2[2];
    const int rq = blockIdx.x * 400 + tid - 112;
    const int rhalf = rq >= 25600, rr = rq - rhalf * 25600, rk = 2 * (rr / 80), rch = rr % 80;
    {
      const int wg = warp >> 2;
      float acc[80];
#pragma unroll
      for (int i = 0; i < 80; i++) acc[i] = 0.f;
      for (int kt = 0; kt < 10; kt++) {
        const int s = kt % K1_STAGES;
        mbar_wait(smem_u32(&bar_full[s]), (kt / K1_STAGES) & 1);
        const uint32_t alo = ((dbase + s * K1_STAGE + wg * 8192) >> 4) | (1u << 16);
        const uint32_t blo = ((dbase + s * K1_STAGE + K1_A_BYTES) >> 4) | ((4096u >> 4) << 16);
        fence_regs(acc);
        wg_fence();
#pragma unroll
        for (int k = 0; k < 4; k++) wgmma_ss_n160_tb(acc, mkd(alo + k * 2, DHI_SW128_K), mkd(blo + k * 64, DHI_SW64_MN));
        wg_commit();
        if (kt == RP_LD && tid >= 112) {
          const uint4* src = reinterpret_cast<const uint4*>((rhalf ? woB : woA) + rk * D_MODEL + rch * 8);
          wv2[0] = __ldg(src); wv2[1] = __ldg(src + D_MODEL / 8);
        }
        if (kt == RP_ST && tid >= 112) {
          uint4* dst = reinterpret_cast<uint4*>(g_wimg + ((rhalf * 8 + rch / 10) * 10 + (rk >> 6)) * 10240 + (rch % 10) * 1024 + (rk & 63) * 16);
          dst[0] = wv2[0]; dst[1] = wv2[1];
        }
        __syncwarp();
        if (kt > 0 && kt - 1 + K1_STAGES < 10) {
          wg_wait<1>();
          const uint32_t eb = smem_u32(&bar_empty[(kt - 1) % K1_STAGES]);
          if (lane == 0) mbar_arrive(eb);
          if (tid == 0) { mbar_wait(eb, ((kt - 1) / K1_STAGES) & 1); load(kt - 1 + K1_STAGES); }
          __syncwarp();
        }
      }
      wg_wait<0>();
      fence_regs(acc);
      asm volatile("bar.sync %0, 128;" :: "r"(wg + 1) : "memory");
      const int w4 = warp & 3;
      const uint32_t off = w4 * K1_STAGE + wg * 8192;
      const int row0 = mb * 256 + wg * 64 + w4 * 16;
      if (nb < 4) {
        store_tile_bf16<160>(acc, 0.22360679774997896f * 1.4426950408889634f, sbase + off, smem + off,
                             g_q + (size_t)row0 * D_MODEL + nb * 160, D_MODEL, lane);
      } else {
        store_tile_bf16<160>(acc, 1.0f, sbase + off, smem + off, g_qkv + (size_t)row0 * (3 * D_MODEL) + (nb - 4) * 160, 3 * D_MODEL, lane);
      }
    }
  } else {
    const int cb = blockIdx.x - 128;
    if (warp == 8 && lane == 0) {
      for (int it = 0; it < KV_STAGES; it++) {
        const uint32_t fb = smem_u32(&bar_full[it]);
        mbar_expect_tx(fb, K1_A_BYTES);
        tma_2d(sbase + it * K1_A_BYTES, &tmX, it * 64, cb * 512, fb);
      }
    }
    __syncwarp();
    if (tid < 320) {
#pragma unroll
      for (int r = 0; r < 2; r++) {
        uint4* dst = reinterpret_cast<uint4*>(smem + KVW_OFF + (tid + r * 320) * 16);
        dst[0] = make_uint4(wa[r][0].x, wa[r][0].y, wa[r][1].x, wa[r][1].y);
        dst[640] = make_uint4(wa[r][2].x, wa[r][2].y, wa[r][3].x, wa[r][3].y);
        dst[1280] = make_uint4(wa[r][4].x, wa[r][4].y, 0u, 0u);
        dst[1920] = make_uint4(wb[r][0].x, wb[r][0].y, wb[r][1].x, wb[r][1].y);
        dst[2560] = make_uint4(wb[r][2].x, wb[r][2].y, wb[r][3].x, wb[r][3].y);
        dst[3200] = make_uint4(wb[r][4].x, wb[r][4].y, gw[r], 0u);
      }
    }
    fence_proxy_async();
    asm volatile("bar.sync 1, 512;" ::: "memory");
    auto produce = [&](int it0, int it1) {
      for (int it = it0; it < it1; it++) {
        const int s = it % KV_STAGES;
        mbar_wait(smem_u32(&bar_empty[s]), (it / KV_STAGES - 1) & 1);
        const uint32_t fb = smem_u32(&bar_full[s]);
        mbar_expect_tx(fb, K1_A_BYTES);
        tma_2d(sbase + s * K1_A_BYTES, &tmX, (it >= 10 ? it - 10 : it) * 64, cb * 512 + (it >= 10 ? 256 : 0), fb);
      }
    };
    if (tid == 256) produce(KV_STAGES, 15);
    __syncwarp();
    {
      const int pass = warp >> 3, wg = (warp >> 2) & 1, w4 = warp & 3, g = lane >> 2, t = lane & 3;
      if (pass == 1) asm volatile("bar.sync 2, 512;" ::: "memory");
      {
        float acc[2][24];
#pragma unroll
        for (int i = 0; i < 24; i++) { acc[0][i] = 0.f; acc[1][i] = 0.f; }
        for (int kt = 0; kt < 10; kt++) {
          const int it = pass * 10 + kt, s = it % KV_STAGES;
          mbar_wait(smem_u32(&bar_full[s]), (it / KV_STAGES) & 1);
          const uint32_t alo = ((dbase + s * K1_A_BYTES + wg * 16384) >> 4) | (1u << 16);
          const uint32_t blo = ((dbase + KVW_OFF + kt * 1024) >> 4) | ((128u >> 4) << 16);
          fence_regs(acc[0]); fence_regs(acc[1]);
          wg_fence();
#pragma unroll
          for (int k = 0; k < 4; k++) {
            wgmma_ss_n48_tb(acc[0], mkd(alo + k * 2, DHI_SW128_K), mkd(blo + k * 16, 10240u >> 4));
            wgmma_ss_n48_tb(acc[1], mkd(alo + 512 + k * 2, DHI_SW128_K), mkd(blo + k * 16, 10240u >> 4));
          }
          wg_commit();
          if (kt > 0) {
            wg_wait<1>();
            if (lane == 0) mbar_arrive(smem_u32(&bar_empty[(it - 1) % KV_STAGES]));
          }
        }
        wg_wait<0>();
        fence_regs(acc[0]); fence_regs(acc[1]);
        if (lane == 0) mbar_arrive(smem_u32(&bar_empty[(pass * 10 + 9) % KV_STAGES]));
        if (pass == 0) asm volatile("bar.arrive 2, 512;" ::: "memory");
        if (tid == 0) produce(15, 20);
        __syncwarp();
        float kmax2 = 0.f, vmax = 0.f;
#pragma unroll
        for (int hh = 0; hh < 4; hh++) {
          const int h = hh & 1;
          const float (&a)[24] = acc[hh >> 1];
          const int key = cb * 512 + pass * 256 + wg * 128 + (hh >> 1) * 64 + w4 * 16 + g + h * 8;
          const int grp = key >> 7, kk = key & 127;
          const bool poly = (TMASK >> (kk >> 3)) & 1;
          uint8_t* gp = g_kvimg + grp * GRP_BYTES;
          const uint32_t k0 = pack_bf16(a[2 * h], a[2 * h + 1]);
          const uint32_t k1 = pack_bf16(a[4 + 2 * h], a[5 + 2 * h]);
          uint32_t k2 = pack_bf16(a[8 + 2 * h], a[9 + 2 * h]);
          float n2 = bf_lo(k0) * bf_lo(k0) + bf_hi(k0) * bf_hi(k0) + bf_lo(k1) * bf_lo(k1) + bf_hi(k1) * bf_hi(k1);
          if (t < 2) {
            n2 += bf_lo(k2) * bf_lo(k2) + bf_hi(k2) * bf_hi(k2);
            k2 = pack_bf16(bf_lo(k2) * 0.5f, bf_hi(k2) * 0.5f);
          } else if (t == 2) k2 = poly ? pack_bf16(24.f, 2.5f) : pack_bf16(0.5f, 0.f);
          else k2 = poly ? pack_bf16(0.5f, 0.f) : 0u;
          *reinterpret_cast<uint32_t*>(gp + kk * 16 + t * 4) = k0;
          *reinterpret_cast<uint32_t*>(gp + PLANE + kk * 16 + t * 4) = k1;
          *reinterpret_cast<uint32_t*>(gp + 2 * PLANE + kk * 16 + t * 4) = k2;
          n2 += __shfl_xor_sync(0xffffffffu, n2, 1);
          n2 += __shfl_xor_sync(0xffffffffu, n2, 2);
          kmax2 = (n2 > kmax2 || n2 != n2) ? n2 : kmax2;
          uint32_t v0 = pack_bf16(a[12 + 2 * h], a[13 + 2 * h]);
          uint32_t v1 = pack_bf16(a[16 + 2 * h], a[17 + 2 * h]);
          uint32_t v2 = pack_bf16(a[20 + 2 * h], a[21 + 2 * h]);
          float vm = fmaxf(fmaxf(fabsf(bf_lo(v0)), fabsf(bf_hi(v0))), fmaxf(fabsf(bf_lo(v1)), fabsf(bf_hi(v1))));
          if (t < 2) vm = fmaxf(vm, fmaxf(fabsf(bf_lo(v2)), fabsf(bf_hi(v2))));
          else if (t == 2) {
            const float z = a[20 + 2 * h];
            g_gate[key] = 1.f / (1.f + __expf(-z));
            v2 = 0x00003F80u;
          } else v2 = 0u;
          vmax = fmaxf(vmax, vm);
          if (poly) { v0 ^= 0x80008000u; v1 ^= 0x80008000u; v2 ^= 0x80008000u; }
          uint8_t* vp = gp + 3 * PLANE + (kk >> 3) * 384 + (kk & 7) * 16 + t * 4;
          *reinterpret_cast<uint32_t*>(vp) = v0;
          *reinterpret_cast<uint32_t*>(vp + 128) = v1;
          *reinterpret_cast<uint32_t*>(vp + 256) = v2;
        }
#pragma unroll
        for (int o = 1; o < 32; o <<= 1) {
          const float a = __shfl_xor_sync(0xffffffffu, kmax2, o);
          kmax2 = (a > kmax2 || a != a) ? a : kmax2;
          vmax = fmaxf(vmax, __shfl_xor_sync(0xffffffffu, vmax, o));
        }
        if (lane == 0) { g_kmax2[cb * 16 + warp] = kmax2; g_vmax[cb * 16 + warp] = vmax; }
      }
    }
  }
}

__device__ __forceinline__ uint32_t ex2_pair_poly(float u0, float u1, uint32_t one2) {
  const uint32_t W = __byte_perm(__float_as_uint(u0), __float_as_uint(u1), 0x6521);
  uint32_t v; asm("lop3.b32 %0, %1, 0x007F007F, %2, 0xEA;" : "=r"(v) : "r"(W), "r"(one2));
  uint32_t L, p;
  asm("fma.rn.bf16x2 %0, %1, %2, %3;" : "=r"(L) : "r"(v), "r"(0x1f961f96u), "r"(0x9fe39fe3u));
  asm("fma.rn.bf16x2 %0, %1, %1, %2;" : "=r"(p) : "r"(L), "r"(0x00f500f5u));
  return W + p;
}
template <int JOFF>
__device__ __forceinline__ void softmax_slow(const float (&S)[32], uint32_t (&P)[16], float (&O)[12], float& m0, float& m1) {
  float a0 = m0, a1 = m1;
#pragma unroll
  for (int j = 0; j < 8; j++) {
    a0 = fmaxf(a0, fmaxf(S[4 * j], S[4 * j + 1]));
    a1 = fmaxf(a1, fmaxf(S[4 * j + 2], S[4 * j + 3]));
  }
  a0 = fmaxf(a0, __shfl_xor_sync(0xffffffffu, a0, 1)); a0 = fmaxf(a0, __shfl_xor_sync(0xffffffffu, a0, 2));
  a1 = fmaxf(a1, __shfl_xor_sync(0xffffffffu, a1, 1)); a1 = fmaxf(a1, __shfl_xor_sync(0xffffffffu, a1, 2));
  const float c0 = ex2(m0 - a0), c1 = ex2(m1 - a1);
  m0 = a0; m1 = a1;
#pragma unroll
  for (int j = 0; j < 3; j++) { O[4 * j] *= c0; O[4 * j + 1] *= c0; O[4 * j + 2] *= c1; O[4 * j + 3] *= c1; }
#pragma unroll
  for (int i = 0; i < 16; i++) {
    const float m = (i & 1) ? a1 : a0;
    const uint32_t p = pack_bf16(ex2(S[2 * i] - m), ex2(S[2 * i + 1] - m));
    P[i] = ((TMASK >> (JOFF + i / 2)) & 1) ? (p ^ 0x80008000u) : p;
  }
}
constexpr uint32_t DHI_KV = 128 >> 4;
__device__ __forceinline__ void issue_qk(float (&S)[32], const uint32_t (&q)[8], uint64_t base) {
  wgmma_rs_n64<0>(S, q[0], q[1], q[2], q[3], base + (uint64_t)((PLANE >> 4) << 16));
  wgmma_rs_n64<1>(S, q[4], q[5], q[6], q[7], base + (uint64_t)(2 * PLANE >> 4));
}
__device__ __forceinline__ void issue_pv(float (&O)[12], const uint32_t (&P)[16], uint64_t vbase) {
#pragma unroll
  for (int kk = 0; kk < 4; kk++)
    wgmma_rs_n24_tb<1>(O, P[4 * kk], P[4 * kk + 1], P[4 * kk + 2], P[4 * kk + 3], vbase + (uint64_t)(kk * (768 >> 4)));
}

constexpr uint32_t VOFF = ((3 * PLANE) >> 4) + ((384u >> 4) << 16);
constexpr int KVR = 4;
constexpr int OFF_W = KVR * GRP_BYTES;
constexpr int OFF_X = OFF_W + 10 * 10240;
constexpr int OFF_BAR = OFF_X + 4 * 16384;
constexpr int K2_SMEM = OFF_BAR + 512 + 1024;
constexpr int TSL = 7;
constexpr int BAR_KV = 0, BAR_W = 4, BAR_TA = 5, BAR_TE = 12, BAR_OWN = 19, BAR_L = 20, CNT_KV = 21, BAR_WA = 23, BAR_WF = 33, CNT_TK = 43;
constexpr int NSTEP = 2 * NGRP;

__device__ __forceinline__ void kv_load(uint32_t sbase, int step) {
  const uint32_t bar = sbase + OFF_BAR + (BAR_KV + (step & (KVR - 1))) * 8;
  mbar_expect_tx(bar, GRP_BYTES);
  bulk_g2s(sbase + (step & (KVR - 1)) * GRP_BYTES, g_kvimg + (step & (NGRP - 1)) * GRP_BYTES, GRP_BYTES, bar);
}
__device__ __forceinline__ void kv_release(uint32_t sbase, int step, bool elected) {
  if (elected && step + KVR < NSTEP) {
    uint32_t old;
    asm volatile("atom.acq_rel.cta.shared::cta.inc.u32 %0, [%1], 3;" : "=r"(old) : "r"(sbase + OFF_BAR + CNT_KV * 8 + (step & (KVR - 1)) * 4) : "memory");
    if (old == 3u) kv_load(sbase, step + KVR);
  }
  __syncwarp();
}
__device__ __forceinline__ void kv_wait(uint32_t sbase, int step) {
  mbar_wait(sbase + OFF_BAR + (BAR_KV + (step & (KVR - 1))) * 8, (step / KVR) & 1);
}

__device__ __forceinline__ uint32_t kv_release_begin(uint32_t sbase, int slot, bool doit) {
  uint32_t old = 0;
  asm volatile("{\n.reg .pred p;\nsetp.ne.u32 p, %2, 0;\n@p atom.relaxed.cta.shared::cta.inc.u32 %0, [%1], 3;\n}\n"
               : "+r"(old) : "r"(sbase + OFF_BAR + CNT_KV * 8 + slot * 4), "r"((uint32_t)doit) : "memory");
  return old;
}
template <int H>
__device__ __forceinline__ void softmax_half(const float (&S)[64], uint32_t (&P)[16], uint32_t one2) {
#pragma unroll
  for (int i = 0; i < 16; i++) {
    if ((TMASK >> (8 * H + i / 2)) & 1) P[i] = ex2_pair_poly(S[32 * H + 2 * i], S[32 * H + 2 * i + 1], one2);
    else P[i] = pack_bf16(ex2(S[32 * H + 2 * i]), ex2(S[32 * H + 2 * i + 1]));
  }
}
__device__ __forceinline__ void attn_fast(const uint32_t (&q)[8], float (&O)[12], uint32_t sbase, int step0, int nsteps, bool elected, uint32_t one2) {
  uint64_t kb0 = mkd((sbase & 0x3FFFFu) >> 4, DHI_KV);
  asm volatile("" : "+l"(kb0));
#pragma unroll 1
  for (int step4 = step0; step4 < step0 + nsteps; step4 += KVR) {
#pragma unroll
    for (int j = 0; j < KVR; j++) {
      const int step = step4 + j;
      const uint64_t kb = kb0 + (uint64_t)(j * (GRP_BYTES >> 4));
      float S[64]; uint32_t PA[16], PB[16];
#pragma unroll
      for (int i = 0; i < 64; i++) S[i] = 0.f;
      mbar_wait(sbase + OFF_BAR + (BAR_KV + j) * 8, (step / KVR) & 1);
      fence_regs(S);
      wg_fence();
      wgmma_rs_n128<0>(S, q[0], q[1], q[2], q[3], kb + (uint64_t)((PLANE >> 4) << 16));
      wgmma_rs_n128<1>(S, q[4], q[5], q[6], q[7], kb + (uint64_t)(2 * PLANE >> 4));
      wg_commit();
      const uint32_t old = kv_release_begin(sbase, (j + KVR - 1) & (KVR - 1), elected && step > step0 && step - 1 + KVR < NSTEP);
      wg_wait<0>();
      fence_regs(S);
      softmax_half<0>(S, PA, one2);
      fence_regs(PA); fence_regs(O);
      wg_fence();
      issue_pv(O, PA, kb + VOFF);
      wg_commit();
      softmax_half<1>(S, PB, one2);
      fence_regs(PB);
      wg_fence();
      issue_pv(O, PB, kb + VOFF + 4 * (768 >> 4));
      wg_commit();
      if (old == 3u) kv_load(sbase, step - 1 + KVR);
      wg_wait<0>();
      fence_regs(PA); fence_regs(PB); fence_regs(O);
    }
  }
  kv_release(sbase, step0 + nsteps - 1, elected);
}
template <int H>
__device__ __forceinline__ void slow_step(const uint32_t (&q)[8], float (&O)[12], uint64_t kb, float& m0, float& m1) {
  float S[32]; uint32_t P[16];
#pragma unroll
  for (int i = 0; i < 32; i++) S[i] = 0.f;
  fence_regs(S);
  wg_fence();
  issue_qk(S, q, kb + 64 * H);
  wg_commit();
  wg_wait<0>();
  fence_regs(S);
  softmax_slow<8 * H>(S, P, O, m0, m1);
  fence_regs(P); fence_regs(O);
  wg_fence();
  issue_pv(O, P, kb + VOFF + H * 4 * (768 >> 4));
  wg_commit();
  wg_wait<0>();
  fence_regs(O); fence_regs(P);
}
__device__ __forceinline__ void attn_slow(const uint32_t (&q)[8], float (&O)[12], uint32_t sbase, int step0, int nsteps, bool elected, float& m0, float& m1) {
#pragma unroll 1
  for (int step = step0; step < step0 + nsteps; step++) {
    kv_wait(sbase, step);
    const uint64_t kb = mkd(((sbase & 0x3FFFFu) >> 4) + (step & (KVR - 1)) * (GRP_BYTES >> 4), DHI_KV);
    slow_step<0>(q, O, kb, m0, m1);
    slow_step<1>(q, O, kb, m0, m1);
    kv_release(sbase, step, elected);
  }
}

__device__ __forceinline__ void softmax8(float (&sc)[8], float scale) {
  float mx = sc[0];
#pragma unroll
  for (int w = 1; w < 8; w++) mx = fmaxf(mx, sc[w]);
  float l = 0.f;
#pragma unroll
  for (int w = 0; w < 8; w++) { sc[w] = ex2(sc[w] - mx); l += sc[w]; }
  const float r = __fdividef(scale, l);
#pragma unroll
  for (int w = 0; w < 8; w++) sc[w] *= r;
}
constexpr int LBOX = 32 * 320;
__device__ __forceinline__ uint2 lds64(uint32_t a) {
  uint2 v; asm volatile("ld.shared.v2.u32 {%0, %1}, [%2];" : "=r"(v.x), "=r"(v.y) : "r"(a)); return v;
}
__device__ __forceinline__ void local_attn(uint32_t stage, int t0, int i, int lane) {
  constexpr float SC = 0.22360679774997896f * 1.4426950408889634f, NEG = -1e9f * 1.4426950408889634f;
  const uint32_t base = stage + (lane >> 3) * LBOX + (lane & 7) * 40 + (i + 14 + ((lane >> 3) & 1)) * 320;
  const int t = t0 + i;
  float sc[8];
#pragma unroll
  for (int w = 0; w < 8; w++) sc[w] = 0.f;
#pragma unroll 1
  for (int c = 0; c < 5; c++) {
    const uint2 qv = lds64(base + c * 8);
    const float q0 = bf_lo(qv.x), q1 = bf_hi(qv.x), q2 = bf_lo(qv.y), q3 = bf_hi(qv.y);
#pragma unroll
    for (int w = 0; w < 8; w++) {
      const uint2 k = lds64(base + c * 8 + 4 * LBOX - w * 640);
      sc[w] = fmaf(q0, bf_lo(k.x), sc[w]); sc[w] = fmaf(q1, bf_hi(k.x), sc[w]);
      sc[w] = fmaf(q2, bf_lo(k.y), sc[w]); sc[w] = fmaf(q3, bf_hi(k.y), sc[w]);
    }
  }
#pragma unroll
  for (int w = 0; w < 8; w++) sc[w] = t - 2 * w >= 0 ? sc[w] * SC : NEG;
  softmax8(sc, 1.f - g_gate[t]);
  uint2* dst = reinterpret_cast<uint2*>(g_a2 + (size_t)t * (2 * D_MODEL) + D_MODEL + lane * DH);
#pragma unroll 1
  for (int c = 0; c < 5; c++) {
    float o0 = 0.f, o1 = 0.f, o2 = 0.f, o3 = 0.f;
#pragma unroll
    for (int w = 0; w < 8; w++) {
      const uint2 v = lds64(base + c * 8 + 8 * LBOX - w * 640);
      o0 = fmaf(sc[w], bf_lo(v.x), o0); o1 = fmaf(sc[w], bf_hi(v.x), o1);
      o2 = fmaf(sc[w], bf_lo(v.y), o2); o3 = fmaf(sc[w], bf_hi(v.y), o3);
    }
    dst[c] = make_uint2(pack_bf16(o0, o1), pack_bf16(o2, o3));
  }
}
__device__ __forceinline__ uint32_t ta_slot(int i) { return i < 4 ? OFF_X + i * 16384 : (i - 4) * 16384; }

__global__ void __launch_bounds__(640, 1)
attn_kernel(const __grid_constant__ CUtensorMap tmA2, const __grid_constant__ CUtensorMap tmL, __nv_bfloat16* __restrict__ out, uint32_t one2) {
  extern __shared__ uint8_t smem_raw[];
  uint8_t* smem = reinterpret_cast<uint8_t*>((reinterpret_cast<uintptr_t>(smem_raw) + 1023) & ~(uintptr_t)1023);
  const uint32_t sbase = smem_u32(smem);
  const uint32_t dbase = sbase & 0x3FFFFu;
  const uint32_t bars = sbase + OFF_BAR;
  const int tid = threadIdx.x, wg = tid >> 7, warp = (tid >> 5) & 3, lane = tid & 31, g = lane >> 2, t = lane & 3;
  const int mb = blockIdx.x >> 3, nb = blockIdx.x & 7;
  const bool elected = (tid & 127) == 0;
  if (tid == 512) { prefetch_tmap(&tmL); prefetch_tmap(&tmA2); }
  if (tid == 0) {
    for (int i = 0; i < BAR_TE; i++) mbar_init(bars + i * 8, 1);
    for (int i = BAR_TE; i < BAR_TE + TSL; i++) mbar_init(bars + i * 8, 8);
    mbar_init(bars + BAR_OWN * 8, 4);
    mbar_init(bars + BAR_L * 8, 1);
    for (int i = 0; i < 10; i++) { mbar_init(bars + (BAR_WA + i) * 8, 1); mbar_init(bars + (BAR_WF + i) * 8, 8); }
    for (int i = 0; i < 4; i++) *reinterpret_cast<uint32_t*>(smem + OFF_BAR + CNT_KV * 8 + i * 4) = 0u;
    *reinterpret_cast<uint32_t*>(smem + OFF_BAR + CNT_TK * 8) = 0u;
    fence_mbar_init();
  }
  __syncthreads();
  auto tail_load = [&](int i) {
    const uint32_t fb = bars + (BAR_TA + i % TSL) * 8;
    mbar_expect_tx(fb, 16384);
    tma_2d(sbase + ta_slot(i % TSL), &tmA2, i < 10 ? D_MODEL + i * 64 : (i - 10) * 64, mb * 128, fb);
  };
  if (wg == 4) {
    asm volatile("setmaxnreg.dec.sync.aligned.u32 32;");
    pdl_wait();
    if (tid == 512) {
      for (int j = 0; j < KVR; j++) kv_load(sbase, j);
      mbar_expect_tx(bars + BAR_L * 8, 12 * LBOX);
      for (int i = 0; i < 12; i++) tma_2d(sbase + OFF_W + i * LBOX, &tmL, i * 160, blockIdx.x * 16 - 14 - (i & 1), bars + BAR_L * 8);
    }
    __syncwarp();
    mbar_wait(bars + BAR_L * 8, 0);
#pragma unroll 1
    for (int i = 0; i < 4; i++) local_attn(sbase + OFF_W, blockIdx.x * 16, warp * 4 + i, lane);
    signal_done(&g_doneL[blockIdx.x], wg, tid);
    if (tid == 512) {
      fence_proxy_async();
      mbar_expect_tx(bars + BAR_W * 8, 10 * 10240);
      for (int i = 0; i < 5; i++) bulk_g2s(sbase + OFF_W + i * 20480, g_wimg + ((8 + nb) * 10) * 10240 + i * 20480, 20480, bars + BAR_W * 8);
      wait_flags8(&g_doneL[mb * 8], 1u);
      for (int i = 0; i < 4; i++) tail_load(i);
      mbar_wait(bars + BAR_OWN * 8, 0);
      for (int i = 4; i < 20; i++) {
        if (i >= TSL) mbar_wait(bars + (BAR_TE + i % TSL) * 8, (i / TSL - 1) & 1);
        if (i == 10) { wait_flags8(&g_done[mb * 8], 1u); }
        tail_load(i);
      }
    } else if (tid == 576) {
      mbar_wait(bars + BAR_OWN * 8, 0);
      asm volatile("red.release.gpu.global.add.u32 [%0], 1;" :: "l"(&g_done[blockIdx.x]) : "memory");
    } else if (tid == 544) {
      for (int kt = 0; kt < 10; kt++) {
        mbar_wait(bars + (BAR_WF + kt) * 8, 0);
        mbar_expect_tx(bars + (BAR_WA + kt) * 8, 10240);
        bulk_g2s(sbase + OFF_W + kt * 10240, g_wimg + (nb * 10 + kt) * 10240, 10240, bars + (BAR_WA + kt) * 8);
      }
    }
    return;
  }
  asm volatile("setmaxnreg.inc.sync.aligned.u32 112;");
  pdl_wait();
  uint32_t q[8], q2[6];
  const int rowA = (blockIdx.x * 8 + wg) * 64 + warp * 16 + g;
  {
    const uint32_t* r0 = reinterpret_cast<const uint32_t*>(g_q + (size_t)rowA * DH);
    const uint32_t* r1 = r0 + 8 * (DH / 2);
    const uint32_t* s0 = r0 + 256 * (DH / 2);
    const uint32_t* s1 = s0 + 8 * (DH / 2);
    q[0] = r0[t]; q[1] = r1[t]; q[2] = r0[t + 4]; q[3] = r1[t + 4];
    q[4] = t < 2 ? r0[8 + t] : 0u;
    q[5] = t < 2 ? r1[8 + t] : 0u;
    q2[0] = s0[t]; q2[1] = s1[t]; q2[2] = s0[t + 4]; q2[3] = s1[t + 4];
    q2[4] = t < 2 ? s0[8 + t] : 0u;
    q2[5] = t < 2 ? s1[8 + t] : 0u;
  }
  float kmax2 = 0.f, vmax = 0.f;
#pragma unroll
  for (int i = 0; i < 2; i++) {
    const float a = g_kmax2[lane + 32 * i];
    kmax2 = (a > kmax2 || a != a) ? a : kmax2;
    vmax = fmaxf(vmax, g_vmax[lane + 32 * i]);
  }
#pragma unroll
  for (int o = 1; o < 32; o <<= 1) {
    const float a = __shfl_xor_sync(0xffffffffu, kmax2, o);
    kmax2 = (a > kmax2 || a != a) ? a : kmax2;
    vmax = fmaxf(vmax, __shfl_xor_sync(0xffffffffu, vmax, o));
  }
  const float qlim = (vmax >= 0.00390625f && vmax <= 256.f) ? 9025.f / kmax2 : -1.f;
#pragma unroll 1
  for (int it = 0; it < 2; it++) {
    const int row0 = rowA + it * 256;
    if (it == 1) {
#pragma unroll
      for (int i = 0; i < 6; i++) q[i] = q2[i];
    }
    float n0 = bf_lo(q[0]) * bf_lo(q[0]) + bf_hi(q[0]) * bf_hi(q[0]) + bf_lo(q[2]) * bf_lo(q[2]) + bf_hi(q[2]) * bf_hi(q[2]) +
               bf_lo(q[4]) * bf_lo(q[4]) + bf_hi(q[4]) * bf_hi(q[4]);
    float n1 = bf_lo(q[1]) * bf_lo(q[1]) + bf_hi(q[1]) * bf_hi(q[1]) + bf_lo(q[3]) * bf_lo(q[3]) + bf_hi(q[3]) * bf_hi(q[3]) +
               bf_lo(q[5]) * bf_lo(q[5]) + bf_hi(q[5]) * bf_hi(q[5]);
    n0 += __shfl_xor_sync(0xffffffffu, n0, 1); n0 += __shfl_xor_sync(0xffffffffu, n0, 2);
    n1 += __shfl_xor_sync(0xffffffffu, n1, 1); n1 += __shfl_xor_sync(0xffffffffu, n1, 2);
    const bool safe = (n0 <= qlim) && (n1 <= qlim);
    uint32_t unsafe_any;
    asm volatile("{\n.reg .pred p, r;\nsetp.eq.u32 p, %1, 0;\nbarrier.cta.red.or.pred r, %2, 128, p;\nselp.u32 %0, 1, 0, r;\n}\n"
                 : "=r"(unsafe_any) : "r"((uint32_t)safe), "r"(wg + 1) : "memory");
    float O[12];
#pragma unroll
    for (int i = 0; i < 12; i++) O[i] = 0.f;
    if (!unsafe_any && t >= 2) { q[4] = q[5] = (t == 2) ? 0x3F804100u : 0x00003B80u; }
    q[6] = q[4]; q[7] = q[5];
    fence_regs(q);
    float m0 = -INFINITY, m1 = -INFINITY;
    if (!unsafe_any) attn_fast(q, O, sbase, it * NGRP, NGRP, elected, one2);
    else attn_slow(q, O, sbase, it * NGRP, NGRP, elected, m0, m1);
    const float l0 = __shfl_sync(0xffffffffu, O[8], (lane & ~3) | 2);
    const float l1 = __shfl_sync(0xffffffffu, O[10], (lane & ~3) | 2);
    const int tok = row0 >> 5;
    const float gt = g_gate[tok];
    const float i0 = gt / l0, i1 = gt / l1;
    uint32_t* o0 = reinterpret_cast<uint32_t*>(g_a2 + (size_t)tok * (2 * D_MODEL) + (row0 & 31) * DH);
    uint32_t* o1 = o0 + 8 * (DH / 2);
    o0[t] = pack_bf16(O[0] * i0, O[1] * i0); o1[t] = pack_bf16(O[2] * i1, O[3] * i1);
    o0[t + 4] = pack_bf16(O[4] * i0, O[5] * i0); o1[t + 4] = pack_bf16(O[6] * i1, O[7] * i1);
    if (t < 2) { o0[t + 8] = pack_bf16(O[8] * i0, O[9] * i0); o1[t + 8] = pack_bf16(O[10] * i1, O[11] * i1); }
  }
  uint32_t* ticket = reinterpret_cast<uint32_t*>(smem + OFF_BAR + CNT_TK * 8);
  if (elected) ticket[1 + wg] = atomicAdd(ticket, 1u);
  asm volatile("bar.sync %0, 128;" :: "r"(wg + 1) : "memory");
  if (elected) mbar_arrive(bars + BAR_OWN * 8);
  const int mt = ticket[1 + wg];
  if (mt < 2) {
    float acc[40];
#pragma unroll
    for (int i = 0; i < 40; i++) acc[i] = 0.f;
    mbar_wait(bars + BAR_W * 8, 0);
    int sl = 0, ph = 0;
#pragma unroll 1
    for (int i = 0; i < 20; i++) {
      mbar_wait(bars + (BAR_TA + sl) * 8, ph);
      if (i >= 10) mbar_wait(bars + (BAR_WA + i - 10) * 8, 0);
      const uint32_t alo = ((dbase + ta_slot(sl) + mt * 8192) >> 4) | (1u << 16);
      const uint32_t blo = ((dbase + OFF_W + (i >= 10 ? i - 10 : i) * 10240) >> 4) | ((128u >> 4) << 16);
      fence_regs(acc);
      wg_fence();
#pragma unroll
      for (int k = 0; k < 4; k++) wgmma_ss_n80_tb(acc, mkd(alo + k * 2, DHI_SW128_K), mkd(blo + k * 16, 1024u >> 4));
      wg_commit();
      if (i > 0) {
        wg_wait<1>();
        if (lane == 0) mbar_arrive(bars + (BAR_TE + (sl == 0 ? TSL - 1 : sl - 1)) * 8);
        if (lane == 1 && i <= 10) mbar_arrive(bars + (BAR_WF + i - 1) * 8);
      }
      if (++sl == TSL) { sl = 0; ph ^= 1; }
    }
    wg_wait<0>();
    fence_regs(acc);
    asm volatile("bar.sync %0, 128;" :: "r"(wg + 1) : "memory");
    const uint32_t so = ta_slot(warp) + mt * 8192;
    const int row0 = mb * 128 + mt * 64 + warp * 16;
    store_tile_bf16<80>(acc, 1.0f, sbase + so, smem + so, out + (size_t)row0 * D_MODEL + nb * 80, D_MODEL, lane);
  }
}

typedef CUresult (*EncodeFn)(CUtensorMap*, CUtensorMapDataType, cuuint32_t, void*, const cuuint64_t*, const cuuint64_t*,
                             const cuuint32_t*, const cuuint32_t*, CUtensorMapInterleave, CUtensorMapSwizzle,
                             CUtensorMapL2promotion, CUtensorMapFloatOOBfill);

void make_map(EncodeFn fn, CUtensorMap* tm, const void* ptr, int rank, const cuuint64_t* dims, const cuuint64_t* strides,
              const cuuint32_t* box, CUtensorMapSwizzle sw) {
  const cuuint32_t es[3] = {1, 1, 1};
  fn(tm, CU_TENSOR_MAP_DATA_TYPE_BFLOAT16, rank, const_cast<void*>(ptr), dims, strides, box, es, CU_TENSOR_MAP_INTERLEAVE_NONE, sw,
     CU_TENSOR_MAP_L2_PROMOTION_L2_256B, CU_TENSOR_MAP_FLOAT_OOB_FILL_NONE);
}
void map_a(EncodeFn fn, CUtensorMap* tm, const void* p, int rows, int cols, int box_rows) {
  const cuuint64_t dims[2] = {(cuuint64_t)cols, (cuuint64_t)rows};
  const cuuint64_t str[1] = {(cuuint64_t)cols * 2};
  const cuuint32_t box[2] = {64, (cuuint32_t)box_rows};
  make_map(fn, tm, p, 2, dims, str, box, CU_TENSOR_MAP_SWIZZLE_128B);
}
void map_w(EncodeFn fn, CUtensorMap* tm, const void* p, int K, int N, int atom, CUtensorMapSwizzle sw) {
  const cuuint64_t dims[3] = {(cuuint64_t)atom, (cuuint64_t)K, (cuuint64_t)(N / atom)};
  const cuuint64_t str[2] = {(cuuint64_t)N * 2, (cuuint64_t)atom * 2};
  const cuuint32_t box[3] = {(cuuint32_t)atom, 64, 5};
  make_map(fn, tm, p, 3, dims, str, box, sw);
}

template <typename... KArgs, typename... Args>
void launch(void (*kern)(KArgs...), int grid, int block, int smem, bool pdl, Args... args) {
  cudaLaunchConfig_t cfg = {};
  cfg.gridDim = dim3(grid); cfg.blockDim = dim3(block); cfg.dynamicSmemBytes = smem; cfg.stream = cudaStreamPerThread;
  cudaLaunchAttribute at[1];
  at[0].id = cudaLaunchAttributeProgrammaticStreamSerialization;
  at[0].val.programmaticStreamSerializationAllowed = 1;
  cfg.attrs = at; cfg.numAttrs = pdl ? 1 : 0;
  cudaLaunchKernelEx(&cfg, kern, KArgs(args)...);
}

}

extern "C" void kernel_launch(void* const* d_in, const int* in_sizes, int n_in, void* d_out, int out_size) {
  (void)in_sizes; (void)n_in; (void)out_size;
  const __nv_bfloat16* x = (const __nv_bfloat16*)d_in[0];
  const __nv_bfloat16* wq = (const __nv_bfloat16*)d_in[1];
  const __nv_bfloat16* wk = (const __nv_bfloat16*)d_in[2];
  const __nv_bfloat16* wv = (const __nv_bfloat16*)d_in[3];
  const __nv_bfloat16* woA = (const __nv_bfloat16*)d_in[4];
  const __nv_bfloat16* wqkv = (const __nv_bfloat16*)d_in[6];
  const __nv_bfloat16* woB = (const __nv_bfloat16*)d_in[7];
  const __nv_bfloat16* gate_w = (const __nv_bfloat16*)d_in[8];

  static EncodeFn enc = nullptr;
  static void* a2_ptr = nullptr;
  static void* qkv_ptr = nullptr;
  if (!enc) {
    void* fp = nullptr;
    cudaDriverEntryPointQueryResult qr;
    cudaGetDriverEntryPoint("cuTensorMapEncodeTiled", &fp, cudaEnableDefault, &qr);
    enc = (EncodeFn)fp;
    cudaGetSymbolAddress(&a2_ptr, g_a2);
    cudaGetSymbolAddress(&qkv_ptr, g_qkv);
    cudaFuncSetAttribute(proj_kernel, cudaFuncAttributeMaxDynamicSharedMemorySize, K1_SMEM);
    cudaFuncSetAttribute(attn_kernel, cudaFuncAttributeMaxDynamicSharedMemorySize, K2_SMEM);
  }
  CUtensorMap tmX, tmWq, tmWqkv, tmA2, tmL;
  {
    const cuuint64_t dims[2] = {3 * D_MODEL, S_LEN};
    const cuuint64_t str[1] = {3 * D_MODEL * 2};
    const cuuint32_t box[2] = {160, 32};
    make_map(enc, &tmL, qkv_ptr, 2, dims, str, box, CU_TENSOR_MAP_SWIZZLE_NONE);
  }
  map_a(enc, &tmX, x, S_LEN, D_MODEL, 256);
  map_w(enc, &tmWq, wq, D_MODEL, D_MODEL, 32, CU_TENSOR_MAP_SWIZZLE_64B);
  map_w(enc, &tmWqkv, wqkv, D_MODEL, 3 * D_MODEL, 32, CU_TENSOR_MAP_SWIZZLE_64B);
  map_a(enc, &tmA2, a2_ptr, S_LEN, 2 * D_MODEL, 128);

  launch(proj_kernel, 132, 512, K1_SMEM, false, tmX, tmWq, tmWqkv, wk, wv, gate_w, woA, woB);
  launch(attn_kernel, 128, 640, K2_SMEM, true, tmA2, tmL, (__nv_bfloat16*)d_out, 0x3F803F80u);
}
```
